```python
import torch

def _softmax(x, axis=-1):
    return torch.softmax(x, dim=axis)
def _gelu(x):
    return torch.nn.functional.gelu(x, approximate="tanh")
def _silu(x):
    return torch.nn.functional.silu(x)
def _sigmoid(x):
    return torch.sigmoid(x)
def _layernorm(x, axis=-1, eps=1e-5):
    m = x.mean(dim=axis, keepdim=True)
    v = x.var(dim=axis, keepdim=True, unbiased=False)
    return (x - m) / torch.sqrt(v + eps)
def _scatter_add(tgt, idx, src, axis=0):
    return tgt.clone().index_add_(axis, idx, src)
def _segment_sum(src, seg, n):
    out = torch.zeros((n,) + src.shape[1:], dtype=src.dtype)
    return out.index_add_(0, seg, src)
def _pad(x, pw):
    flat = tuple(v for pair in reversed(pw) for v in pair)
    return torch.nn.functional.pad(x, flat)

kernel_name = 'interleave_layers__ssm_conv_s5__ssm_conv_h3__prompt'

def setup_inputs():

    _w = (lambda a: (lambda t: t.to(torch.bfloat16) if t.is_floating_point() else t)(torch.as_tensor(a)))
    def _A_setup():
        B, S, D = 1, 2048, 640
        P = D
        Lambda_re = -0.5 * (lambda _x: torch.exp(torch.as_tensor(_x)))((lambda *s: torch.randn(*s, dtype=torch.bfloat16) * 0.2)(P))
        Lambda_im = (lambda *s: torch.randn(*s, dtype=torch.bfloat16) * 0.8)(P) * 1.0
        B_re = (lambda *s: torch.randn(*s, dtype=torch.bfloat16) * 0.2)(P, D) * (D ** -0.5)
        B_im = (lambda *s: torch.randn(*s, dtype=torch.bfloat16) * 0.2)(P, D) * (D ** -0.5)
        C_re = (lambda *s: torch.randn(*s, dtype=torch.bfloat16) * 0.2)(D, P) * (P ** -0.5)
        C_im = (lambda *s: torch.randn(*s, dtype=torch.bfloat16) * 0.2)(D, P) * (P ** -0.5)
        log_dt = (lambda *s: torch.randn(*s, dtype=torch.bfloat16) * 0.2)(P) * 0.3 - 2.0
        Dskip = (lambda *s: torch.randn(*s, dtype=torch.bfloat16) * 0.05)(D)
        return {
            "x": _w((lambda *s: torch.randn(*s, dtype=torch.bfloat16) * 0.05)(B, S, D)),
            "Lambda_re": _w(Lambda_re),
            "Lambda_im": _w(Lambda_im),
            "B_re": _w(B_re),
            "B_im": _w(B_im),
            "C_re": _w(C_re),
            "C_im": _w(C_im),
            "log_dt": _w(log_dt),
            "Dskip": _w(Dskip),
        }
    _A_in = _A_setup()

    def _B_setup():
        B, S, D = 1, 2048, 640
        ks = 4
        return {
            "q": _w((lambda *s: torch.randn(*s, dtype=torch.bfloat16) * 0.05)(B, S, D)),
            "k": _w((lambda *s: torch.randn(*s, dtype=torch.bfloat16) * 0.4)(B, S, D)),
            "v": _w((lambda *s: torch.randn(*s, dtype=torch.bfloat16) * 0.4)(B, S, D)),
            "shift_k": _w((lambda *s: torch.randn(*s, dtype=torch.bfloat16) * 0.4)(D, ks) * 0.5),
            "ssm_k": _w((lambda *s: torch.randn(*s, dtype=torch.bfloat16) * 0.4)(D, S) * (1.0 / S ** 0.5)),
            "ssm_D": _w((lambda *s: torch.randn(*s, dtype=torch.bfloat16) * 0.4)(D)),
        }
    _B_in = _B_setup()

    return {
        "A_x": _A_in["x"],
        "A_Lambda_re": _A_in["Lambda_re"],
        "A_Lambda_im": _A_in["Lambda_im"],
        "A_B_re": _A_in["B_re"],
        "A_B_im": _A_in["B_im"],
        "A_C_re": _A_in["C_re"],
        "A_C_im": _A_in["C_im"],
        "A_log_dt": _A_in["log_dt"],
        "A_Dskip": _A_in["Dskip"],
        "B_q": _B_in["q"],
        "B_k": _B_in["k"],
        "B_v": _B_in["v"],
        "B_shift_k": _B_in["shift_k"],
        "B_ssm_k": _B_in["ssm_k"],
        "B_ssm_D": _B_in["ssm_D"],
    }

def reference(A_x, A_Lambda_re, A_Lambda_im, A_B_re, A_B_im, A_C_re, A_C_im, A_log_dt, A_Dskip, B_q, B_k, B_v, B_shift_k, B_ssm_k, B_ssm_D):
    def _A_ref(x, Lambda_re, Lambda_im, B_re, B_im, C_re, C_im, log_dt, Dskip):
        Bsz, L, H = x.shape
        Lam = Lambda_re + 1j * Lambda_im
        Bmat = B_re + 1j * B_im
        Cmat = C_re + 1j * C_im
        dt = torch.exp(log_dt)
        Lam_bar = torch.exp(dt * Lam)
        B_bar = ((Lam_bar - 1.0) / Lam)[:, None] * Bmat
        Bu = torch.einsum("bld,pd->blp", x + 0j, B_bar)
        h = torch.zeros_like(Bu[:, 0, :])
        hs = []
        for t in range(L):
            h = Lam_bar[None, :] * h + Bu[:, t, :]
            hs.append(h)
        hseq = torch.stack(hs, 1)
        y = 2.0 * torch.einsum("blp,dp->bld", hseq, Cmat).real + x * Dskip[None, None, :]
        return y

    def _B_ref(q, k, v, shift_k, ssm_k, ssm_D):
        B, S, D = q.shape
        ks = shift_k.shape[-1]
        k_pad = _pad(k, ((0, 0), (ks - 1, 0), (0, 0)))
        k_shift = torch.zeros_like(k)
        for t in range(ks):
            k_shift = k_shift + k_pad[:, t:t + S, :] * shift_k[:, ks - 1 - t][None, None, :]
        kv = k_shift * v
        L = 2 * S
        kv_pad = _pad(kv, ((0, 0), (0, S), (0, 0)))
        kf_pad = _pad(ssm_k, ((0, 0), (0, S)))
        kv_f = (lambda x, axes=(-2,-1): torch.fft.rfft2(x.float(), dim=axes))(kv_pad[:, None, :, :], axes=(1, 2))
        kf_f = (lambda x, axes=(-2,-1): torch.fft.rfft2(x.float(), dim=axes))(kf_pad[:, None, :], axes=(1, 2))
        kf_f = (lambda x, *d: x.permute(*d))(kf_f, 1, 2, 0)
        y_f = kv_f * kf_f[None, :, :, :]
        y = (lambda x, s, axes=(-2,-1): torch.fft.irfft2(x, s=s, dim=axes).to(torch.bfloat16))(y_f, (1, L), axes=(1, 2))[:, 0, :S, :]
        y = y + kv * ssm_D[None, None, :]
        return q * y

    x = A_x
    x = x + _A_ref(_layernorm(x, axis=-1), A_Lambda_re, A_Lambda_im, A_B_re, A_B_im, A_C_re, A_C_im, A_log_dt, A_Dskip)
    x = x + _B_ref(_layernorm(x, axis=-1), B_k, B_v, B_shift_k, B_ssm_k, B_ssm_D)
    x = x + _A_ref(_layernorm(x, axis=-1), A_Lambda_re, A_Lambda_im, A_B_re, A_B_im, A_C_re, A_C_im, A_log_dt, A_Dskip)
    x = x + _B_ref(_layernorm(x, axis=-1), B_k, B_v, B_shift_k, B_ssm_k, B_ssm_D)
    return x
```

```cpp
#include <cuda_runtime.h>
#include <cuda.h>
#include <cuda_bf16.h>
#include <stdint.h>

namespace {

constexpr int SEQ = 2048, DM = 640;
constexpr int SPIN = 1 << 20;
#define WPACE 2
#define AUXGO 5
#define TDELAY 2000
#define CPACE 2

struct Scratch {
  __nv_bfloat16 u[SEQ * DM];
  __nv_bfloat16 h[2 * SEQ * 1280];
  __nv_bfloat16 kv[DM * SEQ];
  __nv_bfloat16 gt[DM * SEQ];
  float4 E[2 * 13 * 10 * 32];
  uint32_t M[3 * 16 * 8 * 256];
  uint2 S[2 * SEQ];
  uint32_t RS[10 * 13 * 32];
  unsigned flag[512 * 32];
  unsigned cnt[32 * 32];
  unsigned epoch[132 * 8];
  unsigned zero[128];
  unsigned prof[132 * 256];
};
__device__ __align__(1024) Scratch g_scr;
#define PROF(i) do {} while (0)

constexpr int C_KV = 0, C_G = 1;
constexpr int F_U3 = 0, F_H = 128;

constexpr int R_OFF = 163840, H_OFF = 131072, KS_OFF = 49152, CV_OFF = 86272, G_OFF = 102400, US_OFF = 98304, OS_OFF = US_OFF + 20480;
constexpr int ESM_OFF = 229376, SSM_OFF = ESM_OFF + 1024, BAR_OFF = SSM_OFF + 1280;
constexpr int B_WF = 0, B_WE = 10, B_UF = 20, B_UE = 26, B_RF1 = 29, B_I2 = 30;
constexpr int B_CF = 32, B_HF = 42, B_KF = 48, B_GF = 53, B_CE = 54, B_HE = 64, B_GE = 67, B_CD = 68, B_RF2 = 69, B_XF = 70, B_SG = 71, B_GS = 72, B_ST = 77, B_SH = 78, B_HD = 83, B_RF0 = 84, NBAR = 85, B_PS = 31;
constexpr int SMEM_BYTES = BAR_OFF + NBAR * 8;
constexpr int KV_PAD = 512, KC_OFS = KV_PAD + 4096, CH_BYTES = KC_OFS + 4128, CH_STRIDE = 8960;
__device__ __forceinline__ uint32_t conv_buf(uint32_t sb, int slot) { return sb + CV_OFF + slot * CH_STRIDE; }
constexpr uint64_t WSLOT0 = 0x4321098765ull, WSLOT1 = 0x7698432105ull;
constexpr uint64_t CSLOT0 = 0xba9876543210ull, CSLOT1 = 0xba9765432108ull;

struct Params {
  Scratch* s;
  const __nv_bfloat16 *x, *lre, *lim, *ldt, *bre, *bim, *k, *v, *shk, *cre, *cim, *ssmk, *ssmd, *dskip;
  float* out;
  CUtensorMap mB[2], mA[6], mH[2], mC[2], mGT, sH[2], sU, sO, sK;
};

__device__ __forceinline__ uint32_t smem_u32(const void* p) { return (uint32_t)__cvta_generic_to_shared(p); }
__device__ __forceinline__ uint32_t opaque(uint32_t x) { uint32_t y; asm volatile("mov.u32 %0, %1;" : "=r"(y) : "r"(x)); return y; }
__device__ __forceinline__ void mbar_init(uint32_t bar, uint32_t cnt) { asm volatile("mbarrier.init.shared::cta.b64 [%0], %1;" ::"r"(bar), "r"(cnt) : "memory"); }
__device__ __forceinline__ void mbar_expect_tx(uint32_t bar, uint32_t bytes) { asm volatile("mbarrier.arrive.expect_tx.shared::cta.b64 _, [%0], %1;" ::"r"(bar), "r"(bytes) : "memory"); }
__device__ __forceinline__ void mbar_arrive(uint32_t bar) { asm volatile("mbarrier.arrive.shared::cta.b64 _, [%0];" ::"r"(bar) : "memory"); }
__device__ __forceinline__ void mbar_arrive_cl(uint32_t bar, uint32_t cta) {
  asm volatile("{ .reg .b32 ra; mapa.shared::cluster.u32 ra, %0, %1; mbarrier.arrive.shared::cluster.b64 _, [ra]; }" ::"r"(bar), "r"(cta) : "memory");
}
__device__ __forceinline__ void mbar_wait(uint32_t bar, uint32_t parity = 0) {
  asm volatile("{ .reg .pred p; .reg .u32 c; mov.u32 c, 0;\n"
               "W: mbarrier.try_wait.parity.shared::cta.b64 p, [%0], %1; @p bra D;\n"
               "add.u32 c, c, 1; setp.lt.u32 p, c, 0x100000; @p bra W;\nD: }" ::"r"(bar), "r"(parity) : "memory");
}
__device__ __forceinline__ bool elect_one() { uint32_t p; asm volatile("{ .reg .pred P; elect.sync _|P, 0xffffffff; selp.u32 %0,1,0,P; }" : "=r"(p)); return p; }
__device__ __forceinline__ void bar_sync(int id, int n) { __syncwarp(); asm volatile("bar.sync %0, %1;" ::"r"(id), "r"(n) : "memory"); }
__device__ __forceinline__ void tma2d(uint32_t dst, const CUtensorMap* m, int c0, int c1, uint32_t bar) {
  asm volatile("cp.async.bulk.tensor.2d.shared::cluster.global.mbarrier::complete_tx::bytes [%0], [%1, {%3,%4}], [%2];"
               ::"r"(dst), "l"(m), "r"(bar), "r"(c0), "r"(c1) : "memory");
}
__device__ __forceinline__ void tma5d(uint32_t dst, const CUtensorMap* m, int c0, int c4, uint32_t bar) {
  asm volatile("cp.async.bulk.tensor.5d.shared::cluster.global.mbarrier::complete_tx::bytes [%0], [%1, {%3,%5,%5,%5,%4}], [%2];"
               ::"r"(dst), "l"(m), "r"(bar), "r"(c0), "r"(c4), "r"(0) : "memory");
}
__device__ __forceinline__ void tma2d_mc(uint32_t dst, const CUtensorMap* m, int c0, int c1, uint32_t bar, uint32_t mask) {
  asm volatile("cp.async.bulk.tensor.2d.shared::cluster.global.mbarrier::complete_tx::bytes.multicast::cluster [%0], [%1, {%3,%4}], [%2], %5;"
               ::"r"(dst), "l"(m), "r"(bar), "r"(c0), "r"(c1), "h"((uint16_t)mask) : "memory");
}
__device__ __forceinline__ void tma4d_mc(uint32_t dst, const CUtensorMap* m, int c0, int c1, int c2, int c3, uint32_t bar, uint32_t mask) {
  asm volatile("cp.async.bulk.tensor.4d.shared::cluster.global.mbarrier::complete_tx::bytes.multicast::cluster [%0], [%1, {%3,%4,%5,%6}], [%2], %7;"
               ::"r"(dst), "l"(m), "r"(bar), "r"(c0), "r"(c1), "r"(c2), "r"(c3), "h"((uint16_t)mask) : "memory");
}
__device__ __forceinline__ void bulk_g2s(uint32_t dst, const void* src, uint32_t bytes, uint32_t bar) {
  asm volatile("cp.async.bulk.shared::cluster.global.mbarrier::complete_tx::bytes [%0], [%1], %2, [%3];" ::"r"(dst), "l"(src), "r"(bytes), "r"(bar) : "memory");
}
__device__ __forceinline__ void tma4d_store(const CUtensorMap* m, uint32_t src, int c0, int c1, int c2, int c3) {
  asm volatile("cp.async.bulk.tensor.4d.global.shared::cta.bulk_group [%0, {%2,%3,%4,%5}], [%1];" ::"l"(m), "r"(src), "r"(c0), "r"(c1), "r"(c2), "r"(c3) : "memory");
}
__device__ __forceinline__ void tma2d_store(const CUtensorMap* m, uint32_t src, int c0, int c1) {
  asm volatile("cp.async.bulk.tensor.2d.global.shared::cta.bulk_group [%0, {%2,%3}], [%1];" ::"l"(m), "r"(src), "r"(c0), "r"(c1) : "memory");
}
__device__ __forceinline__ void bulk_s2g(void* dst, uint32_t src, uint32_t bytes) {
  asm volatile("cp.async.bulk.global.shared::cta.bulk_group [%0], [%1], %2;" ::"l"(dst), "r"(src), "r"(bytes) : "memory");
}
__device__ __forceinline__ void bulk_commit() { asm volatile("cp.async.bulk.commit_group;" ::: "memory"); }
__device__ __forceinline__ void bulk_wait() { asm volatile("cp.async.bulk.wait_group 0;" ::: "memory"); }
__device__ __forceinline__ void fence_async() { asm volatile("fence.proxy.async.shared::cta;" ::: "memory"); }
__device__ __forceinline__ void prefetch_l2(const void* src, uint32_t bytes) { asm volatile("cp.async.bulk.prefetch.L2.global [%0], %1;" ::"l"(src), "r"(bytes) : "memory"); }
__device__ __forceinline__ void prefetch_map(const CUtensorMap* m) { asm volatile("prefetch.tensormap [%0];" ::"l"(m) : "memory"); }
__device__ __forceinline__ void wg_fence() { __syncwarp(); asm volatile("wgmma.fence.sync.aligned;" ::: "memory"); }
__device__ __forceinline__ void wg_commit() { asm volatile("wgmma.commit_group.sync.aligned;" ::: "memory"); }
template <int N> __device__ __forceinline__ void wg_wait() { asm volatile("wgmma.wait_group.sync.aligned %0;" ::"n"(N) : "memory"); }
template <int N> __device__ __forceinline__ void fence_regs(float (&d)[N]) {
#pragma unroll
  for (int i = 0; i < N; i++) asm volatile("" : "+f"(d[i])::"memory");
}
__device__ __forceinline__ uint64_t make_desc(uint32_t addr, uint32_t lbo, uint32_t sbo, uint32_t swz) {
  return (uint64_t)((addr & 0x3FFFF) >> 4) | ((uint64_t)(lbo >> 4) << 16) | ((uint64_t)(sbo >> 4) << 32) | ((uint64_t)swz << 62);
}
__device__ __forceinline__ uint32_t lds32(uint32_t a) { uint32_t v; asm volatile("ld.shared.u32 %0,[%1];" : "=r"(v) : "r"(a)); return v; }
__device__ __forceinline__ unsigned ld_rlx(const unsigned* p) { unsigned v; asm volatile("ld.relaxed.gpu.global.u32 %0,[%1];" : "=r"(v) : "l"(p) : "memory"); return v; }
__device__ __forceinline__ uint4 ld_rlx4(const void* p) {
  uint4 v; asm volatile("ld.relaxed.gpu.global.v4.u32 {%0,%1,%2,%3},[%4];" : "=r"(v.x), "=r"(v.y), "=r"(v.z), "=r"(v.w) : "l"(p) : "memory"); return v;
}
__device__ __forceinline__ void st_rlx4(void* p, uint32_t a, uint32_t b, uint32_t c, uint32_t d) {
  asm volatile("st.relaxed.gpu.global.v4.u32 [%0],{%1,%2,%3,%4};" ::"l"(p), "r"(a), "r"(b), "r"(c), "r"(d) : "memory");
}
__device__ __forceinline__ void st_rlx(void* p, uint32_t a) { asm volatile("st.relaxed.gpu.global.u32 [%0],%1;" ::"l"(p), "r"(a) : "memory"); }
__device__ __forceinline__ void signal_flag(unsigned* p, unsigned val) {
  asm volatile("st.relaxed.gpu.global.u32 [%0],%1;" ::"l"(p), "r"(val) : "memory");
}
__device__ __forceinline__ void signal_cnt(unsigned* p, unsigned n) {
  asm volatile("red.relaxed.gpu.global.add.u32 [%0],%1;" ::"l"(p), "r"(n) : "memory");
}
__device__ __forceinline__ void wait_flags(const unsigned* p, unsigned val, uint32_t need, uint32_t& ready) {
#pragma unroll 1
  for (int it = 0; (ready & need) != need && it < SPIN; it++) ready = __ballot_sync(0xffffffff, ld_rlx(p) == val);
}
__device__ __forceinline__ void wait_cnt(const unsigned* p, unsigned tgt) {
  asm volatile("{ .reg .pred p; .reg .u32 c; .reg .s32 v; mov.u32 c, 0;\n"
               "W: ld.relaxed.gpu.global.u32 v, [%0]; sub.s32 v, v, %1; setp.ge.s32 p, v, 0; @p bra D;\n"
               "add.u32 c, c, 1; setp.lt.u32 p, c, 0x100000; @p bra W;\nD: }" ::"l"(p), "r"(tgt) : "memory");
}
__device__ __forceinline__ uint32_t pack_bf(float lo, float hi) { uint32_t r; asm("cvt.rn.bf16x2.f32 %0, %1, %2;" : "=r"(r) : "f"(hi), "f"(lo)); return r; }
__device__ __forceinline__ float bf_lo(uint32_t v) { return __uint_as_float(v << 16); }
__device__ __forceinline__ float bf_hi(uint32_t v) { return __uint_as_float(v & 0xffff0000u); }
__device__ __forceinline__ float bf_rn(float x) { return __bfloat162float(__float2bfloat16_rn(x)); }
__device__ __forceinline__ float frcp(float x) { float r; asm("rcp.approx.ftz.f32 %0,%1;" : "=f"(r) : "f"(x)); return r; }
__device__ __forceinline__ float fsqrt(float x) { float r; asm("sqrt.approx.ftz.f32 %0,%1;" : "=f"(r) : "f"(x)); return r; }
__device__ __forceinline__ float frsqrt(float x) { float r; asm("rsqrt.approx.ftz.f32 %0,%1;" : "=f"(r) : "f"(x)); return r; }
__device__ __forceinline__ uint32_t hmul2(uint32_t a, uint32_t b) { uint32_t r; asm("mul.rn.bf16x2 %0,%1,%2;" : "=r"(r) : "r"(a), "r"(b)); return r; }
__device__ __forceinline__ uint32_t hadd2(uint32_t a, uint32_t b) { uint32_t r; asm("add.rn.bf16x2 %0,%1,%2;" : "=r"(r) : "r"(a), "r"(b)); return r; }
__device__ __forceinline__ float2 cmul(float2 a, float2 b) { return make_float2(a.x * b.x - a.y * b.y, a.x * b.y + a.y * b.x); }
__device__ __forceinline__ float2 cfma(float2 a, float2 b, float2 c) {
  return make_float2(fmaf(a.x, b.x, fmaf(-a.y, b.y, c.x)), fmaf(a.x, b.y, fmaf(a.y, b.x, c.y)));
}
__device__ __forceinline__ uint32_t tagf(float v, uint32_t tag) { return (__float_as_uint(v) & ~1u) | tag; }
__device__ __forceinline__ float untag(uint32_t v) { return __uint_as_float(v & ~1u); }
__device__ __forceinline__ bool untagged(const uint4& v, uint32_t tag) { return (((v.x ^ tag) | (v.y ^ tag) | (v.z ^ tag) | (v.w ^ tag)) & 1) != 0; }
__device__ __forceinline__ float2 lam_bar(float lr, float li, float ldt) {
  float dt = bf_rn(expf(ldt)); float e = expf(dt * lr), s, c; sincospif(dt * li * 0.31830988618379067f, &s, &c); return make_float2(e * c, e * s);
}

struct Role {
  uint32_t v, c;
  __device__ __forceinline__ int tb() const { return v & 15; }
  __device__ __forceinline__ int cb() const { return (v >> 4) & 15; }
  __device__ __forceinline__ int b() const { return (v >> 8) & 255; }
  __device__ __forceinline__ int ubase() const { return (v >> 16) & 7; }
  __device__ __forceinline__ int ugs() const { return (v >> 19) & 7; }
  __device__ __forceinline__ int wpart() const { return (int)((v >> 22) & 15) - 1; }
  __device__ __forceinline__ int rank() const { return (v >> 26) & 7; }
  __device__ __forceinline__ int cs() const { return (v >> 29) ? 8 : 2; }
  __device__ __forceinline__ int ch0() const { return c & 1023; }
  __device__ __forceinline__ int nch() const { return (c >> 10) & 7; }
  __device__ __forceinline__ int nprep() const { return (c >> 13) & 255; }
};

__device__ __forceinline__ void wgmma_ss80(float (&d)[40], uint64_t da, uint64_t db, int sd){
  asm volatile("{ .reg .pred p; setp.ne.b32 p, %42, 0;\n"
   "wgmma.mma_async.sync.aligned.m64n80k16.f32.bf16.bf16 {%0, %1, %2, %3, %4, %5, %6, %7, %8, %9, %10, %11, %12, %13, %14, %15, %16, %17, %18, %19, %20, %21, %22, %23, %24, %25, %26, %27, %28, %29, %30, %31, %32, %33, %34, %35, %36, %37, %38, %39}, %40, %41, p, 1, 1, 0, 0; }\n"
   : "+f"(d[0]), "+f"(d[1]), "+f"(d[2]), "+f"(d[3]), "+f"(d[4]), "+f"(d[5]), "+f"(d[6]), "+f"(d[7]), "+f"(d[8]), "+f"(d[9]), "+f"(d[10]), "+f"(d[11]), "+f"(d[12]), "+f"(d[13]), "+f"(d[14]), "+f"(d[15]), "+f"(d[16]), "+f"(d[17]), "+f"(d[18]), "+f"(d[19]), "+f"(d[20]), "+f"(d[21]), "+f"(d[22]), "+f"(d[23]), "+f"(d[24]), "+f"(d[25]), "+f"(d[26]), "+f"(d[27]), "+f"(d[28]), "+f"(d[29]), "+f"(d[30]), "+f"(d[31]), "+f"(d[32]), "+f"(d[33]), "+f"(d[34]), "+f"(d[35]), "+f"(d[36]), "+f"(d[37]), "+f"(d[38]), "+f"(d[39]) : "l"(da), "l"(db), "r"(sd));
}
template<int N> __device__ __forceinline__ void wgmma_rs(float (&d)[N/2], uint32_t a0, uint32_t a1, uint32_t a2, uint32_t a3, uint64_t db, int sd);
template<> __device__ __forceinline__ void wgmma_rs<16>(float (&d)[8], uint32_t a0, uint32_t a1, uint32_t a2, uint32_t a3, uint64_t db, int sd){
  asm volatile("{ .reg .pred p; setp.ne.b32 p, %13, 0;\n"
   "wgmma.mma_async.sync.aligned.m64n16k16.f32.bf16.bf16 {%0, %1, %2, %3, %4, %5, %6, %7}, {%8,%9,%10,%11}, %12, p, 1, 1, 0; }\n"
   : "+f"(d[0]), "+f"(d[1]), "+f"(d[2]), "+f"(d[3]), "+f"(d[4]), "+f"(d[5]), "+f"(d[6]), "+f"(d[7]) : "r"(a0), "r"(a1), "r"(a2), "r"(a3), "l"(db), "r"(sd));
}
template<> __device__ __forceinline__ void wgmma_rs<32>(float (&d)[16], uint32_t a0, uint32_t a1, uint32_t a2, uint32_t a3, uint64_t db, int sd){
  asm volatile("{ .reg .pred p; setp.ne.b32 p, %21, 0;\n"
   "wgmma.mma_async.sync.aligned.m64n32k16.f32.bf16.bf16 {%0, %1, %2, %3, %4, %5, %6, %7, %8, %9, %10, %11, %12, %13, %14, %15}, {%16,%17,%18,%19}, %20, p, 1, 1, 0; }\n"
   : "+f"(d[0]), "+f"(d[1]), "+f"(d[2]), "+f"(d[3]), "+f"(d[4]), "+f"(d[5]), "+f"(d[6]), "+f"(d[7]), "+f"(d[8]), "+f"(d[9]), "+f"(d[10]), "+f"(d[11]), "+f"(d[12]), "+f"(d[13]), "+f"(d[14]), "+f"(d[15]) : "r"(a0), "r"(a1), "r"(a2), "r"(a3), "l"(db), "r"(sd));
}
template<> __device__ __forceinline__ void wgmma_rs<48>(float (&d)[24], uint32_t a0, uint32_t a1, uint32_t a2, uint32_t a3, uint64_t db, int sd){
  asm volatile("{ .reg .pred p; setp.ne.b32 p, %29, 0;\n"
   "wgmma.mma_async.sync.aligned.m64n48k16.f32.bf16.bf16 {%0, %1, %2, %3, %4, %5, %6, %7, %8, %9, %10, %11, %12, %13, %14, %15, %16, %17, %18, %19, %20, %21, %22, %23}, {%24,%25,%26,%27}, %28, p, 1, 1, 0; }\n"
   : "+f"(d[0]), "+f"(d[1]), "+f"(d[2]), "+f"(d[3]), "+f"(d[4]), "+f"(d[5]), "+f"(d[6]), "+f"(d[7]), "+f"(d[8]), "+f"(d[9]), "+f"(d[10]), "+f"(d[11]), "+f"(d[12]), "+f"(d[13]), "+f"(d[14]), "+f"(d[15]), "+f"(d[16]), "+f"(d[17]), "+f"(d[18]), "+f"(d[19]), "+f"(d[20]), "+f"(d[21]), "+f"(d[22]), "+f"(d[23]) : "r"(a0), "r"(a1), "r"(a2), "r"(a3), "l"(db), "r"(sd));
}
template<> __device__ __forceinline__ void wgmma_rs<64>(float (&d)[32], uint32_t a0, uint32_t a1, uint32_t a2, uint32_t a3, uint64_t db, int sd){
  asm volatile("{ .reg .pred p; setp.ne.b32 p, %37, 0;\n"
   "wgmma.mma_async.sync.aligned.m64n64k16.f32.bf16.bf16 {%0, %1, %2, %3, %4, %5, %6, %7, %8, %9, %10, %11, %12, %13, %14, %15, %16, %17, %18, %19, %20, %21, %22, %23, %24, %25, %26, %27, %28, %29, %30, %31}, {%32,%33,%34,%35}, %36, p, 1, 1, 0; }\n"
   : "+f"(d[0]), "+f"(d[1]), "+f"(d[2]), "+f"(d[3]), "+f"(d[4]), "+f"(d[5]), "+f"(d[6]), "+f"(d[7]), "+f"(d[8]), "+f"(d[9]), "+f"(d[10]), "+f"(d[11]), "+f"(d[12]), "+f"(d[13]), "+f"(d[14]), "+f"(d[15]), "+f"(d[16]), "+f"(d[17]), "+f"(d[18]), "+f"(d[19]), "+f"(d[20]), "+f"(d[21]), "+f"(d[22]), "+f"(d[23]), "+f"(d[24]), "+f"(d[25]), "+f"(d[26]), "+f"(d[27]), "+f"(d[28]), "+f"(d[29]), "+f"(d[30]), "+f"(d[31]) : "r"(a0), "r"(a1), "r"(a2), "r"(a3), "l"(db), "r"(sd));
}
template<> __device__ __forceinline__ void wgmma_rs<80>(float (&d)[40], uint32_t a0, uint32_t a1, uint32_t a2, uint32_t a3, uint64_t db, int sd){
  asm volatile("{ .reg .pred p; setp.ne.b32 p, %45, 0;\n"
   "wgmma.mma_async.sync.aligned.m64n80k16.f32.bf16.bf16 {%0, %1, %2, %3, %4, %5, %6, %7, %8, %9, %10, %11, %12, %13, %14, %15, %16, %17, %18, %19, %20, %21, %22, %23, %24, %25, %26, %27, %28, %29, %30, %31, %32, %33, %34, %35, %36, %37, %38, %39}, {%40,%41,%42,%43}, %44, p, 1, 1, 0; }\n"
   : "+f"(d[0]), "+f"(d[1]), "+f"(d[2]), "+f"(d[3]), "+f"(d[4]), "+f"(d[5]), "+f"(d[6]), "+f"(d[7]), "+f"(d[8]), "+f"(d[9]), "+f"(d[10]), "+f"(d[11]), "+f"(d[12]), "+f"(d[13]), "+f"(d[14]), "+f"(d[15]), "+f"(d[16]), "+f"(d[17]), "+f"(d[18]), "+f"(d[19]), "+f"(d[20]), "+f"(d[21]), "+f"(d[22]), "+f"(d[23]), "+f"(d[24]), "+f"(d[25]), "+f"(d[26]), "+f"(d[27]), "+f"(d[28]), "+f"(d[29]), "+f"(d[30]), "+f"(d[31]), "+f"(d[32]), "+f"(d[33]), "+f"(d[34]), "+f"(d[35]), "+f"(d[36]), "+f"(d[37]), "+f"(d[38]), "+f"(d[39]) : "r"(a0), "r"(a1), "r"(a2), "r"(a3), "l"(db), "r"(sd));
}
template<> __device__ __forceinline__ void wgmma_rs<96>(float (&d)[48], uint32_t a0, uint32_t a1, uint32_t a2, uint32_t a3, uint64_t db, int sd){
  asm volatile("{ .reg .pred p; setp.ne.b32 p, %53, 0;\n"
   "wgmma.mma_async.sync.aligned.m64n96k16.f32.bf16.bf16 {%0, %1, %2, %3, %4, %5, %6, %7, %8, %9, %10, %11, %12, %13, %14, %15, %16, %17, %18, %19, %20, %21, %22, %23, %24, %25, %26, %27, %28, %29, %30, %31, %32, %33, %34, %35, %36, %37, %38, %39, %40, %41, %42, %43, %44, %45, %46, %47}, {%48,%49,%50,%51}, %52, p, 1, 1, 0; }\n"
   : "+f"(d[0]), "+f"(d[1]), "+f"(d[2]), "+f"(d[3]), "+f"(d[4]), "+f"(d[5]), "+f"(d[6]), "+f"(d[7]), "+f"(d[8]), "+f"(d[9]), "+f"(d[10]), "+f"(d[11]), "+f"(d[12]), "+f"(d[13]), "+f"(d[14]), "+f"(d[15]), "+f"(d[16]), "+f"(d[17]), "+f"(d[18]), "+f"(d[19]), "+f"(d[20]), "+f"(d[21]), "+f"(d[22]), "+f"(d[23]), "+f"(d[24]), "+f"(d[25]), "+f"(d[26]), "+f"(d[27]), "+f"(d[28]), "+f"(d[29]), "+f"(d[30]), "+f"(d[31]), "+f"(d[32]), "+f"(d[33]), "+f"(d[34]), "+f"(d[35]), "+f"(d[36]), "+f"(d[37]), "+f"(d[38]), "+f"(d[39]), "+f"(d[40]), "+f"(d[41]), "+f"(d[42]), "+f"(d[43]), "+f"(d[44]), "+f"(d[45]), "+f"(d[46]), "+f"(d[47]) : "r"(a0), "r"(a1), "r"(a2), "r"(a3), "l"(db), "r"(sd));
}
template<> __device__ __forceinline__ void wgmma_rs<112>(float (&d)[56], uint32_t a0, uint32_t a1, uint32_t a2, uint32_t a3, uint64_t db, int sd){
  asm volatile("{ .reg .pred p; setp.ne.b32 p, %61, 0;\n"
   "wgmma.mma_async.sync.aligned.m64n112k16.f32.bf16.bf16 {%0, %1, %2, %3, %4, %5, %6, %7, %8, %9, %10, %11, %12, %13, %14, %15, %16, %17, %18, %19, %20, %21, %22, %23, %24, %25, %26, %27, %28, %29, %30, %31, %32, %33, %34, %35, %36, %37, %38, %39, %40, %41, %42, %43, %44, %45, %46, %47, %48, %49, %50, %51, %52, %53, %54, %55}, {%56,%57,%58,%59}, %60, p, 1, 1, 0; }\n"
   : "+f"(d[0]), "+f"(d[1]), "+f"(d[2]), "+f"(d[3]), "+f"(d[4]), "+f"(d[5]), "+f"(d[6]), "+f"(d[7]), "+f"(d[8]), "+f"(d[9]), "+f"(d[10]), "+f"(d[11]), "+f"(d[12]), "+f"(d[13]), "+f"(d[14]), "+f"(d[15]), "+f"(d[16]), "+f"(d[17]), "+f"(d[18]), "+f"(d[19]), "+f"(d[20]), "+f"(d[21]), "+f"(d[22]), "+f"(d[23]), "+f"(d[24]), "+f"(d[25]), "+f"(d[26]), "+f"(d[27]), "+f"(d[28]), "+f"(d[29]), "+f"(d[30]), "+f"(d[31]), "+f"(d[32]), "+f"(d[33]), "+f"(d[34]), "+f"(d[35]), "+f"(d[36]), "+f"(d[37]), "+f"(d[38]), "+f"(d[39]), "+f"(d[40]), "+f"(d[41]), "+f"(d[42]), "+f"(d[43]), "+f"(d[44]), "+f"(d[45]), "+f"(d[46]), "+f"(d[47]), "+f"(d[48]), "+f"(d[49]), "+f"(d[50]), "+f"(d[51]), "+f"(d[52]), "+f"(d[53]), "+f"(d[54]), "+f"(d[55]) : "r"(a0), "r"(a1), "r"(a2), "r"(a3), "l"(db), "r"(sd));
}
template<> __device__ __forceinline__ void wgmma_rs<128>(float (&d)[64], uint32_t a0, uint32_t a1, uint32_t a2, uint32_t a3, uint64_t db, int sd){
  asm volatile("{ .reg .pred p; setp.ne.b32 p, %69, 0;\n"
   "wgmma.mma_async.sync.aligned.m64n128k16.f32.bf16.bf16 {%0, %1, %2, %3, %4, %5, %6, %7, %8, %9, %10, %11, %12, %13, %14, %15, %16, %17, %18, %19, %20, %21, %22, %23, %24, %25, %26, %27, %28, %29, %30, %31, %32, %33, %34, %35, %36, %37, %38, %39, %40, %41, %42, %43, %44, %45, %46, %47, %48, %49, %50, %51, %52, %53, %54, %55, %56, %57, %58, %59, %60, %61, %62, %63}, {%64,%65,%66,%67}, %68, p, 1, 1, 0; }\n"
   : "+f"(d[0]), "+f"(d[1]), "+f"(d[2]), "+f"(d[3]), "+f"(d[4]), "+f"(d[5]), "+f"(d[6]), "+f"(d[7]), "+f"(d[8]), "+f"(d[9]), "+f"(d[10]), "+f"(d[11]), "+f"(d[12]), "+f"(d[13]), "+f"(d[14]), "+f"(d[15]), "+f"(d[16]), "+f"(d[17]), "+f"(d[18]), "+f"(d[19]), "+f"(d[20]), "+f"(d[21]), "+f"(d[22]), "+f"(d[23]), "+f"(d[24]), "+f"(d[25]), "+f"(d[26]), "+f"(d[27]), "+f"(d[28]), "+f"(d[29]), "+f"(d[30]), "+f"(d[31]), "+f"(d[32]), "+f"(d[33]), "+f"(d[34]), "+f"(d[35]), "+f"(d[36]), "+f"(d[37]), "+f"(d[38]), "+f"(d[39]), "+f"(d[40]), "+f"(d[41]), "+f"(d[42]), "+f"(d[43]), "+f"(d[44]), "+f"(d[45]), "+f"(d[46]), "+f"(d[47]), "+f"(d[48]), "+f"(d[49]), "+f"(d[50]), "+f"(d[51]), "+f"(d[52]), "+f"(d[53]), "+f"(d[54]), "+f"(d[55]), "+f"(d[56]), "+f"(d[57]), "+f"(d[58]), "+f"(d[59]), "+f"(d[60]), "+f"(d[61]), "+f"(d[62]), "+f"(d[63]) : "r"(a0), "r"(a1), "r"(a2), "r"(a3), "l"(db), "r"(sd));
}

#define BOFS 0
#define BAR(i) (bars + 8u * (uint32_t)(i))

template <int G> __device__ __forceinline__ void conv_frags(uint32_t (&a)[12], uint32_t abase) {
#pragma unroll
  for (int i = 0; i < 12; i++) a[i] = lds32(abase + (G * 4 + i / 3) * 128 + (i % 3) * 4);
}
template <int N> __device__ __forceinline__ void conv_grp(float (&e)[N / 2], uint32_t (&a)[12], uint64_t bd) {
  uint32_t p[8];
#pragma unroll
  for (int i = 0; i < 4; i++) { p[2 * i] = __byte_perm(a[3 * i], a[3 * i + 1], 0x5432); p[2 * i + 1] = __byte_perm(a[3 * i + 1], a[3 * i + 2], 0x5432); }
  wg_fence();
#pragma unroll
  for (int i = 0; i < 4; i++) wgmma_rs<N>(e, p[2 * i], a[3 * i + 1], p[2 * i + 1], a[3 * i + 2], bd - 8 * i + ((uint64_t)(BOFS & i & 1) << 49), 1);
  wg_commit();
}
template <int M> __device__ __forceinline__ void conv_mv(float (&d)[64], float (&s)[M], float (&t)[M - 8]) {
#pragma unroll
  for (int i = 0; i < 8; i++) d[64 - M + i] = s[i];
#pragma unroll
  for (int i = 8; i < M; i++) asm volatile("mov.b32 %0,%1;" : "=f"(t[i - 8]) : "f"(s[i]));
}
__device__ __forceinline__ void input_stats(const Params& P, uint32_t sb, Role R, int tid, uint32_t tag, long long t_start) {
  const int w = tid >> 5, lane = tid & 31, tb = R.tb(), cb = R.cb(), b = R.b();
  uint2 xv[7][5];
#pragma unroll
  for (int h = 0; h < 7; h++) {
    const int ri = w + 4 * (h - 4), rr = 11 * tb + ri;
    const bool on = h < 4 ? b < 128 : (ri < 11 && rr < 128);
    const __nv_bfloat16* p = h < 4 ? P.x + (size_t)(16 * b + 4 * w + h) * DM : (rr < 64 ? P.bre : P.bim) + (size_t)(64 * cb + (rr & 63)) * DM;
#pragma unroll
    for (int i = 0; i < 5; i++) xv[h][i] = on ? __ldg((const uint2*)(p + 128 * i + 4 * lane)) : make_uint2(0u, 0u);
  }
  float v[8], v2[4];
#pragma unroll
  for (int h = 0; h < 7; h++) {
    float s = 0.f, s2 = 0.f;
#pragma unroll
    for (int i = 0; i < 5; i++) {
      const float a = bf_lo(xv[h][i].x), c = bf_hi(xv[h][i].x), d = bf_lo(xv[h][i].y), e = bf_hi(xv[h][i].y);
      s += (a + c) + (d + e);
      if (h < 4) s2 = fmaf(a, a, fmaf(c, c, fmaf(d, d, fmaf(e, e, s2))));
    }
    v[h] = s; if (h < 4) v2[h] = s2;
  }
  v[7] = 0.f;
#pragma unroll
  for (int o = 4; o; o >>= 1) {
    const bool up = lane & (o << 2);
#pragma unroll
    for (int i = 0; i < o; i++) {
      v[i] = (up ? v[i + o] : v[i]) + __shfl_xor_sync(0xffffffff, up ? v[i] : v[i + o], o << 2);
      if (o < 4) v2[i] = (up ? v2[i + o] : v2[i]) + __shfl_xor_sync(0xffffffff, up ? v2[i] : v2[i + o], o << 2);
      else v2[i] += __shfl_xor_sync(0xffffffff, v2[i], 16);
    }
  }
#pragma unroll
  for (int o = 1; o <= 2; o <<= 1) { v[0] += __shfl_xor_sync(0xffffffff, v[0], o); v2[0] += __shfl_xor_sync(0xffffffff, v2[0], o); }
  if ((lane & 3) == 0) {
    const int h = lane >> 2;
    if (h < 4) {
      const float m = v[0] * (1.f / DM), r = frcp(bf_rn(fsqrt(bf_rn(bf_rn(fmaxf(v2[0] * (1.f / DM) - m * m, 0.f)) + 1e-5f))));
      asm volatile("st.shared.v2.u32 [%0],{%1,%2};" ::"r"(sb + ESM_OFF + 512 + 8 * (4 * w + h)), "r"(tagf(r, tag)), "r"(tagf(-bf_rn(m) * r, tag)) : "memory");
    } else asm volatile("st.shared.u32 [%0],%1;" ::"r"(sb + ESM_OFF + 640 + 4 * (w + 4 * (h - 4))), "r"(tagf(v[0], tag)) : "memory");
  }
  bar_sync(3, 128);
  if (tid < 12) {
    uint4 o;
    asm volatile("ld.shared.v4.u32 {%0,%1,%2,%3},[%4];" : "=r"(o.x), "=r"(o.y), "=r"(o.z), "=r"(o.w) : "r"(sb + ESM_OFF + 512 + 16 * tid));
    if (tid >= 8) st_rlx4(P.s->RS + (cb * 13 + tb) * 32 + 4 * (tid - 8), o.x, o.y, o.z, o.w);
    else if (b < 128) st_rlx4(P.s->S + 16 * b + 2 * tid, o.x, o.y, o.z, o.w);
  }
  if (tid == 0) PROF(3);
}
template <bool AUX>
__device__ __forceinline__ void conv_loop(const Params& P, uint32_t sb, uint32_t rc, int wg, int tid, long long t_start) {
  sb = opaque(sb); rc = opaque(rc);
  const uint32_t bars = sb + BAR_OFF;
  int slot = AUX ? 0 : wg + 1;
  uint32_t Dn = __ldg((const unsigned short*)P.ssmd + min((rc & 1023) + slot, DM - 1));
#pragma unroll 1
  while (slot < (int)((rc >> 10) & 7)) {
    tid = opaque(tid);
    const int w = tid >> 5, lane = tid & 31, g = lane >> 2, q = lane & 3;
    const uint32_t Dv = Dn;
    if (AUX) Dn = __ldg((const unsigned short*)P.ssmd + min((rc & 1023) + max(slot + 1, 3), DM - 1));
    const uint32_t cb_ = conv_buf(sb, slot), c0 = cb_ + KC_OFS;
    const uint32_t abase = c0 + 2 * (2 * (g & 1) + 4 * w + 16 * (g >> 1) + 4 * q);
    const uint64_t bd = make_desc(cb_ + KV_PAD, 16, 256, 3);
    if (tid == 0) PROF(200 + 4 * slot);
    mbar_wait(BAR(B_KF + slot));
    if (tid == 0) PROF(201 + 4 * slot);
    uint32_t a0[12], a1[12];
    float d[64];
    float e0[64]; conv_frags<0>(a0, abase);
    {
      const uint32_t d0 = (g == 1 && q == 3 - w) ? Dv : 0, d1 = (g == 0 && q == 3 - w) ? Dv : 0;
      wg_fence();
      wgmma_rs<128>(e0, d0 << 16, d0, d1 << 16, d1, bd, 0);
    }
    conv_grp<128>(e0, a0, bd); conv_frags<1>(a1, abase);
    wg_wait<0>(); fence_regs(e0);
    float e1[56]; conv_mv<64>(d, e0, e1); conv_grp<112>(e1, a1, bd); conv_frags<2>(a0, abase); wg_wait<0>(); fence_regs(e1);
    float e2[48]; conv_mv<56>(d, e1, e2); conv_grp<96>(e2, a0, bd); conv_frags<3>(a1, abase); wg_wait<0>(); fence_regs(e2);
    float e3[40]; conv_mv<48>(d, e2, e3); conv_grp<80>(e3, a1, bd); conv_frags<4>(a0, abase); wg_wait<0>(); fence_regs(e3);
    float e4[32]; conv_mv<40>(d, e3, e4); conv_grp<64>(e4, a0, bd); conv_frags<5>(a1, abase); wg_wait<0>(); fence_regs(e4);
    float e5[24]; conv_mv<32>(d, e4, e5); conv_grp<48>(e5, a1, bd); conv_frags<6>(a0, abase); wg_wait<0>(); fence_regs(e5);
    float e6[16]; conv_mv<24>(d, e5, e6); conv_grp<32>(e6, a0, bd); conv_frags<7>(a1, abase); wg_wait<0>(); fence_regs(e6);
    float e7[8]; conv_mv<16>(d, e6, e7); conv_grp<16>(e7, a1, bd); wg_wait<0>(); fence_regs(e7);
#pragma unroll
    for (int i = 0; i < 8; i++) d[56 + i] = e7[i];
    if (tid == 0) PROF(202 + 4 * slot);
    bar_sync(wg + 1, 128);
    const int t2 = opaque(tid), ln = t2 & 31, q2 = ln & 3;
    const bool hi = ln & 16, s1 = ln & 8;
    const int qo = hi ? (q2 + 1) & 3 : q2;
    const int srcA = hi ? (ln & 12) | ((q2 + 1) & 3) : (ln & 12) | 16 | ((q2 + 3) & 3);
    const bool h3 = hi && q2 == 3, wrap = s1 && qo == 3, back = wrap && hi;
    const bool chi = wrap ? !hi : hi;
    const int cq = s1 ? (qo + 1) & 3 : qo;
    const int srcB = (ln & 4) | (s1 ? 0 : 8) | (chi ? 16 | ((cq + 3) & 3) : cq);
    const uint32_t gp = conv_buf(sb, slot) + KC_OFS + 16 * (2 * ((ln >> 2) & 1) + 4 * (t2 >> 5)) + (chi ? 256 : 0) + 2 * (2 * cq + (s1 ? 0 : 1));
    float pv[2] = {0.f, 0.f};
#pragma unroll
    for (int jj = 0; jj < 8; jj++) {
      float y[2];
#pragma unroll
      for (int h = 0; h < 2; h++) {
        float S[2];
#pragma unroll
        for (int e = 0; e < 2; e++) {
          const float ev = d[8 * jj + 2 * h + e], od = d[8 * jj + 4 + 2 * h + e], pr = jj ? d[8 * jj - 4 + 2 * h + e] : 0.f;
          S[e] = (hi ? (h3 ? ev : od) : ev) + __shfl_sync(0xffffffff, hi ? (h3 ? pr : ev) : od, srcA);
        }
        y[h] = (back ? pv[h] : S[1]) + __shfl_sync(0xffffffff, S[0], srcB);
        pv[h] = S[1];
      }
      const uint32_t o = pack_bf(y[0], y[1]);
      asm volatile("st.shared.u16 [%0],%1; st.shared.u16 [%0+16],%2;" ::"r"(gp + jj * 512), "h"((uint16_t)o), "h"((uint16_t)(o >> 16)) : "memory");
    }
    if (tid == 0) PROF(203 + 4 * slot);
    fence_async();
    __syncwarp();
    if (ln == 0) mbar_arrive(BAR(B_GS + slot));
    if (!AUX) break;
    slot = max(slot + 1, 3);
  }
}

__device__ __forceinline__ void g1_phase(const int LY, const Params& P, uint32_t sb, int wg, int tid, Role R, float2& lamA, float2& lamB, float4& cf, float4& rs, uint32_t e1,
                                         long long t_start) {
  const uint32_t tag = e1 & 1;
  Scratch* const S = P.s;
  tid = opaque(tid); sb = opaque(sb); R.v = opaque(R.v);
  const uint32_t bars = sb + BAR_OFF;
  const int cb = R.cb(), tb = R.tb();
  const int w = tid >> 5, lane = tid & 31, g = lane >> 2, q = lane & 3;
  const bool full = tb < 12;
  const uint32_t ubytes = full ? 10240 : 8192;
  float4* Eb = S->E + ((LY * 13) * 10 + cb) * 32 + w * 8 + g;
  if (wg == 1 && q == 3) st_rlx4(Eb + tb * 320, tag ^ 1, tag ^ 1, tag ^ 1, tag ^ 1);
  if (LY == 0) {
    asm volatile("ld.shared.v4.f32 {%0,%1,%2,%3},[%4];" : "=f"(lamA.x), "=f"(lamA.y), "=f"(cf.x), "=f"(cf.y) : "r"(sb + SSM_OFF + 16 * (16 * w + g)));
    asm volatile("ld.shared.v4.f32 {%0,%1,%2,%3},[%4];" : "=f"(lamB.x), "=f"(lamB.y), "=f"(cf.z), "=f"(cf.w) : "r"(sb + SSM_OFF + 16 * (16 * w + g + 8)));
  }
  float ar[40], ai[40];
#pragma unroll
  for (int i = 0; i < 40; i++) { ar[i] = 0.f; ai[i] = 0.f; }
  {
    uint64_t slots = LY ? WSLOT1 : WSLOT0;
    uint32_t st = 0, sp = 0, ph = LY ? 6 : 0;
    uint32_t bw = BAR(B_WF);
    const int nrel = R.ugs() >> 1, urank = R.ubase() + wg * nrel + (w & 1);
    mbar_wait(bw, LY); mbar_wait(BAR(B_UF + wg), 0);
    if (tid == 0 && wg == 0) PROF(LY ? 20 : 4);
#pragma unroll 1
    for (int kb = 0; kb < 10; kb++) {
      const uint64_t da = make_desc(sb + ((uint32_t)slots & 15) * 16384, 16, 1024, 1);
      const uint64_t db = make_desc(sb + R_OFF + st * 20480 + wg * 10240, 16, 1024, 1);
      wg_fence();
#pragma unroll
      for (int kk = 0; kk < 4; kk++) {
        wgmma_ss80(ar, da + 2 * kk, db + 2 * kk, 1);
        wgmma_ss80(ai, da + 512 + 2 * kk, db + 2 * kk, 1);
      }
      wg_commit();
      wg_wait<1>();
      if (kb > 0) {
        if (tid == 64) mbar_expect_tx(BAR(B_UF + 2 * sp + wg), ubytes);
        if (tid == 96) mbar_arrive(bw + 8 * (B_WE - B_WF - 1));
        if (kb < 8 && lane == 0 && w < nrel) mbar_arrive_cl(BAR(B_UE + sp), urank);
      }
      bw += 8; ph ^= 1u << st; sp = st;
      slots >>= 4; st = st == 2 ? 0 : st + 1;
      if (kb < 9) { mbar_wait(bw, LY); mbar_wait(BAR(B_UF + 2 * st + wg), (ph >> st) & 1); }
    }
  }
  if (tid == 0 && wg == 0) PROF(LY ? 19 : 2);
  float2 muA, muB, mu2A, mu2B, omA, omB;
  asm volatile("" : "+f"(lamA.x), "+f"(lamA.y), "+f"(lamB.x), "+f"(lamB.y));
  {
    float2 a2 = cmul(lamA, lamA), a4 = cmul(a2, a2), a8 = cmul(a4, a4), a16 = cmul(a8, a8), a20 = cmul(a16, a4);
    float2 b2 = cmul(lamB, lamB), b4 = cmul(b2, b2), b8 = cmul(b4, b4), b16 = cmul(b8, b8), b20 = cmul(b16, b4);
    muA = full ? a20 : a16; muB = full ? b20 : b16; mu2A = cmul(muA, muA); mu2B = cmul(muB, muB);
    omA = cmul(a20, a20); omA = cmul(omA, omA); omA = cmul(omA, omA); omB = cmul(b20, b20); omB = cmul(omB, omB); omB = cmul(omB, omB);
  }
  if (LY == 0) {
    const uint32_t* rp = S->RS + cb * 13 * 32;
    const int r0 = 16 * w + g;
#pragma unroll 1
    for (int it = 0; it < SPIN; it++) {
      uint4 v;
      v.x = ld_rlx(rp + (r0 / 11) * 32 + r0 % 11); v.y = ld_rlx(rp + ((r0 + 8) / 11) * 32 + (r0 + 8) % 11);
      v.z = ld_rlx(rp + ((r0 + 64) / 11) * 32 + (r0 + 64) % 11); v.w = ld_rlx(rp + ((r0 + 72) / 11) * 32 + (r0 + 72) % 11);
      rs = make_float4(untag(v.x), untag(v.y), untag(v.z), untag(v.w));
      if (!__any_sync(0xffffffff, untagged(v, tag))) break;
    }
  }
  mbar_wait(BAR(B_ST), LY);
  const uint32_t ssm = sb + SSM_OFF + 8 * (4 * wg + q) * (full ? 20 : 16);
  wg_wait<0>(); fence_regs(ar); fence_regs(ai);
  if (tid == 0) { mbar_expect_tx(BAR(B_UF + wg), ubytes); mbar_arrive(BAR(B_WE + 9)); if (wg == 0) PROF(LY ? 21 : 5); }
  if (tid == 0 && wg == 1) PROF(94 + 64 * LY);
  const float rsAr = rs.x, rsBr = rs.y, rsAi = rs.z, rsBi = rs.w;
  float2 pA = make_float2(0.f, 0.f), pB = pA;
#pragma unroll
  for (int j = 0; j < 10; j++) {
    if (j < 8 || full) {
      float4 sv;
      asm volatile("ld.shared.v4.f32 {%0,%1,%2,%3},[%4];" : "=f"(sv.x), "=f"(sv.y), "=f"(sv.z), "=f"(sv.w) : "r"(ssm + 16 * j));
#pragma unroll
      for (int e = 0; e < 2; e++) {
        const int o = 4 * j + e;
        const float r = e ? sv.z : sv.x, nm = e ? sv.w : sv.y;
        ar[o] = fmaf(ar[o], r, nm * rsAr); ai[o] = fmaf(ai[o], r, nm * rsAi);
        ar[o + 2] = fmaf(ar[o + 2], r, nm * rsBr); ai[o + 2] = fmaf(ai[o + 2], r, nm * rsBi);
        pA = cfma(lamA, pA, make_float2(ar[o], ai[o])); pB = cfma(lamB, pB, make_float2(ar[o + 2], ai[o + 2]));
      }
    }
  }
  {
    float2 tA = make_float2(__shfl_up_sync(0xffffffff, pA.x, 1, 4), __shfl_up_sync(0xffffffff, pA.y, 1, 4));
    float2 tB = make_float2(__shfl_up_sync(0xffffffff, pB.x, 1, 4), __shfl_up_sync(0xffffffff, pB.y, 1, 4));
    if (q >= 1) { pA = cfma(muA, tA, pA); pB = cfma(muB, tB, pB); }
    tA = make_float2(__shfl_up_sync(0xffffffff, pA.x, 2, 4), __shfl_up_sync(0xffffffff, pA.y, 2, 4));
    tB = make_float2(__shfl_up_sync(0xffffffff, pB.x, 2, 4), __shfl_up_sync(0xffffffff, pB.y, 2, 4));
    if (q >= 2) { pA = cfma(mu2A, tA, pA); pB = cfma(mu2B, tB, pB); }
  }
  if (tid == 0 && wg == 1) PROF(95 + 64 * LY);
  const float2 nuA = cmul(mu2A, mu2A), nuB = cmul(mu2B, mu2B);
  const uint32_t esm = sb + ESM_OFF + (w * 8 + g) * 16;
  if (wg == 0 && q == 3) asm volatile("st.shared.v4.f32 [%0],{%1,%2,%3,%4};" ::"r"(esm), "f"(pA.x), "f"(pA.y), "f"(pB.x), "f"(pB.y) : "memory");
  bar_sync(4, 256);
  float2 e0A = make_float2(0.f, 0.f), e0B = e0A;
  if (wg == 1) {
    asm volatile("ld.shared.v4.f32 {%0,%1,%2,%3},[%4];" : "=f"(e0A.x), "=f"(e0A.y), "=f"(e0B.x), "=f"(e0B.y) : "r"(esm));
    if (q == 3 && full) {
      float2 eA = cfma(nuA, e0A, pA), eB = cfma(nuB, e0B, pB);
      st_rlx4(Eb + tb * 320, tagf(eA.x, tag), tagf(eA.y, tag), tagf(eB.x, tag), tagf(eB.y, tag));
    }
  }
  if (tid == 0 && wg == 1) PROF(96 + 64 * LY);
  uint4 ev[3];
#pragma unroll
  for (int i = 0; i < 3; i++) { const int j = tb - 1 - q - 4 * i; ev[i] = j >= 0 ? ld_rlx4(Eb + j * 320) : make_uint4(tag, tag, tag, tag); }
  float2 xA = make_float2(__shfl_up_sync(0xffffffff, pA.x, 1, 4), __shfl_up_sync(0xffffffff, pA.y, 1, 4));
  float2 xB = make_float2(__shfl_up_sync(0xffffffff, pB.x, 1, 4), __shfl_up_sync(0xffffffff, pB.y, 1, 4));
  if (q == 0) { xA = make_float2(0.f, 0.f); xB = xA; }
  const float2 one = make_float2(1.f, 0.f);
  const float2 mqA = cmul((q & 1) ? muA : one, (q & 2) ? mu2A : one), mqB = cmul((q & 1) ? muB : one, (q & 2) ? mu2B : one);
  const float2 om2A = cmul(omA, omA), om2B = cmul(omB, omB), om4A = cmul(om2A, om2A), om4B = cmul(om2B, om2B);
  const float2 fA = cmul((q & 1) ? omA : one, (q & 2) ? om2A : one), fB = cmul((q & 1) ? omB : one, (q & 2) ? om2B : one);
  xA = cfma(mqA, e0A, xA); xB = cfma(mqB, e0B, xB);
  const float2 kA = wg ? cmul(mqA, nuA) : mqA, kB = wg ? cmul(mqB, nuB) : mqB;
#pragma unroll 1
  for (int it = 0; it < SPIN; it++) {
    const bool m0 = untagged(ev[0], tag), m1 = untagged(ev[1], tag), m2 = untagged(ev[2], tag);
    if (!__any_sync(0xffffffff, m0 || m1 || m2)) break;
    if (m0) ev[0] = ld_rlx4(Eb + (tb - 1 - q) * 320);
    if (m1) ev[1] = ld_rlx4(Eb + (tb - 5 - q) * 320);
    if (m2) ev[2] = ld_rlx4(Eb + (tb - 9 - q) * 320);
  }
  if (tid == 0 && wg == 1) PROF(97 + 64 * LY);
  float2 cA = make_float2(untag(ev[2].x), untag(ev[2].y)), cB = make_float2(untag(ev[2].z), untag(ev[2].w));
#pragma unroll
  for (int i = 1; i >= 0; i--) {
    cA = cfma(om4A, cA, make_float2(untag(ev[i].x), untag(ev[i].y)));
    cB = cfma(om4B, cB, make_float2(untag(ev[i].z), untag(ev[i].w)));
  }
  cA = cmul(fA, cA); cB = cmul(fB, cB);
#pragma unroll
  for (int s = 1; s <= 2; s <<= 1) {
    cA.x += __shfl_xor_sync(0xffffffff, cA.x, s); cA.y += __shfl_xor_sync(0xffffffff, cA.y, s);
    cB.x += __shfl_xor_sync(0xffffffff, cB.x, s); cB.y += __shfl_xor_sync(0xffffffff, cB.y, s);
  }
  float2 hA = cfma(kA, cA, xA), hB = cfma(kB, cB, xB);
  if (tid == 0 && wg == 0) PROF(LY ? 22 : 6);
  const uint32_t hp = sb + R_OFF + ((lane >> 4) * 2 + wg) * 10240 + (lane & 7) * 128 + (((2 * w + ((lane >> 3) & 1)) ^ (lane & 7)) << 4);
#pragma unroll
  for (int j = 0; j < 10; j++) {
    if (j < 8 || full) {
      float2 zA[2], zB[2];
#pragma unroll
      for (int e = 0; e < 2; e++) {
        const int o = 4 * j + e;
        hA = cfma(lamA, hA, make_float2(ar[o], ai[o])); hB = cfma(lamB, hB, make_float2(ar[o + 2], ai[o + 2]));
        zA[e] = make_float2(cf.x * hA.x - cf.y * hA.y, -cf.x * hA.y - cf.y * hA.x);
        zB[e] = make_float2(cf.z * hB.x - cf.w * hB.y, -cf.z * hB.y - cf.w * hB.x);
      }
      asm volatile("stmatrix.sync.aligned.m8n8.x4.trans.shared.b16 [%0], {%1,%2,%3,%4};" ::"r"(hp + j * 1024), "r"(pack_bf(zA[0].x, zA[1].x)),
                   "r"(pack_bf(zB[0].x, zB[1].x)), "r"(pack_bf(zA[0].y, zA[1].y)), "r"(pack_bf(zB[0].y, zB[1].y)) : "memory");
      if (j & 1) { fence_async(); __syncwarp(); if (lane == 0) mbar_arrive(BAR(B_SH + j / 2)); }
    }
  }
  if (tid == 0 && wg == 0) PROF(LY ? 23 : 7);
}

#define IDX(J, c, h) (8 * (J) + 4 * ((c) >> 1) + 2 * (h) + ((c) & 1))
struct Resid { uint2 x[10], d[5]; uint4 s; };
__device__ __forceinline__ uint2 ldg2(const void* p) { uint2 v; asm volatile("ld.global.nc.v2.u32 {%0,%1},[%2];" : "=r"(v.x), "=r"(v.y) : "l"(p)); return v; }
__device__ __forceinline__ void resid_load(const Params& P, int wg, int tid, Role R, Resid& r) {
  tid = opaque(tid);
  const int b = min(R.b(), 127), t0 = 128 * (b >> 3) + 16 * ((tid & 31) >> 2) + 8 * wg + 2 * (tid >> 5), d0 = 80 * (b & 7) + 4 * (tid & 3);
#pragma unroll
  for (int i = 0; i < 10; i++) r.x[i] = ldg2(P.x + (size_t)(t0 + (i & 1)) * DM + d0 + 16 * (i >> 1));
#pragma unroll
  for (int J = 0; J < 5; J++) r.d[J] = ldg2(P.dskip + d0 + 16 * J);
  r.s = ld_rlx4(P.s->S + t0);
}
__device__ __forceinline__ void resid_build(const Params& P, int wg, int tid, Role R, Resid& r, float (&acc)[40], uint32_t tag) {
#pragma unroll 1
  for (int it = 0; it < SPIN && R.b() < 128 && __any_sync(0xffffffff, untagged(r.s, tag)); it++)
    r.s = ld_rlx4(P.s->S + 128 * (R.b() >> 3) + 16 * ((tid & 31) >> 2) + 8 * wg + 2 * (tid >> 5));
#pragma unroll
  for (int i = 0; i < 10; i++) {
    const int J = i >> 1, h = i & 1;
    const float rs = untag(h ? r.s.z : r.s.x), nm = untag(h ? r.s.w : r.s.y);
    const float x0 = bf_lo(r.x[i].x), x1 = bf_hi(r.x[i].x), x2 = bf_lo(r.x[i].y), x3 = bf_hi(r.x[i].y);
    const uint32_t s0 = hmul2(pack_bf(fmaf(x0, rs, nm), fmaf(x1, rs, nm)), r.d[J].x), s1 = hmul2(pack_bf(fmaf(x2, rs, nm), fmaf(x3, rs, nm)), r.d[J].y);
    acc[IDX(J, 0, h)] = x0 + bf_lo(s0); acc[IDX(J, 1, h)] = x1 + bf_hi(s0); acc[IDX(J, 2, h)] = x2 + bf_lo(s1); acc[IDX(J, 3, h)] = x3 + bf_hi(s1);
  }
}

__device__ __forceinline__ void g2_phase(const int LY, const Params& P, uint32_t sb, int wg, int tid, Role R, float (&acc)[40], uint32_t e1, long long t_start) {
  const uint32_t tag = e1 & 1;
  tid = opaque(tid); sb = opaque(sb); R.v = opaque(R.v);
  const uint32_t bars = sb + BAR_OFF;
  const int b = R.b(), tb2 = b >> 3, db_ = b & 7;
  const int w = tid >> 5, lane = tid & 31, g = lane >> 2, q = lane & 3;
  const int t0 = 128 * tb2 + 16 * g + 8 * wg + 2 * w;
  const int d0 = 80 * db_ + 4 * q, mrow = 64 * wg + 16 * w + g;
#define GATE(J, c, h) (((c) & 1) ? bf_hi(G[4 * (J) + 2 * (h) + ((c) >> 1)]) : bf_lo(G[4 * (J) + 2 * (h) + ((c) >> 1)]))
  uint32_t* Mb = P.s->M + ((2 * LY * 16 + tb2) * 8) * 256 + (wg * 4 + w) * 32 + (2 * g + (q & 1)) * 2 + (q >> 1);
  st_rlx(Mb + db_ * 256, tag ^ 1);
  if (LY == 0) st_rlx(Mb + (16 * 8 + db_) * 256, tag ^ 1);
  uint2 dl[5];
#pragma unroll
  for (int J = 0; J < 5; J++) dl[J] = __ldg((const uint2*)(P.dskip + d0 + 16 * J));
  const int nrel = R.cs() >> 1, nw = R.wpart() >= 0 ? 2 : 1, wrank = (w & 1) ? R.wpart() : R.rank();
  const bool rel_h = lane == 0 && w < nrel, rel_c = lane == 0 && (w >> 1) == 1 && (w & 1) < nw;
  {
    uint64_t sl = LY ? CSLOT1 : CSLOT0;
    sl |= sl << 48;
    uint32_t bc = BAR(B_CF), st = 0, sp = 0, ph = LY ? 6 : 0;
        const int nres = LY ? 6 : 4;
#pragma unroll
    for (int i = 1; i <= CPACE; i++) mbar_wait(bc + 8 * (nres - i), LY);
    mbar_wait(BAR(B_HF + wg), 0);
    if (tid == 0 && wg == 0) PROF(LY ? 25 : 10);
#pragma unroll 1
    for (int kp = 0; kp < 10; kp++) {
      const uint64_t da = make_desc(sb + H_OFF + st * 32768 + wg * 8192, 16, 1024, 1);
      const uint64_t db0 = make_desc(sb + ((uint32_t)sl & 15) * 10240, 16, 1024, 1), db1 = make_desc(sb + (((uint32_t)sl >> 4) & 15) * 10240, 16, 1024, 1);
      wg_fence();
#pragma unroll
      for (int kk = 0; kk < 4; kk++) wgmma_ss80(acc, da + 2 * kk, db0 + 2 * kk, 1);
#pragma unroll
      for (int kk = 0; kk < 4; kk++) wgmma_ss80(acc, da + 1024 + 2 * kk, db1 + 2 * kk, 1);
      wg_commit();
      wg_wait<1>();
      if (kp > 0) {
        if (tid == 32) mbar_expect_tx(BAR(B_HF + 2 * sp + wg), 16384);
        if (kp < 8 && rel_h) mbar_arrive_cl(BAR(B_HE + sp), wg * nrel + w);
        if (rel_c && (LY == 0 || kp < 7)) mbar_arrive_cl(bc + 8 * (B_CE - B_CF - 1), wrank);
      }
      bc += 8; ph ^= 1u << st; sp = st; st = st == 2 ? 0 : st + 1;
      sl = (sl >> 8) | ((sl >> 16) << 56);
      if (kp < 9) { if (kp + 1 >= nres) mbar_wait(bc, LY); mbar_wait(BAR(B_HF + 2 * st + wg), (ph >> st) & 1); }
    }
  }
  uint32_t G[20];
  mbar_wait(BAR(B_GF), LY);
  __syncwarp();
  {
    const uint32_t gb = sb + G_OFF + wg * 10240;
    const int dr = 4 * ((lane & 7) >> 1) + (lane & 1) + 2 * ((lane >> 3) & 1), ck = 2 * w + (lane >> 4);
#pragma unroll
    for (int J = 0; J < 5; J++) {
      const int dd = 16 * J + dr;
      asm volatile("ldmatrix.sync.aligned.m8n8.x4.trans.shared.b16 {%0,%1,%2,%3},[%4];"
                   : "=r"(G[4 * J]), "=r"(G[4 * J + 1]), "=r"(G[4 * J + 2]), "=r"(G[4 * J + 3]) : "r"(gb + dd * 128 + ((ck ^ (dd & 7)) << 4)) : "memory");
    }
  }
  wg_wait<0>(); fence_regs(acc);
  if (LY == 0) {
    if (tid == 32) mbar_expect_tx(BAR(B_HF + wg), 16384);
    if (rel_c) mbar_arrive_cl(BAR(B_CE + 9), wrank);
    if (lane < 2 && 2 * w + lane < R.cs()) mbar_arrive_cl(BAR(B_RF2), 2 * w + lane);
  }
  if (tid == 0 && wg == 0) PROF(LY ? 26 : 11);
  if (lane == 0) PROF(116 + 64 * LY + wg * 4 + w);

  float mm[2], rr[2], m1 = 0.f;
#pragma unroll 1
  for (int rep = 0;; rep++) {
    float m[2][2];
#pragma unroll
    for (int h = 0; h < 2; h++) {
      m[h][0] = m[h][1] = 0.f;
#pragma unroll
      for (int J = 0; J < 5; J++)
#pragma unroll
        for (int c = 0; c < 4; c++) { const float xv = acc[IDX(J, c, h)]; m[h][0] += xv; m[h][1] = fmaf(xv, xv, m[h][1]); }
    }
    float r1[2];
#pragma unroll
    for (int i = 0; i < 2; i++) { const float snd = (q & 1) ? m[0][i] : m[1][i], kp = (q & 1) ? m[1][i] : m[0][i]; r1[i] = kp + __shfl_xor_sync(0xffffffff, snd, 1); }
    const float r2 = ((q & 2) ? r1[1] : r1[0]) + __shfl_xor_sync(0xffffffff, (q & 2) ? r1[0] : r1[1], 2);
    st_rlx(Mb + db_ * 256, tagf(r2, tag));
    if (lane == 0 && rep == 0) PROF(100 + 64 * LY + wg * 4 + w);
    uint32_t mv[8];
#pragma unroll
    for (int i = 0; i < 8; i++) mv[i] = ld_rlx(Mb + i * 256);
#pragma unroll 1
    for (int it = 0; it < SPIN; it++) {
      uint32_t miss = 0;
#pragma unroll
      for (int i = 0; i < 8; i++) miss |= ((mv[i] ^ tag) & 1) << i;
      if (!__any_sync(0xffffffff, miss)) break;
#pragma unroll
      for (int i = 0; i < 8; i++) if ((miss >> i) & 1) mv[i] = ld_rlx(Mb + i * 256);
    }
    bar_sync(4, 256);
    if (tid == 0 && wg == 0) PROF(LY ? 27 : 12 + 3 * rep);
    if (lane == 0 && rep == 0) PROF(108 + 64 * LY + wg * 4 + w);
    const float s = ((untag(mv[0]) + untag(mv[1])) + (untag(mv[2]) + untag(mv[3]))) + ((untag(mv[4]) + untag(mv[5])) + (untag(mv[6]) + untag(mv[7])));
    const float o = __shfl_xor_sync(0xffffffff, s, 2);
    const float S1 = (q & 2) ? o : s, S2 = (q & 2) ? s : o;
    const float mean = S1 * (1.f / DM), rs = frsqrt(fmaxf(S2 * (1.f / DM) - mean * mean, 0.f) + 1e-5f);
    const float mo = __shfl_xor_sync(0xffffffff, mean, 1), ro = __shfl_xor_sync(0xffffffff, rs, 1);
    mm[0] = (q & 1) ? mo : mean; mm[1] = (q & 1) ? mean : mo; rr[0] = (q & 1) ? ro : rs; rr[1] = (q & 1) ? rs : ro;
    if (rep) {
      if (db_ == 0) {
        if (q < 2) asm volatile("st.shared.v2.u32 [%0],{%1,%2};" ::"r"(sb + ESM_OFF + 8 * (t0 - 128 * tb2 + q)), "r"(tagf(rs, tag)), "r"(tagf((m1 - mean) * rs, tag)) : "memory");
        bar_sync(4, 256);
        if (wg == 0 && tid < 64) {
          uint4 v;
          asm volatile("ld.shared.v4.u32 {%0,%1,%2,%3},[%4];" : "=r"(v.x), "=r"(v.y), "=r"(v.z), "=r"(v.w) : "r"(sb + ESM_OFF + 16 * tid));
          st_rlx4(P.s->S + SEQ + 128 * tb2 + 2 * tid, v.x, v.y, v.z, v.w);
        }
      }
      break;
    }
#pragma unroll
    for (int h = 0; h < 2; h++)
#pragma unroll
      for (int J = 0; J < 5; J++)
#pragma unroll
        for (int c = 0; c < 4; c++) { const float xv = acc[IDX(J, c, h)]; acc[IDX(J, c, h)] = fmaf((xv - mm[h]) * rr[h], GATE(J, c, h), xv); }
    if (LY) break;
    m1 = mean;
#pragma unroll
    for (int i = 0; i < 10; i++) {
      const int J = i >> 1, h = i & 1;
      asm volatile("st.shared.v2.u32 [%0],{%1,%2};" ::"r"(sb + US_OFF + (mrow + 8 * h) * 160 + 32 * J + 8 * q),
                   "r"(pack_bf(acc[IDX(J, 0, h)] - mm[h], acc[IDX(J, 1, h)] - mm[h])), "r"(pack_bf(acc[IDX(J, 2, h)] - mm[h], acc[IDX(J, 3, h)] - mm[h])) : "memory");
    }
    fence_async();
    __syncwarp();
    if (lane == 0) mbar_arrive(BAR(B_SG));
    if (tid == 0 && wg == 0) PROF(13);
    Mb += 16 * 8 * 256;
  }
  if (LY == 0) {
#pragma unroll
    for (int h = 0; h < 2; h++)
#pragma unroll
      for (int J = 0; J < 5; J++)
#pragma unroll
        for (int c = 0; c < 4; c++) {
          const float x2 = acc[IDX(J, c, h)];
          const uint32_t dw = (c & 2) ? dl[J].y : dl[J].x;
          acc[IDX(J, c, h)] = fmaf((x2 - mm[h]) * rr[h], (c & 1) ? bf_hi(dw) : bf_lo(dw), x2);
        }
  }
  else {
#pragma unroll
  for (int i = 0; i < 10; i++) {
    const int J = i >> 1, h = i & 1;
    asm volatile("st.shared.v4.f32 [%0],{%1,%2,%3,%4};" ::"r"(sb + OS_OFF + (mrow + 8 * h) * 320 + 64 * J + 16 * q),
                 "f"(acc[IDX(J, 0, h)]), "f"(acc[IDX(J, 1, h)]), "f"(acc[IDX(J, 2, h)]), "f"(acc[IDX(J, 3, h)]) : "memory");
  }
  fence_async();
  __syncwarp();
  if (lane == 0) mbar_arrive(BAR(B_SG));
  }
  if (tid == 0 && wg == 0 && LY) PROF(28);
#undef IDX
#undef GATE
}

__global__ void __launch_bounds__(512, 1) fused_kernel(const __grid_constant__ Params P) {
  extern __shared__ __align__(1024) uint8_t smem[];
  asm volatile("griddepcontrol.launch_dependents;");
  const uint32_t sb = opaque(smem_u32(smem)), bars = sb + BAR_OFF;
  const int wi = __shfl_sync(0xffffffff, threadIdx.x >> 5, 0), wg = wi >> 2, tid = threadIdx.x & 127;
  Role R;
  int id;
  {
    uint32_t cs; asm("mov.u32 %0, %%cluster_nctarank;" : "=r"(cs));
    const uint32_t bx = blockIdx.x, c = bx >> 3, r = bx & 7;
    const bool big = cs == 8, comp = gridDim.x == 12;
    id = comp ? 120 + bx : bx;
    const uint32_t vA = c < 12 ? (2 * (c >> 1) + (r >> 2)) | (4 * (c & 1) + (r & 3)) << 4 | (r & 4) << 16 | 4 << 19 | ((r ^ 4) + 1) << 22
                               : (4 * (c - 12) + (r >> 1)) | (8 + (r & 1)) << 4 | (r & 6) << 16 | 2 << 19 | ((r ^ 2) + 1) << 22;
    const uint32_t vB = (comp ? (bx < 10 ? 12 : 13) | bx << 4 : bx / 10 | (bx % 10) << 4) | 2 << 19 | (bx & 1) << 26;
    R.v = __shfl_sync(0xffffffff, (big ? vA | r << 26 | 1u << 29 : vB) | id << 8, 0);
    const uint32_t cB = bx < 8 ? (600 + 3 * bx) | 3 << 10 : (592 + 4 * bx) | 4 << 10;
    R.c = __shfl_sync(0xffffffff, (comp ? cB : bx < 128 ? 5 * bx | 5 << 10 : 0) | (big || comp ? 120 : 128) << 13, 0);
  }
  const int tb = R.tb(), cb = R.cb(), b = R.b(), tb2 = b >> 3, db = b & 7, rank = R.rank();
  const bool has1 = tb <= 12, has2 = b < 128, full = tb < 12;
  const int wlo = R.wpart() < 0 ? 0 : (rank > R.wpart()), whi = R.wpart() < 0 ? 1 : wlo;
  const uint32_t wmask = R.wpart() < 0 ? 1u << rank : (1u << rank) | (1u << R.wpart());
  const int ui = rank - R.ubase(), uw = R.ugs() == 4 ? ui >> 1 : ui, uh = R.ugs() == 4 ? ui & 1 : 0;
  const uint32_t umask = ((1u << R.ugs()) - 1) << R.ubase();
  const int umap = !full ? 2 : R.ugs() == 4 ? 0 : 1, uj0 = 80 * tb + (full ? 40 * uw + 5 * uh : 32 * uw);
  Scratch* const S = P.s;
  unsigned* const epoch_p = &S->epoch[id * 8];
  const long long t_start = 0;
  if (__builtin_expect(wg == 3, 1)) {
    asm volatile("setmaxnreg.dec.sync.aligned.u32 24;");
    if (elect_one()) {
      if (wi < 14) {
        prefetch_map(wi == 12 ? &P.mB[wlo] : &P.mA[umap]);
#pragma unroll
        for (int i = 0; i < 10; i++) mbar_init(BAR(10 * (wi - 12) + i), wi - 11);
      } else if (wi == 14) {
#pragma unroll
        for (int i = 0; i < 9; i++) mbar_init(BAR(B_UF + i), i < 6 ? 1 : R.ugs());
        mbar_init(BAR(B_RF1), R.cs()); mbar_init(BAR(B_I2), 1); mbar_init(BAR(B_PS), 12);
      }
    }
    __syncwarp();
    asm volatile("fence.mbarrier_init.release.cluster;" ::: "memory");
    asm volatile("barrier.cluster.arrive.relaxed.aligned;" ::: "memory");
    asm volatile("bar.arrive 6, 512;" ::: "memory");
    asm volatile("barrier.cluster.wait.aligned;" ::: "memory");
    const unsigned e1 = ld_rlx(epoch_p) + 1;
    if (wi == 12) {
      if (elect_one()) {
        { const long long t0 = clock64(); while (clock64() - t0 < TDELAY) {} }
#pragma unroll 1
        for (int ly = 0; ly < 2; ly++) {
#pragma unroll 1
          for (int kb = 0; kb <= 10; kb++) {
            if (ly == 0 && kb == 10) {
              mbar_wait(BAR(has1 ? B_WE + 2 : B_I2));
              wait_cnt(&S->cnt[C_KV * 32], e1 * R.nprep());
              PROF(30);
#pragma unroll 1
              for (int s = 0; s < R.nch(); s++) {
                const uint32_t cbuf = conv_buf(sb, s);
                bulk_g2s(cbuf + KV_PAD, S->kv + (size_t)(R.ch0() + s) * SEQ, 4096, BAR(B_KF + s));
                bulk_g2s(cbuf + KC_OFS + 32, P.ssmk + (size_t)(R.ch0() + s) * SEQ, 4096, BAR(B_KF + s));
                bulk_g2s(cbuf, S->zero, KV_PAD, BAR(B_KF + s));
                bulk_g2s(cbuf + KC_OFS, S->zero, 32, BAR(B_KF + s));
              }
            }
            if (ly == 0 && kb == 10 && has2) { prefetch_l2(P.cre + (size_t)5 * b * DM, 5 * DM * 2); prefetch_l2(P.cim + (size_t)5 * b * DM, 5 * DM * 2); }
            if (!has1 || kb == 10) continue;
            const int slot = ((ly ? WSLOT1 : WSLOT0) >> (4 * kb)) & 15;
            if (ly == 0) { if (kb == 8) { mbar_wait(BAR(B_I2)); mbar_wait(BAR(B_XF)); } }
            else if (has2) {
              if (kb < 6) mbar_wait(BAR(B_CE + ((0x998764u >> (4 * kb)) & 15)));
              else if (kb == 6) mbar_wait(BAR(B_GE));
            } else if (kb == 0) { mbar_wait(BAR(B_WE + 9)); if (R.nch()) mbar_wait(BAR(B_CD)); }
            mbar_expect_tx(BAR(B_WF + kb), 16384);
            if (kb >= WPACE) mbar_wait(BAR(B_WF + kb - WPACE), ly);
#pragma unroll 1
            for (int h = wlo; h <= whi; h++) tma2d_mc(sb + slot * 16384 + h * 8192, &P.mB[h], kb * 64, cb * 64, BAR(B_WF + kb), wmask);
          }
          if (has2) {
#pragma unroll 1
            for (int kp = 0; kp < 10; kp++) {
              const uint32_t sig = (ly ? CSLOT1 : CSLOT0) >> (8 * (kp < 6 ? kp : kp - 6));
              if (kp >= 6) mbar_wait(BAR(B_CE + kp - 6), ly);
              else if (ly) mbar_wait(BAR(B_WE + ((0x985421u >> (4 * kp)) & 15)), 1);
              else if (kp < 4) mbar_wait(BAR(B_WE + 5 + (20 * kp + 19) / 16));
              else mbar_wait(BAR(B_CD));
              if (kp >= CPACE) mbar_wait(BAR(B_CF + kp - CPACE), ly);
              mbar_expect_tx(BAR(B_CF + kp), 20480);
              tma5d(sb + (sig & 15) * 10240, &P.mC[0], kp * 64, db * 5, BAR(B_CF + kp));
              tma5d(sb + ((sig >> 4) & 15) * 10240, &P.mC[1], kp * 64, db * 5, BAR(B_CF + kp));
            }
            mbar_wait(BAR(B_CE + 5), ly);
            wait_cnt(&S->cnt[(C_G + db) * 32], e1 * 80);
            mbar_expect_tx(BAR(B_GF), 20480);
            tma2d(sb + G_OFF, &P.mGT, tb2 * 128, db * 80, BAR(B_GF));
            tma2d(sb + G_OFF + 10240, &P.mGT, tb2 * 128 + 64, db * 80, BAR(B_GF));
          }
        }
      }
    } else if (wi == 13) {
      if (!has1) return;
      const int h0 = R.cs() == 8 ? rank : 4 * rank, hw = h0 >> 2, lane = tid & 31;
      if (elect_one()) {
#pragma unroll
        for (int i = 0; i < 6; i++) mbar_expect_tx(BAR(B_UF + i), full ? 10240 : 8192);
      }
      __syncwarp();
#pragma unroll 1
      for (int ly = 0; ly < 2; ly++) {
        {
          const int r0 = 160 * tb + (full ? 80 : 64) * uw, f0 = r0 >> 7;
          const bool two = min(15, (r0 + 79) >> 7) != f0;
          const unsigned* fp = &S->flag[(F_U3 + 8 * f0 + (lane & (two ? 15 : 7))) * 32];
          uint32_t ready = ly ? __ballot_sync(0xffffffff, ld_rlx(fp) == e1) : ~0u, st = 0, ph = ly;
          if (ly) mbar_wait(BAR(has2 ? B_RF2 : B_RF1));
          else { const long long t0 = clock64(); while (clock64() - t0 < TDELAY) {} }
          if (ly && has2) mbar_wait(BAR(B_GE));
#pragma unroll 1
          for (int kb = 0; kb < 10; kb++) {
            wait_flags(fp, e1, 0x101u * ((1u << (64 * kb / 80)) | (1u << ((64 * kb + 63) / 80))), ready);
            if (kb >= 3) { mbar_wait(BAR(B_UE + st), (ph >> st) & 1); ph ^= 1u << st; }
            if (elect_one()) {
              if (ly && kb == 0) PROF(34);
              tma4d_mc(sb + R_OFF + st * 20480 + uw * 10240 + uh * 5120, &P.mA[3 * ly + umap], kb * 64, 0, 0, uj0, BAR(B_UF + 2 * st + uw), umask);
            }
            __syncwarp();
            st = st == 2 ? 0 : st + 1;
          }
        }
        if (has2) {
          const int s0 = 128 * tb2 / 160;
          const bool two = (128 * tb2 + 127) / 160 != s0;
          const unsigned* fp = &S->flag[(F_H + (ly * 13 + s0) * 10 + min(lane & 15, 9) + (two && lane >= 16 ? 10 : 0)) * 32];
          uint32_t ready = __ballot_sync(0xffffffff, ld_rlx(fp) == e1), st = 0, ph = ly;
          mbar_wait(BAR(B_HD), ly);
          mbar_wait(BAR(B_RF0), ly);
#pragma unroll 1
          for (int kp = 0; kp < 10; kp++) {
            wait_flags(fp, e1, 0x10001u << kp, ready);
            if (kp == 1) mbar_wait(BAR(B_RF1), ly);
            if (kp >= 3) { mbar_wait(BAR(B_HE + st), (ph >> st) & 1); ph ^= 1u << st; }
            if (elect_one()) {
              if (kp == 0) PROF(33 + 2 * ly);
#pragma unroll
              for (int hf = 0; hf < 2; hf++)
                tma4d_mc(sb + H_OFF + st * 32768 + hf * 16384 + h0 * 2048, &P.mH[R.cs() == 8 ? 0 : 1], kp * 128 + hf * 64, 0, 2 * h0,
                         ly * 16 + tb2, BAR(B_HF + 2 * st + hw), (1u << R.cs()) - 1);
            }
            __syncwarp();
            st = st == 2 ? 0 : st + 1;
          }
        }
      }
    } else if (wi == 14) {
      if (elect_one()) { prefetch_map(&P.mC[0]); prefetch_map(&P.mC[1]); prefetch_map(&P.mH[R.cs() == 8 ? 0 : 1]); prefetch_map(&P.mGT); prefetch_map(&P.mA[3 + umap]); }
      __syncwarp();
      mbar_wait(BAR(B_I2));
      {
        const int lane = tid & 31;
#pragma unroll 1
        for (int ly = 0; ly < 2; ly++) {
          if (has1) {
            mbar_wait(BAR(B_WE + 6), ly);
            const uint2* p = S->S + ly * SEQ + 160 * tb + 2 * lane;
            const bool third = full && lane < 16;
            const uint32_t a = sb + SSM_OFF + 16 * lane;
#pragma unroll 1
            for (int it = 0; it < SPIN; it++) {
              const uint4 v0 = ld_rlx4(p), v1 = ld_rlx4(p + 64), v2 = third ? ld_rlx4(p + 128) : v0;
              asm volatile("st.shared.v4.u32 [%0],{%1,%2,%3,%4};" ::"r"(a), "r"(v0.x & ~1u), "r"(v0.y & ~1u), "r"(v0.z & ~1u), "r"(v0.w & ~1u) : "memory");
              asm volatile("st.shared.v4.u32 [%0],{%1,%2,%3,%4};" ::"r"(a + 512), "r"(v1.x & ~1u), "r"(v1.y & ~1u), "r"(v1.z & ~1u), "r"(v1.w & ~1u) : "memory");
              if (third) asm volatile("st.shared.v4.u32 [%0],{%1,%2,%3,%4};" ::"r"(a + 1024), "r"(v2.x & ~1u), "r"(v2.y & ~1u), "r"(v2.z & ~1u), "r"(v2.w & ~1u) : "memory");
              if (!__any_sync(0xffffffff, untagged(v0, e1 & 1) || untagged(v1, e1 & 1) || untagged(v2, e1 & 1))) break;
            }
            __syncwarp();
          }
          if (has1) {
            if (lane == 0) mbar_arrive(BAR(B_ST));
            mbar_wait(BAR(B_WE + 9), ly);
            if (lane < R.cs() && has2) mbar_arrive_cl(BAR(B_RF0), lane);
            if (lane == 0) {
#pragma unroll 1
              for (int pc = 0; pc < (full ? 5 : 4); pc++) {
                mbar_wait(BAR(B_SH + pc), ly);
#pragma unroll
                for (int i = 0; i < 4; i++)
                  tma4d_store(&P.sH[full ? 0 : 1], sb + R_OFF + i * 10240 + pc * 2048, 128 * cb + 64 * (i >> 1), 0, 0,
                              ly * 1024 + 80 * tb + (full ? 40 : 32) * (i & 1) + 2 * pc);
              }
              bulk_commit(); bulk_wait();
              signal_flag(&S->flag[(F_H + (ly * 13 + tb) * 10 + cb) * 32], e1);
              PROF(ly ? 24 : 8);
              mbar_arrive(BAR(B_HD));
            }
            __syncwarp();
            if (lane < R.cs() && (ly == 0 || has2)) mbar_arrive_cl(BAR(B_RF1), lane);
          }
          if (lane == 0) {
          if (has2) {
            if (ly == 0) {
              mbar_wait(BAR(B_SG), 0);
              tma4d_store(&P.sU, sb + US_OFF, 80 * db, 0, 0, tb2);
              bulk_commit(); bulk_wait();
              signal_flag(&S->flag[(F_U3 + b) * 32], e1);
              PROF(14);
              mbar_arrive(BAR(B_GE)); if (R.wpart() >= 0) mbar_arrive_cl(BAR(B_GE), R.wpart());
            }
            else {
              mbar_wait(BAR(B_SG), 1);
              tma4d_store(&P.sO, sb + OS_OFF, 80 * db, 0, 0, tb2);
              bulk_commit(); bulk_wait();
              PROF(29);
            }
          }
          }
          __syncwarp();
        }
      }
    } else {
      if (elect_one()) {
        const int nw = R.wpart() >= 0 ? 2 : 1;
#pragma unroll
        for (int i = B_CF; i < B_GE; i++) mbar_init(BAR(i), i < B_CE ? 1 : i < B_HE ? 2 * nw : R.cs());
        mbar_init(BAR(B_GE), nw); mbar_init(BAR(B_XF), nw); mbar_init(BAR(B_CD), 1); mbar_init(BAR(B_RF2), 2 * R.cs()); mbar_init(BAR(B_SG), 8); mbar_init(BAR(B_ST), 1); mbar_init(BAR(B_HD), 1); mbar_init(BAR(B_RF0), R.cs());
#pragma unroll
        for (int i = 0; i < 6; i++) mbar_expect_tx(BAR(B_HF + i), 16384);
#pragma unroll
        for (int i = 0; i < 5; i++) { mbar_expect_tx(BAR(B_KF + i), CH_BYTES); mbar_init(BAR(B_GS + i), 4); mbar_init(BAR(B_SH + i), 8); }
        asm volatile("fence.mbarrier_init.release.cluster;" ::: "memory");
        mbar_arrive(BAR(B_I2));
        mbar_wait(BAR(B_PS));
        if (b < R.nprep()) {
#pragma unroll 1
          for (int task = b, r = 0; task < 320; task += R.nprep(), r++) tma2d_store(&P.sK, sb + KS_OFF + r * 8192, 64 * (task / 10), 64 * (task % 10));
          bulk_commit(); bulk_wait();
          signal_cnt(&S->cnt[C_KV * 32], 1);
          PROF(41);
        }
        mbar_arrive(BAR(B_XF));
        if (R.wpart() >= 0) mbar_arrive_cl(BAR(B_XF), R.wpart());
#pragma unroll 1
        for (int i = 0; i < 5; i++) {
          const int s = (0x43210 >> (4 * i)) & 15;
          if (s >= R.nch()) continue;
          mbar_wait(BAR(B_GS + s));
          bulk_s2g(S->gt + (size_t)(R.ch0() + s) * SEQ, conv_buf(sb, s) + KC_OFS, 4096); bulk_commit();
        }
        asm volatile("cp.async.bulk.wait_group.read 0;" ::: "memory");
        if (R.nch()) { mbar_arrive(BAR(B_CD)); bulk_wait(); signal_cnt(&S->cnt[(C_G + R.ch0() / 80) * 32], R.nch()); }
      }
    }
  } else {
    asm volatile("barrier.cluster.arrive.relaxed.aligned;" ::: "memory");
    asm volatile("setmaxnreg.inc.sync.aligned.u32 136;");
    if (threadIdx.x == 0) PROF(50);
    const int w = wi & 3, lane = tid & 31;
    const uint32_t epoch = ld_rlx(epoch_p), tag = (epoch + 1) & 1;
    const int task = b + wg * R.nprep();
    const bool kvon = b < R.nprep() && task < 320;
    uint32_t k_[19], v_[16];
    uint4 sk;
    if (kvon) {
      const int row = 64 * (task / 10) + 16 * w, ch = 64 * (task % 10) + 2 * lane;
      const uint32_t* kp = (const uint32_t*)(P.k + (size_t)row * DM + ch);
      const uint32_t* vp = (const uint32_t*)(P.v + (size_t)row * DM + ch);
#pragma unroll
      for (int i = 0; i < 19; i++) k_[i] = (i >= 3 || row > 0) ? __ldg(kp + (i - 3) * (DM / 2)) : 0u;
#pragma unroll
      for (int i = 0; i < 16; i++) v_[i] = __ldg(vp + i * (DM / 2));
      sk = __ldg((const uint4*)(P.shk + ch * 4));
    }
    if (wg == 1 && tid < 64 && has1) {
      const int c = 64 * cb + tid;
      const float lr = bf_lo(__ldg((const unsigned short*)P.lre + c)), li = bf_lo(__ldg((const unsigned short*)P.lim + c));
      const float2 lb = lam_bar(lr, li, bf_lo(__ldg((const unsigned short*)P.ldt + c)));
      const float nx = lb.x - 1.f, ny = lb.y, inv = 2.f * frcp(lr * lr + li * li);
      asm volatile("st.shared.v4.f32 [%0],{%1,%2,%3,%4};" ::"r"(sb + SSM_OFF + 16 * tid), "f"(lb.x), "f"(lb.y), "f"((nx * lr + ny * li) * inv), "f"((ny * lr - nx * li) * inv) : "memory");
    }
    if (kvon) {
      const uint32_t T0 = __byte_perm(sk.x, sk.z, 0x5410), T1 = __byte_perm(sk.x, sk.z, 0x7632);
      const uint32_t T2 = __byte_perm(sk.y, sk.w, 0x5410), T3 = __byte_perm(sk.y, sk.w, 0x7632);
      uint32_t o[16];
#pragma unroll
      for (int t = 0; t < 16; t += 2) {
        const uint32_t a = hmul2(hadd2(hadd2(hadd2(hmul2(k_[t], T3), hmul2(k_[t + 1], T2)), hmul2(k_[t + 2], T1)), hmul2(k_[t + 3], T0)), v_[t]);
        const uint32_t c = hmul2(hadd2(hadd2(hadd2(hmul2(k_[t + 1], T3), hmul2(k_[t + 2], T2)), hmul2(k_[t + 3], T1)), hmul2(k_[t + 4], T0)), v_[t + 1]);
        const int wd = ((7 - t / 2) >> 1) + 4 * ((7 - t / 2) & 1);
        o[wd] = __byte_perm(c, a, 0x5410); o[8 + wd] = __byte_perm(c, a, 0x7632);
      }
      const int ph = (task / 10) & 1;
#pragma unroll
      for (int i = 0; i < 4; i++) {
        const int row = 2 * lane + (i >> 1);
        asm volatile("st.shared.v4.u32 [%0],{%1,%2,%3,%4};" ::"r"(sb + KS_OFF + wg * 8192 + row * 128 + (((2 * w + ((i & 1) ^ ph)) ^ (row & 7)) << 4)),
                     "r"(o[4 * i]), "r"(o[4 * i + 1]), "r"(o[4 * i + 2]), "r"(o[4 * i + 3]) : "memory");
      }
      fence_async();
    }
    bar_sync(6, 512);
    if (lane == 0) mbar_arrive(BAR(B_PS));
    if (threadIdx.x == 0) PROF(40);
    mbar_wait(BAR(B_I2));
    if (wg == 2) {
      if (has1) { input_stats(P, sb, R, tid, tag, t_start); mbar_wait(BAR(B_WE + AUXGO)); }
      conv_loop<true>(P, sb, R.c, wg, tid, t_start);
      if (tid == 0) PROF(44);
      return;
    }
    asm volatile("setmaxnreg.inc.sync.aligned.u32 176;");
    float xr[40];
#pragma unroll
    for (int i = 0; i < 40; i++) xr[i] = 0.f;
    float2 lamA = make_float2(0.f, 0.f), lamB = lamA;
    float4 cf = make_float4(0.f, 0.f, 0.f, 0.f), rs = cf;
#pragma unroll 1
    for (int ly = 0; ly < 2; ly++) {
      if (has1) g1_phase(ly, P, sb, wg, tid, R, lamA, lamB, cf, rs, epoch + 1, t_start);
      if (ly == 0) {
        Resid rd;
        resid_load(P, wg, tid, R, rd);
        conv_loop<false>(P, sb, R.c, wg, tid, t_start);
        if (tid == 0 && wg == 0) PROF(9);
        resid_build(P, wg, tid, R, rd, xr, tag);
      }
      if (has2) g2_phase(ly, P, sb, wg, tid, R, xr, epoch + 1, t_start);
    }
    if (tid == 0 && wg == 0) st_rlx(epoch_p, epoch + 1);
  }
}

typedef CUresult (*EncFn)(CUtensorMap*, CUtensorMapDataType, cuuint32_t, void*, const cuuint64_t*, const cuuint64_t*, const cuuint32_t*,
                          const cuuint32_t*, CUtensorMapInterleave, CUtensorMapSwizzle, CUtensorMapL2promotion, CUtensorMapFloatOOBfill);
void enc(EncFn f, CUtensorMap* m, const void* base, int rank, const cuuint64_t* dims, const cuuint64_t* strides, const cuuint32_t* box, bool swz,
         bool f32 = false) {
  const cuuint32_t es[5] = {1, 1, 1, 1, 1};
  f(m, f32 ? CU_TENSOR_MAP_DATA_TYPE_FLOAT32 : CU_TENSOR_MAP_DATA_TYPE_BFLOAT16, rank, const_cast<void*>(base), dims, strides, box, es, CU_TENSOR_MAP_INTERLEAVE_NONE,
    swz ? CU_TENSOR_MAP_SWIZZLE_128B : CU_TENSOR_MAP_SWIZZLE_NONE, CU_TENSOR_MAP_L2_PROMOTION_L2_256B, CU_TENSOR_MAP_FLOAT_OOB_FILL_NONE);
}
void launch(const Params& P, int grid, int cs, bool dependent) {
  cudaLaunchConfig_t cfg = {};
  cfg.gridDim = grid; cfg.blockDim = 512; cfg.dynamicSmemBytes = SMEM_BYTES; cfg.stream = cudaStreamPerThread;
  cudaLaunchAttribute at[2];
  at[0].id = cudaLaunchAttributeClusterDimension; at[0].val.clusterDim.x = cs; at[0].val.clusterDim.y = 1; at[0].val.clusterDim.z = 1;
  at[1].id = cudaLaunchAttributeProgrammaticStreamSerialization; at[1].val.programmaticStreamSerializationAllowed = 1;
  cfg.attrs = at; cfg.numAttrs = dependent ? 2 : 1;
  cudaLaunchKernelEx(&cfg, fused_kernel, P);
}

}

extern "C" void kernel_launch(void* const* d_in, const int* in_sizes, int n_in, void* d_out, int out_size) {
  (void)in_sizes; (void)n_in; (void)out_size;
  typedef const __nv_bfloat16* cb;
  void* fp = nullptr; cudaDriverEntryPointQueryResult qr;
  cudaGetDriverEntryPoint("cuTensorMapEncodeTiled", &fp, cudaEnableDefault, &qr);
  EncFn f = (EncFn)fp;
  Scratch* sp = nullptr;
  cudaGetSymbolAddress((void**)&sp, g_scr);
  void *pu = sp->u, *ph = sp->h, *pgt = sp->gt;
  Params P;
  { const cuuint64_t d[2] = {640, 640}, s[1] = {1280}; const cuuint32_t bx[2] = {64, 64};
    enc(f, &P.mB[0], d_in[3], 2, d, s, bx, true); enc(f, &P.mB[1], d_in[4], 2, d, s, bx, true); }
  for (int i = 0; i < 6; i++) {
    const int k = i % 3;
    const cuuint64_t d[4] = {640, 2, 4, 1024}, s[3] = {1280, (cuuint64_t)(k == 2 ? 16 : 20) * 1280, 2 * 1280};
    const cuuint32_t bx[4] = {64, 2, 4, (cuuint32_t)(k == 0 ? 5 : k == 1 ? 10 : 8)};
    enc(f, &P.mA[i], i < 3 ? d_in[0] : pu, 4, d, s, bx, true);
  }
  for (int i = 0; i < 2; i++) {
    const cuuint64_t d[4] = {1280, 8, 16, 32}, s[3] = {16 * 2560, 2560, 128 * 2560}; const cuuint32_t bx[4] = {64, 8, (cuuint32_t)(i ? 8 : 2), 1};
    enc(f, &P.mH[i], ph, 4, d, s, bx, true);
  }
  {
    const cuuint64_t d[5] = {640, 2, 4, 2, 40}, s[4] = {1280, 4 * 1280, 2 * 1280, 16 * 1280}; const cuuint32_t bx[5] = {64, 2, 4, 2, 5};
    enc(f, &P.mC[0], d_in[5], 5, d, s, bx, true); enc(f, &P.mC[1], d_in[6], 5, d, s, bx, true); }
  { const cuuint64_t d[2] = {2048, 640}, s[1] = {4096}; const cuuint32_t bx[2] = {64, 80}; enc(f, &P.mGT, pgt, 2, d, s, bx, true); }
  for (int i = 0; i < 2; i++) {
    const cuuint64_t d[4] = {1280, 2, 4, 2048}, s[3] = {2560, (cuuint64_t)(i ? 16 : 20) * 2560, 2 * 2560}; const cuuint32_t bx[4] = {64, 2, 4, 2};
    enc(f, &P.sH[i], ph, 4, d, s, bx, true);
  }
  { const cuuint64_t d[4] = {640, 8, 16, 16}, s[3] = {16 * 1280, 1280, 128 * 1280}, so[3] = {16 * 2560, 2560, 128 * 2560}; const cuuint32_t bx[4] = {80, 8, 16, 1};
    enc(f, &P.sU, pu, 4, d, s, bx, false); enc(f, &P.sO, d_out, 4, d, so, bx, false, true); }
  { const cuuint64_t d[2] = {2048, 640}, s[1] = {4096}; const cuuint32_t bx[2] = {64, 64}; enc(f, &P.sK, sp->kv, 2, d, s, bx, true); }
  P.x = (cb)d_in[0]; P.lre = (cb)d_in[1]; P.lim = (cb)d_in[2]; P.bre = (cb)d_in[3]; P.bim = (cb)d_in[4]; P.cre = (cb)d_in[5]; P.cim = (cb)d_in[6];
  P.ldt = (cb)d_in[7]; P.dskip = (cb)d_in[8];
  P.k = (cb)d_in[10]; P.v = (cb)d_in[11]; P.shk = (cb)d_in[12]; P.ssmk = (cb)d_in[13]; P.ssmd = (cb)d_in[14];
  P.out = (float*)d_out; P.s = sp;
  cudaFuncSetAttribute(fused_kernel, cudaFuncAttributeMaxDynamicSharedMemorySize, SMEM_BYTES);
  launch(P, 120, 8, false);
  launch(P, 12, 2, true);
}
```

```cpp
#include <cuda_runtime.h>
#include <cuda.h>
#include <cuda_bf16.h>
#include <stdint.h>

namespace {

constexpr int SEQ = 2048, DM = 640;
constexpr int SPIN = 1 << 20;
#define PFAT 0
#define KVDLY 500
#define PFD 0
#define XPFAT 2

struct Scratch {
  uint2 E[2 * 13 * 10 * 8 * 16];
  uint32_t M[3 * 16 * 8 * 256];
  uint2 S[2 * SEQ];
  uint2 RS[80 * 16];
  unsigned flag[512 * 32];
  unsigned cnt[32 * 32];
  unsigned epoch[132 * 8];
  unsigned zero[128];
  unsigned prof[132 * 512];
  __align__(1024)
  __nv_bfloat16 u[SEQ * DM];
  __nv_bfloat16 h[2 * SEQ * 1280];
  __nv_bfloat16 kv[DM * SEQ];
  __nv_bfloat16 gt[DM * SEQ];
  __nv_bfloat16 bcopy[2 * DM * DM];
};
__device__ __align__(1024) Scratch g_scr;
#define PROF(i) do {} while (0)
#define PROFC(c, i) do {} while (0)

constexpr int C_KV = 0, C_G = 10;
constexpr int F_U3 = 0, F_H = 128;

constexpr int R_OFF = 163840, H_OFF = 131072, KS_OFF = 131072, TMP_OFF = 225280, CV_OFF = 86272, G_OFF = 102400, US_OFF = 98304, OS_OFF = US_OFF + 20480;
constexpr int LAM_OFF = 229376, SSM_OFF = LAM_OFF + 1024, BAR_OFF = SSM_OFF + 1344;
constexpr int B_F1 = 0, B_E1 = 10, B_RF0 = 20, B_RF1 = 21, NBAR1 = 22;
constexpr int B_F2 = 22, B_KF = 32, B_GF = 37, B_CD = 38, B_XF = 40, B_ST = 41, B_HD = 42, B_LM = 43, B_E2 = 44, B_GS = 54, B_PS = 59, B_AX = 62, B_SH = 64, B_SG = 69, B_GE = 70, NBAR = 71;
__host__ __device__ constexpr int bar_count(int i) { return i < B_E1 ? 1 : i < B_RF0 ? 9 : i < B_F2 ? 8 : i < B_E2 ? 1 : i < B_GS ? 12 : i < B_SH ? 4 : i < B_GE ? 8 : 2; }
constexpr int MISC_OFF = BAR_OFF + NBAR * 8, SMEM_BYTES = MISC_OFF + 32;
constexpr int KV_PAD = 512, KC_OFS = KV_PAD + 4096, CH_BYTES = KC_OFS + 4128, CH_STRIDE = 8960;
__device__ __forceinline__ uint32_t conv_buf(uint32_t sb, int slot) { return sb + CV_OFF + slot * CH_STRIDE; }
constexpr uint64_t tab6(int a, int b, int c, int d, int e, int f, int g, int h, int i, int j) {
  return (uint64_t)a | (uint64_t)b << 6 | (uint64_t)c << 12 | (uint64_t)d << 18 | (uint64_t)e << 24 | (uint64_t)f << 30 | (uint64_t)g << 36 | (uint64_t)h << 42 |
         (uint64_t)i << 48 | (uint64_t)j << 54;
}
constexpr uint64_t WTAB0 = tab6(0, 4, 8, 30, 12, 26, 0, 4, 8, 12), XTAB0 = tab6(40, 45, 50, 34, 16, 21, 40, 45, 50, 16);
constexpr uint64_t WTAB1 = tab6(20, 0, 4, 8, 12, 16, 32, 36, 24, 28), XTAB1 = tab6(40, 45, 50, 40, 45, 50, 40, 45, 50, 40);
constexpr uint32_t DEP0 = 0x4210;
constexpr uint64_t CSLOT0 = 0xba9876543210ull, CSLOT1 = 0xba9765432108ull;

struct Head {
  Scratch* s;
  const __nv_bfloat16 *x, *b0, *b1;
  uint32_t base, swap;
};
struct Params {
  const __nv_bfloat16 *lre, *lim, *ldt, *k, *v, *shk, *cre, *cim, *ssmk, *ssmd, *dskip;
  uint4 role[120];
  CUtensorMap mB, mA[4], mH, mC[2], mGT, sH, sU, sO, sK;
};

__device__ __forceinline__ uint32_t smem_u32(const void* p) { return (uint32_t)__cvta_generic_to_shared(p); }
__device__ __forceinline__ uint32_t opaque(uint32_t x) { uint32_t y; asm volatile("mov.u32 %0, %1;" : "=r"(y) : "r"(x)); return y; }
__device__ __forceinline__ int lane_id() { int y; asm volatile("mov.u32 %0, %%laneid;" : "=r"(y)); return y; }
__device__ __forceinline__ void delay(uint32_t n) {
  asm volatile("{ .reg .pred p; .reg .u32 a, b; mov.u32 a, %%clock; L: mov.u32 b, %%clock; sub.u32 b, b, a; setp.lt.u32 p, b, %0; @p bra.uni L; }" ::"r"(n) : "memory");
}
__device__ __forceinline__ void mbar_init(uint32_t bar, uint32_t cnt) { asm volatile("mbarrier.init.shared::cta.b64 [%0], %1;" ::"r"(bar), "r"(cnt) : "memory"); }
__device__ __forceinline__ void mbar_expect_tx(uint32_t bar, uint32_t bytes) { asm volatile("mbarrier.arrive.expect_tx.shared::cta.b64 _, [%0], %1;" ::"r"(bar), "r"(bytes) : "memory"); }
__device__ __forceinline__ void mbar_arrive(uint32_t bar) { asm volatile("mbarrier.arrive.shared::cta.b64 _, [%0];" ::"r"(bar) : "memory"); }
__device__ __forceinline__ void mbar_arrive_if(uint32_t bar, bool c) {
  asm volatile("{ .reg .pred p; setp.ne.u32 p, %1, 0; @p mbarrier.arrive.shared::cta.b64 _, [%0]; }" ::"r"(bar), "r"((uint32_t)c) : "memory");
}
__device__ __forceinline__ void prefetch_if(const void* p, bool c) { asm volatile("{ .reg .pred p; setp.ne.u32 p, %1, 0; @p prefetch.global.L2 [%0]; }" ::"l"(p), "r"((uint32_t)c)); }
__device__ __forceinline__ void mbar_arrive_cl(uint32_t bar, uint32_t cta) {
  asm volatile("{ .reg .b32 ra; mapa.shared::cluster.u32 ra, %0, %1; mbarrier.arrive.shared::cluster.b64 _, [ra]; }" ::"r"(bar), "r"(cta) : "memory");
}
__device__ __forceinline__ uint32_t mapa(uint32_t a, uint32_t cta) { uint32_t r; asm("mapa.shared::cluster.u32 %0, %1, %2;" : "=r"(r) : "r"(a), "r"(cta)); return r; }
__device__ __forceinline__ void mbar_arrive_at(uint32_t ra) { asm volatile("mbarrier.arrive.shared::cluster.b64 _, [%0];" ::"r"(ra) : "memory"); }
__device__ __forceinline__ void mbar_wait(uint32_t bar, uint32_t parity = 0) {
  asm volatile("{ .reg .pred p; .reg .u32 c; mov.u32 c, 0;\n"
               "W: mbarrier.try_wait.parity.shared::cta.b64 p, [%0], %1; @p bra.uni D;\n"
               "add.u32 c, c, 1; setp.lt.u32 p, c, 0x100000; @p bra.uni W;\nD: }" ::"r"(bar), "r"(parity) : "memory");
}
__device__ __forceinline__ bool elect_one() { uint32_t p; asm volatile("{ .reg .pred P; elect.sync _|P, 0xffffffff; selp.u32 %0,1,0,P; }" : "=r"(p)); return p; }
__device__ __forceinline__ void bar_sync(int id, int n) { __syncwarp(); asm volatile("bar.sync %0, %1;" ::"r"(id), "r"(n) : "memory"); }
__device__ __forceinline__ void tma2d(uint32_t dst, const CUtensorMap* m, int c0, int c1, uint32_t bar) {
  asm volatile("cp.async.bulk.tensor.2d.shared::cluster.global.mbarrier::complete_tx::bytes [%0], [%1, {%3,%4}], [%2];"
               ::"r"(dst), "l"(m), "r"(bar), "r"(c0), "r"(c1) : "memory");
}
__device__ __forceinline__ void tma5d(uint32_t dst, const CUtensorMap* m, int c0, int c4, uint32_t bar) {
  asm volatile("cp.async.bulk.tensor.5d.shared::cluster.global.mbarrier::complete_tx::bytes [%0], [%1, {%3,%5,%5,%5,%4}], [%2];"
               ::"r"(dst), "l"(m), "r"(bar), "r"(c0), "r"(c4), "r"(0) : "memory");
}
__device__ __forceinline__ void tma4d_mc(uint32_t dst, const CUtensorMap* m, int c0, int c1, int c2, int c3, uint32_t bar, uint32_t mask) {
  asm volatile("cp.async.bulk.tensor.4d.shared::cluster.global.mbarrier::complete_tx::bytes.multicast::cluster [%0], [%1, {%3,%4,%5,%6}], [%2], %7;"
               ::"r"(dst), "l"(m), "r"(bar), "r"(c0), "r"(c1), "r"(c2), "r"(c3), "h"((uint16_t)mask) : "memory");
}
__device__ __forceinline__ void bulk_g2s(uint32_t dst, const void* src, uint32_t bytes, uint32_t bar) {
  asm volatile("cp.async.bulk.shared::cluster.global.mbarrier::complete_tx::bytes [%0], [%1], %2, [%3];" ::"r"(dst), "l"(src), "r"(bytes), "r"(bar) : "memory");
}
__device__ __forceinline__ void tma4d_store(const CUtensorMap* m, uint32_t src, int c0, int c1, int c2, int c3) {
  asm volatile("cp.async.bulk.tensor.4d.global.shared::cta.bulk_group [%0, {%2,%3,%4,%5}], [%1];" ::"l"(m), "r"(src), "r"(c0), "r"(c1), "r"(c2), "r"(c3) : "memory");
}
__device__ __forceinline__ void tma2d_store(const CUtensorMap* m, uint32_t src, int c0, int c1) {
  asm volatile("cp.async.bulk.tensor.2d.global.shared::cta.bulk_group [%0, {%2,%3}], [%1];" ::"l"(m), "r"(src), "r"(c0), "r"(c1) : "memory");
}
__device__ __forceinline__ void bulk_s2g(void* dst, uint32_t src, uint32_t bytes) {
  asm volatile("cp.async.bulk.global.shared::cta.bulk_group [%0], [%1], %2;" ::"l"(dst), "r"(src), "r"(bytes) : "memory");
}
__device__ __forceinline__ void bulk_commit() { asm volatile("cp.async.bulk.commit_group;" ::: "memory"); }
__device__ __forceinline__ void bulk_wait() { asm volatile("cp.async.bulk.wait_group 0;" ::: "memory"); }
__device__ __forceinline__ void fence_async() { asm volatile("fence.proxy.async.shared::cta;" ::: "memory"); }
__device__ __forceinline__ void prefetch_l2(const void* src, uint32_t bytes) { asm volatile("cp.async.bulk.prefetch.L2.global [%0], %1;" ::"l"(src), "r"(bytes) : "memory"); }
__device__ __forceinline__ void prefetch_map(const CUtensorMap* m) { asm volatile("prefetch.tensormap [%0];" ::"l"(m) : "memory"); }
__device__ __forceinline__ void wg_fence() { __syncwarp(); asm volatile("wgmma.fence.sync.aligned;" ::: "memory"); }
__device__ __forceinline__ void wg_commit() { asm volatile("wgmma.commit_group.sync.aligned;" ::: "memory"); }
template <int N> __device__ __forceinline__ void wg_wait() { asm volatile("wgmma.wait_group.sync.aligned %0;" ::"n"(N) : "memory"); }
template <int N> __device__ __forceinline__ void fence_regs(float (&d)[N]) {
#pragma unroll
  for (int i = 0; i < N; i++) asm volatile("" : "+f"(d[i])::"memory");
}
__device__ __forceinline__ uint64_t make_desc(uint32_t addr, uint32_t lbo, uint32_t sbo, uint32_t swz) {
  return (uint64_t)((addr & 0x3FFFF) >> 4) | ((uint64_t)(lbo >> 4) << 16) | ((uint64_t)(sbo >> 4) << 32) | ((uint64_t)swz << 62);
}
__device__ __forceinline__ uint2 ldg2(const void* p) { uint2 v; asm volatile("ld.global.nc.v2.u32 {%0,%1},[%2];" : "=r"(v.x), "=r"(v.y) : "l"(p)); return v; }
__device__ __forceinline__ uint32_t ldg1(const void* p) { uint32_t v; asm volatile("ld.global.nc.u32 %0,[%1];" : "=r"(v) : "l"(p)); return v; }
__device__ __forceinline__ uint32_t lds32(uint32_t a) { uint32_t v; asm volatile("ld.shared.u32 %0,[%1];" : "=r"(v) : "r"(a)); return v; }
__device__ __forceinline__ unsigned ld_rlx(const unsigned* p) { unsigned v; asm volatile("ld.relaxed.gpu.global.u32 %0,[%1];" : "=r"(v) : "l"(p) : "memory"); return v; }
__device__ __forceinline__ uint4 ld_rlx4(const void* p) {
  uint4 v; asm volatile("ld.relaxed.gpu.global.v4.u32 {%0,%1,%2,%3},[%4];" : "=r"(v.x), "=r"(v.y), "=r"(v.z), "=r"(v.w) : "l"(p) : "memory"); return v;
}
__device__ __forceinline__ uint2 ld_rlx2(const void* p) { uint2 v; asm volatile("ld.relaxed.gpu.global.v2.u32 {%0,%1},[%2];" : "=r"(v.x), "=r"(v.y) : "l"(p) : "memory"); return v; }
__device__ __forceinline__ void st_rlx2(void* p, uint32_t a, uint32_t b) { asm volatile("st.relaxed.gpu.global.v2.u32 [%0],{%1,%2};" ::"l"(p), "r"(a), "r"(b) : "memory"); }
__device__ __forceinline__ void st_rlx4(void* p, uint32_t a, uint32_t b, uint32_t c, uint32_t d) {
  asm volatile("st.relaxed.gpu.global.v4.u32 [%0],{%1,%2,%3,%4};" ::"l"(p), "r"(a), "r"(b), "r"(c), "r"(d) : "memory");
}
__device__ __forceinline__ void st_rlx(void* p, uint32_t a) { asm volatile("st.relaxed.gpu.global.u32 [%0],%1;" ::"l"(p), "r"(a) : "memory"); }
#define PUB 15
template <int SITE> __device__ __forceinline__ void release() { if (PUB & SITE) asm volatile("fence.acq_rel.gpu;" ::: "memory"); }
__device__ __forceinline__ void signal_flag(unsigned* p, unsigned val) { asm volatile("st.relaxed.gpu.global.u32 [%0],%1;" ::"l"(p), "r"(val) : "memory"); }
__device__ __forceinline__ void signal_cnt(unsigned* p, unsigned n) { asm volatile("red.relaxed.gpu.global.add.u32 [%0],%1;" ::"l"(p), "r"(n) : "memory"); }
__device__ __forceinline__ void wait_flags(const unsigned* p, unsigned val, uint32_t need, uint32_t& ready) {
#pragma unroll 1
  for (int it = 0; (ready & need) != need && it < SPIN; it++) ready = __ballot_sync(0xffffffff, ld_rlx(p) == val);
}
__device__ __forceinline__ void wait_cnt(const unsigned* p, unsigned tgt) {
  asm volatile("{ .reg .pred p; .reg .u32 c; .reg .s32 v; mov.u32 c, 0;\n"
               "W: ld.relaxed.gpu.global.u32 v, [%0]; sub.s32 v, v, %1; setp.ge.s32 p, v, 0; @p bra.uni D;\n"
               "add.u32 c, c, 1; setp.lt.u32 p, c, 0x100000; @p bra.uni W;\nD: }" ::"l"(p), "r"(tgt) : "memory");
}
__device__ __forceinline__ uint32_t pack_bf(float lo, float hi) { uint32_t r; asm("cvt.rn.bf16x2.f32 %0, %1, %2;" : "=r"(r) : "f"(hi), "f"(lo)); return r; }
__device__ __forceinline__ float bf_lo(uint32_t v) { return __uint_as_float(v << 16); }
__device__ __forceinline__ float bf_hi(uint32_t v) { return __uint_as_float(v & 0xffff0000u); }
__device__ __forceinline__ float bf_rn(float x) { return __bfloat162float(__float2bfloat16_rn(x)); }
__device__ __forceinline__ float frcp(float x) { float r; asm("rcp.approx.ftz.f32 %0,%1;" : "=f"(r) : "f"(x)); return r; }
__device__ __forceinline__ float fsqrt(float x) { float r; asm("sqrt.approx.ftz.f32 %0,%1;" : "=f"(r) : "f"(x)); return r; }
__device__ __forceinline__ float frsqrt(float x) { float r; asm("rsqrt.approx.ftz.f32 %0,%1;" : "=f"(r) : "f"(x)); return r; }
__device__ __forceinline__ uint32_t hmul2(uint32_t a, uint32_t b) { uint32_t r; asm("mul.rn.bf16x2 %0,%1,%2;" : "=r"(r) : "r"(a), "r"(b)); return r; }
__device__ __forceinline__ uint32_t hadd2(uint32_t a, uint32_t b) { uint32_t r; asm("add.rn.bf16x2 %0,%1,%2;" : "=r"(r) : "r"(a), "r"(b)); return r; }
__device__ __forceinline__ float2 cmul(float2 a, float2 b) { return make_float2(a.x * b.x - a.y * b.y, a.x * b.y + a.y * b.x); }
__device__ __forceinline__ float2 cfma(float2 a, float2 b, float2 c) {
  return make_float2(fmaf(a.x, b.x, fmaf(-a.y, b.y, c.x)), fmaf(a.x, b.y, fmaf(a.y, b.x, c.y)));
}
__device__ __forceinline__ uint32_t tagf(float v, uint32_t tag) { return (__float_as_uint(v) & ~1u) | tag; }
__device__ __forceinline__ float untag(uint32_t v) { return __uint_as_float(v & ~1u); }
__device__ __forceinline__ bool untagged(const uint4& v, uint32_t tag) { return (((v.x ^ tag) | (v.y ^ tag) | (v.z ^ tag) | (v.w ^ tag)) & 1) != 0; }
__device__ __forceinline__ bool untagged(const uint2& v, uint32_t tag) { return (((v.x ^ tag) | (v.y ^ tag)) & 1) != 0; }
__device__ __forceinline__ float2 lam_bar(float lr, float li, float ldt) {
  float dt = bf_rn(expf(ldt)); float e = expf(dt * lr), s, c; sincospif(dt * li * 0.31830988618379067f, &s, &c); return make_float2(e * c, e * s);
}

__device__ __forceinline__ int conv_ch(uint32_t c, int s) { return s * ((c >> 21) & 255) + (c & 255) - (s >= (int)(c >> 29) ? 8 : 0); }
struct Role {
  uint32_t v, c, p;
  __device__ __forceinline__ int tb() const { return v & 15; }
  __device__ __forceinline__ int cb() const { return (v >> 4) & 15; }
  __device__ __forceinline__ int b() const { return (v >> 8) & 255; }
  __device__ __forceinline__ int ubase() const { return (v >> 16) & 7; }
  __device__ __forceinline__ int ugs() const { return (v >> 19) & 7; }
  __device__ __forceinline__ int wpart() const { return (v >> 22) & 7; }
  __device__ __forceinline__ int rank() const { return (v >> 26) & 7; }
  __device__ __forceinline__ int cs() const { return (v >> 29) ? 8 : 2; }
  __device__ __forceinline__ int ch(int s) const { return conv_ch(c, s); }
  __device__ __forceinline__ int wlo() const { return p & 1; }
  __device__ __forceinline__ int whi() const { return (p >> 1) & 1; }
  __device__ __forceinline__ uint32_t wmask() const { return (p >> 2) & 255; }
  __device__ __forceinline__ uint32_t umask() const { return (p >> 10) & 255; }
  __device__ __forceinline__ int uj() const { return (p >> 20) & 31; }
  __device__ __forceinline__ int sm() const { return (p >> 25) & 15; }
  __device__ __forceinline__ int nch() const { return (c >> 10) & 7; }
  __device__ __forceinline__ int nprep() const { return (c >> 13) & 255; }
};

__device__ __forceinline__ void wgmma_ss80(float (&d)[40], uint64_t da, uint64_t db, int sd){
  asm volatile("{ .reg .pred p; setp.ne.b32 p, %42, 0;\n"
   "wgmma.mma_async.sync.aligned.m64n80k16.f32.bf16.bf16 {%0, %1, %2, %3, %4, %5, %6, %7, %8, %9, %10, %11, %12, %13, %14, %15, %16, %17, %18, %19, %20, %21, %22, %23, %24, %25, %26, %27, %28, %29, %30, %31, %32, %33, %34, %35, %36, %37, %38, %39}, %40, %41, p, 1, 1, 0, 0; }\n"
   : "+f"(d[0]), "+f"(d[1]), "+f"(d[2]), "+f"(d[3]), "+f"(d[4]), "+f"(d[5]), "+f"(d[6]), "+f"(d[7]), "+f"(d[8]), "+f"(d[9]), "+f"(d[10]), "+f"(d[11]), "+f"(d[12]), "+f"(d[13]), "+f"(d[14]), "+f"(d[15]), "+f"(d[16]), "+f"(d[17]), "+f"(d[18]), "+f"(d[19]), "+f"(d[20]), "+f"(d[21]), "+f"(d[22]), "+f"(d[23]), "+f"(d[24]), "+f"(d[25]), "+f"(d[26]), "+f"(d[27]), "+f"(d[28]), "+f"(d[29]), "+f"(d[30]), "+f"(d[31]), "+f"(d[32]), "+f"(d[33]), "+f"(d[34]), "+f"(d[35]), "+f"(d[36]), "+f"(d[37]), "+f"(d[38]), "+f"(d[39]) : "l"(da), "l"(db), "r"(sd));
}
__device__ __forceinline__ void wgmma_ss160(float (&d)[80], uint64_t da, uint64_t db, int sd){
  asm volatile("{ .reg .pred p; setp.ne.b32 p, %82, 0;\n"
   "wgmma.mma_async.sync.aligned.m64n160k16.f32.bf16.bf16 {%0, %1, %2, %3, %4, %5, %6, %7, %8, %9, %10, %11, %12, %13, %14, %15, %16, %17, %18, %19, %20, %21, %22, %23, %24, %25, %26, %27, %28, %29, %30, %31, %32, %33, %34, %35, %36, %37, %38, %39, %40, %41, %42, %43, %44, %45, %46, %47, %48, %49, %50, %51, %52, %53, %54, %55, %56, %57, %58, %59, %60, %61, %62, %63, %64, %65, %66, %67, %68, %69, %70, %71, %72, %73, %74, %75, %76, %77, %78, %79}, %80, %81, p, 1, 1, 0, 0; }\n"
   : "+f"(d[0]), "+f"(d[1]), "+f"(d[2]), "+f"(d[3]), "+f"(d[4]), "+f"(d[5]), "+f"(d[6]), "+f"(d[7]), "+f"(d[8]), "+f"(d[9]), "+f"(d[10]), "+f"(d[11]), "+f"(d[12]), "+f"(d[13]), "+f"(d[14]), "+f"(d[15]), "+f"(d[16]), "+f"(d[17]), "+f"(d[18]), "+f"(d[19]), "+f"(d[20]), "+f"(d[21]), "+f"(d[22]), "+f"(d[23]), "+f"(d[24]), "+f"(d[25]), "+f"(d[26]), "+f"(d[27]), "+f"(d[28]), "+f"(d[29]), "+f"(d[30]), "+f"(d[31]), "+f"(d[32]), "+f"(d[33]), "+f"(d[34]), "+f"(d[35]), "+f"(d[36]), "+f"(d[37]), "+f"(d[38]), "+f"(d[39]), "+f"(d[40]), "+f"(d[41]), "+f"(d[42]), "+f"(d[43]), "+f"(d[44]), "+f"(d[45]), "+f"(d[46]), "+f"(d[47]), "+f"(d[48]), "+f"(d[49]), "+f"(d[50]), "+f"(d[51]), "+f"(d[52]), "+f"(d[53]), "+f"(d[54]), "+f"(d[55]), "+f"(d[56]), "+f"(d[57]), "+f"(d[58]), "+f"(d[59]), "+f"(d[60]), "+f"(d[61]), "+f"(d[62]), "+f"(d[63]), "+f"(d[64]), "+f"(d[65]), "+f"(d[66]), "+f"(d[67]), "+f"(d[68]), "+f"(d[69]), "+f"(d[70]), "+f"(d[71]), "+f"(d[72]), "+f"(d[73]), "+f"(d[74]), "+f"(d[75]), "+f"(d[76]), "+f"(d[77]), "+f"(d[78]), "+f"(d[79]) : "l"(da), "l"(db), "r"(sd));
}
template<int N> __device__ __forceinline__ void wgmma_rs(float (&d)[N/2], uint32_t a0, uint32_t a1, uint32_t a2, uint32_t a3, uint64_t db, int sd);
template<> __device__ __forceinline__ void wgmma_rs<16>(float (&d)[8], uint32_t a0, uint32_t a1, uint32_t a2, uint32_t a3, uint64_t db, int sd){
  asm volatile("{ .reg .pred p; setp.ne.b32 p, %13, 0;\n"
   "wgmma.mma_async.sync.aligned.m64n16k16.f32.bf16.bf16 {%0, %1, %2, %3, %4, %5, %6, %7}, {%8,%9,%10,%11}, %12, p, 1, 1, 0; }\n"
   : "+f"(d[0]), "+f"(d[1]), "+f"(d[2]), "+f"(d[3]), "+f"(d[4]), "+f"(d[5]), "+f"(d[6]), "+f"(d[7]) : "r"(a0), "r"(a1), "r"(a2), "r"(a3), "l"(db), "r"(sd));
}
template<> __device__ __forceinline__ void wgmma_rs<32>(float (&d)[16], uint32_t a0, uint32_t a1, uint32_t a2, uint32_t a3, uint64_t db, int sd){
  asm volatile("{ .reg .pred p; setp.ne.b32 p, %21, 0;\n"
   "wgmma.mma_async.sync.aligned.m64n32k16.f32.bf16.bf16 {%0, %1, %2, %3, %4, %5, %6, %7, %8, %9, %10, %11, %12, %13, %14, %15}, {%16,%17,%18,%19}, %20, p, 1, 1, 0; }\n"
   : "+f"(d[0]), "+f"(d[1]), "+f"(d[2]), "+f"(d[3]), "+f"(d[4]), "+f"(d[5]), "+f"(d[6]), "+f"(d[7]), "+f"(d[8]), "+f"(d[9]), "+f"(d[10]), "+f"(d[11]), "+f"(d[12]), "+f"(d[13]), "+f"(d[14]), "+f"(d[15]) : "r"(a0), "r"(a1), "r"(a2), "r"(a3), "l"(db), "r"(sd));
}
template<> __device__ __forceinline__ void wgmma_rs<48>(float (&d)[24], uint32_t a0, uint32_t a1, uint32_t a2, uint32_t a3, uint64_t db, int sd){
  asm volatile("{ .reg .pred p; setp.ne.b32 p, %29, 0;\n"
   "wgmma.mma_async.sync.aligned.m64n48k16.f32.bf16.bf16 {%0, %1, %2, %3, %4, %5, %6, %7, %8, %9, %10, %11, %12, %13, %14, %15, %16, %17, %18, %19, %20, %21, %22, %23}, {%24,%25,%26,%27}, %28, p, 1, 1, 0; }\n"
   : "+f"(d[0]), "+f"(d[1]), "+f"(d[2]), "+f"(d[3]), "+f"(d[4]), "+f"(d[5]), "+f"(d[6]), "+f"(d[7]), "+f"(d[8]), "+f"(d[9]), "+f"(d[10]), "+f"(d[11]), "+f"(d[12]), "+f"(d[13]), "+f"(d[14]), "+f"(d[15]), "+f"(d[16]), "+f"(d[17]), "+f"(d[18]), "+f"(d[19]), "+f"(d[20]), "+f"(d[21]), "+f"(d[22]), "+f"(d[23]) : "r"(a0), "r"(a1), "r"(a2), "r"(a3), "l"(db), "r"(sd));
}
template<> __device__ __forceinline__ void wgmma_rs<64>(float (&d)[32], uint32_t a0, uint32_t a1, uint32_t a2, uint32_t a3, uint64_t db, int sd){
  asm volatile("{ .reg .pred p; setp.ne.b32 p, %37, 0;\n"
   "wgmma.mma_async.sync.aligned.m64n64k16.f32.bf16.bf16 {%0, %1, %2, %3, %4, %5, %6, %7, %8, %9, %10, %11, %12, %13, %14, %15, %16, %17, %18, %19, %20, %21, %22, %23, %24, %25, %26, %27, %28, %29, %30, %31}, {%32,%33,%34,%35}, %36, p, 1, 1, 0; }\n"
   : "+f"(d[0]), "+f"(d[1]), "+f"(d[2]), "+f"(d[3]), "+f"(d[4]), "+f"(d[5]), "+f"(d[6]), "+f"(d[7]), "+f"(d[8]), "+f"(d[9]), "+f"(d[10]), "+f"(d[11]), "+f"(d[12]), "+f"(d[13]), "+f"(d[14]), "+f"(d[15]), "+f"(d[16]), "+f"(d[17]), "+f"(d[18]), "+f"(d[19]), "+f"(d[20]), "+f"(d[21]), "+f"(d[22]), "+f"(d[23]), "+f"(d[24]), "+f"(d[25]), "+f"(d[26]), "+f"(d[27]), "+f"(d[28]), "+f"(d[29]), "+f"(d[30]), "+f"(d[31]) : "r"(a0), "r"(a1), "r"(a2), "r"(a3), "l"(db), "r"(sd));
}
template<> __device__ __forceinline__ void wgmma_rs<80>(float (&d)[40], uint32_t a0, uint32_t a1, uint32_t a2, uint32_t a3, uint64_t db, int sd){
  asm volatile("{ .reg .pred p; setp.ne.b32 p, %45, 0;\n"
   "wgmma.mma_async.sync.aligned.m64n80k16.f32.bf16.bf16 {%0, %1, %2, %3, %4, %5, %6, %7, %8, %9, %10, %11, %12, %13, %14, %15, %16, %17, %18, %19, %20, %21, %22, %23, %24, %25, %26, %27, %28, %29, %30, %31, %32, %33, %34, %35, %36, %37, %38, %39}, {%40,%41,%42,%43}, %44, p, 1, 1, 0; }\n"
   : "+f"(d[0]), "+f"(d[1]), "+f"(d[2]), "+f"(d[3]), "+f"(d[4]), "+f"(d[5]), "+f"(d[6]), "+f"(d[7]), "+f"(d[8]), "+f"(d[9]), "+f"(d[10]), "+f"(d[11]), "+f"(d[12]), "+f"(d[13]), "+f"(d[14]), "+f"(d[15]), "+f"(d[16]), "+f"(d[17]), "+f"(d[18]), "+f"(d[19]), "+f"(d[20]), "+f"(d[21]), "+f"(d[22]), "+f"(d[23]), "+f"(d[24]), "+f"(d[25]), "+f"(d[26]), "+f"(d[27]), "+f"(d[28]), "+f"(d[29]), "+f"(d[30]), "+f"(d[31]), "+f"(d[32]), "+f"(d[33]), "+f"(d[34]), "+f"(d[35]), "+f"(d[36]), "+f"(d[37]), "+f"(d[38]), "+f"(d[39]) : "r"(a0), "r"(a1), "r"(a2), "r"(a3), "l"(db), "r"(sd));
}
template<> __device__ __forceinline__ void wgmma_rs<96>(float (&d)[48], uint32_t a0, uint32_t a1, uint32_t a2, uint32_t a3, uint64_t db, int sd){
  asm volatile("{ .reg .pred p; setp.ne.b32 p, %53, 0;\n"
   "wgmma.mma_async.sync.aligned.m64n96k16.f32.bf16.bf16 {%0, %1, %2, %3, %4, %5, %6, %7, %8, %9, %10, %11, %12, %13, %14, %15, %16, %17, %18, %19, %20, %21, %22, %23, %24, %25, %26, %27, %28, %29, %30, %31, %32, %33, %34, %35, %36, %37, %38, %39, %40, %41, %42, %43, %44, %45, %46, %47}, {%48,%49,%50,%51}, %52, p, 1, 1, 0; }\n"
   : "+f"(d[0]), "+f"(d[1]), "+f"(d[2]), "+f"(d[3]), "+f"(d[4]), "+f"(d[5]), "+f"(d[6]), "+f"(d[7]), "+f"(d[8]), "+f"(d[9]), "+f"(d[10]), "+f"(d[11]), "+f"(d[12]), "+f"(d[13]), "+f"(d[14]), "+f"(d[15]), "+f"(d[16]), "+f"(d[17]), "+f"(d[18]), "+f"(d[19]), "+f"(d[20]), "+f"(d[21]), "+f"(d[22]), "+f"(d[23]), "+f"(d[24]), "+f"(d[25]), "+f"(d[26]), "+f"(d[27]), "+f"(d[28]), "+f"(d[29]), "+f"(d[30]), "+f"(d[31]), "+f"(d[32]), "+f"(d[33]), "+f"(d[34]), "+f"(d[35]), "+f"(d[36]), "+f"(d[37]), "+f"(d[38]), "+f"(d[39]), "+f"(d[40]), "+f"(d[41]), "+f"(d[42]), "+f"(d[43]), "+f"(d[44]), "+f"(d[45]), "+f"(d[46]), "+f"(d[47]) : "r"(a0), "r"(a1), "r"(a2), "r"(a3), "l"(db), "r"(sd));
}
template<> __device__ __forceinline__ void wgmma_rs<112>(float (&d)[56], uint32_t a0, uint32_t a1, uint32_t a2, uint32_t a3, uint64_t db, int sd){
  asm volatile("{ .reg .pred p; setp.ne.b32 p, %61, 0;\n"
   "wgmma.mma_async.sync.aligned.m64n112k16.f32.bf16.bf16 {%0, %1, %2, %3, %4, %5, %6, %7, %8, %9, %10, %11, %12, %13, %14, %15, %16, %17, %18, %19, %20, %21, %22, %23, %24, %25, %26, %27, %28, %29, %30, %31, %32, %33, %34, %35, %36, %37, %38, %39, %40, %41, %42, %43, %44, %45, %46, %47, %48, %49, %50, %51, %52, %53, %54, %55}, {%56,%57,%58,%59}, %60, p, 1, 1, 0; }\n"
   : "+f"(d[0]), "+f"(d[1]), "+f"(d[2]), "+f"(d[3]), "+f"(d[4]), "+f"(d[5]), "+f"(d[6]), "+f"(d[7]), "+f"(d[8]), "+f"(d[9]), "+f"(d[10]), "+f"(d[11]), "+f"(d[12]), "+f"(d[13]), "+f"(d[14]), "+f"(d[15]), "+f"(d[16]), "+f"(d[17]), "+f"(d[18]), "+f"(d[19]), "+f"(d[20]), "+f"(d[21]), "+f"(d[22]), "+f"(d[23]), "+f"(d[24]), "+f"(d[25]), "+f"(d[26]), "+f"(d[27]), "+f"(d[28]), "+f"(d[29]), "+f"(d[30]), "+f"(d[31]), "+f"(d[32]), "+f"(d[33]), "+f"(d[34]), "+f"(d[35]), "+f"(d[36]), "+f"(d[37]), "+f"(d[38]), "+f"(d[39]), "+f"(d[40]), "+f"(d[41]), "+f"(d[42]), "+f"(d[43]), "+f"(d[44]), "+f"(d[45]), "+f"(d[46]), "+f"(d[47]), "+f"(d[48]), "+f"(d[49]), "+f"(d[50]), "+f"(d[51]), "+f"(d[52]), "+f"(d[53]), "+f"(d[54]), "+f"(d[55]) : "r"(a0), "r"(a1), "r"(a2), "r"(a3), "l"(db), "r"(sd));
}
template<> __device__ __forceinline__ void wgmma_rs<128>(float (&d)[64], uint32_t a0, uint32_t a1, uint32_t a2, uint32_t a3, uint64_t db, int sd){
  asm volatile("{ .reg .pred p; setp.ne.b32 p, %69, 0;\n"
   "wgmma.mma_async.sync.aligned.m64n128k16.f32.bf16.bf16 {%0, %1, %2, %3, %4, %5, %6, %7, %8, %9, %10, %11, %12, %13, %14, %15, %16, %17, %18, %19, %20, %21, %22, %23, %24, %25, %26, %27, %28, %29, %30, %31, %32, %33, %34, %35, %36, %37, %38, %39, %40, %41, %42, %43, %44, %45, %46, %47, %48, %49, %50, %51, %52, %53, %54, %55, %56, %57, %58, %59, %60, %61, %62, %63}, {%64,%65,%66,%67}, %68, p, 1, 1, 0; }\n"
   : "+f"(d[0]), "+f"(d[1]), "+f"(d[2]), "+f"(d[3]), "+f"(d[4]), "+f"(d[5]), "+f"(d[6]), "+f"(d[7]), "+f"(d[8]), "+f"(d[9]), "+f"(d[10]), "+f"(d[11]), "+f"(d[12]), "+f"(d[13]), "+f"(d[14]), "+f"(d[15]), "+f"(d[16]), "+f"(d[17]), "+f"(d[18]), "+f"(d[19]), "+f"(d[20]), "+f"(d[21]), "+f"(d[22]), "+f"(d[23]), "+f"(d[24]), "+f"(d[25]), "+f"(d[26]), "+f"(d[27]), "+f"(d[28]), "+f"(d[29]), "+f"(d[30]), "+f"(d[31]), "+f"(d[32]), "+f"(d[33]), "+f"(d[34]), "+f"(d[35]), "+f"(d[36]), "+f"(d[37]), "+f"(d[38]), "+f"(d[39]), "+f"(d[40]), "+f"(d[41]), "+f"(d[42]), "+f"(d[43]), "+f"(d[44]), "+f"(d[45]), "+f"(d[46]), "+f"(d[47]), "+f"(d[48]), "+f"(d[49]), "+f"(d[50]), "+f"(d[51]), "+f"(d[52]), "+f"(d[53]), "+f"(d[54]), "+f"(d[55]), "+f"(d[56]), "+f"(d[57]), "+f"(d[58]), "+f"(d[59]), "+f"(d[60]), "+f"(d[61]), "+f"(d[62]), "+f"(d[63]) : "r"(a0), "r"(a1), "r"(a2), "r"(a3), "l"(db), "r"(sd));
}

#define BAR(i) (bars + 8u * (uint32_t)(i))

template <int G> __device__ __forceinline__ void conv_frags(uint32_t (&a)[12], uint32_t abase) {
#pragma unroll
  for (int i = 0; i < 12; i++) a[i] = lds32(abase + (G * 4 + i / 3) * 128 + (i % 3) * 4);
}
__device__ __forceinline__ void kv_prefetch(const __nv_bfloat16* pf, int task) { prefetch_if(pf + 64 * (task & 31) * DM + 64 * (task >> 5), task < 320); }
__device__ __forceinline__ void kv_load(const Params& P, Scratch* S, int task, int tid, uint32_t (&k_)[19], uint32_t (&v_)[16], uint4& sk) {
  const int row = 64 * (task & 31) + 16 * (tid >> 5), ch = 64 * (task >> 5) + 2 * (tid & 31);
  const uint32_t* kp = (const uint32_t*)(P.k + (size_t)row * DM + ch);
  const uint32_t* vp = (const uint32_t*)(P.v + (size_t)row * DM + ch);
  const uint32_t* hp = row > 0 ? kp - 3 * (DM / 2) : S->zero;
  const int hs = row > 0 ? DM / 2 : 0;
  asm volatile("ld.global.nc.v4.u32 {%0,%1,%2,%3},[%4];" : "=r"(sk.x), "=r"(sk.y), "=r"(sk.z), "=r"(sk.w) : "l"(P.shk + ch * 4));
#pragma unroll
  for (int i = 0; i < 3; i++) k_[i] = ldg1(hp + i * hs);
#pragma unroll
  for (int i = 0; i < 16; i++) { k_[i + 3] = ldg1(kp + i * (DM / 2)); v_[i] = ldg1(vp + i * (DM / 2)); }
}
template <int SH> __device__ __forceinline__ void xb_prefetch(const Head& H, int id, int tid, int c0) {
  const int ri = tid >> SH, rr = 11 * id + ri - 16;
  const __nv_bfloat16* p = ri < 16 ? H.x + (size_t)(16 * min(id, 127) + ri) * DM : (rr < DM ? H.b0 : H.b1 - DM * DM) + (size_t)rr * DM;
  prefetch_if(p + c0 + 64 * (tid & ((1 << SH) - 1)), ri < 16 || (ri < 27 && rr < 2 * DM));
}
__device__ __forceinline__ uint4 lds4(uint32_t a) { uint4 v; asm volatile("ld.shared.v4.u32 {%0,%1,%2,%3},[%4];" : "=r"(v.x), "=r"(v.y), "=r"(v.z), "=r"(v.w) : "r"(a) : "memory"); return v; }
__device__ __forceinline__ void discretise(const Head& H, const Params& P, uint32_t sb, Role R, int lane, uint32_t e1) {
  const uint32_t dn = __ldg((const unsigned short*)P.ssmd + min(conv_ch(R.c, (lane + 7) & 7), DM - 1));
  const int c = 32 * min(R.cb(), 9) + lane;
  const uint32_t lr2 = ldg1(P.lre + 2 * c), li2 = ldg1(P.lim + 2 * c), ld2 = ldg1(P.ldt + 2 * c);
  asm volatile("st.shared.u32 [%0],%1;" ::"r"(sb + MISC_OFF + 4 * (lane & 7)), "r"((lane & 7) ? dn : e1) : "memory");
#pragma unroll 1
  for (int i = 0; i < 2; i++) {
    const float lr = bf_hi(lr2 << (16 - 16 * i)), li = bf_hi(li2 << (16 - 16 * i));
    const float2 lb = lam_bar(lr, li, bf_hi(ld2 << (16 - 16 * i)));
    const float nx = lb.x - 1.f, ny = lb.y, inv = 2.f * frcp(lr * lr + li * li), cx = (nx * lr + ny * li) * inv, cy = (ny * lr - nx * li) * inv;
    const bool sw = !H.swap;
    asm volatile("st.shared.v4.f32 [%0],{%1,%2,%3,%4};" ::"r"(sb + LAM_OFF + 32 * lane + 16 * i), "f"(lb.x), "f"(sw ? -lb.y : lb.y), "f"(sw ? -cy : cx), "f"(sw ? cx : -cy) : "memory");
  }
  __syncwarp();
}
__device__ __forceinline__ void aux_prep(const Head& H, const Params& P, uint32_t sb, Role R, int tid, long long t_start) {
  Scratch* const S = H.s;
  const uint32_t bars = sb + BAR_OFF;
  const int w = tid >> 5, lane = tid & 31, tb = R.tb(), cb = R.cb(), id = R.c & 255;
  uint32_t k_[19], v_[16];
  uint4 sk;
  int task = R.b() < R.nprep() ? R.b() : 320;
  delay(KVDLY);
  PROFC(tid == 0, 345);
  kv_load(P, S, min(task, 319), tid, k_, v_, sk);
  const __nv_bfloat16* pf = (tid < 64 ? P.k : P.v) + (tid & 63) * DM;
  float s = 0.f, s2 = 0.f, sr = 0.f;
  const uint32_t xo = sb + 16 * tid + min(R.sm(), 9) * 2048, wo = sb + 16 * tid + (tb & 1) * 8192 + (tb & 6) * 1024;
#pragma unroll 1
  for (int r = 0; r < 3; r++) {
    if (r < 2) {
#pragma unroll 1
      for (int kb = 6 * r; kb < 6 + 4 * r; kb++) {
        mbar_wait(BAR(B_F1 + kb));
        const uint4 m = lds4(xo + ((uint32_t)(XTAB0 >> (6 * kb)) & 63) * 4096), n = lds4(wo + ((uint32_t)(WTAB0 >> (6 * kb)) & 63) * 4096);
        const uint32_t xw[4] = {m.x, m.y, m.z, m.w}, bw[4] = {n.x, n.y, n.z, n.w};
#pragma unroll
        for (int i = 0; i < 4; i++) {
          const float a = bf_lo(xw[i]), c = bf_hi(xw[i]);
          s += a + c; s2 = fmaf(a, a, fmaf(c, c, s2)); sr += bf_lo(bw[i]) + bf_hi(bw[i]);
        }
        asm volatile("" : "+f"(s), "+f"(s2), "+f"(sr));
        __syncwarp();
        if (kb == XPFAT) xb_prefetch<2>(H, id, tid, 384);
        mbar_arrive_if(BAR(B_AX + (kb >> 2)), (kb == 2 || kb == 5) && lane == 0);
      }
      PROFC(tid == 0, 346 + r);
    }
    if (r == 1) {
      mbar_wait(BAR(B_LM));
      const uint32_t tag = lds32(sb + MISC_OFF) & 1;
#pragma unroll
      for (int o = 1; o <= 4; o <<= 1) { s += __shfl_xor_sync(0xffffffff, s, o); s2 += __shfl_xor_sync(0xffffffff, s2, o); sr += __shfl_xor_sync(0xffffffff, sr, o); }
      const int ri = tid >> 3;
      const float m = s * (1.f / DM), rs = frcp(bf_rn(fsqrt(bf_rn(bf_rn(fmaxf(s2 * (1.f / DM) - m * m, 0.f)) + 1e-5f))));
      asm volatile("st.shared.v2.u32 [%0],{%1,%2};" ::"r"(sb + TMP_OFF + 8 * ri), "r"(tagf(rs, tag)), "r"(tagf(-bf_rn(m) * rs, tag)) : "memory");
      asm volatile("st.shared.u32 [%0],%1;" ::"r"(sb + TMP_OFF + 128 + 8 * (ri & 7) + 4 * (ri >> 3)), "r"(tagf(sr, tag)) : "memory");
      bar_sync(3, 128);
      const uint4 o = lds4(sb + TMP_OFF + 16 * (tid & 15));
      asm volatile("{ .reg .pred p; setp.ne.u32 p, %5, 0; @p st.relaxed.gpu.global.v4.u32 [%0],{%1,%2,%3,%4}; }"
                   ::"l"(tid < 8 ? S->S + 160 * tb + (tb < 12 ? 40 : 32) * (tid & 3) + 4 * R.sm() + 2 * (tid >> 2) : S->RS + (8 * cb + 4 * (tb & 1) + (tb >> 1)) * 16 + 2 * (tid - 8)),
                   "r"(o.x), "r"(o.y), "r"(o.z), "r"(o.w), "r"((uint32_t)(tid < 8 ? R.sm() < 10 : tid < 12 && tb < 8)) : "memory");
      PROFC(tid == 0, 3);
    }
    if (task >= 320) continue;
    const uint32_t T0 = __byte_perm(sk.x, sk.z, 0x5410), T1 = __byte_perm(sk.x, sk.z, 0x7632);
    const uint32_t T2 = __byte_perm(sk.y, sk.w, 0x5410), T3 = __byte_perm(sk.y, sk.w, 0x7632);
    uint32_t o[16];
#pragma unroll
    for (int t = 0; t < 16; t += 2) {
      const uint32_t a = hmul2(hadd2(hadd2(hadd2(hmul2(k_[t], T3), hmul2(k_[t + 1], T2)), hmul2(k_[t + 2], T1)), hmul2(k_[t + 3], T0)), v_[t]);
      const uint32_t c = hmul2(hadd2(hadd2(hadd2(hmul2(k_[t + 1], T3), hmul2(k_[t + 2], T2)), hmul2(k_[t + 3], T1)), hmul2(k_[t + 4], T0)), v_[t + 1]);
      const int wd = ((7 - t / 2) >> 1) + 4 * ((7 - t / 2) & 1);
      o[wd] = __byte_perm(c, a, 0x5410); o[8 + wd] = __byte_perm(c, a, 0x7632);
      asm volatile("" : "+r"(o[wd]), "+r"(o[8 + wd]));
      if (t == PFAT) kv_prefetch(pf, task + (1 + PFD) * R.nprep());
    }
    PROFC(tid == 0, 330 + 2 * r);
    const int ph = task & 1;
    task += R.nprep();
    if (task < 320) kv_load(P, S, task, tid, k_, v_, sk);
    mbar_wait(BAR(B_E1 + 3)); mbar_wait(BAR(B_AX + 1));
#pragma unroll
    for (int i = 0; i < 4; i++) {
      const int row = 2 * lane + (i >> 1);
      asm volatile("st.shared.v4.u32 [%0],{%1,%2,%3,%4};" ::"r"(sb + KS_OFF + r * 8192 + row * 128 + (((2 * w + ((i & 1) ^ ph)) ^ (row & 7)) << 4)),
                   "r"(o[4 * i]), "r"(o[4 * i + 1]), "r"(o[4 * i + 2]), "r"(o[4 * i + 3]) : "memory");
    }
    __syncwarp();
    mbar_arrive_if(BAR(B_PS + r), lane == 0);
    PROFC(tid == 0, 331 + 2 * r);
  }
  PROFC(tid == 0, 40);
}
#define SPLIT(G) asm volatile("{ .reg .pred p; .reg .u32 r; L: mov.u32 r, %%clock; setp.eq.u32 p, r, %0; @p bra.uni L; }" ::"n"(G) : "memory")
template <bool AUX>
__device__ __forceinline__ void conv_loop(uint32_t sb, uint32_t rc, int wg, int tid, long long t_start) {
  sb = opaque(sb); rc = opaque(rc);
  const uint32_t bars = sb + BAR_OFF;
  int slot = AUX ? 0 : wg + 2;
  mbar_wait(BAR(B_LM));
#pragma unroll 1
  while (slot < (int)((rc >> 10) & 7)) {
    tid = opaque(tid);
    const int w = tid >> 5, lane = tid & 31, g = lane >> 2, q = lane & 3;
    const uint32_t Dn = lds32(sb + MISC_OFF + 4 + 4 * slot);
    const uint32_t d0 = (g == 1 && q == 3 - w) ? Dn : 0, d1 = (g == 0 && q == 3 - w) ? Dn : 0;
    const uint32_t cb_ = conv_buf(sb, slot), c0 = cb_ + KC_OFS;
    const uint32_t abase = c0 + 2 * (2 * (g & 1) + 4 * w + 16 * (g >> 1) + 4 * q);
    const uint64_t bd = make_desc(cb_ + KV_PAD, 16, 256, 3);
    const bool hi = lane & 16, s1 = lane & 8;
    const int qo = hi ? (q + 1) & 3 : q;
    const int srcA = hi ? (lane & 12) | ((q + 1) & 3) : (lane & 12) | 16 | ((q + 3) & 3);
    const bool h3 = hi && q == 3, wrap = s1 && qo == 3, back = wrap && hi;
    const bool chi = wrap ? !hi : hi;
    const int cq = s1 ? (qo + 1) & 3 : qo;
    const int srcB = (lane & 4) | (s1 ? 0 : 8) | (chi ? 16 | ((cq + 3) & 3) : cq);
    const uint32_t gp = c0 + 16 * (2 * (g & 1) + 4 * w) + (chi ? 256 : 0) + 2 * (2 * cq + (s1 ? 0 : 1));
    uint32_t a[12], f[16], o[8];
    float S[4], T[4], U[2], keep[2], pv[2] = {0.f, 0.f}, pr[4] = {0.f, 0.f, 0.f, 0.f};
    float e0[64], e1[56], e2[48], e3[40], e4[32], e5[24], e6[16], e7[8];
#define UNR _Pragma("unroll")
#define PERM() UNR for (int i = 0; i < 4; i++) { f[4 * i] = __byte_perm(a[3 * i], a[3 * i + 1], 0x5432); f[4 * i + 1] = a[3 * i + 1]; \
                                                 f[4 * i + 2] = __byte_perm(a[3 * i + 1], a[3 * i + 2], 0x5432); f[4 * i + 3] = a[3 * i + 2]; }
#define MMA(N, E) UNR for (int i = 0; i < 4; i++) wgmma_rs<N>(E, f[4 * i], f[4 * i + 1], f[4 * i + 2], f[4 * i + 3], bd - 8 * i, 1); wg_commit();
#define L1(c) UNR for (int i = 0; i < 4; i++) { const float ev = c[i], od = c[4 + i]; S[i] = hi ? (h3 ? ev : od) : ev; \
                                                T[i] = __shfl_sync(0xffffffff, hi ? (h3 ? pr[i] : ev) : od, srcA); pr[i] = od; }
#define L1E() UNR for (int i = 0; i < 4; i++) S[i] += T[i];
#define L2() UNR for (int h = 0; h < 2; h++) { keep[h] = back ? pv[h] : S[2 * h + 1]; pv[h] = S[2 * h + 1]; U[h] = __shfl_sync(0xffffffff, S[2 * h], srcB); }
#define L2E(j) o[j] = pack_bf(keep[0] + U[0], keep[1] + U[1]);
#define GRP(G, N, P, E) UNR for (int i = 0; i < N / 2; i++) asm volatile("mov.b32 %0,%1;" : "=f"(E[i]) : "f"(P[i + 8])); \
    wg_fence(); if (G < 7) conv_frags<(G + 1) & 7>(a, abase); if (G >= 2) { L2() } L1(P) MMA(N, E) SPLIT(G); \
    if (G < 7) { PERM() } if (G >= 2) { L2E((G + 6) & 7) } L1E() wg_wait<0>(); fence_regs(E);
    PROFC(tid == 0, 300 + 4 * slot);
    mbar_wait(BAR(B_KF + slot));
    PROFC(tid == 0, 301 + 4 * slot);
    conv_frags<0>(a, abase);
    wg_fence();
    wgmma_rs<128>(e0, d0 << 16, d0, d1 << 16, d1, bd, 0);
    PERM() conv_frags<1>(a, abase); wg_fence(); MMA(128, e0) SPLIT(0); PERM() wg_wait<0>(); fence_regs(e0);
    GRP(1, 112, e0, e1) GRP(2, 96, e1, e2) GRP(3, 80, e2, e3) GRP(4, 64, e3, e4) GRP(5, 48, e4, e5) GRP(6, 32, e5, e6) GRP(7, 16, e6, e7)
    PROFC(tid == 0, 302 + 4 * slot);
    L2() L1(e7) L2E(6) L1E() L2() L2E(7)
    bar_sync(wg + 1, 128);
#pragma unroll
    for (int jj = 0; jj < 8; jj++)
      asm volatile("st.shared.u16 [%0],%1; st.shared.u16 [%0+16],%2;" ::"r"(gp + jj * 512), "h"((uint16_t)o[jj]), "h"((uint16_t)(o[jj] >> 16)) : "memory");
#undef PERM
#undef MMA
#undef L1
#undef L1E
#undef L2
#undef L2E
#undef GRP
    PROFC(tid == 0, 303 + 4 * slot);
    __syncwarp();
    if (lane == 0) mbar_arrive(BAR(B_GS + slot));
    if (!AUX) break;
    slot = 3 * slot + 1;
  }
}

__device__ __forceinline__ float flip(float v, uint32_t m) { return __uint_as_float(__float_as_uint(v) ^ m); }
__device__ __forceinline__ void g1_phase(const int LY, const Head& H, uint32_t sb, int wg, int tid, Role R, long long t_start) {
  Scratch* const S = H.s;
  tid = opaque(tid); sb = opaque(sb); R.v = opaque(R.v);
  const uint32_t bars = sb + BAR_OFF;
  const int cb = R.cb(), tb = R.tb();
  const int w = tid >> 5, lane = tid & 31, g = lane >> 2, q = lane & 3;
  const bool full = tb < 12;
  uint2* Eb = S->E + ((LY * 130 + cb) * 8 + 4 * wg + w) * 16 + g;
  float a[80];
#pragma unroll
  for (int i = 0; i < 80; i++) a[i] = 0.f;
  uint32_t rel = mapa(BAR(B_E1), lane ? R.wpart() : R.ubase() + (w & (R.ugs() - 1)));
  const bool rels = lane == 0 || (tid == 1 && wg != R.wlo());
  {
    uint64_t tw = LY ? WTAB1 : WTAB0, tx = LY ? XTAB1 : XTAB0;
    uint32_t bf = BAR(B_F1);
    if (tid == 0 && wg == 0 && !LY) PROF(351);
    mbar_wait(bf, LY);
    if (tid == 0 && wg == 0) PROF(LY ? 20 : 4);
#pragma unroll 1
    for (int kb = 0; kb < 10; kb++) {
      const uint64_t da = make_desc(sb + ((uint32_t)tw & 63) * 4096 + wg * 8192, 16, 1024, 1);
      const uint64_t db = make_desc(sb + ((uint32_t)tx & 63) * 4096, 16, 1024, 1);
      wg_fence();
#pragma unroll
      for (int kk = 0; kk < 4; kk++) wgmma_ss160(a, da + 2 * kk, db + 2 * kk, 1);
      wg_commit();
      wg_wait<1>();
      if (kb > 0) { if (rels) mbar_arrive_at(rel); rel += 8; }
      bf += 8; tw >>= 6; tx >>= 6;
      if (kb < 9) mbar_wait(bf, LY);
    }
  }
  if (tid == 0 && wg == 0) PROF(LY ? 19 : 2);
  mbar_wait(BAR(B_LM));
  const uint32_t tag = lds32(sb + MISC_OFF) & 1;
  if (q == 3) st_rlx2(Eb + tb * 1280, tag ^ 1, tag ^ 1);
  float2 lam, mu, mu2;
  float rs0, rs1;
  const uint32_t lamp = sb + LAM_OFF + 16 * (32 * wg + 8 * w + g);
  {
    const uint2* rp = S->RS + (8 * cb + 4 * wg + w) * 16 + g;
    uint2 v = ld_rlx2(rp);
    asm volatile("ld.shared.v2.f32 {%0,%1},[%2];" : "=f"(lam.x), "=f"(lam.y) : "r"(lamp));
    const float2 l2 = cmul(lam, lam), l4 = cmul(l2, l2), l8 = cmul(l4, l4), l16 = cmul(l8, l8), l32 = cmul(l16, l16);
    mu = full ? cmul(l32, l8) : l32; mu2 = cmul(mu, mu);
#pragma unroll 1
    for (int it = 0; it < SPIN && __any_sync(0xffffffff, untagged(v, tag)); it++) v = ld_rlx2(rp);
    rs0 = untag(v.x); rs1 = untag(v.y);
  }
  mbar_wait(BAR(B_ST), LY);
  const uint32_t ssm = sb + SSM_OFF + q * (full ? 336 : 272);
  wg_wait<0>(); fence_regs(a);
  if (rels) mbar_arrive_at(rel);
  if (tid == 0 && wg == 0) PROF(LY ? 21 : 5);
  float2 p = make_float2(0.f, 0.f);
#pragma unroll
  for (int j = 0; j < 20; j++) {
    if (j < 16 || full) {
      float4 sv;
      asm volatile("ld.shared.v4.f32 {%0,%1,%2,%3},[%4];" : "=f"(sv.x), "=f"(sv.y), "=f"(sv.z), "=f"(sv.w) : "r"(ssm + 16 * j));
#pragma unroll
      for (int e = 0; e < 2; e++) {
        const int o = 4 * j + e;
        const float r = e ? sv.z : sv.x, nm = e ? sv.w : sv.y;
        a[o] = fmaf(a[o], r, nm * rs0); a[o + 2] = fmaf(a[o + 2], r, nm * rs1);
        p = cfma(lam, p, make_float2(a[o], a[o + 2]));
      }
    }
  }
  {
    float2 t = make_float2(__shfl_up_sync(0xffffffff, p.x, 1, 4), __shfl_up_sync(0xffffffff, p.y, 1, 4));
    if (q >= 1) p = cfma(mu, t, p);
    t = make_float2(__shfl_up_sync(0xffffffff, p.x, 2, 4), __shfl_up_sync(0xffffffff, p.y, 2, 4));
    if (q >= 2) p = cfma(mu2, t, p);
  }
  if (q == 3 && full) st_rlx2(Eb + tb * 1280, tagf(p.x, tag), tagf(p.y, tag));
  if (tid == 0 && wg == 1) PROF(96 + 64 * LY);
  uint2 ev[3];
#pragma unroll
  for (int i = 0; i < 3; i++) { const int j = tb - 1 - q - 4 * i; ev[i] = j >= 0 ? ld_rlx2(Eb + j * 1280) : make_uint2(tag, tag); }
  float2 x = make_float2(__shfl_up_sync(0xffffffff, p.x, 1, 4), __shfl_up_sync(0xffffffff, p.y, 1, 4));
  if (q == 0) x = make_float2(0.f, 0.f);
  float c0, c1;
  asm volatile("ld.shared.v2.f32 {%0,%1},[%2+8];" : "=f"(c0), "=f"(c1) : "r"(lamp));
  const float c2 = -flip(c1, H.swap), c3 = flip(c0, H.swap);
#pragma unroll
  for (int i = 0; i < 40; i++) {
    const int o = 4 * (i >> 1) + (i & 1);
    const float u = a[o], v = a[o + 2];
    a[o] = fmaf(c0, u, c1 * v); a[o + 2] = fmaf(c2, u, c3 * v);
  }
  fence_regs(a);
  float2 mq, om4, fq;
  {
    asm volatile("" : "+f"(lam.x), "+f"(lam.y));
    const float2 one = make_float2(1.f, 0.f), l2 = cmul(lam, lam), l4 = cmul(l2, l2), l8 = cmul(l4, l4), l16 = cmul(l8, l8);
    const float2 l80 = full ? mu2 : cmul(mu2, l16), om = cmul(l80, l80), om2 = cmul(om, om);
    mq = cmul((q & 1) ? mu : one, (q & 2) ? mu2 : one);
    om4 = cmul(om2, om2); fq = cmul((q & 1) ? om : one, (q & 2) ? om2 : one);
  }
  mbar_wait(BAR(B_E1 + 9), LY);
#pragma unroll 1
  for (int it = 0; it < SPIN; it++) {
    const bool m0 = untagged(ev[0], tag), m1 = untagged(ev[1], tag), m2 = untagged(ev[2], tag);
    if (!__any_sync(0xffffffff, m0 || m1 || m2)) break;
    if (m0) ev[0] = ld_rlx2(Eb + (tb - 1 - q) * 1280);
    if (m1) ev[1] = ld_rlx2(Eb + (tb - 5 - q) * 1280);
    if (m2) ev[2] = ld_rlx2(Eb + (tb - 9 - q) * 1280);
  }
  if (tid == 0 && wg == 1) PROF(97 + 64 * LY);
  float2 c = make_float2(untag(ev[2].x), untag(ev[2].y));
#pragma unroll
  for (int i = 1; i >= 0; i--) c = cfma(om4, c, make_float2(untag(ev[i].x), untag(ev[i].y)));
  c = cmul(fq, c);
#pragma unroll
  for (int s = 1; s <= 2; s <<= 1) { c.x += __shfl_xor_sync(0xffffffff, c.x, s); c.y += __shfl_xor_sync(0xffffffff, c.y, s); }
  c = cfma(mq, c, x);
  float2 z = make_float2(fmaf(c0, c.x, c1 * c.y), fmaf(c2, c.x, c3 * c.y));
  if (tid == 0 && wg == 0) PROF(LY ? 22 : 6);
  const float2 lc = make_float2(lam.x, flip(lam.y, H.swap));
  const uint32_t hp = sb + R_OFF + ((lane >> 3) & 1) * 20480 + (lane >> 4) * 1024 + (lane & 7) * 128 + (((4 * wg + w) ^ (lane & 7)) << 4);
#pragma unroll
  for (int j = 0; j < 20; j += 2) {
    if (j < 16 || full) {
      uint32_t o[4];
#pragma unroll
      for (int i = 0; i < 2; i++) {
        const float2 z0 = cfma(lc, z, make_float2(a[4 * (j + i)], a[4 * (j + i) + 2]));
        z = cfma(lc, z0, make_float2(a[4 * (j + i) + 1], a[4 * (j + i) + 3]));
        o[2 * i] = pack_bf(z0.x, z.x); o[2 * i + 1] = pack_bf(z0.y, z.y);
      }
      asm volatile("stmatrix.sync.aligned.m8n8.x4.trans.shared.b16 [%0], {%1,%2,%3,%4};" ::"r"(hp + j * 1024), "r"(o[0]), "r"(o[1]), "r"(o[2]), "r"(o[3]) : "memory");
      if (j & 2) { __syncwarp(); if (lane == 0) mbar_arrive(BAR(B_SH + j / 4)); }
    }
  }
  if (tid == 0 && wg == 0) PROF(LY ? 23 : 7);
}

#define IDX(J, c, h) (8 * (J) + 4 * ((c) >> 1) + 2 * (h) + ((c) & 1))
__device__ __forceinline__ void resid_init(const Head& H, const Params& P, int wg, int tid, Role R, float (&acc)[40], uint32_t tag) {
  tid = opaque(tid);
  const int b = min(R.b(), 127), t0 = 128 * (b >> 3) + 16 * ((tid & 31) >> 2) + 8 * wg + 2 * (tid >> 5), d0 = 80 * (b & 7) + 4 * (tid & 3);
  uint2 x[10], d[5];
  uint4 s = ld_rlx4(H.s->S + t0);
#pragma unroll
  for (int i = 0; i < 10; i++) x[i] = ldg2(H.x + (size_t)(t0 + (i & 1)) * DM + d0 + 16 * (i >> 1));
#pragma unroll
  for (int J = 0; J < 5; J++) d[J] = ldg2(P.dskip + d0 + 16 * J);
#pragma unroll 1
  for (int it = 0; it < SPIN && R.b() < 128 && __any_sync(0xffffffff, untagged(s, tag)); it++) s = ld_rlx4(H.s->S + t0);
#pragma unroll
  for (int i = 0; i < 10; i++) {
    const int J = i >> 1, h = i & 1;
    const float rs = untag(h ? s.z : s.x), nm = untag(h ? s.w : s.y);
    const float x0 = bf_lo(x[i].x), x1 = bf_hi(x[i].x), x2 = bf_lo(x[i].y), x3 = bf_hi(x[i].y);
    const uint32_t s0 = hmul2(pack_bf(fmaf(x0, rs, nm), fmaf(x1, rs, nm)), d[J].x), s1 = hmul2(pack_bf(fmaf(x2, rs, nm), fmaf(x3, rs, nm)), d[J].y);
    acc[IDX(J, 0, h)] = x0 + bf_lo(s0); acc[IDX(J, 1, h)] = x1 + bf_hi(s0); acc[IDX(J, 2, h)] = x2 + bf_lo(s1); acc[IDX(J, 3, h)] = x3 + bf_hi(s1);
  }
}

__device__ __forceinline__ void g2_phase(const int LY, const Params& P, Scratch* S, uint32_t sb, int wg, int tid, Role R, float (&acc)[40], long long t_start) {
  tid = opaque(tid); sb = opaque(sb); R.v = opaque(R.v);
  const uint32_t tag = lds32(sb + MISC_OFF) & 1;
  const uint32_t bars = sb + BAR_OFF;
  const int b = R.b(), tb2 = b >> 3, db_ = b & 7;
  const int w = tid >> 5, lane = tid & 31, g = lane >> 2, q = lane & 3;
  const int t0 = 128 * tb2 + 16 * g + 8 * wg + 2 * w;
  const int d0 = 80 * db_ + 4 * q, mrow = 64 * wg + 16 * w + g;
#define GATE(J, c, h) (((c) & 1) ? bf_hi(G[4 * (J) + 2 * (h) + ((c) >> 1)]) : bf_lo(G[4 * (J) + 2 * (h) + ((c) >> 1)]))
  uint32_t* Mb = S->M + ((2 * LY * 16 + tb2) * 8) * 256 + (wg * 4 + w) * 32 + (2 * g + (q & 1)) * 2 + (q >> 1);
  st_rlx(Mb + db_ * 256, tag ^ 1);
  if (LY == 0) st_rlx(Mb + (16 * 8 + db_) * 256, tag ^ 1);
  uint2 dl[5];
#pragma unroll
  for (int J = 0; J < 5; J++) dl[J] = __ldg((const uint2*)(P.dskip + d0 + 16 * J));
  uint32_t rel = mapa(BAR(B_E2), lane ? ((w & 1) ? R.wpart() : R.rank()) : R.cs() == 8 ? 4 * wg + w : wg);
  const bool rels = lane == 0 || (lane == 1 && w < 2);
  {
    uint64_t sl = LY ? CSLOT1 : CSLOT0;
    sl |= sl << 48;
    uint32_t bf = BAR(B_F2), st = 0;
    mbar_wait(bf, LY);
    if (tid == 0 && wg == 0) PROF(LY ? 25 : 10);
#pragma unroll 1
    for (int kp = 0; kp < 10; kp++) {
      const uint64_t da = make_desc(sb + H_OFF + st * 32768 + wg * 8192, 16, 1024, 1);
      const uint64_t db0 = make_desc(sb + ((uint32_t)sl & 15) * 10240, 16, 1024, 1), db1 = make_desc(sb + (((uint32_t)sl >> 4) & 15) * 10240, 16, 1024, 1);
      wg_fence();
#pragma unroll
      for (int kk = 0; kk < 4; kk++) wgmma_ss80(acc, da + 2 * kk, db0 + 2 * kk, 1);
#pragma unroll
      for (int kk = 0; kk < 4; kk++) wgmma_ss80(acc, da + 1024 + 2 * kk, db1 + 2 * kk, 1);
      wg_commit();
      wg_wait<1>();
      if (kp > 0) { if (rels && (LY == 0 || kp < 8)) mbar_arrive_at(rel); rel += 8; }
      bf += 8; st = st == 2 ? 0 : st + 1;
      sl = (sl >> 8) | ((sl >> 16) << 56);
      if (kp < 9) mbar_wait(bf, LY);
    }
  }
  uint32_t G[20];
  mbar_wait(BAR(B_GF), LY);
  __syncwarp();
  {
    const uint32_t gb = sb + G_OFF + wg * 10240;
    const int dr = 4 * ((lane & 7) >> 1) + (lane & 1) + 2 * ((lane >> 3) & 1), ck = 2 * w + (lane >> 4);
#pragma unroll
    for (int J = 0; J < 5; J++) {
      const int dd = 16 * J + dr;
      asm volatile("ldmatrix.sync.aligned.m8n8.x4.trans.shared.b16 {%0,%1,%2,%3},[%4];"
                   : "=r"(G[4 * J]), "=r"(G[4 * J + 1]), "=r"(G[4 * J + 2]), "=r"(G[4 * J + 3]) : "r"(gb + dd * 128 + ((ck ^ (dd & 7)) << 4)) : "memory");
    }
  }
  wg_wait<0>(); fence_regs(acc);
  if (LY == 0 && rels) mbar_arrive_at(rel);
  if (tid == 0 && wg == 0) PROF(LY ? 26 : 11);
  if (lane == 0) PROF(116 + 64 * LY + wg * 4 + w);

  float mm[2], rr[2], m1 = 0.f;
#pragma unroll 1
  for (int rep = 0;; rep++) {
    float m[2][2];
#pragma unroll
    for (int h = 0; h < 2; h++) {
      m[h][0] = m[h][1] = 0.f;
#pragma unroll
      for (int J = 0; J < 5; J++)
#pragma unroll
        for (int c = 0; c < 4; c++) { const float xv = acc[IDX(J, c, h)]; m[h][0] += xv; m[h][1] = fmaf(xv, xv, m[h][1]); }
    }
    float r1[2];
#pragma unroll
    for (int i = 0; i < 2; i++) { const float snd = (q & 1) ? m[0][i] : m[1][i], kp = (q & 1) ? m[1][i] : m[0][i]; r1[i] = kp + __shfl_xor_sync(0xffffffff, snd, 1); }
    const float r2 = ((q & 2) ? r1[1] : r1[0]) + __shfl_xor_sync(0xffffffff, (q & 2) ? r1[0] : r1[1], 2);
    st_rlx(Mb + db_ * 256, tagf(r2, tag));
    if (lane == 0 && rep == 0) PROF(100 + 64 * LY + wg * 4 + w);
    uint32_t mv[8];
#pragma unroll
    for (int i = 0; i < 8; i++) mv[i] = ld_rlx(Mb + i * 256);
#pragma unroll 1
    for (int it = 0; it < SPIN; it++) {
      uint32_t miss = 0;
#pragma unroll
      for (int i = 0; i < 8; i++) miss |= ((mv[i] ^ tag) & 1) << i;
      if (!__any_sync(0xffffffff, miss)) break;
#pragma unroll
      for (int i = 0; i < 8; i++) if ((miss >> i) & 1) mv[i] = ld_rlx(Mb + i * 256);
    }
    bar_sync(4, 256);
    if (tid == 0 && wg == 0) PROF(LY ? 27 : 12 + 3 * rep);
    if (lane == 0 && rep == 0) PROF(108 + 64 * LY + wg * 4 + w);
    const float s = ((untag(mv[0]) + untag(mv[1])) + (untag(mv[2]) + untag(mv[3]))) + ((untag(mv[4]) + untag(mv[5])) + (untag(mv[6]) + untag(mv[7])));
    const float o = __shfl_xor_sync(0xffffffff, s, 2);
    const float S1 = (q & 2) ? o : s, S2 = (q & 2) ? s : o;
    const float mean = S1 * (1.f / DM), rs = frsqrt(fmaxf(S2 * (1.f / DM) - mean * mean, 0.f) + 1e-5f);
    const float mo = __shfl_xor_sync(0xffffffff, mean, 1), ro = __shfl_xor_sync(0xffffffff, rs, 1);
    mm[0] = (q & 1) ? mo : mean; mm[1] = (q & 1) ? mean : mo; rr[0] = (q & 1) ? ro : rs; rr[1] = (q & 1) ? rs : ro;
    if (rep) {
      if (db_ == 0) {
        if (q < 2) asm volatile("st.shared.v2.u32 [%0],{%1,%2};" ::"r"(sb + SSM_OFF + 8 * (t0 - 128 * tb2 + q)), "r"(tagf(rs, tag)), "r"(tagf((m1 - mean) * rs, tag)) : "memory");
        bar_sync(4, 256);
        if (wg == 0 && tid < 64) {
          uint4 v;
          asm volatile("ld.shared.v4.u32 {%0,%1,%2,%3},[%4];" : "=r"(v.x), "=r"(v.y), "=r"(v.z), "=r"(v.w) : "r"(sb + SSM_OFF + 16 * tid));
          st_rlx4(S->S + SEQ + 128 * tb2 + 2 * tid, v.x, v.y, v.z, v.w);
        }
      }
      break;
    }
#pragma unroll
    for (int h = 0; h < 2; h++)
#pragma unroll
      for (int J = 0; J < 5; J++)
#pragma unroll
        for (int c = 0; c < 4; c++) { const float xv = acc[IDX(J, c, h)]; acc[IDX(J, c, h)] = fmaf((xv - mm[h]) * rr[h], GATE(J, c, h), xv); }
    if (LY) break;
    m1 = mean;
#pragma unroll
    for (int i = 0; i < 10; i++) {
      const int J = i >> 1, h = i & 1;
      asm volatile("st.shared.v2.u32 [%0],{%1,%2};" ::"r"(sb + US_OFF + (mrow + 8 * h) * 160 + 32 * J + 8 * q),
                   "r"(pack_bf(acc[IDX(J, 0, h)] - mm[h], acc[IDX(J, 1, h)] - mm[h])), "r"(pack_bf(acc[IDX(J, 2, h)] - mm[h], acc[IDX(J, 3, h)] - mm[h])) : "memory");
    }
    __syncwarp();
    if (lane == 0) mbar_arrive(BAR(B_SG));
    if (tid == 0 && wg == 0) PROF(13);
    Mb += 16 * 8 * 256;
  }
  if (LY == 0) {
#pragma unroll
    for (int h = 0; h < 2; h++)
#pragma unroll
      for (int J = 0; J < 5; J++)
#pragma unroll
        for (int c = 0; c < 4; c++) {
          const float x2 = acc[IDX(J, c, h)];
          const uint32_t dw = (c & 2) ? dl[J].y : dl[J].x;
          acc[IDX(J, c, h)] = fmaf((x2 - mm[h]) * rr[h], (c & 1) ? bf_hi(dw) : bf_lo(dw), x2);
        }
  }
  else {
#pragma unroll
  for (int i = 0; i < 10; i++) {
    const int J = i >> 1, h = i & 1;
    asm volatile("st.shared.v4.f32 [%0],{%1,%2,%3,%4};" ::"r"(sb + OS_OFF + (mrow + 8 * h) * 320 + 64 * J + 16 * q),
                 "f"(acc[IDX(J, 0, h)]), "f"(acc[IDX(J, 1, h)]), "f"(acc[IDX(J, 2, h)]), "f"(acc[IDX(J, 3, h)]) : "memory");
  }
  __syncwarp();
  if (lane == 0) mbar_arrive(BAR(B_SG));
  }
  if (tid == 0 && wg == 0 && LY) PROF(28);
#undef IDX
#undef GATE
}

template <int I0, int I1> __device__ __forceinline__ void init_barriers(uint32_t bars) {
#pragma unroll
  for (int i = I0; i < I1; i++) mbar_init(BAR(i), bar_count(i));
}
__global__ void __cluster_dims__() __launch_bounds__(512, 1) fused_kernel(const Head H, const __grid_constant__ Params P) {
  extern __shared__ __align__(1024) uint8_t smem[];
  const uint32_t sb = opaque(smem_u32(smem)), bars = sb + BAR_OFF;
  const int wi = __shfl_sync(0xffffffff, threadIdx.x >> 5, 0), wg = wi >> 2, tid = threadIdx.x & 127;
  const int umap = blockIdx.x >= 96;
#define CLK(v)
  CLK(c_a);
  if (wi == 14) {
    if (elect_one()) { init_barriers<0, NBAR1>(bars); asm volatile("fence.mbarrier_init.release.cluster;" ::: "memory"); }
    __syncwarp();
  } else if (wi >= 12) prefetch_map(wi == 12 ? &P.mB : &P.mA[umap]);
  else if (wg == 2) xb_prefetch<1>(H, blockIdx.x + H.base, tid, 0);
  else if (P.role[blockIdx.x].w) return;
  CLK(c_b);
  asm volatile("barrier.cluster.arrive.relaxed.aligned;" ::: "memory");
  CLK(c_c);
  Role R;
  { const uint4 r = P.role[blockIdx.x]; R.v = r.x; R.c = r.y; R.p = r.z; }
  const int id = R.c & 255;
  const int tb = R.tb(), cb = R.cb(), b = R.b(), tb2 = b >> 3, db = b & 7, rank = R.rank();
  const bool has1 = tb <= 12, has2 = b < 128, full = tb < 12;
  Scratch* const S = H.s;
  unsigned* const epoch_p = &S->epoch[id * 8];
  const long long t_start = 0;
  if (wg < 2) {
    if (threadIdx.x == 0) PROF(50);
    asm volatile("griddepcontrol.launch_dependents;");
    bar_sync(6, 448);
    asm volatile("setmaxnreg.inc.sync.aligned.u32 176;");
    float xr[40];
#pragma unroll
    for (int i = 0; i < 40; i++) xr[i] = 0.f;
#pragma unroll 1
    for (int ly = 0; ly < 2; ly++) {
      if (has1) g1_phase(ly, H, sb, wg, tid, R, t_start);
      if (ly == 0) {
        conv_loop<false>(sb, R.c, wg, tid, t_start);
        if (tid == 0 && wg == 0) PROF(9);
        resid_init(H, P, wg, tid, R, xr, lds32(sb + MISC_OFF) & 1);
      }
      if (has2) g2_phase(ly, P, S, sb, wg, tid, R, xr, t_start);
    }
    if (tid == 0 && wg == 0) st_rlx(epoch_p, lds32(sb + MISC_OFF));
  } else if (wg == 2) {
    bar_sync(6, 448);
    if (has1) aux_prep(H, P, sb, R, tid, t_start);
    asm volatile("setmaxnreg.inc.sync.aligned.u32 136;");
    conv_loop<true>(sb, R.c, wg, tid, t_start);
    if (tid == 0) PROF(44);
  } else {
    if (threadIdx.x == 384) PROF(354);
    asm volatile("setmaxnreg.dec.sync.aligned.u32 24;");
    const int wlo = R.wlo(), whi = R.whi();
    const uint32_t wmask = R.wmask(), umask = R.umask(), f1bytes = full ? 36864 : 32768;
    if (wi < 14) {
      if (threadIdx.x == 384) PROF(340);
      asm volatile("barrier.cluster.wait.aligned;" ::: "memory");
      if (has1 && elect_one()) {
        uint64_t tab = wi == 12 ? WTAB0 : XTAB0;
        PROF(329 + wi);
#pragma unroll 1
        for (int kb = 0; kb < 6; kb++, tab >>= 6) {
          const uint32_t dst = sb + ((uint32_t)tab & 63) * 4096;
          if (wi == 12) {
#pragma unroll 1
            for (int h = wlo; h <= whi; h++) tma4d_mc(dst + h * 8192, &P.mB, kb * 64, 0, 0, 8 * cb + 4 * h, BAR(B_F1 + kb), wmask);
          } else {
            tma4d_mc(dst + R.uj() * 1024, &P.mA[umap], kb * 64, 0, 0, 80 * tb + R.uj(), BAR(B_F1 + kb), umask);
            mbar_expect_tx(BAR(B_F1 + kb), f1bytes);
          }
        }
      }
      if (!has1 && wi == 12) bar_sync(7, 64);
    } else {
      if (wi == 15 && elect_one()) { init_barriers<NBAR1, NBAR>(bars); asm volatile("fence.mbarrier_init.release.cluster;" ::: "memory"); }
      bar_sync(6, 448);
      if (!has1 && wi == 14) bar_sync(7, 64);
    }
    const unsigned e1 = ld_rlx(epoch_p) + 1;
    if (wi == 12) {
      if (elect_one()) {
#pragma unroll 1
        for (int ly = 0; ly < 2; ly++) {
#pragma unroll 1
          for (int kb = ly ? 0 : 6; kb < 10 && has1; kb++) {
            if (ly == 0) { mbar_wait(BAR(B_E1 + ((DEP0 >> (4 * kb - 24)) & 15))); mbar_wait(BAR(B_AX + (kb == 9))); }
            else if (has2) {
              if (kb < 6) mbar_wait(BAR(B_E2 + ((0x998764u >> (4 * kb)) & 15)));
              else { mbar_wait(BAR(B_GE)); mbar_wait(BAR(B_F1 + kb - 6), 1); }
            } else if (kb == 0) { mbar_wait(BAR(B_E1 + 9)); mbar_wait(BAR(B_CD + 1)); }
            const uint32_t dst = sb + ((uint32_t)((ly ? WTAB1 : WTAB0) >> (6 * kb)) & 63) * 4096;
#pragma unroll 1
            for (int h = wlo; h <= whi; h++) tma4d_mc(dst + h * 8192, &P.mB, kb * 64, 0, 0, 8 * cb + 4 * h, BAR(B_F1 + kb), wmask);
          }
          if (ly == 0) {
            if (has2) { prefetch_l2(P.cre + (size_t)5 * b * DM, 5 * DM * 2); prefetch_l2(P.cim + (size_t)5 * b * DM, 5 * DM * 2); }
#pragma unroll 1
            for (int s = 0; s < R.nch(); s++) prefetch_l2(P.ssmk + (size_t)R.ch(s) * SEQ, 4096);
            if (has1) mbar_wait(BAR(B_E1 + 5));
#pragma unroll 1
            for (int s = 0; s < R.nch(); s++) {
              const uint32_t cbuf = conv_buf(sb, s);
              mbar_expect_tx(BAR(B_KF + s), CH_BYTES);
              bulk_g2s(cbuf + KC_OFS + 32, P.ssmk + (size_t)R.ch(s) * SEQ, 4096, BAR(B_KF + s));
              bulk_g2s(cbuf, S->zero, KV_PAD, BAR(B_KF + s));
              bulk_g2s(cbuf + KC_OFS, S->zero, 32, BAR(B_KF + s));
              wait_cnt(&S->cnt[(C_KV + (R.ch(s) >> 6)) * 32], e1 * 32);
              if (s == 0) PROF(30);
              bulk_g2s(cbuf + KV_PAD, S->kv + (size_t)R.ch(s) * SEQ, 4096, BAR(B_KF + s));
            }
            PROF(31);
          }
          if (has2) {
#pragma unroll 1
            for (int kp = 0; kp < 10; kp++) {
              const uint32_t sig = (ly ? CSLOT1 : CSLOT0) >> (8 * (kp < 6 ? kp : kp - 6));
              mbar_wait(BAR(kp >= 6 ? B_E2 + kp - 6 : ly ? B_E1 + ((0x985421u >> (4 * kp)) & 15) : kp < 4 ? B_SH : B_CD + kp - 4), ly);
              mbar_expect_tx(BAR(B_F2 + kp), 20480 + 32768);
              tma5d(sb + (sig & 15) * 10240, &P.mC[0], kp * 64, db * 5, BAR(B_F2 + kp));
              tma5d(sb + ((sig >> 4) & 15) * 10240, &P.mC[1], kp * 64, db * 5, BAR(B_F2 + kp));
            }
            mbar_wait(BAR(B_E2 + 5), ly);
            wait_cnt(&S->cnt[(C_G + db) * 32], e1 * 80);
            mbar_expect_tx(BAR(B_GF), 20480);
            tma2d(sb + G_OFF, &P.mGT, tb2 * 128, db * 80, BAR(B_GF));
            tma2d(sb + G_OFF + 10240, &P.mGT, tb2 * 128 + 64, db * 80, BAR(B_GF));
          }
        }
      }
    } else if (wi == 13) {
      if (!has1) return;
      const int h0 = R.cs() == 8 ? rank : 4 * rank, lane = tid & 31;
#pragma unroll 1
      for (int ly = 0; ly < 2; ly++) {
        {
          const unsigned* fp = &S->flag[(F_U3 + 8 * ((160 * tb) >> 7) + (lane & (full ? 15 : 7))) * 32];
          uint32_t ready = ly ? __ballot_sync(0xffffffff, ld_rlx(fp) == e1) : ~0u;
          if (ly) mbar_wait(BAR(has2 ? B_GE : B_RF1));
#pragma unroll 1
          for (int kb = ly ? 0 : 6; kb < 10; kb++) {
            wait_flags(fp, e1, 0x101u * ((1u << (64 * kb / 80)) | (1u << ((64 * kb + 63) / 80))), ready);
            if (kb >= 3) mbar_wait(BAR(B_E1 + (ly ? kb - 3 : (DEP0 >> (4 * kb - 24)) & 15)), ly);
            mbar_wait(BAR(B_AX + (kb == 9)));
            if (elect_one()) {
              if (ly && kb == 0) PROF(34);
              tma4d_mc(sb + ((uint32_t)((ly ? XTAB1 : XTAB0) >> (6 * kb)) & 63) * 4096 + R.uj() * 1024, &P.mA[2 * ly + umap], kb * 64, 0, 0, 80 * tb + R.uj(),
                       BAR(B_F1 + kb), umask);
              mbar_expect_tx(BAR(B_F1 + kb), f1bytes);
            }
            __syncwarp();
          }
        }
        const int s0 = 128 * min(tb2, 15) / 160;
        const bool two = (128 * tb2 + 127) / 160 != s0;
        const unsigned* fp = &S->flag[(F_H + (ly * 13 + s0) * 10 + min(lane & 15, 9) + (two && lane >= 16 ? 10 : 0)) * 32];
        uint32_t ready = __ballot_sync(0xffffffff, ld_rlx(fp) == e1), st = 0;
        if (has2 || ly == 0) {
          mbar_wait(BAR(B_HD), ly);
          if (lane < 8) mbar_arrive_cl(BAR(B_RF1), lane & (R.cs() - 1));
        }
        if (has2) {
          mbar_wait(BAR(B_RF0), ly);
#pragma unroll 1
          for (int kp = 0; kp < 10; kp++) {
            wait_flags(fp, e1, 0x10001u << kp, ready);
            if (kp == 1) mbar_wait(BAR(B_RF1), ly);
            if (kp >= 3) mbar_wait(BAR(B_E2 + kp - 3), ly);
            if (elect_one()) {
              if (kp == 0) PROF(33 + 2 * ly);
#pragma unroll
              for (int hf = 0; hf < 2; hf++)
                tma4d_mc(sb + H_OFF + st * 32768 + hf * 16384 + h0 * 2048, &P.mH, kp * 128 + hf * 64, 0, 2 * h0,
                         ly * 16 + tb2, BAR(B_F2 + kp), (1u << R.cs()) - 1);
            }
            __syncwarp();
            st = st == 2 ? 0 : st + 1;
          }
        }
      }
    } else if (wi == 14) {
      if (!has1) return;
      if (elect_one()) { prefetch_map(&P.mC[0]); prefetch_map(&P.mC[1]); prefetch_map(&P.mH); prefetch_map(&P.mGT); prefetch_map(&P.mA[2 + umap]); }
      __syncwarp();
#pragma unroll 1
      for (int ly = 0; ly < 2; ly++) {
        const int lane = lane_id();
        mbar_wait(BAR(B_E1 + 6), ly);
        {
          const int l = lane - (full ? 0 : 16);
          const uint2* p = S->S + ly * SEQ + 160 * tb + 2 * l;
          uint4 v[3];
#pragma unroll 1
          for (int it = 0; it < SPIN; it++) {
            v[0] = ld_rlx4(p); v[1] = ld_rlx4(p + 64); v[2] = ld_rlx4(p + 96);
            if (!__any_sync(0xffffffff, untagged(v[0], e1 & 1) | untagged(v[1], e1 & 1) | untagged(v[2], e1 & 1))) break;
          }
#pragma unroll
          for (int i = 0; i < 3; i++) {
            const int pr = l + (i == 2 ? 48 : 32 * i);
            if (pr >= 0) asm volatile("st.shared.v4.u32 [%0],{%1,%2,%3,%4};" ::"r"(sb + SSM_OFF + 16 * (pr + ((pr * (full ? 205 : 256)) >> 12))), "r"(v[i].x & ~1u),
                                      "r"(v[i].y & ~1u), "r"(v[i].z & ~1u), "r"(v[i].w & ~1u) : "memory");
          }
          __syncwarp();
        }
        if (lane == 0) mbar_arrive(BAR(B_ST));
        mbar_wait(BAR(B_E1 + 9), ly);
        mbar_wait(BAR(B_XF));
        if (lane < 8 && has2) mbar_arrive_cl(BAR(B_RF0), lane & (R.cs() - 1));
        if (lane == 0) {
#pragma unroll 1
          for (int pc = 0; pc < (full ? 5 : 4); pc++) {
            mbar_wait(BAR(B_SH + pc), ly);
            fence_async();
#pragma unroll
            for (int i = 0; i < 2; i++) tma4d_store(&P.sH, sb + R_OFF + i * 20480 + pc * 4096, 128 * cb + 64 * i, 0, 0, ly * 1024 + 80 * tb + 4 * pc);
          }
          bulk_commit(); bulk_wait();
          PROF(ly ? 17 : 16);
          mbar_arrive(BAR(B_HD));
          release<1>();
          signal_flag(&S->flag[(F_H + (ly * 13 + tb) * 10 + cb) * 32], e1);
          PROF(ly ? 24 : 8);
        }
        if (lane == 0 && has2) {
          mbar_wait(BAR(B_SG), ly);
          fence_async();
          tma4d_store(ly ? &P.sO : &P.sU, sb + (ly ? OS_OFF : US_OFF), 80 * db, 0, 0, tb2);
          bulk_commit(); bulk_wait();
          if (ly == 0) { PROF(18); mbar_arrive(BAR(B_GE)); mbar_arrive_cl(BAR(B_GE), R.wpart()); release<2>(); signal_flag(&S->flag[(F_U3 + b) * 32], e1); }
          PROF(ly ? 29 : 14);
        }
        __syncwarp();
      }
    } else {
      discretise(H, P, sb, R, tid & 31, e1);
      if (elect_one()) {
        mbar_arrive(BAR(B_LM));
        PROF(348);
        if (b < R.nprep()) {
#pragma unroll 1
          for (int task = b, r = 0; task < 320; task += R.nprep(), r++) {
            mbar_wait(BAR(B_PS + r));
            fence_async();
            tma2d_store(&P.sK, sb + KS_OFF + r * 8192, 64 * (task & 31), 64 * (task >> 5));
            bulk_commit(); bulk_wait();
            PROF(42);
            release<4>();
            signal_cnt(&S->cnt[(C_KV + (task >> 5)) * 32], 1);
          }
          PROF(41);
        }
        mbar_arrive(BAR(B_XF));
#pragma unroll 1
        for (int s = 0; s < R.nch(); s++) {
          mbar_wait(BAR(B_GS + s));
          fence_async();
          bulk_s2g(S->gt + (size_t)R.ch(s) * SEQ, conv_buf(sb, s) + KC_OFS, 4096); bulk_commit();
          if (s == 1 || s == R.nch() - 1) { asm volatile("cp.async.bulk.wait_group.read 0;" ::: "memory"); mbar_arrive(BAR(B_CD + (s > 1))); }
        }
        bulk_wait();
        PROF(45);
        release<8>();
#pragma unroll 1
        for (int s = 0; s < R.nch(); s++) signal_cnt(&S->cnt[(C_G + R.ch(s) / 80) * 32], 1);
        PROF(46);
      }
    }
  }
}

typedef CUresult (*EncFn)(CUtensorMap*, CUtensorMapDataType, cuuint32_t, void*, const cuuint64_t*, const cuuint64_t*, const cuuint32_t*,
                          const cuuint32_t*, CUtensorMapInterleave, CUtensorMapSwizzle, CUtensorMapL2promotion, CUtensorMapFloatOOBfill);
bool enc(EncFn f, CUtensorMap* m, const void* base, int rank, const cuuint64_t* dims, const cuuint64_t* strides, const cuuint32_t* box, bool swz,
         bool f32 = false) {
  const cuuint32_t es[5] = {1, 1, 1, 1, 1};
  return f(m, f32 ? CU_TENSOR_MAP_DATA_TYPE_FLOAT32 : CU_TENSOR_MAP_DATA_TYPE_BFLOAT16, rank, const_cast<void*>(base), dims, strides, box, es,
           CU_TENSOR_MAP_INTERLEAVE_NONE, swz ? CU_TENSOR_MAP_SWIZZLE_128B : CU_TENSOR_MAP_SWIZZLE_NONE, CU_TENSOR_MAP_L2_PROMOTION_L2_256B,
           CU_TENSOR_MAP_FLOAT_OOB_FILL_NONE) == CUDA_SUCCESS;
}
void make_roles(Params& P, bool big) {
  for (uint32_t bx = 0; bx < (big ? 120u : 12u); bx++) {
    const uint32_t c = bx >> 3, r = bx & 7, id = big ? bx : 120 + bx;
    const uint32_t vA = c < 12 ? (2 * (c >> 1) + (r >> 2)) | (4 * (c & 1) + (r & 3)) << 4 | (r & 4) << 16 | 4 << 19 | (r ^ 4) << 22
                               : (4 * (c - 12) + (r >> 1)) | (8 + (r & 1)) << 4 | (r & 6) << 16 | 2 << 19 | (r ^ 2) << 22;
    const uint32_t vB = (bx < 10 ? 12 : 13) | bx << 4 | 2 << 19 | (bx & 1) << 22 | (bx & 1) << 26;
    P.role[bx].x = (big ? vA | r << 26 | 1u << 29 : vB) | id << 8;
    P.role[bx].y = id | (big ? 5 : bx < 8 ? 3 : 4) << 10 | 120 << 13 | 132 << 21 | (big ? 4u : 3u) << 29;
    const uint32_t v = P.role[bx].x, cb = (v >> 4) & 15, rank = (v >> 26) & 7, ubase = (v >> 16) & 7, ugs = (v >> 19) & 7, wp = (v >> 22) & 7;
    const uint32_t wlo = rank > wp, whi = wp != rank ? wlo : 1, wmask = 1u << rank | 1u << wp;
    const uint32_t uj = (rank - ubase) * (!big ? 8 : ugs == 4 ? 5 : 10), sm = big ? (0x7296418530ull >> (4 * cb)) & 15 : bx < 8 ? 4 * (bx & 1) + (bx >> 1) : 15;
    P.role[bx].z = wlo | whi << 1 | wmask << 2 | ((1u << ugs) - 1) << (10 + ubase) | uj << 20 | sm << 25;
    P.role[bx].w = 0;
  }
}
void launch(const Head& H, const Params& P, int grid, int cs, bool dependent) {
  cudaLaunchConfig_t cfg = {};
  cfg.gridDim = grid; cfg.blockDim = 512; cfg.dynamicSmemBytes = SMEM_BYTES; cfg.stream = cudaStreamPerThread;
  cudaLaunchAttribute at[2];
  at[0].id = cudaLaunchAttributeClusterDimension; at[0].val.clusterDim.x = cs; at[0].val.clusterDim.y = 1; at[0].val.clusterDim.z = 1;
  at[1].id = cudaLaunchAttributeProgrammaticStreamSerialization; at[1].val.programmaticStreamSerializationAllowed = 1;
  cfg.attrs = at; cfg.numAttrs = dependent ? 2 : 1;
  cudaLaunchKernelEx(&cfg, fused_kernel, H, P);
}

}

extern "C" void kernel_launch(void* const* d_in, const int* in_sizes, int n_in, void* d_out, int out_size) {
  (void)in_sizes; (void)n_in; (void)out_size;
  typedef const __nv_bfloat16* cb;
  void* fp = nullptr; cudaDriverEntryPointQueryResult qr;
  cudaGetDriverEntryPoint("cuTensorMapEncodeTiled", &fp, cudaEnableDefault, &qr);
  EncFn f = (EncFn)fp;
  Scratch* sp = nullptr;
  cudaGetSymbolAddress((void**)&sp, g_scr);
  void *pu = sp->u, *ph = sp->h, *pgt = sp->gt;
  Params P;
  Head H;
  H.s = sp; H.x = (cb)d_in[0]; H.swap = (uintptr_t)d_in[4] < (uintptr_t)d_in[3] ? 0 : 0x80000000u; H.b0 = (cb)d_in[H.swap ? 3 : 4]; H.b1 = (cb)d_in[H.swap ? 4 : 3];
  for (int i = 0; i < 2; i++) {
    const cuuint64_t d[4] = {640, 8, 2, 80}, s[3] = {1280, (cuuint64_t)((uintptr_t)H.b1 - (uintptr_t)H.b0), 8 * 1280}; const cuuint32_t bx[4] = {64, 8, 2, 4};
    if (enc(f, &P.mB, H.b0, 4, d, s, bx, true)) break;
    cudaMemcpyAsync(sp->bcopy, H.b0, DM * DM * 2, cudaMemcpyDeviceToDevice, cudaStreamPerThread);
    cudaMemcpyAsync(sp->bcopy + DM * DM, H.b1, DM * DM * 2, cudaMemcpyDeviceToDevice, cudaStreamPerThread);
    H.b0 = sp->bcopy; H.b1 = sp->bcopy + DM * DM;
  }
  {
    const cuuint64_t d[5] = {640, 2, 4, 2, 40}, s[4] = {1280, 4 * 1280, 2 * 1280, 16 * 1280}; const cuuint32_t bx[5] = {64, 2, 4, 2, 5};
    enc(f, &P.mC[0], d_in[5], 5, d, s, bx, true); enc(f, &P.mC[1], d_in[6], 5, d, s, bx, true); }
  { const cuuint64_t d[2] = {2048, 640}, s[1] = {4096}; const cuuint32_t bx[2] = {64, 80}; enc(f, &P.mGT, pgt, 2, d, s, bx, true); }
  { const cuuint64_t d[4] = {640, 8, 16, 16}, s[3] = {16 * 1280, 1280, 128 * 1280}, so[3] = {16 * 2560, 2560, 128 * 2560}; const cuuint32_t bx[4] = {80, 8, 16, 1};
    enc(f, &P.sU, pu, 4, d, s, bx, false); enc(f, &P.sO, d_out, 4, d, so, bx, false, true); }
  { const cuuint64_t d[2] = {2048, 640}, s[1] = {4096}; const cuuint32_t bx[2] = {64, 64}; enc(f, &P.sK, sp->kv, 2, d, s, bx, true); }
  P.lre = (cb)d_in[1]; P.lim = (cb)d_in[2]; P.cre = (cb)d_in[5]; P.cim = (cb)d_in[6]; P.ldt = (cb)d_in[7]; P.dskip = (cb)d_in[8];
  P.k = (cb)d_in[10]; P.v = (cb)d_in[11]; P.shk = (cb)d_in[12]; P.ssmk = (cb)d_in[13]; P.ssmd = (cb)d_in[14];
  cudaFuncSetAttribute(fused_kernel, cudaFuncAttributeMaxDynamicSharedMemorySize, SMEM_BYTES);
  for (int big = 1; big >= 0; big--) {
    const cuuint64_t seg = big ? 40 : 32;
    for (int i = 0; i < 4; i++) {
      const cuuint64_t d[4] = {640, 2, 4, 1024}, s[3] = {1280, seg * 1280, 2 * 1280}; const cuuint32_t bx[4] = {64, 2, 4, !big ? 8u : (i & 1) ? 10u : 5u};
      enc(f, &P.mA[i], i < 2 ? d_in[0] : pu, 4, d, s, bx, true);
    }
    {
      const cuuint64_t d[4] = {1280, 8, 16, 32}, s[3] = {16 * 2560, 2560, 128 * 2560}; const cuuint32_t bx[4] = {64, 8, big ? 2u : 8u, 1};
      enc(f, &P.mH, ph, 4, d, s, bx, true); }
    { const cuuint64_t d[4] = {1280, 2, 4, 2048}, s[3] = {2560, seg * 2560, 2 * 2560}; const cuuint32_t bx[4] = {64, 2, 4, 4};
      enc(f, &P.sH, ph, 4, d, s, bx, true); }
    make_roles(P, big);
    H.base = big ? 0 : 120;
    launch(H, P, big ? 120 : 12, big ? 8 : 2, !big);
  }
}
```

```cpp
#include <cuda_runtime.h>
#include <cuda.h>
#include <cuda_bf16.h>
#include <stdint.h>

namespace {

constexpr int SEQ = 2048, DM = 640;
constexpr int SPIN = 1 << 20;
#define PFAT 99
#define KVDLY 500
#define PFD 1
#define XPFAT 9
#define STAT_AT 6
#define KPFAT 3
#define KPFAT2 5
#define CPF 2
#define KPF 7
#define ODIR 1
#define UDIR 0
#define HDLY 1900
#define XRAT 9
#define CEARLY 0
#define CWAIT 0
#define CWK 0
#define ORD 1

struct Scratch {
  uint2 E[2 * 13 * 10 * 8 * 16];
  uint32_t M[3 * 16 * 8 * 256];
  uint2 S[2 * SEQ];
  uint2 RS[80 * 16];
  unsigned flag[512 * 32];
  unsigned cnt[32 * 32];
  unsigned epoch[132 * 8];
  unsigned zero[128];
  unsigned prof[132 * 512];
  __align__(1024)
  __nv_bfloat16 u[SEQ * DM];
  __nv_bfloat16 h[2 * SEQ * 1280];
  __nv_bfloat16 kv[DM * SEQ];
  __nv_bfloat16 gt[DM * SEQ];
  __nv_bfloat16 bcopy[2 * DM * DM];
};
__device__ __align__(1024) Scratch g_scr;
#define PROF(i) do {} while (0)
#define PROFC(c, i) do {} while (0)

constexpr int C_KV = 0, C_G = 10;
constexpr int F_U3 = 0, F_H = 128;

constexpr int R_OFF = 196608, R4_OFF0 = 188416, R4_OFF1 = 122880, H_OFF = 131072, KS_OFF = 131072, CV_OFF = 86272, G_OFF = 102400, US_OFF = 98304, OS_OFF = US_OFF + 20480, XR_OFF = 163840;
constexpr int LAM_OFF = 229376, SSM_OFF = LAM_OFF + 1024, BAR_OFF = SSM_OFF + 1344;
constexpr int B_F1 = 0, B_E1 = 10, B_RF0 = 20, B_RF1 = 21, NBAR1 = 22;
constexpr int B_F2 = 22, B_KF = 32, B_GF = 37, B_CD = 38, B_XF = 40, B_ST = 41, B_HD = 42, B_LM = 43, B_E2 = 44, B_GS = 54, B_PS = 59, B_AX = 62, B_SH = 64, B_SG = 69, B_GE = 70, B_XR = 71, NBAR = 72;
__host__ __device__ constexpr int bar_count(int i) { return i < B_E1 ? 1 : i < B_RF0 ? 9 : i < B_F2 ? 8 : i < B_E2 ? 1 : i < B_GS ? 12 : i < B_SH ? 4 : i < B_GE ? 8 : i < B_XR ? 2 : 1; }
constexpr int MISC_OFF = BAR_OFF + NBAR * 8, SMEM_BYTES = MISC_OFF + 32;
constexpr int KV_PAD = 512, KC_OFS = KV_PAD + 4096, CH_BYTES = KC_OFS + 4128, CH_STRIDE = 8960;
__device__ __forceinline__ uint32_t conv_buf(uint32_t sb, int slot) { return sb + CV_OFF + slot * CH_STRIDE; }
constexpr uint64_t tab6(int a, int b, int c, int d, int e, int f, int g, int h, int i, int j) {
  return (uint64_t)a | (uint64_t)b << 6 | (uint64_t)c << 12 | (uint64_t)d << 18 | (uint64_t)e << 24 | (uint64_t)f << 30 | (uint64_t)g << 36 | (uint64_t)h << 42 |
         (uint64_t)i << 48 | (uint64_t)j << 54;
}
constexpr uint64_t WTAB0 = tab6(0, 4, 8, 30, 12, 26, 0, 4, 8, 12), XTAB0 = tab6(40, 45, 50, 34, 16, 21, 40, 45, 50, 16);
constexpr uint64_t WTAB1 = tab6(0, 4, 8, 12, 16, 20, 32, 36, 24, 28), XTAB1 = tab6(40, 45, 50, 40, 45, 50, 40, 45, 50, 40);
constexpr uint32_t DEP0 = 0x4210;

struct Head {
  Scratch* s;
  const __nv_bfloat16 *x, *b0, *b1;
  uint32_t base, swap;
};
struct Params {
  const __nv_bfloat16 *lre, *lim, *ldt, *k, *v, *shk, *cre, *cim, *ssmk, *ssmd, *dskip;
  float* out;
  uint4 role[120];
  CUtensorMap mB, mA[4], mH, mC[2], mGT, mX, sH, sU, sO, sK;
};

__device__ __forceinline__ uint32_t smem_u32(const void* p) { return (uint32_t)__cvta_generic_to_shared(p); }
__device__ __forceinline__ uint32_t opaque(uint32_t x) { uint32_t y; asm volatile("mov.u32 %0, %1;" : "=r"(y) : "r"(x)); return y; }
__device__ __forceinline__ int lane_id() { int y; asm volatile("mov.u32 %0, %%laneid;" : "=r"(y)); return y; }
__device__ __forceinline__ void delay(uint32_t n) {
  asm volatile("{ .reg .pred p; .reg .u32 a, b; mov.u32 a, %%clock; L: mov.u32 b, %%clock; sub.u32 b, b, a; setp.lt.u32 p, b, %0; @p bra.uni L; }" ::"r"(n) : "memory");
}
__device__ __forceinline__ void mbar_init(uint32_t bar, uint32_t cnt) { asm volatile("mbarrier.init.shared::cta.b64 [%0], %1;" ::"r"(bar), "r"(cnt) : "memory"); }
__device__ __forceinline__ void mbar_expect_tx(uint32_t bar, uint32_t bytes) { asm volatile("mbarrier.arrive.expect_tx.shared::cta.b64 _, [%0], %1;" ::"r"(bar), "r"(bytes) : "memory"); }
__device__ __forceinline__ void mbar_arrive(uint32_t bar) { asm volatile("mbarrier.arrive.shared::cta.b64 _, [%0];" ::"r"(bar) : "memory"); }
__device__ __forceinline__ void mbar_arrive_if(uint32_t bar, bool c) {
  asm volatile("{ .reg .pred p; setp.ne.u32 p, %1, 0; @p mbarrier.arrive.shared::cta.b64 _, [%0]; }" ::"r"(bar), "r"((uint32_t)c) : "memory");
}
__device__ __forceinline__ void prefetch_if(const void* p, bool c) { asm volatile("{ .reg .pred p; setp.ne.u32 p, %1, 0; @p prefetch.global.L2 [%0]; }" ::"l"(p), "r"((uint32_t)c)); }
__device__ __forceinline__ void mbar_arrive_cl(uint32_t bar, uint32_t cta) {
  asm volatile("{ .reg .b32 ra; mapa.shared::cluster.u32 ra, %0, %1; mbarrier.arrive.shared::cluster.b64 _, [ra]; }" ::"r"(bar), "r"(cta) : "memory");
}
__device__ __forceinline__ uint32_t mapa(uint32_t a, uint32_t cta) { uint32_t r; asm("mapa.shared::cluster.u32 %0, %1, %2;" : "=r"(r) : "r"(a), "r"(cta)); return r; }
__device__ __forceinline__ void mbar_arrive_at(uint32_t ra) { asm volatile("mbarrier.arrive.shared::cluster.b64 _, [%0];" ::"r"(ra) : "memory"); }
__device__ __forceinline__ void mbar_wait(uint32_t bar, uint32_t parity = 0) {
  asm volatile("{ .reg .pred p; .reg .u32 c; mov.u32 c, 0;\n"
               "W: mbarrier.try_wait.parity.shared::cta.b64 p, [%0], %1; @p bra.uni D;\n"
               "add.u32 c, c, 1; setp.lt.u32 p, c, 0x100000; @p bra.uni W;\nD: }" ::"r"(bar), "r"(parity) : "memory");
}
__device__ __forceinline__ bool elect_one() { uint32_t p; asm volatile("{ .reg .pred P; elect.sync _|P, 0xffffffff; selp.u32 %0,1,0,P; }" : "=r"(p)); return p; }
__device__ __forceinline__ void bar_sync(int id, int n) { __syncwarp(); asm volatile("bar.sync %0, %1;" ::"r"(id), "r"(n) : "memory"); }
__device__ __forceinline__ void tma2d(uint32_t dst, const CUtensorMap* m, int c0, int c1, uint32_t bar) {
  asm volatile("cp.async.bulk.tensor.2d.shared::cluster.global.mbarrier::complete_tx::bytes [%0], [%1, {%3,%4}], [%2];"
               ::"r"(dst), "l"(m), "r"(bar), "r"(c0), "r"(c1) : "memory");
}
__device__ __forceinline__ void tma5d(uint32_t dst, const CUtensorMap* m, int c0, int c4, uint32_t bar) {
  asm volatile("cp.async.bulk.tensor.5d.shared::cluster.global.mbarrier::complete_tx::bytes [%0], [%1, {%3,%5,%5,%5,%4}], [%2];"
               ::"r"(dst), "l"(m), "r"(bar), "r"(c0), "r"(c4), "r"(0) : "memory");
}
__device__ __forceinline__ void tma4d(uint32_t dst, const CUtensorMap* m, int c0, int c3, uint32_t bar) {
  asm volatile("cp.async.bulk.tensor.4d.shared::cluster.global.mbarrier::complete_tx::bytes [%0], [%1, {%3,%5,%5,%4}], [%2];"
               ::"r"(dst), "l"(m), "r"(bar), "r"(c0), "r"(c3), "r"(0) : "memory");
}
__device__ __forceinline__ void tma4d_mc(uint32_t dst, const CUtensorMap* m, int c0, int c1, int c2, int c3, uint32_t bar, uint32_t mask) {
  asm volatile("cp.async.bulk.tensor.4d.shared::cluster.global.mbarrier::complete_tx::bytes.multicast::cluster [%0], [%1, {%3,%4,%5,%6}], [%2], %7;"
               ::"r"(dst), "l"(m), "r"(bar), "r"(c0), "r"(c1), "r"(c2), "r"(c3), "h"((uint16_t)mask) : "memory");
}
__device__ __forceinline__ void bulk_g2s(uint32_t dst, const void* src, uint32_t bytes, uint32_t bar) {
  asm volatile("cp.async.bulk.shared::cluster.global.mbarrier::complete_tx::bytes [%0], [%1], %2, [%3];" ::"r"(dst), "l"(src), "r"(bytes), "r"(bar) : "memory");
}
__device__ __forceinline__ void tma4d_store(const CUtensorMap* m, uint32_t src, int c0, int c1, int c2, int c3) {
  asm volatile("cp.async.bulk.tensor.4d.global.shared::cta.bulk_group [%0, {%2,%3,%4,%5}], [%1];" ::"l"(m), "r"(src), "r"(c0), "r"(c1), "r"(c2), "r"(c3) : "memory");
}
__device__ __forceinline__ void tma2d_store(const CUtensorMap* m, uint32_t src, int c0, int c1) {
  asm volatile("cp.async.bulk.tensor.2d.global.shared::cta.bulk_group [%0, {%2,%3}], [%1];" ::"l"(m), "r"(src), "r"(c0), "r"(c1) : "memory");
}
__device__ __forceinline__ void bulk_s2g(void* dst, uint32_t src, uint32_t bytes) {
  asm volatile("cp.async.bulk.global.shared::cta.bulk_group [%0], [%1], %2;" ::"l"(dst), "r"(src), "r"(bytes) : "memory");
}
__device__ __forceinline__ void bulk_commit() { asm volatile("cp.async.bulk.commit_group;" ::: "memory"); }
__device__ __forceinline__ void bulk_wait() { asm volatile("cp.async.bulk.wait_group 0;" ::: "memory"); }
__device__ __forceinline__ void fence_async() { asm volatile("fence.proxy.async.shared::cta;" ::: "memory"); }
__device__ __forceinline__ void prefetch_l2(const void* src, uint32_t bytes) { asm volatile("cp.async.bulk.prefetch.L2.global [%0], %1;" ::"l"(src), "r"(bytes) : "memory"); }
__device__ __forceinline__ void prefetch_map(const CUtensorMap* m) { asm volatile("prefetch.tensormap [%0];" ::"l"(m) : "memory"); }
__device__ __forceinline__ void wg_fence() { __syncwarp(); asm volatile("wgmma.fence.sync.aligned;" ::: "memory"); }
__device__ __forceinline__ void wg_commit() { asm volatile("wgmma.commit_group.sync.aligned;" ::: "memory"); }
template <int N> __device__ __forceinline__ void wg_wait() { asm volatile("wgmma.wait_group.sync.aligned %0;" ::"n"(N) : "memory"); }
template <int N> __device__ __forceinline__ void fence_regs(float (&d)[N]) {
#pragma unroll
  for (int i = 0; i < N; i++) asm volatile("" : "+f"(d[i])::"memory");
}
__device__ __forceinline__ uint64_t make_desc(uint32_t addr, uint32_t lbo, uint32_t sbo, uint32_t swz) {
  return (uint64_t)((addr & 0x3FFFF) >> 4) | ((uint64_t)(lbo >> 4) << 16) | ((uint64_t)(sbo >> 4) << 32) | ((uint64_t)swz << 62);
}
__device__ __forceinline__ uint32_t ldg1(const void* p) { uint32_t v; asm volatile("ld.global.nc.u32 %0,[%1];" : "=r"(v) : "l"(p)); return v; }
__device__ __forceinline__ uint32_t lds32(uint32_t a) { uint32_t v; asm volatile("ld.shared.u32 %0,[%1];" : "=r"(v) : "r"(a)); return v; }
__device__ __forceinline__ unsigned ld_rlx(const unsigned* p) { unsigned v; asm volatile("ld.relaxed.gpu.global.u32 %0,[%1];" : "=r"(v) : "l"(p) : "memory"); return v; }
__device__ __forceinline__ uint4 ld_rlx4(const void* p) {
  uint4 v; asm volatile("ld.relaxed.gpu.global.v4.u32 {%0,%1,%2,%3},[%4];" : "=r"(v.x), "=r"(v.y), "=r"(v.z), "=r"(v.w) : "l"(p) : "memory"); return v;
}
__device__ __forceinline__ uint2 ld_rlx2(const void* p) { uint2 v; asm volatile("ld.relaxed.gpu.global.v2.u32 {%0,%1},[%2];" : "=r"(v.x), "=r"(v.y) : "l"(p) : "memory"); return v; }
__device__ __forceinline__ void st_rlx2(void* p, uint32_t a, uint32_t b) { asm volatile("st.relaxed.gpu.global.v2.u32 [%0],{%1,%2};" ::"l"(p), "r"(a), "r"(b) : "memory"); }
__device__ __forceinline__ void st_rlx4(void* p, uint32_t a, uint32_t b, uint32_t c, uint32_t d) {
  asm volatile("st.relaxed.gpu.global.v4.u32 [%0],{%1,%2,%3,%4};" ::"l"(p), "r"(a), "r"(b), "r"(c), "r"(d) : "memory");
}
__device__ __forceinline__ void st_rlx(void* p, uint32_t a) { asm volatile("st.relaxed.gpu.global.u32 [%0],%1;" ::"l"(p), "r"(a) : "memory"); }
#define PUB 15
template <int SITE> __device__ __forceinline__ void release() { if (PUB & SITE) asm volatile("fence.acq_rel.gpu;" ::: "memory"); }
__device__ __forceinline__ void signal_flag(unsigned* p, unsigned val) { asm volatile("st.relaxed.gpu.global.u32 [%0],%1;" ::"l"(p), "r"(val) : "memory"); }
__device__ __forceinline__ void signal_cnt(unsigned* p, unsigned n) { asm volatile("red.relaxed.gpu.global.add.u32 [%0],%1;" ::"l"(p), "r"(n) : "memory"); }
__device__ __forceinline__ void wait_flags(const unsigned* p, unsigned val, uint32_t need, uint32_t& ready) {
#pragma unroll 1
  for (int it = 0; (ready & need) != need && it < SPIN; it++) ready = __ballot_sync(0xffffffff, ld_rlx(p) == val);
}
__device__ __forceinline__ void wait_cnt(const unsigned* p, unsigned tgt) {
  asm volatile("{ .reg .pred p; .reg .u32 c; .reg .s32 v; mov.u32 c, 0;\n"
               "W: ld.relaxed.gpu.global.u32 v, [%0]; sub.s32 v, v, %1; setp.ge.s32 p, v, 0; @p bra.uni D;\n"
               "add.u32 c, c, 1; setp.lt.u32 p, c, 0x100000; @p bra.uni W;\nD: }" ::"l"(p), "r"(tgt) : "memory");
}
__device__ __forceinline__ uint32_t pack_bf(float lo, float hi) { uint32_t r; asm("cvt.rn.bf16x2.f32 %0, %1, %2;" : "=r"(r) : "f"(hi), "f"(lo)); return r; }
__device__ __forceinline__ float bf_lo(uint32_t v) { return __uint_as_float(v << 16); }
__device__ __forceinline__ float bf_hi(uint32_t v) { return __uint_as_float(v & 0xffff0000u); }
__device__ __forceinline__ float bf_rn(float x) { return __bfloat162float(__float2bfloat16_rn(x)); }
__device__ __forceinline__ float frcp(float x) { float r; asm("rcp.approx.ftz.f32 %0,%1;" : "=f"(r) : "f"(x)); return r; }
__device__ __forceinline__ float fsqrt(float x) { float r; asm("sqrt.approx.ftz.f32 %0,%1;" : "=f"(r) : "f"(x)); return r; }
__device__ __forceinline__ float frsqrt(float x) { float r; asm("rsqrt.approx.ftz.f32 %0,%1;" : "=f"(r) : "f"(x)); return r; }
__device__ __forceinline__ uint32_t hmul2(uint32_t a, uint32_t b) { uint32_t r; asm("mul.rn.bf16x2 %0,%1,%2;" : "=r"(r) : "r"(a), "r"(b)); return r; }
__device__ __forceinline__ uint32_t hfma2(uint32_t a, uint32_t b, uint32_t c) { uint32_t r; asm("fma.rn.bf16x2 %0,%1,%2,%3;" : "=r"(r) : "r"(a), "r"(b), "r"(c)); return r; }
__device__ __forceinline__ float2 cmul(float2 a, float2 b) { return make_float2(a.x * b.x - a.y * b.y, a.x * b.y + a.y * b.x); }
__device__ __forceinline__ float2 cfma(float2 a, float2 b, float2 c) {
  return make_float2(fmaf(a.x, b.x, fmaf(-a.y, b.y, c.x)), fmaf(a.x, b.y, fmaf(a.y, b.x, c.y)));
}
__device__ __forceinline__ uint32_t tagf(float v, uint32_t tag) { return (__float_as_uint(v) & ~1u) | tag; }
__device__ __forceinline__ float untag(uint32_t v) { return __uint_as_float(v & ~1u); }
__device__ __forceinline__ bool untagged(const uint4& v, uint32_t tag) { return (((v.x ^ tag) | (v.y ^ tag) | (v.z ^ tag) | (v.w ^ tag)) & 1) != 0; }
__device__ __forceinline__ bool untagged(const uint2& v, uint32_t tag) { return (((v.x ^ tag) | (v.y ^ tag)) & 1) != 0; }
__device__ __forceinline__ float2 lam_bar(float lr, float li, float ldt) {
  float dt = bf_rn(expf(ldt)); float e = expf(dt * lr), s, c; sincospif(dt * li * 0.31830988618379067f, &s, &c); return make_float2(e * c, e * s);
}

__device__ __forceinline__ int conv_ch(uint32_t c, int s) { return s * ((c >> 21) & 255) + (c & 255) - (s >= (int)(c >> 29) ? 8 : 0); }
struct Role {
  uint32_t v, c, p;
  __device__ __forceinline__ int tb() const { return v & 15; }
  __device__ __forceinline__ int cb() const { return (v >> 4) & 15; }
  __device__ __forceinline__ int b() const { return (v >> 8) & 255; }
  __device__ __forceinline__ int ubase() const { return (v >> 16) & 7; }
  __device__ __forceinline__ int ugs() const { return (v >> 19) & 7; }
  __device__ __forceinline__ int wpart() const { return (v >> 22) & 7; }
  __device__ __forceinline__ int rank() const { return (v >> 26) & 7; }
  __device__ __forceinline__ int cs() const { return (v >> 29) ? 8 : 2; }
  __device__ __forceinline__ int ch(int s) const { return conv_ch(c, s); }
  __device__ __forceinline__ int wlo() const { return p & 1; }
  __device__ __forceinline__ int whi() const { return (p >> 1) & 1; }
  __device__ __forceinline__ uint32_t wmask() const { return (p >> 2) & 255; }
  __device__ __forceinline__ uint32_t umask() const { return (p >> 10) & 255; }
  __device__ __forceinline__ int uj() const { return (p >> 20) & 31; }
  __device__ __forceinline__ int sm() const { return (p >> 25) & 15; }
  __device__ __forceinline__ int nch() const { return (c >> 10) & 7; }
  __device__ __forceinline__ int nprep() const { return (c >> 13) & 255; }
};

__device__ __forceinline__ void wgmma_ss80(float (&d)[40], uint64_t da, uint64_t db, int sd){
  asm volatile("{ .reg .pred p; setp.ne.b32 p, %42, 0;\n"
   "wgmma.mma_async.sync.aligned.m64n80k16.f32.bf16.bf16 {%0, %1, %2, %3, %4, %5, %6, %7, %8, %9, %10, %11, %12, %13, %14, %15, %16, %17, %18, %19, %20, %21, %22, %23, %24, %25, %26, %27, %28, %29, %30, %31, %32, %33, %34, %35, %36, %37, %38, %39}, %40, %41, p, 1, 1, 0, 0; }\n"
   : "+f"(d[0]), "+f"(d[1]), "+f"(d[2]), "+f"(d[3]), "+f"(d[4]), "+f"(d[5]), "+f"(d[6]), "+f"(d[7]), "+f"(d[8]), "+f"(d[9]), "+f"(d[10]), "+f"(d[11]), "+f"(d[12]), "+f"(d[13]), "+f"(d[14]), "+f"(d[15]), "+f"(d[16]), "+f"(d[17]), "+f"(d[18]), "+f"(d[19]), "+f"(d[20]), "+f"(d[21]), "+f"(d[22]), "+f"(d[23]), "+f"(d[24]), "+f"(d[25]), "+f"(d[26]), "+f"(d[27]), "+f"(d[28]), "+f"(d[29]), "+f"(d[30]), "+f"(d[31]), "+f"(d[32]), "+f"(d[33]), "+f"(d[34]), "+f"(d[35]), "+f"(d[36]), "+f"(d[37]), "+f"(d[38]), "+f"(d[39]) : "l"(da), "l"(db), "r"(sd));
}
__device__ __forceinline__ void wgmma_ss160(float (&d)[80], uint64_t da, uint64_t db, int sd){
  asm volatile("{ .reg .pred p; setp.ne.b32 p, %82, 0;\n"
   "wgmma.mma_async.sync.aligned.m64n160k16.f32.bf16.bf16 {%0, %1, %2, %3, %4, %5, %6, %7, %8, %9, %10, %11, %12, %13, %14, %15, %16, %17, %18, %19, %20, %21, %22, %23, %24, %25, %26, %27, %28, %29, %30, %31, %32, %33, %34, %35, %36, %37, %38, %39, %40, %41, %42, %43, %44, %45, %46, %47, %48, %49, %50, %51, %52, %53, %54, %55, %56, %57, %58, %59, %60, %61, %62, %63, %64, %65, %66, %67, %68, %69, %70, %71, %72, %73, %74, %75, %76, %77, %78, %79}, %80, %81, p, 1, 1, 0, 0; }\n"
   : "+f"(d[0]), "+f"(d[1]), "+f"(d[2]), "+f"(d[3]), "+f"(d[4]), "+f"(d[5]), "+f"(d[6]), "+f"(d[7]), "+f"(d[8]), "+f"(d[9]), "+f"(d[10]), "+f"(d[11]), "+f"(d[12]), "+f"(d[13]), "+f"(d[14]), "+f"(d[15]), "+f"(d[16]), "+f"(d[17]), "+f"(d[18]), "+f"(d[19]), "+f"(d[20]), "+f"(d[21]), "+f"(d[22]), "+f"(d[23]), "+f"(d[24]), "+f"(d[25]), "+f"(d[26]), "+f"(d[27]), "+f"(d[28]), "+f"(d[29]), "+f"(d[30]), "+f"(d[31]), "+f"(d[32]), "+f"(d[33]), "+f"(d[34]), "+f"(d[35]), "+f"(d[36]), "+f"(d[37]), "+f"(d[38]), "+f"(d[39]), "+f"(d[40]), "+f"(d[41]), "+f"(d[42]), "+f"(d[43]), "+f"(d[44]), "+f"(d[45]), "+f"(d[46]), "+f"(d[47]), "+f"(d[48]), "+f"(d[49]), "+f"(d[50]), "+f"(d[51]), "+f"(d[52]), "+f"(d[53]), "+f"(d[54]), "+f"(d[55]), "+f"(d[56]), "+f"(d[57]), "+f"(d[58]), "+f"(d[59]), "+f"(d[60]), "+f"(d[61]), "+f"(d[62]), "+f"(d[63]), "+f"(d[64]), "+f"(d[65]), "+f"(d[66]), "+f"(d[67]), "+f"(d[68]), "+f"(d[69]), "+f"(d[70]), "+f"(d[71]), "+f"(d[72]), "+f"(d[73]), "+f"(d[74]), "+f"(d[75]), "+f"(d[76]), "+f"(d[77]), "+f"(d[78]), "+f"(d[79]) : "l"(da), "l"(db), "r"(sd));
}
template<int N> __device__ __forceinline__ void wgmma_rs(float (&d)[N/2], uint32_t a0, uint32_t a1, uint32_t a2, uint32_t a3, uint64_t db, int sd);
template<> __device__ __forceinline__ void wgmma_rs<16>(float (&d)[8], uint32_t a0, uint32_t a1, uint32_t a2, uint32_t a3, uint64_t db, int sd){
  asm volatile("{ .reg .pred p; setp.ne.b32 p, %13, 0;\n"
   "wgmma.mma_async.sync.aligned.m64n16k16.f32.bf16.bf16 {%0, %1, %2, %3, %4, %5, %6, %7}, {%8,%9,%10,%11}, %12, p, 1, 1, 0; }\n"
   : "+f"(d[0]), "+f"(d[1]), "+f"(d[2]), "+f"(d[3]), "+f"(d[4]), "+f"(d[5]), "+f"(d[6]), "+f"(d[7]) : "r"(a0), "r"(a1), "r"(a2), "r"(a3), "l"(db), "r"(sd));
}
template<> __device__ __forceinline__ void wgmma_rs<32>(float (&d)[16], uint32_t a0, uint32_t a1, uint32_t a2, uint32_t a3, uint64_t db, int sd){
  asm volatile("{ .reg .pred p; setp.ne.b32 p, %21, 0;\n"
   "wgmma.mma_async.sync.aligned.m64n32k16.f32.bf16.bf16 {%0, %1, %2, %3, %4, %5, %6, %7, %8, %9, %10, %11, %12, %13, %14, %15}, {%16,%17,%18,%19}, %20, p, 1, 1, 0; }\n"
   : "+f"(d[0]), "+f"(d[1]), "+f"(d[2]), "+f"(d[3]), "+f"(d[4]), "+f"(d[5]), "+f"(d[6]), "+f"(d[7]), "+f"(d[8]), "+f"(d[9]), "+f"(d[10]), "+f"(d[11]), "+f"(d[12]), "+f"(d[13]), "+f"(d[14]), "+f"(d[15]) : "r"(a0), "r"(a1), "r"(a2), "r"(a3), "l"(db), "r"(sd));
}
template<> __device__ __forceinline__ void wgmma_rs<48>(float (&d)[24], uint32_t a0, uint32_t a1, uint32_t a2, uint32_t a3, uint64_t db, int sd){
  asm volatile("{ .reg .pred p; setp.ne.b32 p, %29, 0;\n"
   "wgmma.mma_async.sync.aligned.m64n48k16.f32.bf16.bf16 {%0, %1, %2, %3, %4, %5, %6, %7, %8, %9, %10, %11, %12, %13, %14, %15, %16, %17, %18, %19, %20, %21, %22, %23}, {%24,%25,%26,%27}, %28, p, 1, 1, 0; }\n"
   : "+f"(d[0]), "+f"(d[1]), "+f"(d[2]), "+f"(d[3]), "+f"(d[4]), "+f"(d[5]), "+f"(d[6]), "+f"(d[7]), "+f"(d[8]), "+f"(d[9]), "+f"(d[10]), "+f"(d[11]), "+f"(d[12]), "+f"(d[13]), "+f"(d[14]), "+f"(d[15]), "+f"(d[16]), "+f"(d[17]), "+f"(d[18]), "+f"(d[19]), "+f"(d[20]), "+f"(d[21]), "+f"(d[22]), "+f"(d[23]) : "r"(a0), "r"(a1), "r"(a2), "r"(a3), "l"(db), "r"(sd));
}
template<> __device__ __forceinline__ void wgmma_rs<64>(float (&d)[32], uint32_t a0, uint32_t a1, uint32_t a2, uint32_t a3, uint64_t db, int sd){
  asm volatile("{ .reg .pred p; setp.ne.b32 p, %37, 0;\n"
   "wgmma.mma_async.sync.aligned.m64n64k16.f32.bf16.bf16 {%0, %1, %2, %3, %4, %5, %6, %7, %8, %9, %10, %11, %12, %13, %14, %15, %16, %17, %18, %19, %20, %21, %22, %23, %24, %25, %26, %27, %28, %29, %30, %31}, {%32,%33,%34,%35}, %36, p, 1, 1, 0; }\n"
   : "+f"(d[0]), "+f"(d[1]), "+f"(d[2]), "+f"(d[3]), "+f"(d[4]), "+f"(d[5]), "+f"(d[6]), "+f"(d[7]), "+f"(d[8]), "+f"(d[9]), "+f"(d[10]), "+f"(d[11]), "+f"(d[12]), "+f"(d[13]), "+f"(d[14]), "+f"(d[15]), "+f"(d[16]), "+f"(d[17]), "+f"(d[18]), "+f"(d[19]), "+f"(d[20]), "+f"(d[21]), "+f"(d[22]), "+f"(d[23]), "+f"(d[24]), "+f"(d[25]), "+f"(d[26]), "+f"(d[27]), "+f"(d[28]), "+f"(d[29]), "+f"(d[30]), "+f"(d[31]) : "r"(a0), "r"(a1), "r"(a2), "r"(a3), "l"(db), "r"(sd));
}
template<> __device__ __forceinline__ void wgmma_rs<80>(float (&d)[40], uint32_t a0, uint32_t a1, uint32_t a2, uint32_t a3, uint64_t db, int sd){
  asm volatile("{ .reg .pred p; setp.ne.b32 p, %45, 0;\n"
   "wgmma.mma_async.sync.aligned.m64n80k16.f32.bf16.bf16 {%0, %1, %2, %3, %4, %5, %6, %7, %8, %9, %10, %11, %12, %13, %14, %15, %16, %17, %18, %19, %20, %21, %22, %23, %24, %25, %26, %27, %28, %29, %30, %31, %32, %33, %34, %35, %36, %37, %38, %39}, {%40,%41,%42,%43}, %44, p, 1, 1, 0; }\n"
   : "+f"(d[0]), "+f"(d[1]), "+f"(d[2]), "+f"(d[3]), "+f"(d[4]), "+f"(d[5]), "+f"(d[6]), "+f"(d[7]), "+f"(d[8]), "+f"(d[9]), "+f"(d[10]), "+f"(d[11]), "+f"(d[12]), "+f"(d[13]), "+f"(d[14]), "+f"(d[15]), "+f"(d[16]), "+f"(d[17]), "+f"(d[18]), "+f"(d[19]), "+f"(d[20]), "+f"(d[21]), "+f"(d[22]), "+f"(d[23]), "+f"(d[24]), "+f"(d[25]), "+f"(d[26]), "+f"(d[27]), "+f"(d[28]), "+f"(d[29]), "+f"(d[30]), "+f"(d[31]), "+f"(d[32]), "+f"(d[33]), "+f"(d[34]), "+f"(d[35]), "+f"(d[36]), "+f"(d[37]), "+f"(d[38]), "+f"(d[39]) : "r"(a0), "r"(a1), "r"(a2), "r"(a3), "l"(db), "r"(sd));
}
template<> __device__ __forceinline__ void wgmma_rs<96>(float (&d)[48], uint32_t a0, uint32_t a1, uint32_t a2, uint32_t a3, uint64_t db, int sd){
  asm volatile("{ .reg .pred p; setp.ne.b32 p, %53, 0;\n"
   "wgmma.mma_async.sync.aligned.m64n96k16.f32.bf16.bf16 {%0, %1, %2, %3, %4, %5, %6, %7, %8, %9, %10, %11, %12, %13, %14, %15, %16, %17, %18, %19, %20, %21, %22, %23, %24, %25, %26, %27, %28, %29, %30, %31, %32, %33, %34, %35, %36, %37, %38, %39, %40, %41, %42, %43, %44, %45, %46, %47}, {%48,%49,%50,%51}, %52, p, 1, 1, 0; }\n"
   : "+f"(d[0]), "+f"(d[1]), "+f"(d[2]), "+f"(d[3]), "+f"(d[4]), "+f"(d[5]), "+f"(d[6]), "+f"(d[7]), "+f"(d[8]), "+f"(d[9]), "+f"(d[10]), "+f"(d[11]), "+f"(d[12]), "+f"(d[13]), "+f"(d[14]), "+f"(d[15]), "+f"(d[16]), "+f"(d[17]), "+f"(d[18]), "+f"(d[19]), "+f"(d[20]), "+f"(d[21]), "+f"(d[22]), "+f"(d[23]), "+f"(d[24]), "+f"(d[25]), "+f"(d[26]), "+f"(d[27]), "+f"(d[28]), "+f"(d[29]), "+f"(d[30]), "+f"(d[31]), "+f"(d[32]), "+f"(d[33]), "+f"(d[34]), "+f"(d[35]), "+f"(d[36]), "+f"(d[37]), "+f"(d[38]), "+f"(d[39]), "+f"(d[40]), "+f"(d[41]), "+f"(d[42]), "+f"(d[43]), "+f"(d[44]), "+f"(d[45]), "+f"(d[46]), "+f"(d[47]) : "r"(a0), "r"(a1), "r"(a2), "r"(a3), "l"(db), "r"(sd));
}
template<> __device__ __forceinline__ void wgmma_rs<112>(float (&d)[56], uint32_t a0, uint32_t a1, uint32_t a2, uint32_t a3, uint64_t db, int sd){
  asm volatile("{ .reg .pred p; setp.ne.b32 p, %61, 0;\n"
   "wgmma.mma_async.sync.aligned.m64n112k16.f32.bf16.bf16 {%0, %1, %2, %3, %4, %5, %6, %7, %8, %9, %10, %11, %12, %13, %14, %15, %16, %17, %18, %19, %20, %21, %22, %23, %24, %25, %26, %27, %28, %29, %30, %31, %32, %33, %34, %35, %36, %37, %38, %39, %40, %41, %42, %43, %44, %45, %46, %47, %48, %49, %50, %51, %52, %53, %54, %55}, {%56,%57,%58,%59}, %60, p, 1, 1, 0; }\n"
   : "+f"(d[0]), "+f"(d[1]), "+f"(d[2]), "+f"(d[3]), "+f"(d[4]), "+f"(d[5]), "+f"(d[6]), "+f"(d[7]), "+f"(d[8]), "+f"(d[9]), "+f"(d[10]), "+f"(d[11]), "+f"(d[12]), "+f"(d[13]), "+f"(d[14]), "+f"(d[15]), "+f"(d[16]), "+f"(d[17]), "+f"(d[18]), "+f"(d[19]), "+f"(d[20]), "+f"(d[21]), "+f"(d[22]), "+f"(d[23]), "+f"(d[24]), "+f"(d[25]), "+f"(d[26]), "+f"(d[27]), "+f"(d[28]), "+f"(d[29]), "+f"(d[30]), "+f"(d[31]), "+f"(d[32]), "+f"(d[33]), "+f"(d[34]), "+f"(d[35]), "+f"(d[36]), "+f"(d[37]), "+f"(d[38]), "+f"(d[39]), "+f"(d[40]), "+f"(d[41]), "+f"(d[42]), "+f"(d[43]), "+f"(d[44]), "+f"(d[45]), "+f"(d[46]), "+f"(d[47]), "+f"(d[48]), "+f"(d[49]), "+f"(d[50]), "+f"(d[51]), "+f"(d[52]), "+f"(d[53]), "+f"(d[54]), "+f"(d[55]) : "r"(a0), "r"(a1), "r"(a2), "r"(a3), "l"(db), "r"(sd));
}
template<> __device__ __forceinline__ void wgmma_rs<128>(float (&d)[64], uint32_t a0, uint32_t a1, uint32_t a2, uint32_t a3, uint64_t db, int sd){
  asm volatile("{ .reg .pred p; setp.ne.b32 p, %69, 0;\n"
   "wgmma.mma_async.sync.aligned.m64n128k16.f32.bf16.bf16 {%0, %1, %2, %3, %4, %5, %6, %7, %8, %9, %10, %11, %12, %13, %14, %15, %16, %17, %18, %19, %20, %21, %22, %23, %24, %25, %26, %27, %28, %29, %30, %31, %32, %33, %34, %35, %36, %37, %38, %39, %40, %41, %42, %43, %44, %45, %46, %47, %48, %49, %50, %51, %52, %53, %54, %55, %56, %57, %58, %59, %60, %61, %62, %63}, {%64,%65,%66,%67}, %68, p, 1, 1, 0; }\n"
   : "+f"(d[0]), "+f"(d[1]), "+f"(d[2]), "+f"(d[3]), "+f"(d[4]), "+f"(d[5]), "+f"(d[6]), "+f"(d[7]), "+f"(d[8]), "+f"(d[9]), "+f"(d[10]), "+f"(d[11]), "+f"(d[12]), "+f"(d[13]), "+f"(d[14]), "+f"(d[15]), "+f"(d[16]), "+f"(d[17]), "+f"(d[18]), "+f"(d[19]), "+f"(d[20]), "+f"(d[21]), "+f"(d[22]), "+f"(d[23]), "+f"(d[24]), "+f"(d[25]), "+f"(d[26]), "+f"(d[27]), "+f"(d[28]), "+f"(d[29]), "+f"(d[30]), "+f"(d[31]), "+f"(d[32]), "+f"(d[33]), "+f"(d[34]), "+f"(d[35]), "+f"(d[36]), "+f"(d[37]), "+f"(d[38]), "+f"(d[39]), "+f"(d[40]), "+f"(d[41]), "+f"(d[42]), "+f"(d[43]), "+f"(d[44]), "+f"(d[45]), "+f"(d[46]), "+f"(d[47]), "+f"(d[48]), "+f"(d[49]), "+f"(d[50]), "+f"(d[51]), "+f"(d[52]), "+f"(d[53]), "+f"(d[54]), "+f"(d[55]), "+f"(d[56]), "+f"(d[57]), "+f"(d[58]), "+f"(d[59]), "+f"(d[60]), "+f"(d[61]), "+f"(d[62]), "+f"(d[63]) : "r"(a0), "r"(a1), "r"(a2), "r"(a3), "l"(db), "r"(sd));
}

#define BAR(i) (bars + 8u * (uint32_t)(i))

template <int G> __device__ __forceinline__ void conv_frags(uint32_t (&a)[12], uint32_t abase) {
#pragma unroll
  for (int i = 0; i < 12; i++) a[i] = lds32(abase + (G * 4 + i / 3) * 128 + (i % 3) * 4);
}
__device__ __forceinline__ void kv_prefetch(const __nv_bfloat16* pf, int task) { prefetch_if(pf + 64 * (task & 31) * DM + 64 * (task >> 5), task < 320); }
__device__ __forceinline__ void kv_load(const Params& P, Scratch* S, int task, int tid, uint32_t (&k_)[19], uint32_t (&v_)[16], uint4& sk) {
  const int row = 64 * (task & 31) + 16 * (tid >> 5), ch = 64 * (task >> 5) + 2 * (tid & 31);
  const uint32_t* kp = (const uint32_t*)(P.k + (size_t)row * DM + ch);
  const uint32_t* vp = (const uint32_t*)(P.v + (size_t)row * DM + ch);
  const uint32_t* hp = row > 0 ? kp - 3 * (DM / 2) : S->zero;
  const int hs = row > 0 ? DM / 2 : 0;
  asm volatile("ld.global.nc.v4.u32 {%0,%1,%2,%3},[%4];" : "=r"(sk.x), "=r"(sk.y), "=r"(sk.z), "=r"(sk.w) : "l"(P.shk + ch * 4));
#pragma unroll
  for (int i = 0; i < 3; i++) k_[i] = ldg1(hp + i * hs);
#pragma unroll
  for (int i = 0; i < 16; i++) { k_[i + 3] = ldg1(kp + i * (DM / 2)); v_[i] = ldg1(vp + i * (DM / 2)); }
}
template <int SH> __device__ __forceinline__ void xb_prefetch(const Head& H, int id, int tid, int c0) {
  const int ri = tid >> SH, rr = 11 * id + ri - 16;
  const __nv_bfloat16* p = ri < 16 ? H.x + (size_t)(16 * min(id, 127) + ri) * DM : (rr < DM ? H.b0 : H.b1 - DM * DM) + (size_t)rr * DM;
  prefetch_if(p + c0 + 64 * (tid & ((1 << SH) - 1)), ri < 16 || (ri < 27 && rr < 2 * DM));
}
__device__ __forceinline__ uint4 ldg4(const void* p) { uint4 v; asm volatile("ld.global.nc.v4.u32 {%0,%1,%2,%3},[%4];" : "=r"(v.x), "=r"(v.y), "=r"(v.z), "=r"(v.w) : "l"(p)); return v; }
__device__ __forceinline__ uint4 lds4(uint32_t a) { uint4 v; asm volatile("ld.shared.v4.u32 {%0,%1,%2,%3},[%4];" : "=r"(v.x), "=r"(v.y), "=r"(v.z), "=r"(v.w) : "r"(a) : "memory"); return v; }
__device__ __forceinline__ void discretise(const Head& H, const Params& P, uint32_t sb, Role R, int lane, uint32_t e1) {
  const uint32_t dn = __ldg((const unsigned short*)P.ssmd + min(conv_ch(R.c, (lane + 7) & 7), DM - 1));
  const int c = 32 * min(R.cb(), 9) + lane;
  const uint32_t lr2 = ldg1(P.lre + 2 * c), li2 = ldg1(P.lim + 2 * c), ld2 = ldg1(P.ldt + 2 * c);
  asm volatile("st.shared.u32 [%0],%1;" ::"r"(sb + MISC_OFF + 4 * (lane & 7)), "r"((lane & 7) ? dn : e1) : "memory");
#pragma unroll 1
  for (int i = 0; i < 2; i++) {
    const float lr = bf_hi(lr2 << (16 - 16 * i)), li = bf_hi(li2 << (16 - 16 * i));
    const float2 lb = lam_bar(lr, li, bf_hi(ld2 << (16 - 16 * i)));
    const float nx = lb.x - 1.f, ny = lb.y, inv = 2.f * frcp(lr * lr + li * li), cx = (nx * lr + ny * li) * inv, cy = (ny * lr - nx * li) * inv;
    const bool sw = !H.swap;
    asm volatile("st.shared.v4.f32 [%0],{%1,%2,%3,%4};" ::"r"(sb + LAM_OFF + 32 * lane + 16 * i), "f"(lb.x), "f"(sw ? -lb.y : lb.y), "f"(sw ? -cy : cx), "f"(sw ? cx : -cy) : "memory");
  }
  __syncwarp();
}
__device__ __forceinline__ void aux_prep(const Head& H, const Params& P, uint32_t sb, Role R, int tid, long long t_start) {
  Scratch* const S = H.s;
  const uint32_t bars = sb + BAR_OFF;
  tid = opaque(tid);
  const int w = tid >> 5, lane = tid & 31, tb = R.tb(), cb = R.cb();
  uint32_t k_[19], v_[16];
  uint4 sk;
  int task = R.b() < R.nprep() ? R.b() : 320;
  delay(KVDLY);
  PROFC(tid == 0, 345);
  kv_load(P, S, min(task, 319), tid, k_, v_, sk);
  const __nv_bfloat16* pf = (tid < 64 ? P.k : P.v) + (tid & 63) * DM;
  const int j = lane >> 3, sm = min(R.sm(), 9), trow = 160 * tb + 4 * sm + (tb < 12 ? 40 : 32) * w + j;
  const uint32_t so = sb + (2 * w + (j & 1) + 8 * (j >> 1)) * 128 + 16 * (lane & 7), xo = so + sm * 2048, wo = so + (tb & 1) * 8192 + (tb & 6) * 1024;
  const __nv_bfloat16* xp = H.x + (size_t)min(trow, SEQ - 1) * DM + 384 + 8 * (lane & 7);
  const __nv_bfloat16* bp = (j < 2 ? H.b0 : H.b1) + (size_t)(64 * cb + 32 * (tb & 1) + 4 * (tb & 6) + 2 * w + (j & 1)) * DM + 384 + 8 * (lane & 7);
  float s = 0.f, s2 = 0.f, sr = 0.f;
#define STAT(m, n) { const uint32_t xw[4] = {m.x, m.y, m.z, m.w}, bw[4] = {n.x, n.y, n.z, n.w}; \
  _Pragma("unroll") for (int i = 0; i < 4; i++) { const float u = bf_lo(xw[i]), v = bf_hi(xw[i]); s += u + v; s2 = fmaf(u, u, fmaf(v, v, s2)); sr += bf_lo(bw[i]) + bf_hi(bw[i]); } }
#define STATS(K0, K1) _Pragma("unroll 1") for (int kb = K0; kb < K1; kb++) { \
    mbar_wait(BAR(B_F1 + kb)); \
    const uint4 a = lds4(xo + ((uint32_t)(XTAB0 >> (6 * kb)) & 63) * 4096), c = lds4(wo + ((uint32_t)(WTAB0 >> (6 * kb)) & 63) * 4096); \
    STAT(a, c) \
    asm volatile("" : "+f"(s), "+f"(s2), "+f"(sr)); \
    if (XPFAT >= K0 && XPFAT < K1) prefetch_if(((lane & 4) ? bp : xp) + 64 * (lane & 3), kb == XPFAT); \
    kv_prefetch(pf, kb == KPFAT ? task + R.nprep() : kb == KPFAT2 ? task + 2 * R.nprep() : 320); \
  } \
  __syncwarp(); mbar_arrive_if(BAR(B_AX + K0 / 3), lane == 0);
  STATS(0, 3)
  PROFC(tid == 0, 349);
    {
      uint4 m[4], n[4];
#pragma unroll
      for (int i = 0; i < 4; i++) { m[i] = ldg4(xp + 64 * i); n[i] = ldg4(bp + 64 * i); }
      STATS(3, 6)
      PROFC(tid == 0, 346);
      mbar_wait(BAR(B_LM));
      const uint32_t tag = lds32(sb + MISC_OFF) & 1;
#pragma unroll
      for (int i = 0; i < 4; i++) { const uint4 a = m[i], c = n[i]; STAT(a, c) }
      PROFC(tid == 0 && s2 != 1.2345f, 347);
#pragma unroll
      for (int o = 1; o <= 4; o <<= 1) { s += __shfl_xor_sync(0xffffffff, s, o); s2 += __shfl_xor_sync(0xffffffff, s2, o); sr += __shfl_xor_sync(0xffffffff, sr, o); }
      const float mn = s * (1.f / DM), rs = frcp(bf_rn(fsqrt(bf_rn(bf_rn(fmaxf(s2 * (1.f / DM) - mn * mn, 0.f)) + 1e-5f))));
      asm volatile("{ .reg .pred p; setp.ne.u32 p, %2, 0; @p st.relaxed.gpu.global.u32 [%0],%1; }"
                   ::"l"((uint32_t*)(S->RS + (8 * cb + 4 * (tb & 1) + (tb >> 1)) * 16 + 4 * w + (j & 1)) + (lane & 4) + (j >> 1)), "r"(tagf(sr, tag)),
                   "r"((uint32_t)(tb < 8 && (lane & 3) == 0)) : "memory");
      asm volatile("{ .reg .pred p; setp.ne.u32 p, %3, 0; @p st.relaxed.gpu.global.v2.u32 [%0],{%1,%2}; }"
                   ::"l"(S->S + trow), "r"(tagf(rs, tag)), "r"(tagf(-bf_rn(mn) * rs, tag)), "r"((uint32_t)(R.sm() < 10 && (lane & 7) == 0)) : "memory");
      PROFC(tid == 0, 3);
    }
#pragma unroll 1
  for (int r = 0; task < 320; r++) {
    {
      const uint32_t T0 = __byte_perm(sk.x, sk.z, 0x5410), T1 = __byte_perm(sk.x, sk.z, 0x7632);
      const uint32_t T2 = __byte_perm(sk.y, sk.w, 0x5410), T3 = __byte_perm(sk.y, sk.w, 0x7632);
      PROFC(tid == 0 && v_[15] != 0x12345, 336 + r);
      uint32_t o[16];
#pragma unroll
      for (int t = 0; t < 16; t += 2) {
        const uint32_t a = hmul2(hfma2(k_[t + 3], T0, hfma2(k_[t + 2], T1, hfma2(k_[t + 1], T2, hmul2(k_[t], T3)))), v_[t]);
        const uint32_t c = hmul2(hfma2(k_[t + 4], T0, hfma2(k_[t + 3], T1, hfma2(k_[t + 2], T2, hmul2(k_[t + 1], T3)))), v_[t + 1]);
        const int wd = ((7 - t / 2) >> 1) + 4 * ((7 - t / 2) & 1);
        o[wd] = __byte_perm(c, a, 0x5410); o[8 + wd] = __byte_perm(c, a, 0x7632);
        asm volatile("" : "+r"(o[wd]), "+r"(o[8 + wd]));
        if (t == PFAT) kv_prefetch(pf, task + (1 + PFD) * R.nprep());
      }
      PROFC(tid == 0, 330 + 2 * r);
      const int ph = task & 1;
      task += R.nprep();
      if (ORD == 0 && task < 320) kv_load(P, S, task, tid, k_, v_, sk);
      mbar_wait(BAR(B_E1 + 3)); mbar_wait(BAR(B_AX + 1));
#pragma unroll
      for (int i = 0; i < 4; i++) {
        const int row = 2 * lane + (i >> 1);
        asm volatile("st.shared.v4.u32 [%0],{%1,%2,%3,%4};" ::"r"(sb + KS_OFF + r * 8192 + row * 128 + (((2 * w + ((i & 1) ^ ph)) ^ (row & 7)) << 4)),
                     "r"(o[4 * i]), "r"(o[4 * i + 1]), "r"(o[4 * i + 2]), "r"(o[4 * i + 3]) : "memory");
      }
      __syncwarp();
      mbar_arrive_if(BAR(B_PS + r), lane == 0);
      PROFC(tid == 0, 331 + 2 * r);
      if (ORD == 1 && task < 320) kv_load(P, S, task, tid, k_, v_, sk);
    }
  }
#undef STAT
#undef STATS
  PROFC(tid == 0, 40);
}
#define SPLIT(G) asm volatile("{ .reg .pred p; .reg .u32 r; L: mov.u32 r, %%clock; setp.eq.u32 p, r, %0; @p bra.uni L; }" ::"n"(G) : "memory")
template <bool AUX>
__device__ __forceinline__ void conv_loop(uint32_t sb, uint32_t rc, int wg, int tid, long long t_start) {
  sb = opaque(sb); rc = opaque(rc);
  const uint32_t bars = sb + BAR_OFF;
  int slot = AUX ? 0 : wg + 1;
  mbar_wait(BAR(B_LM));
#pragma unroll 1
  while (slot < (int)((rc >> 10) & 7)) {
    tid = opaque(tid);
    const int w = tid >> 5, lane = tid & 31, g = lane >> 2, q = lane & 3;
    const uint32_t Dn = lds32(sb + MISC_OFF + 4 + 4 * slot);
    const uint32_t d0 = (g == 1 && q == 3 - w) ? Dn : 0, d1 = (g == 0 && q == 3 - w) ? Dn : 0;
    const uint32_t cb_ = conv_buf(sb, slot), c0 = cb_ + KC_OFS;
    const uint32_t abase = c0 + 2 * (2 * (g & 1) + 4 * w + 16 * (g >> 1) + 4 * q);
    const uint64_t bd = make_desc(cb_ + KV_PAD, 16, 256, 3);
    const bool hi = lane & 16, s1 = lane & 8;
    const int qo = hi ? (q + 1) & 3 : q;
    const int srcA = hi ? (lane & 12) | ((q + 1) & 3) : (lane & 12) | 16 | ((q + 3) & 3);
    const bool h3 = hi && q == 3, wrap = s1 && qo == 3, back = wrap && hi;
    const bool chi = wrap ? !hi : hi;
    const int cq = s1 ? (qo + 1) & 3 : qo;
    const int srcB = (lane & 4) | (s1 ? 0 : 8) | (chi ? 16 | ((cq + 3) & 3) : cq);
    const uint32_t gp = c0 + 16 * (2 * (g & 1) + 4 * w) + (chi ? 256 : 0) + 2 * (2 * cq + (s1 ? 0 : 1));
    uint32_t a[12], f[16], o[8];
    float S[4], T[4], U[2], keep[2], pv[2] = {0.f, 0.f}, pr[4] = {0.f, 0.f, 0.f, 0.f};
    float e0[64], e1[56], e2[48], e3[40], e4[32], e5[24], e6[16], e7[8];
#define UNR _Pragma("unroll")
#define PERM() UNR for (int i = 0; i < 4; i++) { f[4 * i] = __byte_perm(a[3 * i], a[3 * i + 1], 0x5432); f[4 * i + 1] = a[3 * i + 1]; \
                                                 f[4 * i + 2] = __byte_perm(a[3 * i + 1], a[3 * i + 2], 0x5432); f[4 * i + 3] = a[3 * i + 2]; }
#define MMA(N, E) UNR for (int i = 0; i < 4; i++) wgmma_rs<N>(E, f[4 * i], f[4 * i + 1], f[4 * i + 2], f[4 * i + 3], bd - 8 * i, 1); wg_commit();
#define L1(c) UNR for (int i = 0; i < 4; i++) { const float ev = c[i], od = c[4 + i]; S[i] = hi ? (h3 ? ev : od) : ev; \
                                                T[i] = __shfl_sync(0xffffffff, hi ? (h3 ? pr[i] : ev) : od, srcA); pr[i] = od; }
#define L1E() UNR for (int i = 0; i < 4; i++) S[i] += T[i];
#define L2() UNR for (int h = 0; h < 2; h++) { keep[h] = back ? pv[h] : S[2 * h + 1]; pv[h] = S[2 * h + 1]; U[h] = __shfl_sync(0xffffffff, S[2 * h], srcB); }
#define L2E(j) o[j] = pack_bf(keep[0] + U[0], keep[1] + U[1]);
#define GRP(G, N, P, E) UNR for (int i = 0; i < N / 2; i++) asm volatile("mov.b32 %0,%1;" : "=f"(E[i]) : "f"(P[i + 8])); \
    wg_fence(); if (G < 7) conv_frags<(G + 1) & 7>(a, abase); if (G >= 2) { L2() } L1(P) MMA(N, E) SPLIT(G); \
    if (G < 7) { PERM() } if (G >= 2) { L2E((G + 6) & 7) } L1E() wg_wait<0>(); fence_regs(E);
    PROFC(tid == 0, 300 + 4 * slot);
    mbar_wait(BAR(B_KF + slot));
    PROFC(tid == 0, 301 + 4 * slot);
    conv_frags<0>(a, abase);
    wg_fence();
    wgmma_rs<128>(e0, d0 << 16, d0, d1 << 16, d1, bd, 0);
    PERM() conv_frags<1>(a, abase); wg_fence(); MMA(128, e0) SPLIT(0); PERM() wg_wait<0>(); fence_regs(e0);
    GRP(1, 112, e0, e1) GRP(2, 96, e1, e2) GRP(3, 80, e2, e3) GRP(4, 64, e3, e4) GRP(5, 48, e4, e5) GRP(6, 32, e5, e6) GRP(7, 16, e6, e7)
    PROFC(tid == 0, 302 + 4 * slot);
    L2() L1(e7) L2E(6) L1E() L2() L2E(7)
    bar_sync(wg + 1, 128);
#pragma unroll
    for (int jj = 0; jj < 8; jj++)
      asm volatile("st.shared.u16 [%0],%1; st.shared.u16 [%0+16],%2;" ::"r"(gp + jj * 512), "h"((uint16_t)o[jj]), "h"((uint16_t)(o[jj] >> 16)) : "memory");
#undef PERM
#undef MMA
#undef L1
#undef L1E
#undef L2
#undef L2E
#undef GRP
    PROFC(tid == 0, 303 + 4 * slot);
    __syncwarp();
    if (lane == 0) mbar_arrive(BAR(B_GS + slot));
    if (!AUX) break;
    slot = slot ? slot + 1 : 3;
  }
}

#define IDX(J, c, h) (8 * (J) + 4 * ((c) >> 1) + 2 * (h) + ((c) & 1))
__device__ __forceinline__ uint2 lds2(uint32_t a) { uint2 v; asm volatile("ld.shared.v2.u32 {%0,%1},[%2];" : "=r"(v.x), "=r"(v.y) : "r"(a) : "memory"); return v; }
__device__ __forceinline__ void resid_load(float (&r)[40], uint32_t sb, int wg, int tid, const uint4& s) {
  const uint32_t dp = sb + XR_OFF + 8 * (tid & 3), xp = dp + (64 * wg + 16 * (tid >> 5) + ((tid & 31) >> 2)) * 160;
#pragma unroll
  for (int J = 0; J < 5; J++) {
    const uint2 u = lds2(xp + 32 * J), v = lds2(xp + 32 * J + 1280), d = lds2(dp + 20480 + 32 * J);
    r[8 * J] = __uint_as_float(u.x); r[8 * J + 1] = __uint_as_float(u.y); r[8 * J + 2] = __uint_as_float(v.x); r[8 * J + 3] = __uint_as_float(v.y);
    r[8 * J + 4] = __uint_as_float(d.x); r[8 * J + 5] = __uint_as_float(d.y);
  }
  r[30] = untag(s.x); r[31] = untag(s.y); r[38] = untag(s.z); r[39] = untag(s.w);
}
__device__ __forceinline__ void resid_init(float (&r)[40]) {
  const float s[4] = {r[30], r[31], r[38], r[39]};
#pragma unroll
  for (int J = 0; J < 5; J++) {
    uint32_t w[6];
#pragma unroll
    for (int i = 0; i < 6; i++) w[i] = __float_as_uint(r[8 * J + i]);
#pragma unroll
    for (int i = 0; i < 4; i++) {
      const int h = i >> 1, c = 2 * (i & 1);
      const float rs = s[2 * h], nm = s[2 * h + 1], x0 = bf_lo(w[i]), x1 = bf_hi(w[i]);
      const uint32_t t = hmul2(pack_bf(fmaf(x0, rs, nm), fmaf(x1, rs, nm)), w[4 + (i & 1)]);
      r[IDX(J, c, h)] = x0 + bf_lo(t); r[IDX(J, c + 1, h)] = x1 + bf_hi(t);
    }
  }
}

__device__ __forceinline__ float flip(float v, uint32_t m) { return __uint_as_float(__float_as_uint(v) ^ m); }
__device__ __forceinline__ void g1_phase(const int LY, const Head& H, uint32_t sb, int wg, int tid, Role R, float (&xr)[40], long long t_start) {
  Scratch* const S = H.s;
  tid = opaque(tid); sb = opaque(sb); R.v = opaque(R.v);
  const uint32_t bars = sb + BAR_OFF;
  const int cb = R.cb(), tb = R.tb();
  const int w = tid >> 5, lane = tid & 31, g = lane >> 2, q = lane & 3;
  const bool full = tb < 12;
  uint2* Eb = S->E + ((LY * 130 + cb) * 8 + 4 * wg + w) * 16 + g;
  float a[80];
#pragma unroll
  for (int i = 0; i < 80; i++) a[i] = 0.f;
  uint32_t rel = mapa(BAR(B_E1), lane ? R.wpart() : R.ubase() + (w & (R.ugs() - 1)));
  const bool rels = lane == 0 || (tid == 1 && wg != R.wlo());
  {
    uint64_t tw = LY ? WTAB1 : WTAB0, tx = LY ? XTAB1 : XTAB0;
    uint32_t bf = BAR(B_F1);
    if (tid == 0 && wg == 0 && !LY) PROF(351);
    fence_regs(a);
    mbar_wait(bf, LY);
    if (tid == 0 && wg == 0) PROF(LY ? 20 : 4);
#pragma unroll 1
    for (int kb = 0; kb < 10; kb++) {
      const uint64_t da = make_desc(sb + ((uint32_t)tw & 63) * 4096 + wg * 8192, 16, 1024, 1);
      const uint64_t db = make_desc(sb + ((uint32_t)tx & 63) * 4096, 16, 1024, 1);
      wg_fence();
#pragma unroll
      for (int kk = 0; kk < 4; kk++) wgmma_ss160(a, da + 2 * kk, db + 2 * kk, 1);
      wg_commit();
      wg_wait<1>();
      if (kb > 0) { if (rels) mbar_arrive_at(rel); rel += 8; }
      bf += 8; tw >>= 6; tx >>= 6;
      if (kb < 9) mbar_wait(bf, LY);
    }
  }
  if (tid == 0 && wg == 0) PROF(LY ? 19 : 2);
  mbar_wait(BAR(B_LM));
  const uint32_t tag = lds32(sb + MISC_OFF) & 1;
  if (q == 3) st_rlx2(Eb + tb * 1280, tag ^ 1, tag ^ 1);
  float2 lam, mu, mu2;
  float rs0, rs1;
  const uint32_t lamp = sb + LAM_OFF + 16 * (32 * wg + 8 * w + g);
  {
    const uint2* rp = S->RS + (8 * cb + 4 * wg + w) * 16 + 2 * g - (g & 1);
    uint2 v = ld_rlx2(rp);
    asm volatile("ld.shared.v2.f32 {%0,%1},[%2];" : "=f"(lam.x), "=f"(lam.y) : "r"(lamp));
    const float2 l2 = cmul(lam, lam), l4 = cmul(l2, l2), l8 = cmul(l4, l4), l16 = cmul(l8, l8), l32 = cmul(l16, l16);
    mu = full ? cmul(l32, l8) : l32; mu2 = cmul(mu, mu);
#pragma unroll 1
    for (int it = 0; it < SPIN && __any_sync(0xffffffff, untagged(v, tag)); it++) v = ld_rlx2(rp);
    rs0 = untag(v.x); rs1 = untag(v.y);
  }
  if (tid == 0 && wg == 0 && !LY) PROF(39);
  mbar_wait(BAR(B_ST), LY);
  const uint32_t ssm = sb + SSM_OFF + q * (full ? 336 : 272);
  wg_wait<0>(); fence_regs(a);
  if (rels) mbar_arrive_at(rel);
  if (tid == 0 && wg == 0) PROF(LY ? 21 : 5);
  float2 p = make_float2(0.f, 0.f);
#pragma unroll
  for (int j = 0; j < 20; j++) {
    if (j < 16 || full) {
      float4 sv;
      asm volatile("ld.shared.v4.f32 {%0,%1,%2,%3},[%4];" : "=f"(sv.x), "=f"(sv.y), "=f"(sv.z), "=f"(sv.w) : "r"(ssm + 16 * j));
#pragma unroll
      for (int e = 0; e < 2; e++) {
        const int o = 4 * j + e;
        const float r = e ? sv.z : sv.x, nm = e ? sv.w : sv.y;
        a[o] = fmaf(a[o], r, nm * rs0); a[o + 2] = fmaf(a[o + 2], r, nm * rs1);
        p = cfma(lam, p, make_float2(a[o], a[o + 2]));
      }
    }
  }
  {
    float2 t = make_float2(__shfl_up_sync(0xffffffff, p.x, 1, 4), __shfl_up_sync(0xffffffff, p.y, 1, 4));
    if (q >= 1) p = cfma(mu, t, p);
    t = make_float2(__shfl_up_sync(0xffffffff, p.x, 2, 4), __shfl_up_sync(0xffffffff, p.y, 2, 4));
    if (q >= 2) p = cfma(mu2, t, p);
  }
  if (q == 3 && full) st_rlx2(Eb + tb * 1280, tagf(p.x, tag), tagf(p.y, tag));
  if (tid == 0 && wg == 1) PROF(96 + 64 * LY);
  uint2 ev[3];
#pragma unroll
  for (int i = 0; i < 3; i++) { const int j = tb - 1 - q - 4 * i; ev[i] = j >= 0 ? ld_rlx2(Eb + j * 1280) : make_uint2(tag, tag); }
  float2 x = make_float2(__shfl_up_sync(0xffffffff, p.x, 1, 4), __shfl_up_sync(0xffffffff, p.y, 1, 4));
  if (q == 0) x = make_float2(0.f, 0.f);
  float c0, c1;
  asm volatile("ld.shared.v2.f32 {%0,%1},[%2+8];" : "=f"(c0), "=f"(c1) : "r"(lamp));
  const float c2 = -flip(c1, H.swap), c3 = flip(c0, H.swap);
#pragma unroll
  for (int i = 0; i < 40; i++) {
    const int o = 4 * (i >> 1) + (i & 1);
    const float u = a[o], v = a[o + 2];
    a[o] = fmaf(c0, u, c1 * v); a[o + 2] = fmaf(c2, u, c3 * v);
  }
  fence_regs(a);
  if (LY == 0 && R.b() < 128) {
    const int t0 = 16 * g + 8 * wg + 2 * w;
    mbar_wait(BAR(B_XR));
    uint4 s = lds4(sb + XR_OFF + 20480 + 256 + 8 * t0);
    if (__any_sync(0xffffffff, untagged(s, tag))) {
#pragma unroll 1
      for (int it = 0; it < SPIN; it++) { s = ld_rlx4(S->S + 128 * (R.b() >> 3) + t0); if (!__any_sync(0xffffffff, untagged(s, tag))) break; }
    }
    resid_load(xr, sb, wg, tid, s);
  }
  float2 mq, om4, fq;
  {
    asm volatile("" : "+f"(lam.x), "+f"(lam.y));
    const float2 one = make_float2(1.f, 0.f), l2 = cmul(lam, lam), l4 = cmul(l2, l2), l8 = cmul(l4, l4), l16 = cmul(l8, l8);
    const float2 l80 = full ? mu2 : cmul(mu2, l16), om = cmul(l80, l80), om2 = cmul(om, om);
    mq = cmul((q & 1) ? mu : one, (q & 2) ? mu2 : one);
    om4 = cmul(om2, om2); fq = cmul((q & 1) ? om : one, (q & 2) ? om2 : one);
  }
  mbar_wait(BAR(B_E1 + 9), LY);
#pragma unroll 1
  for (int it = 0; it < SPIN; it++) {
    const bool m0 = untagged(ev[0], tag), m1 = untagged(ev[1], tag), m2 = untagged(ev[2], tag);
    if (!__any_sync(0xffffffff, m0 || m1 || m2)) break;
    if (m0) ev[0] = ld_rlx2(Eb + (tb - 1 - q) * 1280);
    if (m1) ev[1] = ld_rlx2(Eb + (tb - 5 - q) * 1280);
    if (m2) ev[2] = ld_rlx2(Eb + (tb - 9 - q) * 1280);
  }
  if (tid == 0 && wg == 1) PROF(97 + 64 * LY);
  float2 c = make_float2(untag(ev[2].x), untag(ev[2].y));
#pragma unroll
  for (int i = 1; i >= 0; i--) c = cfma(om4, c, make_float2(untag(ev[i].x), untag(ev[i].y)));
  c = cmul(fq, c);
#pragma unroll
  for (int s = 1; s <= 2; s <<= 1) { c.x += __shfl_xor_sync(0xffffffff, c.x, s); c.y += __shfl_xor_sync(0xffffffff, c.y, s); }
  c = cfma(mq, c, x);
  float2 z = make_float2(fmaf(c0, c.x, c1 * c.y), fmaf(c2, c.x, c3 * c.y));
  if (tid == 0 && wg == 0) PROF(LY ? 22 : 6);
  const float2 lc = make_float2(lam.x, flip(lam.y, H.swap));
  const uint32_t hq = sb + (lane >> 4) * 1024 + (lane & 7) * 128 + (((4 * wg + w) ^ (lane & 7)) << 4);
  const uint32_t hp = hq + R_OFF + (lane & 8) * 2048, hp4 = hq + (LY ? R4_OFF1 : R4_OFF0) + (lane & 8) * 512;
#pragma unroll
  for (int j = 0; j < 20; j += 2) {
    if (j < 16 || full) {
      uint32_t o[4];
#pragma unroll
      for (int i = 0; i < 2; i++) {
        const float2 z0 = cfma(lc, z, make_float2(a[4 * (j + i)], a[4 * (j + i) + 2]));
        z = cfma(lc, z0, make_float2(a[4 * (j + i) + 1], a[4 * (j + i) + 3]));
        o[2 * i] = pack_bf(z0.x, z.x); o[2 * i + 1] = pack_bf(z0.y, z.y);
      }
      asm volatile("stmatrix.sync.aligned.m8n8.x4.trans.shared.b16 [%0], {%1,%2,%3,%4};" ::"r"(j < 16 ? hp + j * 1024 : hp4 + (j - 16) * 1024), "r"(o[0]), "r"(o[1]), "r"(o[2]), "r"(o[3]) : "memory");
      if (j & 2) { __syncwarp(); if (lane == 0) mbar_arrive(BAR(B_SH + j / 4)); }
    }
  }
  if (tid == 0 && wg == 0) PROF(LY ? 23 : 7);
}

__device__ __forceinline__ void g2_phase(const int LY, const Params& P, Scratch* S, uint32_t sb, int wg, int tid, Role R, float (&xr)[40], long long t_start) {
  float acc[40];
#pragma unroll
  for (int i = 0; i < 40; i++) acc[i] = 0.f;
  tid = opaque(tid); sb = opaque(sb); R.v = opaque(R.v);
  const uint32_t tag = lds32(sb + MISC_OFF) & 1;
  const uint32_t bars = sb + BAR_OFF;
  const int b = R.b(), tb2 = b >> 3, db_ = b & 7;
  const int w = tid >> 5, lane = tid & 31, g = lane >> 2, q = lane & 3;
  const int t0 = 128 * tb2 + 16 * g + 8 * wg + 2 * w;
  const int d0 = 80 * db_ + 4 * q, mrow = 64 * wg + 16 * w + g;
#define GATE(J, c, h) (((c) & 1) ? bf_hi(G[4 * (J) + 2 * (h) + ((c) >> 1)]) : bf_lo(G[4 * (J) + 2 * (h) + ((c) >> 1)]))
  uint32_t* Mb = S->M + ((2 * LY * 16 + tb2) * 8) * 256 + (wg * 4 + w) * 32 + (2 * g + (q & 1)) * 2 + (q >> 1);
  st_rlx(Mb + db_ * 256, tag ^ 1);
  if (LY == 0) st_rlx(Mb + (16 * 8 + db_) * 256, tag ^ 1);
  uint2 dl[5];
#pragma unroll
  for (int J = 0; J < 5; J++) dl[J] = __ldg((const uint2*)(P.dskip + d0 + 16 * J));
  uint32_t rel = mapa(BAR(B_E2), lane ? ((w & 1) ? R.wpart() : R.rank()) : R.cs() == 8 ? 4 * wg + w : wg);
  const bool rels = lane == 0 || (lane == 1 && w < 2);
  {
    uint32_t bf = BAR(B_F2), st = 0;
    fence_regs(acc);
    mbar_wait(bf, LY);
    if (tid == 0 && wg == 0) PROF(LY ? 25 : 10);
#pragma unroll 1
    for (int kp = 0; kp < 10; kp++) {
      const uint64_t da = make_desc(sb + H_OFF + st * 32768 + wg * 8192, 16, 1024, 1);
      const uint64_t db0 = make_desc(sb + (kp < 5 ? kp : kp - 5) * 20480, 16, 1024, 1), db1 = db0 + 640;
      wg_fence();
#pragma unroll
      for (int kk = 0; kk < 4; kk++) wgmma_ss80(acc, da + 2 * kk, db0 + 2 * kk, 1);
#pragma unroll
      for (int kk = 0; kk < 4; kk++) wgmma_ss80(acc, da + 1024 + 2 * kk, db1 + 2 * kk, 1);
      wg_commit();
      if (kp + LY == 0) resid_init(xr);
      wg_wait<1>();
      if (kp > 0) { if (rels && (LY == 0 || kp < 8)) mbar_arrive_at(rel); rel += 8; }
      bf += 8; st = st == 2 ? 0 : st + 1;
      if (kp < 9) mbar_wait(bf, LY);
    }
  }
  wg_wait<0>(); fence_regs(acc);
  if (LY == 0 && rels) mbar_arrive_at(rel);
#pragma unroll
  for (int i = 0; i < 40; i++) acc[i] += xr[i];
  if (tid == 0 && wg == 0) PROF(LY ? 26 : 11);
  if (lane == 0) PROF(116 + 64 * LY + wg * 4 + w);

  float mm[2], rr[2], m1 = 0.f;
#pragma unroll 1
  for (int rep = 0;; rep++) {
    float m[2][2];
#pragma unroll
    for (int h = 0; h < 2; h++) {
      m[h][0] = m[h][1] = 0.f;
#pragma unroll
      for (int J = 0; J < 5; J++)
#pragma unroll
        for (int c = 0; c < 4; c++) { const float xv = acc[IDX(J, c, h)]; m[h][0] += xv; m[h][1] = fmaf(xv, xv, m[h][1]); }
    }
    float r1[2];
#pragma unroll
    for (int i = 0; i < 2; i++) { const float snd = (q & 1) ? m[0][i] : m[1][i], kp = (q & 1) ? m[1][i] : m[0][i]; r1[i] = kp + __shfl_xor_sync(0xffffffff, snd, 1); }
    const float r2 = ((q & 2) ? r1[1] : r1[0]) + __shfl_xor_sync(0xffffffff, (q & 2) ? r1[0] : r1[1], 2);
    st_rlx(Mb + db_ * 256, tagf(r2, tag));
    if (lane == 0 && rep == 0) PROF(100 + 64 * LY + wg * 4 + w);
    uint32_t G[20];
    mbar_wait(BAR(B_GF), LY);
    __syncwarp();
    {
      const uint32_t gb = sb + G_OFF + wg * 10240;
      const int dr = 4 * ((lane & 7) >> 1) + (lane & 1) + 2 * ((lane >> 3) & 1), ck = 2 * w + (lane >> 4);
#pragma unroll
      for (int J = 0; J < 5; J++) {
        const int dd = 16 * J + dr;
        asm volatile("ldmatrix.sync.aligned.m8n8.x4.trans.shared.b16 {%0,%1,%2,%3},[%4];"
                     : "=r"(G[4 * J]), "=r"(G[4 * J + 1]), "=r"(G[4 * J + 2]), "=r"(G[4 * J + 3]) : "r"(gb + dd * 128 + ((ck ^ (dd & 7)) << 4)) : "memory");
      }
    }
    uint32_t mv[8];
#pragma unroll
    for (int i = 0; i < 8; i++) mv[i] = ld_rlx(Mb + i * 256);
#pragma unroll 1
    for (int it = 0; it < SPIN; it++) {
      uint32_t miss = 0;
#pragma unroll
      for (int i = 0; i < 8; i++) miss |= ((mv[i] ^ tag) & 1) << i;
      if (!__any_sync(0xffffffff, miss)) break;
#pragma unroll
      for (int i = 0; i < 8; i++) if ((miss >> i) & 1) mv[i] = ld_rlx(Mb + i * 256);
    }
    bar_sync(4, 256);
    if (tid == 0 && wg == 0) PROF(LY ? 27 : 12 + 3 * rep);
    if (lane == 0 && rep == 0) PROF(108 + 64 * LY + wg * 4 + w);
    const float s = ((untag(mv[0]) + untag(mv[1])) + (untag(mv[2]) + untag(mv[3]))) + ((untag(mv[4]) + untag(mv[5])) + (untag(mv[6]) + untag(mv[7])));
    const float o = __shfl_xor_sync(0xffffffff, s, 2);
    const float S1 = (q & 2) ? o : s, S2 = (q & 2) ? s : o;
    const float mean = S1 * (1.f / DM), rs = frsqrt(fmaxf(S2 * (1.f / DM) - mean * mean, 0.f) + 1e-5f);
    const float mo = __shfl_xor_sync(0xffffffff, mean, 1), ro = __shfl_xor_sync(0xffffffff, rs, 1);
    mm[0] = (q & 1) ? mo : mean; mm[1] = (q & 1) ? mean : mo; rr[0] = (q & 1) ? ro : rs; rr[1] = (q & 1) ? rs : ro;
    if (rep) {
      if (db_ == 0) {
        if (q < 2) asm volatile("st.shared.v2.u32 [%0],{%1,%2};" ::"r"(sb + SSM_OFF + 8 * (t0 - 128 * tb2 + q)), "r"(tagf(rs, tag)), "r"(tagf((m1 - mean) * rs, tag)) : "memory");
        bar_sync(4, 256);
        if (wg == 0 && tid < 64) {
          uint4 v;
          asm volatile("ld.shared.v4.u32 {%0,%1,%2,%3},[%4];" : "=r"(v.x), "=r"(v.y), "=r"(v.z), "=r"(v.w) : "r"(sb + SSM_OFF + 16 * tid));
          st_rlx4(S->S + SEQ + 128 * tb2 + 2 * tid, v.x, v.y, v.z, v.w);
        }
      }
      break;
    }
#pragma unroll
    for (int h = 0; h < 2; h++)
#pragma unroll
      for (int J = 0; J < 5; J++)
#pragma unroll
        for (int c = 0; c < 4; c++) { const float xv = acc[IDX(J, c, h)]; acc[IDX(J, c, h)] = fmaf((xv - mm[h]) * rr[h], GATE(J, c, h), xv); }
    if (LY) break;
    m1 = mean;
#pragma unroll
    for (int i = 0; i < 10; i++) {
      const int J = i >> 1, h = i & 1;
      const uint32_t u0 = pack_bf(acc[IDX(J, 0, h)] - mm[h], acc[IDX(J, 1, h)] - mm[h]), u1 = pack_bf(acc[IDX(J, 2, h)] - mm[h], acc[IDX(J, 3, h)] - mm[h]);
      asm volatile("st.shared.v2.u32 [%0],{%1,%2};" ::"r"(sb + US_OFF + (mrow + 8 * h) * 160 + 32 * J + 8 * q), "r"(u0), "r"(u1) : "memory");
    }
    __syncwarp();
    if (lane == 0) mbar_arrive(BAR(B_SG));
    if (tid == 0 && wg == 0) PROF(13);
    Mb += 16 * 8 * 256;
  }
  if (LY == 0) {
#pragma unroll
    for (int h = 0; h < 2; h++)
#pragma unroll
      for (int J = 0; J < 5; J++)
#pragma unroll
        for (int c = 0; c < 4; c++) {
          const float x2 = acc[IDX(J, c, h)];
          const uint32_t dw = (c & 2) ? dl[J].y : dl[J].x;
          xr[IDX(J, c, h)] = fmaf((x2 - mm[h]) * rr[h], (c & 1) ? bf_hi(dw) : bf_lo(dw), x2);
        }
  }
  else {
    float* op = P.out + (size_t)t0 * DM + d0;
#pragma unroll
    for (int i = 0; i < 10; i++) {
      const int J = i >> 1, h = i & 1;
      asm volatile("st.global.v4.f32 [%0],{%1,%2,%3,%4};" ::"l"(op + h * DM + 16 * J),
                   "f"(acc[IDX(J, 0, h)]), "f"(acc[IDX(J, 1, h)]), "f"(acc[IDX(J, 2, h)]), "f"(acc[IDX(J, 3, h)]) : "memory");
    }
  }
  if (tid == 0 && wg == 0 && LY) PROF(28);
#undef IDX
#undef GATE
}

template <int I0, int I1> __device__ __forceinline__ void init_barriers(uint32_t bars) {
#pragma unroll
  for (int i = I0; i < I1; i++) mbar_init(BAR(i), bar_count(i));
}
__device__ __forceinline__ int g2_cb(int kp) { return kp < 5 ? 2 * kp : 2 * kp - 9; }
__global__ void __cluster_dims__() __launch_bounds__(512, 1) fused_kernel(const Head H, const __grid_constant__ Params P) {
  extern __shared__ __align__(1024) uint8_t smem[];
  const uint32_t sb = opaque(smem_u32(smem)), bars = sb + BAR_OFF;
  const int wi = __shfl_sync(0xffffffff, threadIdx.x >> 5, 0), wg = wi >> 2, tid = threadIdx.x & 127;
  const int umap = blockIdx.x >= 96;
#define CLK(v)
  CLK(c_a);
  if (wi == 14) {
    if (elect_one()) { init_barriers<0, NBAR1>(bars); asm volatile("fence.mbarrier_init.release.cluster;" ::: "memory"); }
    __syncwarp();
  } else if (wi >= 12) prefetch_map(wi == 12 ? &P.mB : &P.mA[umap]);
  else if (wg == 2) xb_prefetch<1>(H, blockIdx.x + H.base, tid, 0);
  else if (P.role[blockIdx.x].w) return;
  CLK(c_b);
  asm volatile("barrier.cluster.arrive.relaxed.aligned;" ::: "memory");
  CLK(c_c);
  Role R;
  { const uint4 r = P.role[blockIdx.x]; R.v = r.x; R.c = r.y; R.p = r.z; }
  const int id = R.c & 255;
  const int tb = R.tb(), cb = R.cb(), b = R.b(), tb2 = b >> 3, db = b & 7, rank = R.rank();
  const bool has1 = tb <= 12, has2 = b < 128, full = tb < 12;
  Scratch* const S = H.s;
  unsigned* const epoch_p = &S->epoch[id * 8];
  const long long t_start = 0;
  if (wg < 2) {
    if (threadIdx.x == 0) PROF(50);
    asm volatile("griddepcontrol.launch_dependents;");
    bar_sync(6, 448);
    asm volatile("setmaxnreg.inc.sync.aligned.u32 176;");
    float xr[40];
#pragma unroll
    for (int i = 0; i < 40; i++) xr[i] = 0.f;
#pragma unroll 1
    for (int ly = 0; ly < 2; ly++) {
      if (has1) g1_phase(ly, H, sb, wg, tid, R, xr, t_start);
      if (ly == 0) {
        conv_loop<false>(sb, R.c, wg, tid, t_start);
        if (tid == 0 && wg == 0) PROF(9);
      }
      if (has2) g2_phase(ly, P, S, sb, wg, tid, R, xr, t_start);
    }
    if (tid == 0 && wg == 0) st_rlx(epoch_p, lds32(sb + MISC_OFF));
  } else if (wg == 2) {
    bar_sync(6, 448);
    if (has1) aux_prep(H, P, sb, R, tid, t_start);
    asm volatile("setmaxnreg.inc.sync.aligned.u32 136;");
    conv_loop<true>(sb, R.c, wg, tid, t_start);
    if (tid == 0) PROF(44);
  } else {
    if (threadIdx.x == 384) PROF(354);
    asm volatile("setmaxnreg.dec.sync.aligned.u32 24;");
    const int wlo = R.wlo(), whi = R.whi();
    const uint32_t wmask = R.wmask(), umask = R.umask(), f1bytes = full ? 36864 : 32768;
    if (wi < 14) {
      if (threadIdx.x == 384) PROF(340);
      asm volatile("barrier.cluster.wait.aligned;" ::: "memory");
      if (has1 && elect_one()) {
        uint64_t tab = wi == 12 ? WTAB0 : XTAB0;
        PROF(329 + wi);
#pragma unroll 1
        for (int kb = 0; kb < 6; kb++, tab >>= 6) {
          const uint32_t dst = sb + ((uint32_t)tab & 63) * 4096;
          if (wi == 12) {
#pragma unroll 1
            for (int h = wlo; h <= whi; h++) tma4d_mc(dst + h * 8192, &P.mB, kb * 64, 0, 0, 8 * cb + 4 * h, BAR(B_F1 + kb), wmask);
          } else {
            tma4d_mc(dst + R.uj() * 1024, &P.mA[umap], kb * 64, 0, 0, 80 * tb + R.uj(), BAR(B_F1 + kb), umask);
            mbar_expect_tx(BAR(B_F1 + kb), f1bytes);
          }
        }
      }
      if (!has1 && wi == 13) bar_sync(7, 64);
    } else {
      if (wi == 15 && elect_one()) { init_barriers<NBAR1, NBAR>(bars); asm volatile("fence.mbarrier_init.release.cluster;" ::: "memory"); }
      bar_sync(6, 448);
      if (!has1 && wi == 14) bar_sync(7, 64);
    }
    const unsigned e1 = ld_rlx(epoch_p) + 1;
    if (wi == 12) {
      if (elect_one()) {
#pragma unroll 1
        for (int ly = 0; ly < 2; ly++) {
#pragma unroll 1
          for (int kb = ly ? 0 : 6; kb < 10 && has1; kb++) {
            if (ly == 0) { mbar_wait(BAR(B_E1 + ((DEP0 >> (4 * kb - 24)) & 15))); mbar_wait(BAR(B_AX + (kb == 9))); }
            else if (has2) {
              if (kb < 6) mbar_wait(BAR(B_E2 + ((0x988765u >> (4 * kb)) & 15)));
              else { mbar_wait(BAR(B_GE)); mbar_wait(BAR(B_F1 + kb - 6), 1); }
            } else if (kb == 0) { mbar_wait(BAR(B_E1 + 9)); mbar_wait(BAR(B_CD + 1)); }
            const uint32_t dst = sb + ((uint32_t)((ly ? WTAB1 : WTAB0) >> (6 * kb)) & 63) * 4096;
#pragma unroll 1
            for (int h = wlo; h <= whi; h++) tma4d_mc(dst + h * 8192, &P.mB, kb * 64, 0, 0, 8 * cb + 4 * h, BAR(B_F1 + kb), wmask);
          }
          if (has2) {
            if (ly == 0) {
              mbar_wait(BAR(B_E1 + XRAT));
              mbar_expect_tx(BAR(B_XR), 20480 + 160 + 1024);
              tma4d(sb + XR_OFF, &P.mX, 80 * db, tb2, BAR(B_XR));
              bulk_g2s(sb + XR_OFF + 20480, P.dskip + 80 * db, 160, BAR(B_XR));
              bulk_g2s(sb + XR_OFF + 20480 + 256, S->S + 128 * tb2, 1024, BAR(B_XR));
            }
#pragma unroll 1
            for (int kp = 0; kp < 10; kp++) {
              const uint32_t dst = sb + (kp < 5 ? kp : kp - 5) * 20480;
              mbar_wait(BAR(kp >= 5 ? B_E2 + kp - 5 : ly ? B_E1 + ((0x84321u >> (4 * kp)) & 15) : kp < 4 ? B_SH : B_CD), ly);
              mbar_expect_tx(BAR(B_F2 + kp), 20480 + 32768);
              tma5d(dst, &P.mC[0], g2_cb(kp) * 64, db * 5, BAR(B_F2 + kp));
              tma5d(dst + 10240, &P.mC[1], g2_cb(kp) * 64, db * 5, BAR(B_F2 + kp));
              if (kp == (ly ? 4 : 9)) {
                mbar_wait(BAR(ly ? B_E1 + 9 : B_CD + 1), ly);
                wait_cnt(&S->cnt[(C_G + db) * 32], e1 * 80);
                if (!ly) PROF(47);
                mbar_expect_tx(BAR(B_GF), 20480);
                tma2d(sb + G_OFF, &P.mGT, tb2 * 128, db * 80, BAR(B_GF));
                tma2d(sb + G_OFF + 10240, &P.mGT, tb2 * 128 + 64, db * 80, BAR(B_GF));
              }
            }
          }
        }
      }
    } else if (wi == 13) {
      const int h0 = R.cs() == 8 ? rank : 4 * rank;
#pragma unroll 1
      for (int ly = 0; ly < 2; ly++) {
        int lane = lane_id();
        if (has1) {
          const unsigned* fp = &S->flag[(F_U3 + 8 * ((160 * tb) >> 7) + (lane & (full ? 15 : 7))) * 32];
          uint32_t ready = ly ? __ballot_sync(0xffffffff, ld_rlx(fp) == e1) : ~0u;
          if (ly) mbar_wait(BAR(has2 ? B_SG : B_RF1));
#pragma unroll 1
          for (int kb = ly ? 0 : 6; kb < 10; kb++) {
            wait_flags(fp, e1, 0x101u * ((1u << (64 * kb / 80)) | (1u << ((64 * kb + 63) / 80))), ready);
            if (kb >= 3) mbar_wait(BAR(B_E1 + (ly ? kb - 3 : (DEP0 >> (4 * kb - 24)) & 15)), ly);
            mbar_wait(BAR(B_AX + (kb == 9)));
            if (elect_one()) {
              if (ly && kb == 0) PROF(34);
              tma4d_mc(sb + ((uint32_t)((ly ? XTAB1 : XTAB0) >> (6 * kb)) & 63) * 4096 + R.uj() * 1024, &P.mA[2 * ly + umap], kb * 64, 0, 0, 80 * tb + R.uj(),
                       BAR(B_F1 + kb), umask);
              mbar_expect_tx(BAR(B_F1 + kb), f1bytes);
            }
            __syncwarp();
          }
        }
        if (ly == 0) {
          if (elect_one()) {
            if (CPF == 0 && has2) { prefetch_l2(P.cre + (size_t)5 * b * DM, 5 * DM * 2); prefetch_l2(P.cim + (size_t)5 * b * DM, 5 * DM * 2); }
            if (KPF >= 0 && has1) mbar_wait(BAR(B_E1 + KPF));
#pragma unroll 1
            for (int s = 0; s < R.nch(); s++) prefetch_l2(P.ssmk + (size_t)R.ch(s) * SEQ, 4096);
            if (CPF == 1 && has2) { prefetch_l2(P.cre + (size_t)5 * b * DM, 5 * DM * 2); prefetch_l2(P.cim + (size_t)5 * b * DM, 5 * DM * 2); }
            if (has1) mbar_wait(BAR(B_E1 + 5));
#pragma unroll 1
            for (int s = 0; s < R.nch(); s++) {
              const uint32_t cbuf = conv_buf(sb, s);
              mbar_expect_tx(BAR(B_KF + s), CH_BYTES);
              bulk_g2s(cbuf + KC_OFS + 32, P.ssmk + (size_t)R.ch(s) * SEQ, 4096, BAR(B_KF + s));
              bulk_g2s(cbuf, S->zero, KV_PAD, BAR(B_KF + s));
              bulk_g2s(cbuf + KC_OFS, S->zero, 32, BAR(B_KF + s));
              if (s == 0) PROF(329);
              wait_cnt(&S->cnt[(C_KV + (R.ch(s) >> 6)) * 32], e1 * 32);
              if (s == 0) PROF(30);
              if (CPF == 2 && s == 0 && has2) { prefetch_l2(P.cre + (size_t)5 * b * DM, 5 * DM * 2); prefetch_l2(P.cim + (size_t)5 * b * DM, 5 * DM * 2); }
              bulk_g2s(cbuf + KV_PAD, S->kv + (size_t)R.ch(s) * SEQ, 4096, BAR(B_KF + s));
            }
            PROF(31);
          }
          __syncwarp();
          if (!has1) return;
        }
        lane = lane_id();
        const int s0 = 128 * min(tb2, 15) / 160;
        const bool two = (128 * tb2 + 127) / 160 != s0;
        const unsigned* fp = &S->flag[(F_H + (ly * 13 + s0) * 10 + min(lane & 15, 9) + (two && lane >= 16 ? 10 : 0)) * 32];
        uint32_t ready = __ballot_sync(0xffffffff, ld_rlx(fp) == e1), st = 0;
        if (ly == 0) {
          mbar_wait(BAR(B_HD));
          if (lane < 8) mbar_arrive_cl(BAR(B_RF1), lane & (R.cs() - 1));
        }
        if (has2) {
          mbar_wait(BAR(B_RF0), ly);
#pragma unroll 1
          for (int kp = 0; kp < 10; kp++) {
            if (ly && kp == 2) { mbar_wait(BAR(B_HD), 1); if (lane < 8) mbar_arrive_cl(BAR(B_RF1), lane & (R.cs() - 1)); }
            wait_flags(fp, e1, 0x10001u << g2_cb(kp), ready);
            if (kp == 1 + ly) mbar_wait(BAR(B_RF1), ly);
            if (kp >= 3) mbar_wait(BAR(B_E2 + kp - 3), ly);
            if (elect_one()) {
              if (kp == 0) PROF(33 + 2 * ly);
#pragma unroll
              for (int hf = 0; hf < 2; hf++)
                tma4d_mc(sb + H_OFF + st * 32768 + hf * 16384 + h0 * 2048, &P.mH, g2_cb(kp) * 128 + hf * 64, 0, 2 * h0,
                         ly * 16 + tb2, BAR(B_F2 + kp), (1u << R.cs()) - 1);
            }
            __syncwarp();
            st = st == 2 ? 0 : st + 1;
          }
        }
      }
    } else if (wi == 14) {
      if (!has1) return;
      prefetch_if(P.dskip + 64 * (tid & 31), (tid & 31) < 10);
      if (elect_one()) { prefetch_map(&P.sK); prefetch_map(&P.mX); prefetch_map(&P.sH); prefetch_map(&P.sU); prefetch_map(&P.sO); prefetch_map(&P.mC[0]); prefetch_map(&P.mC[1]); prefetch_map(&P.mH); prefetch_map(&P.mGT); prefetch_map(&P.mA[2 + umap]); }
      __syncwarp();
#pragma unroll 1
      for (int ly = 0; ly < 2; ly++) {
        const int lane = lane_id();
        mbar_wait(BAR(B_E1 + STAT_AT), ly);
        PROFC(lane == 0 && ly == 0, 36);
        {
          const int l = lane - (full ? 0 : 16);
          const uint2* p = S->S + ly * SEQ + 160 * tb + 2 * l;
          uint4 v[3];
#pragma unroll 1
          for (int it = 0; it < SPIN; it++) {
            v[0] = ld_rlx4(p); v[1] = ld_rlx4(p + 64); v[2] = ld_rlx4(p + 96);
            const bool miss = __any_sync(0xffffffff, untagged(v[0], e1 & 1) | untagged(v[1], e1 & 1) | untagged(v[2], e1 & 1));
            PROFC(lane == 0 && ly == 0 && it == 0, 37);
            if (!miss) break;
          }
          PROFC(lane == 0 && ly == 0, 38);
#pragma unroll
          for (int i = 0; i < 3; i++) {
            const int pr = l + (i == 2 ? 48 : 32 * i);
            if (pr >= 0) asm volatile("st.shared.v4.u32 [%0],{%1,%2,%3,%4};" ::"r"(sb + SSM_OFF + 16 * (pr + ((pr * (full ? 205 : 256)) >> 12))), "r"(v[i].x & ~1u),
                                      "r"(v[i].y & ~1u), "r"(v[i].z & ~1u), "r"(v[i].w & ~1u) : "memory");
          }
          __syncwarp();
        }
        if (lane == 0) mbar_arrive(BAR(B_ST));
        mbar_wait(BAR(B_E1 + 9), ly);
        mbar_wait(BAR(B_XF));
        if (lane < 8 && has2) mbar_arrive_cl(BAR(B_RF0), lane & (R.cs() - 1));
        if (lane == 0) {
#pragma unroll 1
          for (int pc = 0; pc < (full ? 5 : 4); pc++) {
            mbar_wait(BAR(B_SH + pc), ly);
            if (pc == 0 && ly && (cb & 1)) delay(HDLY);
            fence_async();
#pragma unroll
            for (int i = 0; i < 2; i++) tma4d_store(&P.sH, sb + (pc < 4 ? R_OFF + i * 16384 + pc * 4096 : (ly ? R4_OFF1 : R4_OFF0) + i * 4096), 128 * cb + 64 * i, 0, 0, ly * 1024 + 80 * tb + 4 * pc);
          }
          bulk_commit(); bulk_wait();
          PROF(ly ? 17 : 16);
          mbar_arrive(BAR(B_HD));
          release<1>();
          signal_flag(&S->flag[(F_H + (ly * 13 + tb) * 10 + cb) * 32], e1);
          PROF(ly ? 24 : 8);
        }
        if (lane == 0 && has2 && !(ODIR && ly)) {
          mbar_wait(BAR(B_SG), ly);
          if (!(ly ? ODIR : UDIR)) {
          fence_async();
          tma4d_store(ly ? &P.sO : &P.sU, sb + (ly ? OS_OFF : US_OFF), 80 * db, 0, 0, tb2);
          bulk_commit(); bulk_wait();
          }
          if (ly == 0) { PROF(18); mbar_arrive(BAR(B_GE)); mbar_arrive_cl(BAR(B_GE), R.wpart()); release<2>(); signal_flag(&S->flag[(F_U3 + b) * 32], e1); }
          PROF(ly ? 29 : 14);
        }
        __syncwarp();
      }
    } else {
      discretise(H, P, sb, R, tid & 31, e1);
      if (elect_one()) {
        mbar_arrive(BAR(B_LM));
        PROF(348);
        if (b < R.nprep()) {
#pragma unroll 1
          for (int task = b, r = 0; task < 320; task += R.nprep(), r++) {
            mbar_wait(BAR(B_PS + r));
            PROF(320 + 3 * r);
            fence_async();
            tma2d_store(&P.sK, sb + KS_OFF + r * 8192, 64 * (task & 31), 64 * (task >> 5));
            bulk_commit(); bulk_wait();
            PROF(321 + 3 * r);
            release<4>();
            signal_cnt(&S->cnt[(C_KV + (task >> 5)) * 32], 1);
            PROF(322 + 3 * r);
          }
          PROF(41);
        }
        mbar_arrive(BAR(B_XF));
#pragma unroll 1
        for (int s = 0; s < R.nch(); s++) {
          mbar_wait(BAR(B_GS + s));
          fence_async();
          bulk_s2g(S->gt + (size_t)R.ch(s) * SEQ, conv_buf(sb, s) + KC_OFS, 4096); bulk_commit();
          if (s == 1 || s == R.nch() - 1) { asm volatile("cp.async.bulk.wait_group.read 0;" ::: "memory"); mbar_arrive(BAR(B_CD + (s > 1))); }
        }
        bulk_wait();
        PROF(45);
        release<8>();
#pragma unroll 1
        for (int s = 0; s < R.nch(); s++) signal_cnt(&S->cnt[(C_G + R.ch(s) / 80) * 32], 1);
        PROF(46);
      }
    }
  }
}

typedef CUresult (*EncFn)(CUtensorMap*, CUtensorMapDataType, cuuint32_t, void*, const cuuint64_t*, const cuuint64_t*, const cuuint32_t*,
                          const cuuint32_t*, CUtensorMapInterleave, CUtensorMapSwizzle, CUtensorMapL2promotion, CUtensorMapFloatOOBfill);
bool enc(EncFn f, CUtensorMap* m, const void* base, int rank, const cuuint64_t* dims, const cuuint64_t* strides, const cuuint32_t* box, bool swz,
         bool f32 = false) {
  const cuuint32_t es[5] = {1, 1, 1, 1, 1};
  return f(m, f32 ? CU_TENSOR_MAP_DATA_TYPE_FLOAT32 : CU_TENSOR_MAP_DATA_TYPE_BFLOAT16, rank, const_cast<void*>(base), dims, strides, box, es,
           CU_TENSOR_MAP_INTERLEAVE_NONE, swz ? CU_TENSOR_MAP_SWIZZLE_128B : CU_TENSOR_MAP_SWIZZLE_NONE, CU_TENSOR_MAP_L2_PROMOTION_L2_256B,
           CU_TENSOR_MAP_FLOAT_OOB_FILL_NONE) == CUDA_SUCCESS;
}
void make_roles(Params& P, bool big) {
  for (uint32_t bx = 0; bx < (big ? 120u : 12u); bx++) {
    const uint32_t c = bx >> 3, r = bx & 7, id = big ? bx : 120 + bx;
    const uint32_t vA = c < 12 ? (2 * (c >> 1) + (r >> 2)) | (4 * (c & 1) + (r & 3)) << 4 | (r & 4) << 16 | 4 << 19 | (r ^ 4) << 22
                               : (4 * (c - 12) + (r >> 1)) | (8 + (r & 1)) << 4 | (r & 6) << 16 | 2 << 19 | (r ^ 2) << 22;
    const uint32_t vB = (bx < 10 ? 12 : 13) | bx << 4 | 2 << 19 | (bx & 1) << 22 | (bx & 1) << 26;
    P.role[bx].x = (big ? vA | r << 26 | 1u << 29 : vB) | (id < 128 ? (id & ~7u) | (r >> 1) | (r & 1) << 2 : id) << 8;
    P.role[bx].y = id | (big ? 5 : bx < 8 ? 3 : 4) << 10 | 120 << 13 | 132 << 21 | (big ? 4u : 3u) << 29;
    const uint32_t v = P.role[bx].x, cb = (v >> 4) & 15, rank = (v >> 26) & 7, ubase = (v >> 16) & 7, ugs = (v >> 19) & 7, wp = (v >> 22) & 7;
    const uint32_t wlo = rank > wp, whi = wp != rank ? wlo : 1, wmask = 1u << rank | 1u << wp;
    const uint32_t uj = (rank - ubase) * (!big ? 8 : ugs == 4 ? 5 : 10), sm = big ? (0x7296418530ull >> (4 * cb)) & 15 : bx < 8 ? 4 * (bx & 1) + (bx >> 1) : 15;
    P.role[bx].z = wlo | whi << 1 | wmask << 2 | ((1u << ugs) - 1) << (10 + ubase) | uj << 20 | sm << 25;
    P.role[bx].w = 0;
  }
}
void launch(const Head& H, const Params& P, int grid, int cs, bool dependent) {
  cudaLaunchConfig_t cfg = {};
  cfg.gridDim = grid; cfg.blockDim = 512; cfg.dynamicSmemBytes = SMEM_BYTES; cfg.stream = cudaStreamPerThread;
  cudaLaunchAttribute at[2];
  at[0].id = cudaLaunchAttributeClusterDimension; at[0].val.clusterDim.x = cs; at[0].val.clusterDim.y = 1; at[0].val.clusterDim.z = 1;
  at[1].id = cudaLaunchAttributeProgrammaticStreamSerialization; at[1].val.programmaticStreamSerializationAllowed = 1;
  cfg.attrs = at; cfg.numAttrs = dependent ? 2 : 1;
  cudaLaunchKernelEx(&cfg, fused_kernel, H, P);
}

}

extern "C" void kernel_launch(void* const* d_in, const int* in_sizes, int n_in, void* d_out, int out_size) {
  (void)in_sizes; (void)n_in; (void)out_size;
  typedef const __nv_bfloat16* cb;
  void* fp = nullptr; cudaDriverEntryPointQueryResult qr;
  cudaGetDriverEntryPoint("cuTensorMapEncodeTiled", &fp, cudaEnableDefault, &qr);
  EncFn f = (EncFn)fp;
  Scratch* sp = nullptr;
  cudaGetSymbolAddress((void**)&sp, g_scr);
  void *pu = sp->u, *ph = sp->h, *pgt = sp->gt;
  Params P;
  Head H;
  H.s = sp; H.x = (cb)d_in[0]; H.swap = (uintptr_t)d_in[4] < (uintptr_t)d_in[3] ? 0 : 0x80000000u; H.b0 = (cb)d_in[H.swap ? 3 : 4]; H.b1 = (cb)d_in[H.swap ? 4 : 3];
  for (int i = 0; i < 2; i++) {
    const cuuint64_t d[4] = {640, 8, 2, 80}, s[3] = {1280, (cuuint64_t)((uintptr_t)H.b1 - (uintptr_t)H.b0), 8 * 1280}; const cuuint32_t bx[4] = {64, 8, 2, 4};
    if (enc(f, &P.mB, H.b0, 4, d, s, bx, true)) break;
    cudaMemcpyAsync(sp->bcopy, H.b0, DM * DM * 2, cudaMemcpyDeviceToDevice, cudaStreamPerThread);
    cudaMemcpyAsync(sp->bcopy + DM * DM, H.b1, DM * DM * 2, cudaMemcpyDeviceToDevice, cudaStreamPerThread);
    H.b0 = sp->bcopy; H.b1 = sp->bcopy + DM * DM;
  }
  {
    const cuuint64_t d[5] = {640, 2, 4, 2, 40}, s[4] = {1280, 4 * 1280, 2 * 1280, 16 * 1280}; const cuuint32_t bx[5] = {64, 2, 4, 2, 5};
    enc(f, &P.mC[0], d_in[5], 5, d, s, bx, true); enc(f, &P.mC[1], d_in[6], 5, d, s, bx, true); }
  { const cuuint64_t d[2] = {2048, 640}, s[1] = {4096}; const cuuint32_t bx[2] = {64, 80}; enc(f, &P.mGT, pgt, 2, d, s, bx, true); }
  { const cuuint64_t d[4] = {640, 8, 16, 16}, s[3] = {16 * 1280, 1280, 128 * 1280}, so[3] = {16 * 2560, 2560, 128 * 2560}; const cuuint32_t bx[4] = {80, 8, 16, 1};
    enc(f, &P.sU, pu, 4, d, s, bx, false); enc(f, &P.mX, d_in[0], 4, d, s, bx, false); enc(f, &P.sO, d_out, 4, d, so, bx, false, true); }
  { const cuuint64_t d[2] = {2048, 640}, s[1] = {4096}; const cuuint32_t bx[2] = {64, 64}; enc(f, &P.sK, sp->kv, 2, d, s, bx, true); }
  P.lre = (cb)d_in[1]; P.lim = (cb)d_in[2]; P.cre = (cb)d_in[5]; P.cim = (cb)d_in[6]; P.ldt = (cb)d_in[7]; P.dskip = (cb)d_in[8];
  P.out = (float*)d_out;
  P.k = (cb)d_in[10]; P.v = (cb)d_in[11]; P.shk = (cb)d_in[12]; P.ssmk = (cb)d_in[13]; P.ssmd = (cb)d_in[14];
  cudaFuncSetAttribute(fused_kernel, cudaFuncAttributeMaxDynamicSharedMemorySize, SMEM_BYTES);
  for (int big = 1; big >= 0; big--) {
    const cuuint64_t seg = big ? 40 : 32;
    for (int i = 0; i < 4; i++) {
      const cuuint64_t d[4] = {640, 2, 4, 1024}, s[3] = {1280, seg * 1280, 2 * 1280}; const cuuint32_t bx[4] = {64, 2, 4, !big ? 8u : (i & 1) ? 10u : 5u};
      enc(f, &P.mA[i], i < 2 ? d_in[0] : pu, 4, d, s, bx, true);
    }
    {
      const cuuint64_t d[4] = {1280, 8, 16, 32}, s[3] = {16 * 2560, 2560, 128 * 2560}; const cuuint32_t bx[4] = {64, 8, big ? 2u : 8u, 1};
      enc(f, &P.mH, ph, 4, d, s, bx, true); }
    { const cuuint64_t d[4] = {1280, 2, 4, 2048}, s[3] = {2560, seg * 2560, 2 * 2560}; const cuuint32_t bx[4] = {64, 2, 4, 4};
      enc(f, &P.sH, ph, 4, d, s, bx, true); }
    make_roles(P, big);
    H.base = big ? 0 : 120;
    launch(H, P, big ? 120 : 12, big ? 8 : 2, !big);
  }
}
```

```cpp
#include <cuda_runtime.h>
#include <cuda.h>
#include <cuda_bf16.h>
#include <stdint.h>

namespace {

constexpr int SEQ = 2048, DM = 640;
constexpr int SPIN = 1 << 20;
#define PFAT 99
#define KVDLY 500
#define PFD 1
#define XPFAT 9
#define STAT_AT 6
#define KPFAT 3
#define KPFAT2 5
#define KPF 7
#define ODIR 1
#define UDIR 0
#define HDLY 1900
#define GSPL 2
#define CWAIT 0
#define HDLY0 1900
#define RIAT 1
#define GLATE 6
#define KUP 1
#define XRAT 9
#define ORD 1

struct Scratch {
  uint2 E[2 * 13 * 10 * 8 * 16];
  uint32_t M[3 * 16 * 8 * 256];
  uint2 S[2 * SEQ];
  uint2 RS[80 * 16];
  unsigned flag[512 * 32];
  unsigned cnt[32 * 32];
  unsigned epoch[132 * 8];
  unsigned zero[128];
  unsigned prof[132 * 512];
  __align__(1024)
  __nv_bfloat16 u[SEQ * DM];
  __nv_bfloat16 h[2 * SEQ * 1280];
  __nv_bfloat16 kv[DM * SEQ];
  __nv_bfloat16 gt[DM * SEQ];
  __nv_bfloat16 bcopy[2 * DM * DM];
};
__device__ __align__(1024) Scratch g_scr;
#define PROF(i) do {} while (0)
#define PROFC(c, i) do {} while (0)

constexpr int C_KV = 0, C_G = 10;
constexpr int F_U3 = 0, F_H = 128;

constexpr int R_OFF = 196608, R4_OFF0 = 73728, R4_OFF1 = 122880, H_OFF = 131072, KS_OFF = 131072, CV_OFF = 86272, G_OFF = 102400, US_OFF = 98304, OS_OFF = US_OFF + 20480, XR_OFF = 163840;
constexpr int LAM_OFF = 229376, SSM_OFF = LAM_OFF + 1024, BAR_OFF = SSM_OFF + 1344;
constexpr int B_F1 = 0, B_E1 = 10, B_RF0 = 20, B_RF1 = 21, NBAR1 = 22;
constexpr int B_F2 = 22, B_KF = 32, B_GF = 37, B_CD = 38, B_ST = 41, B_HD = 42, B_LM = 43, B_E2 = 44, B_GS = 54, B_PS = 59, B_AX = 62, B_SH = 64, B_SG = 69, B_GE = 70, B_XR = 71, NBAR = 72;
__host__ __device__ constexpr int bar_count(int i) { return i < B_E1 ? 1 : i < B_RF0 ? 9 : i < B_F2 ? 8 : i < B_E2 ? 1 : i < B_GS ? 12 : i < B_SH ? 4 : i < B_GE ? 8 : i < B_XR ? 2 : 1; }
constexpr int MISC_OFF = BAR_OFF + NBAR * 8, SMEM_BYTES = MISC_OFF + 32;
constexpr int KV_PAD = 512, KC_OFS = KV_PAD + 4096, CH_STRIDE = 8960;
__device__ __forceinline__ uint32_t conv_buf(uint32_t sb, int slot) { return sb + CV_OFF + slot * CH_STRIDE; }
constexpr uint64_t tab6(int a, int b, int c, int d, int e, int f, int g, int h, int i, int j) {
  return (uint64_t)a | (uint64_t)b << 6 | (uint64_t)c << 12 | (uint64_t)d << 18 | (uint64_t)e << 24 | (uint64_t)f << 30 | (uint64_t)g << 36 | (uint64_t)h << 42 |
         (uint64_t)i << 48 | (uint64_t)j << 54;
}
constexpr uint64_t WTAB0 = tab6(0, 4, 8, 30, 12, 26, 0, 4, 8, 12), XTAB0 = tab6(40, 45, 50, 34, 16, 21, 40, 45, 50, 16);
constexpr uint64_t WTAB1 = tab6(0, 4, 8, 12, 16, 20, 32, 36, 24, 28), XTAB1 = tab6(40, 45, 50, 40, 45, 50, 40, 45, 50, 40);
constexpr uint32_t DEP0 = 0x4210;

struct Head {
  Scratch* s;
  const __nv_bfloat16 *x, *b0, *b1;
  uint32_t base, swap;
};
struct Params {
  const __nv_bfloat16 *lre, *lim, *ldt, *k, *v, *shk, *cre, *cim, *ssmk, *ssmd, *dskip;
  float* out;
  uint4 role[120];
  CUtensorMap mB, mA[4], mH, mC[2], mGT, mX, sH, sU, sO, sK;
};

__device__ __forceinline__ uint32_t smem_u32(const void* p) { return (uint32_t)__cvta_generic_to_shared(p); }
__device__ __forceinline__ uint32_t opaque(uint32_t x) { uint32_t y; asm volatile("mov.u32 %0, %1;" : "=r"(y) : "r"(x)); return y; }
__device__ __forceinline__ int lane_id() { int y; asm volatile("mov.u32 %0, %%laneid;" : "=r"(y)); return y; }
__device__ __forceinline__ void delay(uint32_t n) {
  asm volatile("{ .reg .pred p; .reg .u32 a, b; mov.u32 a, %%clock; L: mov.u32 b, %%clock; sub.u32 b, b, a; setp.lt.u32 p, b, %0; @p bra.uni L; }" ::"r"(n) : "memory");
}
__device__ __forceinline__ void mbar_init(uint32_t bar, uint32_t cnt) { asm volatile("mbarrier.init.shared::cta.b64 [%0], %1;" ::"r"(bar), "r"(cnt) : "memory"); }
__device__ __forceinline__ void mbar_expect_tx(uint32_t bar, uint32_t bytes) { asm volatile("mbarrier.arrive.expect_tx.shared::cta.b64 _, [%0], %1;" ::"r"(bar), "r"(bytes) : "memory"); }
__device__ __forceinline__ void mbar_arrive(uint32_t bar) { asm volatile("mbarrier.arrive.shared::cta.b64 _, [%0];" ::"r"(bar) : "memory"); }
__device__ __forceinline__ void mbar_arrive_if(uint32_t bar, bool c) {
  asm volatile("{ .reg .pred p; setp.ne.u32 p, %1, 0; @p mbarrier.arrive.shared::cta.b64 _, [%0]; }" ::"r"(bar), "r"((uint32_t)c) : "memory");
}
__device__ __forceinline__ void prefetch_if(const void* p, bool c) { asm volatile("{ .reg .pred p; setp.ne.u32 p, %1, 0; @p prefetch.global.L2 [%0]; }" ::"l"(p), "r"((uint32_t)c)); }
__device__ __forceinline__ void mbar_arrive_cl(uint32_t bar, uint32_t cta) {
  asm volatile("{ .reg .b32 ra; mapa.shared::cluster.u32 ra, %0, %1; mbarrier.arrive.shared::cluster.b64 _, [ra]; }" ::"r"(bar), "r"(cta) : "memory");
}
__device__ __forceinline__ uint32_t mapa(uint32_t a, uint32_t cta) { uint32_t r; asm("mapa.shared::cluster.u32 %0, %1, %2;" : "=r"(r) : "r"(a), "r"(cta)); return r; }
__device__ __forceinline__ void mbar_arrive_at(uint32_t ra) { asm volatile("mbarrier.arrive.shared::cluster.b64 _, [%0];" ::"r"(ra) : "memory"); }
__device__ __forceinline__ void mbar_wait(uint32_t bar, uint32_t parity = 0) {
  asm volatile("{ .reg .pred p; .reg .u32 c; mov.u32 c, 0;\n"
               "W: mbarrier.try_wait.parity.shared::cta.b64 p, [%0], %1; @p bra.uni D;\n"
               "add.u32 c, c, 1; setp.lt.u32 p, c, 0x100000; @p bra.uni W;\nD: }" ::"r"(bar), "r"(parity) : "memory");
}
__device__ __forceinline__ bool elect_one() { uint32_t p; asm volatile("{ .reg .pred P; elect.sync _|P, 0xffffffff; selp.u32 %0,1,0,P; }" : "=r"(p)); return p; }
__device__ __forceinline__ void bar_sync(int id, int n) { __syncwarp(); asm volatile("bar.sync %0, %1;" ::"r"(id), "r"(n) : "memory"); }
__device__ __forceinline__ void tma2d(uint32_t dst, const CUtensorMap* m, int c0, int c1, uint32_t bar) {
  asm volatile("cp.async.bulk.tensor.2d.shared::cluster.global.mbarrier::complete_tx::bytes [%0], [%1, {%3,%4}], [%2];"
               ::"r"(dst), "l"(m), "r"(bar), "r"(c0), "r"(c1) : "memory");
}
__device__ __forceinline__ void tma5d(uint32_t dst, const CUtensorMap* m, int c0, int c4, uint32_t bar) {
  asm volatile("cp.async.bulk.tensor.5d.shared::cluster.global.mbarrier::complete_tx::bytes [%0], [%1, {%3,%5,%5,%5,%4}], [%2];"
               ::"r"(dst), "l"(m), "r"(bar), "r"(c0), "r"(c4), "r"(0) : "memory");
}
__device__ __forceinline__ void tma4d(uint32_t dst, const CUtensorMap* m, int c0, int c3, uint32_t bar) {
  asm volatile("cp.async.bulk.tensor.4d.shared::cluster.global.mbarrier::complete_tx::bytes [%0], [%1, {%3,%5,%5,%4}], [%2];"
               ::"r"(dst), "l"(m), "r"(bar), "r"(c0), "r"(c3), "r"(0) : "memory");
}
__device__ __forceinline__ void tma4d_mc(uint32_t dst, const CUtensorMap* m, int c0, int c1, int c2, int c3, uint32_t bar, uint32_t mask) {
  asm volatile("cp.async.bulk.tensor.4d.shared::cluster.global.mbarrier::complete_tx::bytes.multicast::cluster [%0], [%1, {%3,%4,%5,%6}], [%2], %7;"
               ::"r"(dst), "l"(m), "r"(bar), "r"(c0), "r"(c1), "r"(c2), "r"(c3), "h"((uint16_t)mask) : "memory");
}
__device__ __forceinline__ void bulk_g2s(uint32_t dst, const void* src, uint32_t bytes, uint32_t bar) {
  asm volatile("cp.async.bulk.shared::cluster.global.mbarrier::complete_tx::bytes [%0], [%1], %2, [%3];" ::"r"(dst), "l"(src), "r"(bytes), "r"(bar) : "memory");
}
__device__ __forceinline__ void tma4d_store(const CUtensorMap* m, uint32_t src, int c0, int c1, int c2, int c3) {
  asm volatile("cp.async.bulk.tensor.4d.global.shared::cta.bulk_group [%0, {%2,%3,%4,%5}], [%1];" ::"l"(m), "r"(src), "r"(c0), "r"(c1), "r"(c2), "r"(c3) : "memory");
}
__device__ __forceinline__ void tma2d_store(const CUtensorMap* m, uint32_t src, int c0, int c1) {
  asm volatile("cp.async.bulk.tensor.2d.global.shared::cta.bulk_group [%0, {%2,%3}], [%1];" ::"l"(m), "r"(src), "r"(c0), "r"(c1) : "memory");
}
__device__ __forceinline__ void bulk_s2g(void* dst, uint32_t src, uint32_t bytes) {
  asm volatile("cp.async.bulk.global.shared::cta.bulk_group [%0], [%1], %2;" ::"l"(dst), "r"(src), "r"(bytes) : "memory");
}
__device__ __forceinline__ void bulk_commit() { asm volatile("cp.async.bulk.commit_group;" ::: "memory"); }
__device__ __forceinline__ void bulk_wait() { asm volatile("cp.async.bulk.wait_group 0;" ::: "memory"); }
__device__ __forceinline__ void fence_async() { asm volatile("fence.proxy.async.shared::cta;" ::: "memory"); }
__device__ __forceinline__ void prefetch_l2(const void* src, uint32_t bytes) { asm volatile("cp.async.bulk.prefetch.L2.global [%0], %1;" ::"l"(src), "r"(bytes) : "memory"); }
__device__ __forceinline__ void prefetch_map(const CUtensorMap* m) { asm volatile("prefetch.tensormap [%0];" ::"l"(m) : "memory"); }
__device__ __forceinline__ void wg_fence() { __syncwarp(); asm volatile("wgmma.fence.sync.aligned;" ::: "memory"); }
__device__ __forceinline__ void wg_commit() { asm volatile("wgmma.commit_group.sync.aligned;" ::: "memory"); }
template <int N> __device__ __forceinline__ void wg_wait() { asm volatile("wgmma.wait_group.sync.aligned %0;" ::"n"(N) : "memory"); }
template <int N> __device__ __forceinline__ void fence_regs(float (&d)[N]) {
#pragma unroll
  for (int i = 0; i < N; i++) asm volatile("" : "+f"(d[i])::"memory");
}
__device__ __forceinline__ uint64_t make_desc(uint32_t addr, uint32_t lbo, uint32_t sbo, uint32_t swz) {
  return (uint64_t)((addr & 0x3FFFF) >> 4) | ((uint64_t)(lbo >> 4) << 16) | ((uint64_t)(sbo >> 4) << 32) | ((uint64_t)swz << 62);
}
__device__ __forceinline__ uint32_t ldg1(const void* p) { uint32_t v; asm volatile("ld.global.nc.u32 %0,[%1];" : "=r"(v) : "l"(p)); return v; }
__device__ __forceinline__ uint32_t lds32(uint32_t a) { uint32_t v; asm volatile("ld.shared.u32 %0,[%1];" : "=r"(v) : "r"(a)); return v; }
__device__ __forceinline__ unsigned ld_rlx(const unsigned* p) { unsigned v; asm volatile("ld.relaxed.gpu.global.u32 %0,[%1];" : "=r"(v) : "l"(p) : "memory"); return v; }
__device__ __forceinline__ uint4 ld_rlx4(const void* p) {
  uint4 v; asm volatile("ld.relaxed.gpu.global.v4.u32 {%0,%1,%2,%3},[%4];" : "=r"(v.x), "=r"(v.y), "=r"(v.z), "=r"(v.w) : "l"(p) : "memory"); return v;
}
__device__ __forceinline__ uint2 ld_rlx2(const void* p) { uint2 v; asm volatile("ld.relaxed.gpu.global.v2.u32 {%0,%1},[%2];" : "=r"(v.x), "=r"(v.y) : "l"(p) : "memory"); return v; }
__device__ __forceinline__ void st_rlx2(void* p, uint32_t a, uint32_t b) { asm volatile("st.relaxed.gpu.global.v2.u32 [%0],{%1,%2};" ::"l"(p), "r"(a), "r"(b) : "memory"); }
__device__ __forceinline__ void st_rlx4(void* p, uint32_t a, uint32_t b, uint32_t c, uint32_t d) {
  asm volatile("st.relaxed.gpu.global.v4.u32 [%0],{%1,%2,%3,%4};" ::"l"(p), "r"(a), "r"(b), "r"(c), "r"(d) : "memory");
}
__device__ __forceinline__ void st_rlx(void* p, uint32_t a) { asm volatile("st.relaxed.gpu.global.u32 [%0],%1;" ::"l"(p), "r"(a) : "memory"); }
#define PUB 15
template <int SITE> __device__ __forceinline__ void release() { if (PUB & SITE) asm volatile("fence.acq_rel.gpu;" ::: "memory"); }
__device__ __forceinline__ void signal_flag(unsigned* p, unsigned val) { asm volatile("st.relaxed.gpu.global.u32 [%0],%1;" ::"l"(p), "r"(val) : "memory"); }
__device__ __forceinline__ void signal_cnt(unsigned* p, unsigned n) { asm volatile("red.relaxed.gpu.global.add.u32 [%0],%1;" ::"l"(p), "r"(n) : "memory"); }
__device__ __forceinline__ void wait_flags(const unsigned* p, unsigned val, uint32_t need, uint32_t& ready) {
#pragma unroll 1
  for (int it = 0; (ready & need) != need && it < SPIN; it++) ready = __ballot_sync(0xffffffff, ld_rlx(p) == val);
}
__device__ __forceinline__ void wait_cnt(const unsigned* p, unsigned tgt) {
  asm volatile("{ .reg .pred p; .reg .u32 c; .reg .s32 v; mov.u32 c, 0;\n"
               "W: ld.relaxed.gpu.global.u32 v, [%0]; sub.s32 v, v, %1; setp.ge.s32 p, v, 0; @p bra.uni D;\n"
               "add.u32 c, c, 1; setp.lt.u32 p, c, 0x100000; @p bra.uni W;\nD: }" ::"l"(p), "r"(tgt) : "memory");
}
__device__ __forceinline__ uint32_t pack_bf(float lo, float hi) { uint32_t r; asm("cvt.rn.bf16x2.f32 %0, %1, %2;" : "=r"(r) : "f"(hi), "f"(lo)); return r; }
__device__ __forceinline__ float bf_lo(uint32_t v) { return __uint_as_float(v << 16); }
__device__ __forceinline__ float bf_hi(uint32_t v) { return __uint_as_float(v & 0xffff0000u); }
__device__ __forceinline__ float bf_rn(float x) { return __bfloat162float(__float2bfloat16_rn(x)); }
__device__ __forceinline__ float frcp(float x) { float r; asm("rcp.approx.ftz.f32 %0,%1;" : "=f"(r) : "f"(x)); return r; }
__device__ __forceinline__ float fsqrt(float x) { float r; asm("sqrt.approx.ftz.f32 %0,%1;" : "=f"(r) : "f"(x)); return r; }
__device__ __forceinline__ float frsqrt(float x) { float r; asm("rsqrt.approx.ftz.f32 %0,%1;" : "=f"(r) : "f"(x)); return r; }
__device__ __forceinline__ uint32_t hmul2(uint32_t a, uint32_t b) { uint32_t r; asm("mul.rn.bf16x2 %0,%1,%2;" : "=r"(r) : "r"(a), "r"(b)); return r; }
__device__ __forceinline__ uint32_t hfma2(uint32_t a, uint32_t b, uint32_t c) { uint32_t r; asm("fma.rn.bf16x2 %0,%1,%2,%3;" : "=r"(r) : "r"(a), "r"(b), "r"(c)); return r; }
__device__ __forceinline__ float2 cmul(float2 a, float2 b) { return make_float2(a.x * b.x - a.y * b.y, a.x * b.y + a.y * b.x); }
__device__ __forceinline__ float2 cfma(float2 a, float2 b, float2 c) {
  return make_float2(fmaf(a.x, b.x, fmaf(-a.y, b.y, c.x)), fmaf(a.x, b.y, fmaf(a.y, b.x, c.y)));
}
__device__ __forceinline__ uint32_t tagf(float v, uint32_t tag) { return (__float_as_uint(v) & ~1u) | tag; }
__device__ __forceinline__ float untag(uint32_t v) { return __uint_as_float(v & ~1u); }
__device__ __forceinline__ bool untagged(const uint4& v, uint32_t tag) { return (((v.x ^ tag) | (v.y ^ tag) | (v.z ^ tag) | (v.w ^ tag)) & 1) != 0; }
__device__ __forceinline__ bool untagged(const uint2& v, uint32_t tag) { return (((v.x ^ tag) | (v.y ^ tag)) & 1) != 0; }
__device__ __forceinline__ float2 lam_bar(float lr, float li, float ldt) {
  float dt = bf_rn(expf(ldt)); float e = expf(dt * lr), s, c; sincospif(dt * li * 0.31830988618379067f, &s, &c); return make_float2(e * c, e * s);
}

__device__ __forceinline__ int conv_ch(uint32_t c, int s) { return s * ((c >> 21) & 255) + (c & 255) - (s >= (int)(c >> 29) ? 8 : 0); }
struct Role {
  uint32_t v, c, p;
  __device__ __forceinline__ int tb() const { return v & 15; }
  __device__ __forceinline__ int cb() const { return (v >> 4) & 15; }
  __device__ __forceinline__ int b() const { return (v >> 8) & 255; }
  __device__ __forceinline__ int ubase() const { return (v >> 16) & 7; }
  __device__ __forceinline__ int ugs() const { return (v >> 19) & 7; }
  __device__ __forceinline__ int wpart() const { return (v >> 22) & 7; }
  __device__ __forceinline__ int rank() const { return (v >> 26) & 7; }
  __device__ __forceinline__ int cs() const { return (v >> 29) ? 8 : 2; }
  __device__ __forceinline__ int ch(int s) const { return conv_ch(c, s); }
  __device__ __forceinline__ int wlo() const { return p & 1; }
  __device__ __forceinline__ int whi() const { return (p >> 1) & 1; }
  __device__ __forceinline__ uint32_t wmask() const { return (p >> 2) & 255; }
  __device__ __forceinline__ uint32_t umask() const { return (p >> 10) & 255; }
  __device__ __forceinline__ int uj() const { return (p >> 20) & 31; }
  __device__ __forceinline__ int sm() const { return (p >> 25) & 15; }
  __device__ __forceinline__ int nch() const { return (c >> 10) & 7; }
  __device__ __forceinline__ int nprep() const { return (c >> 13) & 255; }
};

__device__ __forceinline__ void wgmma_ss80(float (&d)[40], uint64_t da, uint64_t db, int sd){
  asm volatile("{ .reg .pred p; setp.ne.b32 p, %42, 0;\n"
   "wgmma.mma_async.sync.aligned.m64n80k16.f32.bf16.bf16 {%0, %1, %2, %3, %4, %5, %6, %7, %8, %9, %10, %11, %12, %13, %14, %15, %16, %17, %18, %19, %20, %21, %22, %23, %24, %25, %26, %27, %28, %29, %30, %31, %32, %33, %34, %35, %36, %37, %38, %39}, %40, %41, p, 1, 1, 0, 0; }\n"
   : "+f"(d[0]), "+f"(d[1]), "+f"(d[2]), "+f"(d[3]), "+f"(d[4]), "+f"(d[5]), "+f"(d[6]), "+f"(d[7]), "+f"(d[8]), "+f"(d[9]), "+f"(d[10]), "+f"(d[11]), "+f"(d[12]), "+f"(d[13]), "+f"(d[14]), "+f"(d[15]), "+f"(d[16]), "+f"(d[17]), "+f"(d[18]), "+f"(d[19]), "+f"(d[20]), "+f"(d[21]), "+f"(d[22]), "+f"(d[23]), "+f"(d[24]), "+f"(d[25]), "+f"(d[26]), "+f"(d[27]), "+f"(d[28]), "+f"(d[29]), "+f"(d[30]), "+f"(d[31]), "+f"(d[32]), "+f"(d[33]), "+f"(d[34]), "+f"(d[35]), "+f"(d[36]), "+f"(d[37]), "+f"(d[38]), "+f"(d[39]) : "l"(da), "l"(db), "r"(sd));
}
__device__ __forceinline__ void wgmma_ss160(float (&d)[80], uint64_t da, uint64_t db, int sd){
  asm volatile("{ .reg .pred p; setp.ne.b32 p, %82, 0;\n"
   "wgmma.mma_async.sync.aligned.m64n160k16.f32.bf16.bf16 {%0, %1, %2, %3, %4, %5, %6, %7, %8, %9, %10, %11, %12, %13, %14, %15, %16, %17, %18, %19, %20, %21, %22, %23, %24, %25, %26, %27, %28, %29, %30, %31, %32, %33, %34, %35, %36, %37, %38, %39, %40, %41, %42, %43, %44, %45, %46, %47, %48, %49, %50, %51, %52, %53, %54, %55, %56, %57, %58, %59, %60, %61, %62, %63, %64, %65, %66, %67, %68, %69, %70, %71, %72, %73, %74, %75, %76, %77, %78, %79}, %80, %81, p, 1, 1, 0, 0; }\n"
   : "+f"(d[0]), "+f"(d[1]), "+f"(d[2]), "+f"(d[3]), "+f"(d[4]), "+f"(d[5]), "+f"(d[6]), "+f"(d[7]), "+f"(d[8]), "+f"(d[9]), "+f"(d[10]), "+f"(d[11]), "+f"(d[12]), "+f"(d[13]), "+f"(d[14]), "+f"(d[15]), "+f"(d[16]), "+f"(d[17]), "+f"(d[18]), "+f"(d[19]), "+f"(d[20]), "+f"(d[21]), "+f"(d[22]), "+f"(d[23]), "+f"(d[24]), "+f"(d[25]), "+f"(d[26]), "+f"(d[27]), "+f"(d[28]), "+f"(d[29]), "+f"(d[30]), "+f"(d[31]), "+f"(d[32]), "+f"(d[33]), "+f"(d[34]), "+f"(d[35]), "+f"(d[36]), "+f"(d[37]), "+f"(d[38]), "+f"(d[39]), "+f"(d[40]), "+f"(d[41]), "+f"(d[42]), "+f"(d[43]), "+f"(d[44]), "+f"(d[45]), "+f"(d[46]), "+f"(d[47]), "+f"(d[48]), "+f"(d[49]), "+f"(d[50]), "+f"(d[51]), "+f"(d[52]), "+f"(d[53]), "+f"(d[54]), "+f"(d[55]), "+f"(d[56]), "+f"(d[57]), "+f"(d[58]), "+f"(d[59]), "+f"(d[60]), "+f"(d[61]), "+f"(d[62]), "+f"(d[63]), "+f"(d[64]), "+f"(d[65]), "+f"(d[66]), "+f"(d[67]), "+f"(d[68]), "+f"(d[69]), "+f"(d[70]), "+f"(d[71]), "+f"(d[72]), "+f"(d[73]), "+f"(d[74]), "+f"(d[75]), "+f"(d[76]), "+f"(d[77]), "+f"(d[78]), "+f"(d[79]) : "l"(da), "l"(db), "r"(sd));
}
template<int N> __device__ __forceinline__ void wgmma_rs(float (&d)[N/2], uint32_t a0, uint32_t a1, uint32_t a2, uint32_t a3, uint64_t db, int sd);
template<> __device__ __forceinline__ void wgmma_rs<16>(float (&d)[8], uint32_t a0, uint32_t a1, uint32_t a2, uint32_t a3, uint64_t db, int sd){
  asm volatile("{ .reg .pred p; setp.ne.b32 p, %13, 0;\n"
   "wgmma.mma_async.sync.aligned.m64n16k16.f32.bf16.bf16 {%0, %1, %2, %3, %4, %5, %6, %7}, {%8,%9,%10,%11}, %12, p, 1, 1, 0; }\n"
   : "+f"(d[0]), "+f"(d[1]), "+f"(d[2]), "+f"(d[3]), "+f"(d[4]), "+f"(d[5]), "+f"(d[6]), "+f"(d[7]) : "r"(a0), "r"(a1), "r"(a2), "r"(a3), "l"(db), "r"(sd));
}
template<> __device__ __forceinline__ void wgmma_rs<32>(float (&d)[16], uint32_t a0, uint32_t a1, uint32_t a2, uint32_t a3, uint64_t db, int sd){
  asm volatile("{ .reg .pred p; setp.ne.b32 p, %21, 0;\n"
   "wgmma.mma_async.sync.aligned.m64n32k16.f32.bf16.bf16 {%0, %1, %2, %3, %4, %5, %6, %7, %8, %9, %10, %11, %12, %13, %14, %15}, {%16,%17,%18,%19}, %20, p, 1, 1, 0; }\n"
   : "+f"(d[0]), "+f"(d[1]), "+f"(d[2]), "+f"(d[3]), "+f"(d[4]), "+f"(d[5]), "+f"(d[6]), "+f"(d[7]), "+f"(d[8]), "+f"(d[9]), "+f"(d[10]), "+f"(d[11]), "+f"(d[12]), "+f"(d[13]), "+f"(d[14]), "+f"(d[15]) : "r"(a0), "r"(a1), "r"(a2), "r"(a3), "l"(db), "r"(sd));
}
template<> __device__ __forceinline__ void wgmma_rs<48>(float (&d)[24], uint32_t a0, uint32_t a1, uint32_t a2, uint32_t a3, uint64_t db, int sd){
  asm volatile("{ .reg .pred p; setp.ne.b32 p, %29, 0;\n"
   "wgmma.mma_async.sync.aligned.m64n48k16.f32.bf16.bf16 {%0, %1, %2, %3, %4, %5, %6, %7, %8, %9, %10, %11, %12, %13, %14, %15, %16, %17, %18, %19, %20, %21, %22, %23}, {%24,%25,%26,%27}, %28, p, 1, 1, 0; }\n"
   : "+f"(d[0]), "+f"(d[1]), "+f"(d[2]), "+f"(d[3]), "+f"(d[4]), "+f"(d[5]), "+f"(d[6]), "+f"(d[7]), "+f"(d[8]), "+f"(d[9]), "+f"(d[10]), "+f"(d[11]), "+f"(d[12]), "+f"(d[13]), "+f"(d[14]), "+f"(d[15]), "+f"(d[16]), "+f"(d[17]), "+f"(d[18]), "+f"(d[19]), "+f"(d[20]), "+f"(d[21]), "+f"(d[22]), "+f"(d[23]) : "r"(a0), "r"(a1), "r"(a2), "r"(a3), "l"(db), "r"(sd));
}
template<> __device__ __forceinline__ void wgmma_rs<64>(float (&d)[32], uint32_t a0, uint32_t a1, uint32_t a2, uint32_t a3, uint64_t db, int sd){
  asm volatile("{ .reg .pred p; setp.ne.b32 p, %37, 0;\n"
   "wgmma.mma_async.sync.aligned.m64n64k16.f32.bf16.bf16 {%0, %1, %2, %3, %4, %5, %6, %7, %8, %9, %10, %11, %12, %13, %14, %15, %16, %17, %18, %19, %20, %21, %22, %23, %24, %25, %26, %27, %28, %29, %30, %31}, {%32,%33,%34,%35}, %36, p, 1, 1, 0; }\n"
   : "+f"(d[0]), "+f"(d[1]), "+f"(d[2]), "+f"(d[3]), "+f"(d[4]), "+f"(d[5]), "+f"(d[6]), "+f"(d[7]), "+f"(d[8]), "+f"(d[9]), "+f"(d[10]), "+f"(d[11]), "+f"(d[12]), "+f"(d[13]), "+f"(d[14]), "+f"(d[15]), "+f"(d[16]), "+f"(d[17]), "+f"(d[18]), "+f"(d[19]), "+f"(d[20]), "+f"(d[21]), "+f"(d[22]), "+f"(d[23]), "+f"(d[24]), "+f"(d[25]), "+f"(d[26]), "+f"(d[27]), "+f"(d[28]), "+f"(d[29]), "+f"(d[30]), "+f"(d[31]) : "r"(a0), "r"(a1), "r"(a2), "r"(a3), "l"(db), "r"(sd));
}
template<> __device__ __forceinline__ void wgmma_rs<80>(float (&d)[40], uint32_t a0, uint32_t a1, uint32_t a2, uint32_t a3, uint64_t db, int sd){
  asm volatile("{ .reg .pred p; setp.ne.b32 p, %45, 0;\n"
   "wgmma.mma_async.sync.aligned.m64n80k16.f32.bf16.bf16 {%0, %1, %2, %3, %4, %5, %6, %7, %8, %9, %10, %11, %12, %13, %14, %15, %16, %17, %18, %19, %20, %21, %22, %23, %24, %25, %26, %27, %28, %29, %30, %31, %32, %33, %34, %35, %36, %37, %38, %39}, {%40,%41,%42,%43}, %44, p, 1, 1, 0; }\n"
   : "+f"(d[0]), "+f"(d[1]), "+f"(d[2]), "+f"(d[3]), "+f"(d[4]), "+f"(d[5]), "+f"(d[6]), "+f"(d[7]), "+f"(d[8]), "+f"(d[9]), "+f"(d[10]), "+f"(d[11]), "+f"(d[12]), "+f"(d[13]), "+f"(d[14]), "+f"(d[15]), "+f"(d[16]), "+f"(d[17]), "+f"(d[18]), "+f"(d[19]), "+f"(d[20]), "+f"(d[21]), "+f"(d[22]), "+f"(d[23]), "+f"(d[24]), "+f"(d[25]), "+f"(d[26]), "+f"(d[27]), "+f"(d[28]), "+f"(d[29]), "+f"(d[30]), "+f"(d[31]), "+f"(d[32]), "+f"(d[33]), "+f"(d[34]), "+f"(d[35]), "+f"(d[36]), "+f"(d[37]), "+f"(d[38]), "+f"(d[39]) : "r"(a0), "r"(a1), "r"(a2), "r"(a3), "l"(db), "r"(sd));
}
template<> __device__ __forceinline__ void wgmma_rs<96>(float (&d)[48], uint32_t a0, uint32_t a1, uint32_t a2, uint32_t a3, uint64_t db, int sd){
  asm volatile("{ .reg .pred p; setp.ne.b32 p, %53, 0;\n"
   "wgmma.mma_async.sync.aligned.m64n96k16.f32.bf16.bf16 {%0, %1, %2, %3, %4, %5, %6, %7, %8, %9, %10, %11, %12, %13, %14, %15, %16, %17, %18, %19, %20, %21, %22, %23, %24, %25, %26, %27, %28, %29, %30, %31, %32, %33, %34, %35, %36, %37, %38, %39, %40, %41, %42, %43, %44, %45, %46, %47}, {%48,%49,%50,%51}, %52, p, 1, 1, 0; }\n"
   : "+f"(d[0]), "+f"(d[1]), "+f"(d[2]), "+f"(d[3]), "+f"(d[4]), "+f"(d[5]), "+f"(d[6]), "+f"(d[7]), "+f"(d[8]), "+f"(d[9]), "+f"(d[10]), "+f"(d[11]), "+f"(d[12]), "+f"(d[13]), "+f"(d[14]), "+f"(d[15]), "+f"(d[16]), "+f"(d[17]), "+f"(d[18]), "+f"(d[19]), "+f"(d[20]), "+f"(d[21]), "+f"(d[22]), "+f"(d[23]), "+f"(d[24]), "+f"(d[25]), "+f"(d[26]), "+f"(d[27]), "+f"(d[28]), "+f"(d[29]), "+f"(d[30]), "+f"(d[31]), "+f"(d[32]), "+f"(d[33]), "+f"(d[34]), "+f"(d[35]), "+f"(d[36]), "+f"(d[37]), "+f"(d[38]), "+f"(d[39]), "+f"(d[40]), "+f"(d[41]), "+f"(d[42]), "+f"(d[43]), "+f"(d[44]), "+f"(d[45]), "+f"(d[46]), "+f"(d[47]) : "r"(a0), "r"(a1), "r"(a2), "r"(a3), "l"(db), "r"(sd));
}
template<> __device__ __forceinline__ void wgmma_rs<112>(float (&d)[56], uint32_t a0, uint32_t a1, uint32_t a2, uint32_t a3, uint64_t db, int sd){
  asm volatile("{ .reg .pred p; setp.ne.b32 p, %61, 0;\n"
   "wgmma.mma_async.sync.aligned.m64n112k16.f32.bf16.bf16 {%0, %1, %2, %3, %4, %5, %6, %7, %8, %9, %10, %11, %12, %13, %14, %15, %16, %17, %18, %19, %20, %21, %22, %23, %24, %25, %26, %27, %28, %29, %30, %31, %32, %33, %34, %35, %36, %37, %38, %39, %40, %41, %42, %43, %44, %45, %46, %47, %48, %49, %50, %51, %52, %53, %54, %55}, {%56,%57,%58,%59}, %60, p, 1, 1, 0; }\n"
   : "+f"(d[0]), "+f"(d[1]), "+f"(d[2]), "+f"(d[3]), "+f"(d[4]), "+f"(d[5]), "+f"(d[6]), "+f"(d[7]), "+f"(d[8]), "+f"(d[9]), "+f"(d[10]), "+f"(d[11]), "+f"(d[12]), "+f"(d[13]), "+f"(d[14]), "+f"(d[15]), "+f"(d[16]), "+f"(d[17]), "+f"(d[18]), "+f"(d[19]), "+f"(d[20]), "+f"(d[21]), "+f"(d[22]), "+f"(d[23]), "+f"(d[24]), "+f"(d[25]), "+f"(d[26]), "+f"(d[27]), "+f"(d[28]), "+f"(d[29]), "+f"(d[30]), "+f"(d[31]), "+f"(d[32]), "+f"(d[33]), "+f"(d[34]), "+f"(d[35]), "+f"(d[36]), "+f"(d[37]), "+f"(d[38]), "+f"(d[39]), "+f"(d[40]), "+f"(d[41]), "+f"(d[42]), "+f"(d[43]), "+f"(d[44]), "+f"(d[45]), "+f"(d[46]), "+f"(d[47]), "+f"(d[48]), "+f"(d[49]), "+f"(d[50]), "+f"(d[51]), "+f"(d[52]), "+f"(d[53]), "+f"(d[54]), "+f"(d[55]) : "r"(a0), "r"(a1), "r"(a2), "r"(a3), "l"(db), "r"(sd));
}
template<> __device__ __forceinline__ void wgmma_rs<128>(float (&d)[64], uint32_t a0, uint32_t a1, uint32_t a2, uint32_t a3, uint64_t db, int sd){
  asm volatile("{ .reg .pred p; setp.ne.b32 p, %69, 0;\n"
   "wgmma.mma_async.sync.aligned.m64n128k16.f32.bf16.bf16 {%0, %1, %2, %3, %4, %5, %6, %7, %8, %9, %10, %11, %12, %13, %14, %15, %16, %17, %18, %19, %20, %21, %22, %23, %24, %25, %26, %27, %28, %29, %30, %31, %32, %33, %34, %35, %36, %37, %38, %39, %40, %41, %42, %43, %44, %45, %46, %47, %48, %49, %50, %51, %52, %53, %54, %55, %56, %57, %58, %59, %60, %61, %62, %63}, {%64,%65,%66,%67}, %68, p, 1, 1, 0; }\n"
   : "+f"(d[0]), "+f"(d[1]), "+f"(d[2]), "+f"(d[3]), "+f"(d[4]), "+f"(d[5]), "+f"(d[6]), "+f"(d[7]), "+f"(d[8]), "+f"(d[9]), "+f"(d[10]), "+f"(d[11]), "+f"(d[12]), "+f"(d[13]), "+f"(d[14]), "+f"(d[15]), "+f"(d[16]), "+f"(d[17]), "+f"(d[18]), "+f"(d[19]), "+f"(d[20]), "+f"(d[21]), "+f"(d[22]), "+f"(d[23]), "+f"(d[24]), "+f"(d[25]), "+f"(d[26]), "+f"(d[27]), "+f"(d[28]), "+f"(d[29]), "+f"(d[30]), "+f"(d[31]), "+f"(d[32]), "+f"(d[33]), "+f"(d[34]), "+f"(d[35]), "+f"(d[36]), "+f"(d[37]), "+f"(d[38]), "+f"(d[39]), "+f"(d[40]), "+f"(d[41]), "+f"(d[42]), "+f"(d[43]), "+f"(d[44]), "+f"(d[45]), "+f"(d[46]), "+f"(d[47]), "+f"(d[48]), "+f"(d[49]), "+f"(d[50]), "+f"(d[51]), "+f"(d[52]), "+f"(d[53]), "+f"(d[54]), "+f"(d[55]), "+f"(d[56]), "+f"(d[57]), "+f"(d[58]), "+f"(d[59]), "+f"(d[60]), "+f"(d[61]), "+f"(d[62]), "+f"(d[63]) : "r"(a0), "r"(a1), "r"(a2), "r"(a3), "l"(db), "r"(sd));
}

#define BAR(i) (bars + 8u * (uint32_t)(i))

template <int G> __device__ __forceinline__ void conv_frags(uint32_t (&a)[12], uint32_t abase) {
#pragma unroll
  for (int i = 0; i < 12; i++) a[i] = lds32(abase + (G * 4 + i / 3) * 128 + (i % 3) * 4);
}
__device__ __forceinline__ void kv_prefetch(const __nv_bfloat16* pf, int task) { prefetch_if(pf + 64 * (task & 31) * DM + 64 * (task >> 5), task < 320); }
__device__ __forceinline__ void kv_load(const Params& P, Scratch* S, int task, int tid, uint32_t (&k_)[19], uint32_t (&v_)[16], uint4& sk) {
  const int row = 64 * (task & 31) + 16 * (tid >> 5), ch = 64 * (task >> 5) + 2 * (tid & 31);
  const uint32_t* kp = (const uint32_t*)(P.k + (size_t)row * DM + ch);
  const uint32_t* vp = (const uint32_t*)(P.v + (size_t)row * DM + ch);
  const uint32_t* hp = row > 0 ? kp - 3 * (DM / 2) : S->zero;
  const int hs = row > 0 ? DM / 2 : 0;
  asm volatile("ld.global.nc.v4.u32 {%0,%1,%2,%3},[%4];" : "=r"(sk.x), "=r"(sk.y), "=r"(sk.z), "=r"(sk.w) : "l"(P.shk + ch * 4));
#pragma unroll
  for (int i = 0; i < 3; i++) k_[i] = ldg1(hp + i * hs);
#pragma unroll
  for (int i = 0; i < 16; i++) { k_[i + 3] = ldg1(kp + i * (DM / 2)); v_[i] = ldg1(vp + i * (DM / 2)); }
}
template <int SH> __device__ __forceinline__ void xb_prefetch(const Head& H, int id, int tid, int c0) {
  const int ri = tid >> SH, rr = 11 * id + ri - 16;
  const __nv_bfloat16* p = ri < 16 ? H.x + (size_t)(16 * min(id, 127) + ri) * DM : (rr < DM ? H.b0 : H.b1 - DM * DM) + (size_t)rr * DM;
  prefetch_if(p + c0 + 64 * (tid & ((1 << SH) - 1)), ri < 16 || (ri < 27 && rr < 2 * DM));
}
__device__ __forceinline__ uint4 ldg4(const void* p) { uint4 v; asm volatile("ld.global.nc.v4.u32 {%0,%1,%2,%3},[%4];" : "=r"(v.x), "=r"(v.y), "=r"(v.z), "=r"(v.w) : "l"(p)); return v; }
__device__ __forceinline__ uint4 lds4(uint32_t a) { uint4 v; asm volatile("ld.shared.v4.u32 {%0,%1,%2,%3},[%4];" : "=r"(v.x), "=r"(v.y), "=r"(v.z), "=r"(v.w) : "r"(a) : "memory"); return v; }
__device__ __forceinline__ void discretise(const Head& H, const Params& P, uint32_t sb, Role R, int lane, uint32_t e1) {
  const uint32_t dn = __ldg((const unsigned short*)P.ssmd + min(conv_ch(R.c, (lane + 7) & 7), DM - 1));
  const int c = 32 * min(R.cb(), 9) + lane;
  const uint32_t lr2 = ldg1(P.lre + 2 * c), li2 = ldg1(P.lim + 2 * c), ld2 = ldg1(P.ldt + 2 * c);
  asm volatile("st.shared.u32 [%0],%1;" ::"r"(sb + MISC_OFF + 4 * (lane & 7)), "r"((lane & 7) ? dn : e1) : "memory");
#pragma unroll 1
  for (int i = 0; i < 2; i++) {
    const float lr = bf_hi(lr2 << (16 - 16 * i)), li = bf_hi(li2 << (16 - 16 * i));
    const float2 lb = lam_bar(lr, li, bf_hi(ld2 << (16 - 16 * i)));
    const float nx = lb.x - 1.f, ny = lb.y, inv = 2.f * frcp(lr * lr + li * li), cx = (nx * lr + ny * li) * inv, cy = (ny * lr - nx * li) * inv;
    const bool sw = !H.swap;
    asm volatile("st.shared.v4.f32 [%0],{%1,%2,%3,%4};" ::"r"(sb + LAM_OFF + 32 * lane + 16 * i), "f"(lb.x), "f"(sw ? -lb.y : lb.y), "f"(sw ? -cy : cx), "f"(sw ? cx : -cy) : "memory");
  }
  __syncwarp();
}
__device__ __forceinline__ void aux_prep(const Head& H, const Params& P, uint32_t sb, Role R, int tid, long long t_start) {
  Scratch* const S = H.s;
  const uint32_t bars = sb + BAR_OFF;
  tid = opaque(tid);
  const int w = tid >> 5, lane = tid & 31, tb = R.tb(), cb = R.cb();
  uint32_t k_[19], v_[16];
  uint4 sk;
  int task = R.b() < R.nprep() ? R.b() : 320;
  delay(KVDLY);
  PROFC(tid == 0, 345);
  kv_load(P, S, min(task, 319), tid, k_, v_, sk);
  const __nv_bfloat16* pf = (tid < 64 ? P.k : P.v) + (tid & 63) * DM;
  const int j = lane >> 3, sm = min(R.sm(), 9), trow = 160 * tb + 4 * sm + (tb < 12 ? 40 : 32) * w + j;
  const uint32_t so = sb + (2 * w + (j & 1) + 8 * (j >> 1)) * 128 + 16 * (lane & 7), xo = so + sm * 2048, wo = so + (tb & 1) * 8192 + (tb & 6) * 1024;
  const __nv_bfloat16* xp = H.x + (size_t)min(trow, SEQ - 1) * DM + 384 + 8 * (lane & 7);
  const __nv_bfloat16* bp = (j < 2 ? H.b0 : H.b1) + (size_t)(64 * cb + 32 * (tb & 1) + 4 * (tb & 6) + 2 * w + (j & 1)) * DM + 384 + 8 * (lane & 7);
  float s = 0.f, s2 = 0.f, sr = 0.f;
#define STAT(m, n) { const uint32_t xw[4] = {m.x, m.y, m.z, m.w}, bw[4] = {n.x, n.y, n.z, n.w}; \
  _Pragma("unroll") for (int i = 0; i < 4; i++) { const float u = bf_lo(xw[i]), v = bf_hi(xw[i]); s += u + v; s2 = fmaf(u, u, fmaf(v, v, s2)); sr += bf_lo(bw[i]) + bf_hi(bw[i]); } }
#define STATS(K0, K1) _Pragma("unroll 1") for (int kb = K0; kb < K1; kb++) { \
    mbar_wait(BAR(B_F1 + kb)); \
    const uint4 a = lds4(xo + ((uint32_t)(XTAB0 >> (6 * kb)) & 63) * 4096), c = lds4(wo + ((uint32_t)(WTAB0 >> (6 * kb)) & 63) * 4096); \
    STAT(a, c) \
    asm volatile("" : "+f"(s), "+f"(s2), "+f"(sr)); \
    if (XPFAT >= K0 && XPFAT < K1) prefetch_if(((lane & 4) ? bp : xp) + 64 * (lane & 3), kb == XPFAT); \
    kv_prefetch(pf, kb == KPFAT ? task + R.nprep() : kb == KPFAT2 ? task + 2 * R.nprep() : 320); \
  } \
  __syncwarp(); mbar_arrive_if(BAR(B_AX + K0 / 3), lane == 0);
  STATS(0, 3)
  PROFC(tid == 0, 349);
    {
      uint4 m[4], n[4];
#pragma unroll
      for (int i = 0; i < 4; i++) { m[i] = ldg4(xp + 64 * i); n[i] = ldg4(bp + 64 * i); }
      STATS(3, 6)
      PROFC(tid == 0, 346);
      mbar_wait(BAR(B_LM));
      const uint32_t tag = lds32(sb + MISC_OFF) & 1;
#pragma unroll
      for (int i = 0; i < 4; i++) { const uint4 a = m[i], c = n[i]; STAT(a, c) }
      PROFC(tid == 0 && s2 != 1.2345f, 347);
#pragma unroll
      for (int o = 1; o <= 4; o <<= 1) { s += __shfl_xor_sync(0xffffffff, s, o); s2 += __shfl_xor_sync(0xffffffff, s2, o); sr += __shfl_xor_sync(0xffffffff, sr, o); }
      const float mn = s * (1.f / DM), rs = frcp(bf_rn(fsqrt(bf_rn(bf_rn(fmaxf(s2 * (1.f / DM) - mn * mn, 0.f)) + 1e-5f))));
      asm volatile("{ .reg .pred p; setp.ne.u32 p, %2, 0; @p st.relaxed.gpu.global.u32 [%0],%1; }"
                   ::"l"((uint32_t*)(S->RS + (8 * cb + 4 * (tb & 1) + (tb >> 1)) * 16 + 4 * w + (j & 1)) + (lane & 4) + (j >> 1)), "r"(tagf(sr, tag)),
                   "r"((uint32_t)(tb < 8 && (lane & 3) == 0)) : "memory");
      asm volatile("{ .reg .pred p; setp.ne.u32 p, %3, 0; @p st.relaxed.gpu.global.v2.u32 [%0],{%1,%2}; }"
                   ::"l"(S->S + trow), "r"(tagf(rs, tag)), "r"(tagf(-bf_rn(mn) * rs, tag)), "r"((uint32_t)(R.sm() < 10 && (lane & 7) == 0)) : "memory");
      PROFC(tid == 0, 3);
    }
#pragma unroll 1
  for (int r = 0; task < 320; r++) {
    {
      const uint32_t T0 = __byte_perm(sk.x, sk.z, 0x5410), T1 = __byte_perm(sk.x, sk.z, 0x7632);
      const uint32_t T2 = __byte_perm(sk.y, sk.w, 0x5410), T3 = __byte_perm(sk.y, sk.w, 0x7632);
      PROFC(tid == 0 && v_[15] != 0x12345, 336 + r);
      uint32_t o[16];
#pragma unroll
      for (int t = 0; t < 16; t += 2) {
        const uint32_t a = hmul2(hfma2(k_[t + 3], T0, hfma2(k_[t + 2], T1, hfma2(k_[t + 1], T2, hmul2(k_[t], T3)))), v_[t]);
        const uint32_t c = hmul2(hfma2(k_[t + 4], T0, hfma2(k_[t + 3], T1, hfma2(k_[t + 2], T2, hmul2(k_[t + 1], T3)))), v_[t + 1]);
        const int wd = ((7 - t / 2) >> 1) + 4 * ((7 - t / 2) & 1);
        o[wd] = __byte_perm(c, a, 0x5410); o[8 + wd] = __byte_perm(c, a, 0x7632);
        asm volatile("" : "+r"(o[wd]), "+r"(o[8 + wd]));
        if (t == PFAT) kv_prefetch(pf, task + (1 + PFD) * R.nprep());
      }
      PROFC(tid == 0, 330 + 2 * r);
      const int ph = task & 1;
      task += R.nprep();
      if (ORD == 0 && task < 320) kv_load(P, S, task, tid, k_, v_, sk);
      mbar_wait(BAR(B_E1 + 3)); mbar_wait(BAR(B_AX + 1));
#pragma unroll
      for (int i = 0; i < 4; i++) {
        const int row = 2 * lane + (i >> 1);
        asm volatile("st.shared.v4.u32 [%0],{%1,%2,%3,%4};" ::"r"(sb + KS_OFF + r * 8192 + row * 128 + (((2 * w + ((i & 1) ^ ph)) ^ (row & 7)) << 4)),
                     "r"(o[4 * i]), "r"(o[4 * i + 1]), "r"(o[4 * i + 2]), "r"(o[4 * i + 3]) : "memory");
      }
      __syncwarp();
      mbar_arrive_if(BAR(B_PS + r), lane == 0);
      PROFC(tid == 0, 331 + 2 * r);
      if (ORD == 1 && task < 320) kv_load(P, S, task, tid, k_, v_, sk);
    }
  }
#undef STAT
#undef STATS
  PROFC(tid == 0, 40);
}
#define SPLIT(G) asm volatile("{ .reg .pred p; .reg .u32 r; L: mov.u32 r, %%clock; setp.eq.u32 p, r, %0; @p bra.uni L; }" ::"n"(G) : "memory")
template <bool AUX>
__device__ __forceinline__ void conv_loop(uint32_t sb, uint32_t rc, int wg, int tid, long long t_start) {
  sb = opaque(sb); rc = opaque(rc);
  const uint32_t bars = sb + BAR_OFF;
  int slot = AUX ? 0 : wg + 1;
  mbar_wait(BAR(B_LM));
#pragma unroll 1
  while (slot < (int)((rc >> 10) & 7)) {
    tid = opaque(tid);
    const int w = tid >> 5, lane = tid & 31, g = lane >> 2, q = lane & 3;
    const uint32_t Dn = lds32(sb + MISC_OFF + 4 + 4 * slot);
    const uint32_t d0 = (g == 1 && q == 3 - w) ? Dn : 0, d1 = (g == 0 && q == 3 - w) ? Dn : 0;
    const uint32_t cb_ = conv_buf(sb, slot), c0 = cb_ + KC_OFS;
    const uint32_t abase = c0 + 2 * (2 * (g & 1) + 4 * w + 16 * (g >> 1) + 4 * q);
    const uint64_t bd = make_desc(cb_ + KV_PAD, 16, 256, 3);
    const bool hi = lane & 16, s1 = lane & 8;
    const int qo = hi ? (q + 1) & 3 : q;
    const int srcA = hi ? (lane & 12) | ((q + 1) & 3) : (lane & 12) | 16 | ((q + 3) & 3);
    const bool h3 = hi && q == 3, wrap = s1 && qo == 3, back = wrap && hi;
    const bool chi = wrap ? !hi : hi;
    const int cq = s1 ? (qo + 1) & 3 : qo;
    const int srcB = (lane & 4) | (s1 ? 0 : 8) | (chi ? 16 | ((cq + 3) & 3) : cq);
    const uint32_t gp = c0 + 16 * (2 * (g & 1) + 4 * w) + (chi ? 256 : 0) + 2 * (2 * cq + (s1 ? 0 : 1));
    uint32_t a[12], f[16], o[8];
    float S[4], T[4], U[2], keep[2], pv[2] = {0.f, 0.f}, pr[4] = {0.f, 0.f, 0.f, 0.f};
    float e0[64], e1[56], e2[48], e3[40], e4[32], e5[24], e6[16], e7[8];
#define UNR _Pragma("unroll")
#define PERM() UNR for (int i = 0; i < 4; i++) { f[4 * i] = __byte_perm(a[3 * i], a[3 * i + 1], 0x5432); f[4 * i + 1] = a[3 * i + 1]; \
                                                 f[4 * i + 2] = __byte_perm(a[3 * i + 1], a[3 * i + 2], 0x5432); f[4 * i + 3] = a[3 * i + 2]; }
#define MMA(N, E) UNR for (int i = 0; i < 4; i++) wgmma_rs<N>(E, f[4 * i], f[4 * i + 1], f[4 * i + 2], f[4 * i + 3], bd - 8 * i, 1); wg_commit();
#define L1(c) UNR for (int i = 0; i < 4; i++) { const float ev = c[i], od = c[4 + i]; S[i] = hi ? (h3 ? ev : od) : ev; \
                                                T[i] = __shfl_sync(0xffffffff, hi ? (h3 ? pr[i] : ev) : od, srcA); pr[i] = od; }
#define L1E() UNR for (int i = 0; i < 4; i++) S[i] += T[i];
#define L2() UNR for (int h = 0; h < 2; h++) { keep[h] = back ? pv[h] : S[2 * h + 1]; pv[h] = S[2 * h + 1]; U[h] = __shfl_sync(0xffffffff, S[2 * h], srcB); }
#define L2E(j) o[j] = pack_bf(keep[0] + U[0], keep[1] + U[1]);
#define GRP(G, N, P, E) UNR for (int i = 0; i < N / 2; i++) asm volatile("mov.b32 %0,%1;" : "=f"(E[i]) : "f"(P[i + 8])); \
    wg_fence(); if (G < 7) conv_frags<(G + 1) & 7>(a, abase); if (G >= 2) { L2() } L1(P) MMA(N, E) SPLIT(G); \
    if (G < 7) { PERM() } if (G >= 2) { L2E((G + 6) & 7) } L1E() wg_wait<0>(); fence_regs(E);
    PROFC(tid == 0, 300 + 4 * slot);
    mbar_wait(BAR(B_KF + slot));
    PROFC(tid == 0, 301 + 4 * slot);
    conv_frags<0>(a, abase);
    wg_fence();
    wgmma_rs<128>(e0, d0 << 16, d0, d1 << 16, d1, bd, 0);
    PERM() conv_frags<1>(a, abase); wg_fence(); MMA(128, e0) SPLIT(0); PERM() wg_wait<0>(); fence_regs(e0);
    GRP(1, 112, e0, e1) GRP(2, 96, e1, e2) GRP(3, 80, e2, e3) GRP(4, 64, e3, e4) GRP(5, 48, e4, e5) GRP(6, 32, e5, e6) GRP(7, 16, e6, e7)
    PROFC(tid == 0, 302 + 4 * slot);
    L2() L1(e7) L2E(6) L1E() L2() L2E(7)
    bar_sync(wg + 1, 128);
#pragma unroll
    for (int jj = 0; jj < 8; jj++)
      asm volatile("st.shared.u16 [%0],%1; st.shared.u16 [%0+16],%2;" ::"r"(gp + jj * 512), "h"((uint16_t)o[jj]), "h"((uint16_t)(o[jj] >> 16)) : "memory");
#undef PERM
#undef MMA
#undef L1
#undef L1E
#undef L2
#undef L2E
#undef GRP
    PROFC(tid == 0, 303 + 4 * slot);
    __syncwarp();
    if (lane == 0) mbar_arrive(BAR(B_GS + slot));
    if (!AUX) break;
    slot = slot ? slot + 1 : 3;
  }
}

#define IDX(J, c, h) (8 * (J) + 4 * ((c) >> 1) + 2 * (h) + ((c) & 1))
__device__ __forceinline__ uint2 lds2(uint32_t a) { uint2 v; asm volatile("ld.shared.v2.u32 {%0,%1},[%2];" : "=r"(v.x), "=r"(v.y) : "r"(a) : "memory"); return v; }
__device__ __forceinline__ void resid_load(float (&r)[40], uint32_t sb, int wg, int tid, const uint4& s) {
  const uint32_t dp = sb + XR_OFF + 8 * (tid & 3), xp = dp + (64 * wg + 16 * (tid >> 5) + ((tid & 31) >> 2)) * 160;
#pragma unroll
  for (int J = 0; J < 5; J++) {
    const uint2 u = lds2(xp + 32 * J), v = lds2(xp + 32 * J + 1280), d = lds2(dp + 20480 + 32 * J);
    r[8 * J] = __uint_as_float(u.x); r[8 * J + 1] = __uint_as_float(u.y); r[8 * J + 2] = __uint_as_float(v.x); r[8 * J + 3] = __uint_as_float(v.y);
    r[8 * J + 4] = __uint_as_float(d.x); r[8 * J + 5] = __uint_as_float(d.y);
  }
  r[30] = untag(s.x); r[31] = untag(s.y); r[38] = untag(s.z); r[39] = untag(s.w);
}
__device__ __forceinline__ void resid_init(float (&r)[40]) {
  const float s[4] = {r[30], r[31], r[38], r[39]};
#pragma unroll
  for (int J = 0; J < 5; J++) {
    uint32_t w[6];
#pragma unroll
    for (int i = 0; i < 6; i++) w[i] = __float_as_uint(r[8 * J + i]);
#pragma unroll
    for (int i = 0; i < 4; i++) {
      const int h = i >> 1, c = 2 * (i & 1);
      const float rs = s[2 * h], nm = s[2 * h + 1], x0 = bf_lo(w[i]), x1 = bf_hi(w[i]);
      const uint32_t t = hmul2(pack_bf(fmaf(x0, rs, nm), fmaf(x1, rs, nm)), w[4 + (i & 1)]);
      r[IDX(J, c, h)] = x0 + bf_lo(t); r[IDX(J, c + 1, h)] = x1 + bf_hi(t);
    }
  }
}

__device__ __forceinline__ float flip(float v, uint32_t m) { return __uint_as_float(__float_as_uint(v) ^ m); }
__device__ __forceinline__ void g1_phase(const int LY, const Head& H, uint32_t sb, int wg, int tid, Role R, float (&xr)[40], long long t_start) {
  Scratch* const S = H.s;
  tid = opaque(tid); sb = opaque(sb); R.v = opaque(R.v);
  const uint32_t bars = sb + BAR_OFF;
  const int cb = R.cb(), tb = R.tb();
  const int w = tid >> 5, lane = tid & 31, g = lane >> 2, q = lane & 3;
  const bool full = tb < 12;
  uint2* Eb = S->E + ((LY * 130 + cb) * 8 + 4 * wg + w) * 16 + g;
  float a[80];
#pragma unroll
  for (int i = 0; i < 80; i++) a[i] = 0.f;
  uint32_t rel = mapa(BAR(B_E1), lane ? R.wpart() : R.ubase() + (w & (R.ugs() - 1)));
  const bool rels = lane == 0 || (tid == 1 && wg != R.wlo());
  {
    uint64_t tw = LY ? WTAB1 : WTAB0, tx = LY ? XTAB1 : XTAB0;
    uint32_t bf = BAR(B_F1);
    if (tid == 0 && wg == 0 && !LY) PROF(351);
    fence_regs(a);
    mbar_wait(bf, LY);
    if (tid == 0 && wg == 0) PROF(LY ? 20 : 4);
#pragma unroll 1
    for (int kb = 0; kb < 10; kb++) {
      const uint64_t da = make_desc(sb + ((uint32_t)tw & 63) * 4096 + wg * 8192, 16, 1024, 1);
      const uint64_t db = make_desc(sb + ((uint32_t)tx & 63) * 4096, 16, 1024, 1);
      wg_fence();
#pragma unroll
      for (int kk = 0; kk < 4; kk++) wgmma_ss160(a, da + 2 * kk, db + 2 * kk, 1);
      wg_commit();
      wg_wait<1>();
      if (kb > 0) { if (rels) mbar_arrive_at(rel); rel += 8; }
      bf += 8; tw >>= 6; tx >>= 6;
      if (kb < 9) mbar_wait(bf, LY);
    }
  }
  if (tid == 0 && wg == 0) PROF(LY ? 19 : 2);
  mbar_wait(BAR(B_LM));
  const uint32_t tag = lds32(sb + MISC_OFF) & 1;
  if (q == 3) st_rlx2(Eb + tb * 1280, tag ^ 1, tag ^ 1);
  float2 lam, mu, mu2;
  float rs0, rs1;
  const uint32_t lamp = sb + LAM_OFF + 16 * (32 * wg + 8 * w + g);
  {
    const uint2* rp = S->RS + (8 * cb + 4 * wg + w) * 16 + 2 * g - (g & 1);
    uint2 v = ld_rlx2(rp);
    asm volatile("ld.shared.v2.f32 {%0,%1},[%2];" : "=f"(lam.x), "=f"(lam.y) : "r"(lamp));
    const float2 l2 = cmul(lam, lam), l4 = cmul(l2, l2), l8 = cmul(l4, l4), l16 = cmul(l8, l8), l32 = cmul(l16, l16);
    mu = full ? cmul(l32, l8) : l32; mu2 = cmul(mu, mu);
#pragma unroll 1
    for (int it = 0; it < SPIN && __any_sync(0xffffffff, untagged(v, tag)); it++) v = ld_rlx2(rp);
    rs0 = untag(v.x); rs1 = untag(v.y);
  }
  if (tid == 0 && wg == 0 && !LY) PROF(39);
  mbar_wait(BAR(B_ST), LY);
  const uint32_t ssm = sb + SSM_OFF + q * (full ? 336 : 272);
  wg_wait<0>(); fence_regs(a);
  if (rels) mbar_arrive_at(rel);
  if (tid == 0 && wg == 0) PROF(LY ? 21 : 5);
  float2 p = make_float2(0.f, 0.f);
#pragma unroll
  for (int j = 0; j < 20; j++) {
    if (j < 16 || full) {
      float4 sv;
      asm volatile("ld.shared.v4.f32 {%0,%1,%2,%3},[%4];" : "=f"(sv.x), "=f"(sv.y), "=f"(sv.z), "=f"(sv.w) : "r"(ssm + 16 * j));
#pragma unroll
      for (int e = 0; e < 2; e++) {
        const int o = 4 * j + e;
        const float r = e ? sv.z : sv.x, nm = e ? sv.w : sv.y;
        a[o] = fmaf(a[o], r, nm * rs0); a[o + 2] = fmaf(a[o + 2], r, nm * rs1);
        p = cfma(lam, p, make_float2(a[o], a[o + 2]));
      }
    }
  }
  {
    float2 t = make_float2(__shfl_up_sync(0xffffffff, p.x, 1, 4), __shfl_up_sync(0xffffffff, p.y, 1, 4));
    if (q >= 1) p = cfma(mu, t, p);
    t = make_float2(__shfl_up_sync(0xffffffff, p.x, 2, 4), __shfl_up_sync(0xffffffff, p.y, 2, 4));
    if (q >= 2) p = cfma(mu2, t, p);
  }
  if (q == 3 && full) st_rlx2(Eb + tb * 1280, tagf(p.x, tag), tagf(p.y, tag));
  if (tid == 0 && wg == 1) PROF(96 + 64 * LY);
  uint2 ev[3];
#pragma unroll
  for (int i = 0; i < 3; i++) { const int j = tb - 1 - q - 4 * i; ev[i] = j >= 0 ? ld_rlx2(Eb + j * 1280) : make_uint2(tag, tag); }
  float2 x = make_float2(__shfl_up_sync(0xffffffff, p.x, 1, 4), __shfl_up_sync(0xffffffff, p.y, 1, 4));
  if (q == 0) x = make_float2(0.f, 0.f);
  float c0, c1;
  asm volatile("ld.shared.v2.f32 {%0,%1},[%2+8];" : "=f"(c0), "=f"(c1) : "r"(lamp));
  const float c2 = -flip(c1, H.swap), c3 = flip(c0, H.swap);
#pragma unroll
  for (int i = 0; i < 40; i++) {
    const int o = 4 * (i >> 1) + (i & 1);
    const float u = a[o], v = a[o + 2];
    a[o] = fmaf(c0, u, c1 * v); a[o + 2] = fmaf(c2, u, c3 * v);
  }
  fence_regs(a);
  if (LY == 0 && R.b() < 128) {
    const int t0 = 16 * g + 8 * wg + 2 * w;
    mbar_wait(BAR(B_XR));
    uint4 s = lds4(sb + XR_OFF + 20480 + 256 + 8 * t0);
    if (__any_sync(0xffffffff, untagged(s, tag))) {
#pragma unroll 1
      for (int it = 0; it < SPIN; it++) { s = ld_rlx4(S->S + 128 * (R.b() >> 3) + t0); if (!__any_sync(0xffffffff, untagged(s, tag))) break; }
    }
    resid_load(xr, sb, wg, tid, s);
  }
  float2 mq, om4, fq;
  {
    asm volatile("" : "+f"(lam.x), "+f"(lam.y));
    const float2 one = make_float2(1.f, 0.f), l2 = cmul(lam, lam), l4 = cmul(l2, l2), l8 = cmul(l4, l4), l16 = cmul(l8, l8);
    const float2 l80 = full ? mu2 : cmul(mu2, l16), om = cmul(l80, l80), om2 = cmul(om, om);
    mq = cmul((q & 1) ? mu : one, (q & 2) ? mu2 : one);
    om4 = cmul(om2, om2); fq = cmul((q & 1) ? om : one, (q & 2) ? om2 : one);
  }
  mbar_wait(BAR(B_E1 + 9), LY);
#pragma unroll 1
  for (int it = 0; it < SPIN; it++) {
    const bool m0 = untagged(ev[0], tag), m1 = untagged(ev[1], tag), m2 = untagged(ev[2], tag);
    if (!__any_sync(0xffffffff, m0 || m1 || m2)) break;
    if (m0) ev[0] = ld_rlx2(Eb + (tb - 1 - q) * 1280);
    if (m1) ev[1] = ld_rlx2(Eb + (tb - 5 - q) * 1280);
    if (m2) ev[2] = ld_rlx2(Eb + (tb - 9 - q) * 1280);
  }
  if (tid == 0 && wg == 1) PROF(97 + 64 * LY);
  float2 c = make_float2(untag(ev[2].x), untag(ev[2].y));
#pragma unroll
  for (int i = 1; i >= 0; i--) c = cfma(om4, c, make_float2(untag(ev[i].x), untag(ev[i].y)));
  c = cmul(fq, c);
#pragma unroll
  for (int s = 1; s <= 2; s <<= 1) { c.x += __shfl_xor_sync(0xffffffff, c.x, s); c.y += __shfl_xor_sync(0xffffffff, c.y, s); }
  c = cfma(mq, c, x);
  float2 z = make_float2(fmaf(c0, c.x, c1 * c.y), fmaf(c2, c.x, c3 * c.y));
  if (tid == 0 && wg == 0) PROF(LY ? 22 : 6);
  const float2 lc = make_float2(lam.x, flip(lam.y, H.swap));
  const uint32_t hq = sb + (lane >> 4) * 1024 + (lane & 7) * 128 + (((4 * wg + w) ^ (lane & 7)) << 4);
  const uint32_t hp = hq + R_OFF + (lane & 8) * 2048, hp4 = hq + (LY ? R4_OFF1 : R4_OFF0) + (lane & 8) * 512;
#pragma unroll
  for (int j = 0; j < 20; j += 2) {
    if (j < 16 || full) {
      uint32_t o[4];
#pragma unroll
      for (int i = 0; i < 2; i++) {
        const float2 z0 = cfma(lc, z, make_float2(a[4 * (j + i)], a[4 * (j + i) + 2]));
        z = cfma(lc, z0, make_float2(a[4 * (j + i) + 1], a[4 * (j + i) + 3]));
        o[2 * i] = pack_bf(z0.x, z.x); o[2 * i + 1] = pack_bf(z0.y, z.y);
      }
      asm volatile("stmatrix.sync.aligned.m8n8.x4.trans.shared.b16 [%0], {%1,%2,%3,%4};" ::"r"(j < 16 ? hp + j * 1024 : hp4 + (j - 16) * 1024), "r"(o[0]), "r"(o[1]), "r"(o[2]), "r"(o[3]) : "memory");
      if (j & 2) { __syncwarp(); if (lane == 0) mbar_arrive(BAR(B_SH + j / 4)); }
    }
  }
  if (tid == 0 && wg == 0) PROF(LY ? 23 : 7);
}

__device__ __forceinline__ void gate_load(uint32_t (&G)[20], uint32_t sb, int LY, int wg, int tid) {
  const uint32_t bars = sb + BAR_OFF;
  const int lane = tid & 31, w = tid >> 5;
  mbar_wait(BAR(B_GF), LY);
  __syncwarp();
  {
    const uint32_t gb = sb + G_OFF + wg * 10240;
    const int dr = 4 * ((lane & 7) >> 1) + (lane & 1) + 2 * ((lane >> 3) & 1), ck = 2 * w + (lane >> 4);
#pragma unroll
    for (int J = 0; J < 5; J++) {
      const int dd = 16 * J + dr;
      asm volatile("ldmatrix.sync.aligned.m8n8.x4.trans.shared.b16 {%0,%1,%2,%3},[%4];"
                   : "=r"(G[4 * J]), "=r"(G[4 * J + 1]), "=r"(G[4 * J + 2]), "=r"(G[4 * J + 3]) : "r"(gb + dd * 128 + ((ck ^ (dd & 7)) << 4)) : "memory");
    }
  }
}
__device__ __forceinline__ void g2_phase(const int LY, const Params& P, Scratch* S, uint32_t sb, int wg, int tid, Role R, float (&xr)[40], long long t_start) {
  sb = opaque(sb);
  const uint32_t bars = sb + BAR_OFF;
  float acc[40];
#pragma unroll
  for (int i = 0; i < 40; i++) acc[i] = 0.f;
  fence_regs(acc);
#define G2_STEP(st, cs) { \
    const uint64_t da = make_desc(sb + H_OFF + (st) * 32768 + wg * 8192, 16, 1024, 1), db0 = make_desc(sb + (cs) * 20480, 16, 1024, 1), db1 = db0 + 640; \
    wg_fence(); \
    _Pragma("unroll") for (int kk = 0; kk < 4; kk++) wgmma_ss80(acc, da + 2 * kk, db0 + 2 * kk, 1); \
    _Pragma("unroll") for (int kk = 0; kk < 4; kk++) wgmma_ss80(acc, da + 1024 + 2 * kk, db1 + 2 * kk, 1); \
    wg_commit(); }
  mbar_wait(BAR(B_F2), LY);
  if (tid == 0 && wg == 0) PROF(LY ? 25 : 10);
  G2_STEP(0, 0)
  tid = opaque(tid); R.v = opaque(R.v);
  const uint32_t tag = lds32(sb + MISC_OFF) & 1;
  const int b = R.b(), tb2 = b >> 3, db_ = b & 7;
  const int w = tid >> 5, lane = tid & 31, g = lane >> 2, q = lane & 3;
  const int t0 = 128 * tb2 + 16 * g + 8 * wg + 2 * w;
  const int d0 = 80 * db_ + 4 * q, mrow = 64 * wg + 16 * w + g;
#define GATE(J, c, h) (((c) & 1) ? bf_hi(G[4 * (J) + 2 * (h) + ((c) >> 1)]) : bf_lo(G[4 * (J) + 2 * (h) + ((c) >> 1)]))
  uint32_t rel = mapa(BAR(B_E2), lane ? ((w & 1) ? R.wpart() : R.rank()) : R.cs() == 8 ? 4 * wg + w : wg);
  const bool rels = lane == 0 || (lane == 1 && w < 2);
  mbar_wait(BAR(B_F2 + 1), LY);
  G2_STEP(1, 1)
  uint32_t* Mb = S->M + ((2 * LY * 16 + tb2) * 8) * 256 + (wg * 4 + w) * 32 + (2 * g + (q & 1)) * 2 + (q >> 1);
  uint2 dl[5];
#pragma unroll
  for (int J = 0; J < 5; J++) dl[J] = __ldg((const uint2*)(P.dskip + d0 + 16 * J));
  st_rlx(Mb + db_ * 256, tag ^ 1);
  if (LY == 0) st_rlx(Mb + (16 * 8 + db_) * 256, tag ^ 1);
  {
    uint32_t bf = BAR(B_F2 + 2), st = 2;
#pragma unroll 1
    for (int kp = 2; kp < 10; kp++) {
      wg_wait<1>();
      if (rels && (LY == 0 || kp < 9)) mbar_arrive_at(rel);
      rel += 8;
      mbar_wait(bf, LY);
      G2_STEP(st, kp < 5 ? kp : kp - 5)
      bf += 8; st = st == 2 ? 0 : st + 1;
    }
  }
  if (LY == 0) resid_init(xr);
  wg_wait<1>();
  if (LY == 0 && rels) mbar_arrive_at(rel);
  rel += 8;
  wg_wait<0>(); fence_regs(acc);
  if (LY == 0 && rels) mbar_arrive_at(rel);
#pragma unroll
  for (int i = 0; i < 40; i++) acc[i] += xr[i];
  if (tid == 0 && wg == 0) PROF(LY ? 26 : 11);
  if (lane == 0) PROF(116 + 64 * LY + wg * 4 + w);

  float mm[2], rr[2], m1 = 0.f;
#pragma unroll 1
  for (int rep = 0;; rep++) {
    float m[2][2];
#pragma unroll
    for (int h = 0; h < 2; h++) {
      m[h][0] = m[h][1] = 0.f;
#pragma unroll
      for (int J = 0; J < 5; J++)
#pragma unroll
        for (int c = 0; c < 4; c++) { const float xv = acc[IDX(J, c, h)]; m[h][0] += xv; m[h][1] = fmaf(xv, xv, m[h][1]); }
    }
    float r1[2];
#pragma unroll
    for (int i = 0; i < 2; i++) { const float snd = (q & 1) ? m[0][i] : m[1][i], kp = (q & 1) ? m[1][i] : m[0][i]; r1[i] = kp + __shfl_xor_sync(0xffffffff, snd, 1); }
    const float r2 = ((q & 2) ? r1[1] : r1[0]) + __shfl_xor_sync(0xffffffff, (q & 2) ? r1[0] : r1[1], 2);
    st_rlx(Mb + db_ * 256, tagf(r2, tag));
    if (lane == 0 && rep == 0) PROF(100 + 64 * LY + wg * 4 + w);
    uint32_t G[20];
    const bool late = LY == 0 && db_ >= GLATE;
#pragma unroll
    for (int i = 0; i < 20; i++) G[i] = 0;
    if (!late && !rep) gate_load(G, sb, LY, wg, tid);
    uint32_t mv[8];
#pragma unroll
    for (int i = 0; i < 8; i++) mv[i] = ld_rlx(Mb + i * 256);
#pragma unroll 1
    for (int it = 0; it < SPIN; it++) {
      uint32_t miss = 0;
#pragma unroll
      for (int i = 0; i < 8; i++) miss |= ((mv[i] ^ tag) & 1) << i;
      if (!__any_sync(0xffffffff, miss)) break;
#pragma unroll
      for (int i = 0; i < 8; i++) if ((miss >> i) & 1) mv[i] = ld_rlx(Mb + i * 256);
    }
    bar_sync(4, 256);
    if (tid == 0 && wg == 0) PROF(LY ? 27 : 12 + 3 * rep);
    if (lane == 0 && rep == 0) PROF(108 + 64 * LY + wg * 4 + w);
    const float s = ((untag(mv[0]) + untag(mv[1])) + (untag(mv[2]) + untag(mv[3]))) + ((untag(mv[4]) + untag(mv[5])) + (untag(mv[6]) + untag(mv[7])));
    const float o = __shfl_xor_sync(0xffffffff, s, 2);
    const float S1 = (q & 2) ? o : s, S2 = (q & 2) ? s : o;
    const float mean = S1 * (1.f / DM), rs = frsqrt(fmaxf(S2 * (1.f / DM) - mean * mean, 0.f) + 1e-5f);
    const float mo = __shfl_xor_sync(0xffffffff, mean, 1), ro = __shfl_xor_sync(0xffffffff, rs, 1);
    mm[0] = (q & 1) ? mo : mean; mm[1] = (q & 1) ? mean : mo; rr[0] = (q & 1) ? ro : rs; rr[1] = (q & 1) ? rs : ro;
    if (rep) {
      if (db_ == 0) {
        if (q < 2) asm volatile("st.shared.v2.u32 [%0],{%1,%2};" ::"r"(sb + SSM_OFF + 8 * (t0 - 128 * tb2 + q)), "r"(tagf(rs, tag)), "r"(tagf((m1 - mean) * rs, tag)) : "memory");
        bar_sync(4, 256);
        if (wg == 0 && tid < 64) {
          uint4 v;
          asm volatile("ld.shared.v4.u32 {%0,%1,%2,%3},[%4];" : "=r"(v.x), "=r"(v.y), "=r"(v.z), "=r"(v.w) : "r"(sb + SSM_OFF + 16 * tid));
          st_rlx4(S->S + SEQ + 128 * tb2 + 2 * tid, v.x, v.y, v.z, v.w);
        }
      }
      break;
    }
    if (late) gate_load(G, sb, LY, wg, tid);
#pragma unroll
    for (int h = 0; h < 2; h++)
#pragma unroll
      for (int J = 0; J < 5; J++)
#pragma unroll
        for (int c = 0; c < 4; c++) { const float xv = acc[IDX(J, c, h)]; acc[IDX(J, c, h)] = fmaf((xv - mm[h]) * rr[h], GATE(J, c, h), xv); }
    if (LY) break;
    m1 = mean;
#pragma unroll
    for (int i = 0; i < 10; i++) {
      const int J = i >> 1, h = i & 1;
      const uint32_t u0 = pack_bf(acc[IDX(J, 0, h)] - mm[h], acc[IDX(J, 1, h)] - mm[h]), u1 = pack_bf(acc[IDX(J, 2, h)] - mm[h], acc[IDX(J, 3, h)] - mm[h]);
      asm volatile("st.shared.v2.u32 [%0],{%1,%2};" ::"r"(sb + US_OFF + (mrow + 8 * h) * 160 + 32 * J + 8 * q), "r"(u0), "r"(u1) : "memory");
    }
    __syncwarp();
    if (lane == 0) mbar_arrive(BAR(B_SG));
    if (tid == 0 && wg == 0) PROF(13);
    Mb += 16 * 8 * 256;
  }
  if (LY == 0) {
#pragma unroll
    for (int h = 0; h < 2; h++)
#pragma unroll
      for (int J = 0; J < 5; J++)
#pragma unroll
        for (int c = 0; c < 4; c++) {
          const float x2 = acc[IDX(J, c, h)];
          const uint32_t dw = (c & 2) ? dl[J].y : dl[J].x;
          xr[IDX(J, c, h)] = fmaf((x2 - mm[h]) * rr[h], (c & 1) ? bf_hi(dw) : bf_lo(dw), x2);
        }
  }
  else {
    float* op = P.out + (size_t)t0 * DM + d0;
#pragma unroll
    for (int i = 0; i < 10; i++) {
      const int J = i >> 1, h = i & 1;
      asm volatile("st.global.v4.f32 [%0],{%1,%2,%3,%4};" ::"l"(op + h * DM + 16 * J),
                   "f"(acc[IDX(J, 0, h)]), "f"(acc[IDX(J, 1, h)]), "f"(acc[IDX(J, 2, h)]), "f"(acc[IDX(J, 3, h)]) : "memory");
    }
  }
  if (tid == 0 && wg == 0 && LY) PROF(28);
#undef IDX
#undef GATE
}

template <int I0, int I1> __device__ __forceinline__ void init_barriers(uint32_t bars) {
#pragma unroll
  for (int i = I0; i < I1; i++) mbar_init(BAR(i), bar_count(i));
}
__device__ __forceinline__ int g2_cb(int kp) { return kp < 5 ? 2 * kp : 2 * kp - 9; }
__global__ void __cluster_dims__() __launch_bounds__(512, 1) fused_kernel(const Head H, const __grid_constant__ Params P) {
  extern __shared__ __align__(1024) uint8_t smem[];
  const uint32_t sb = opaque(smem_u32(smem)), bars = sb + BAR_OFF;
  const int wi = __shfl_sync(0xffffffff, threadIdx.x >> 5, 0), wg = wi >> 2, tid = threadIdx.x & 127;
  const int umap = blockIdx.x >= 96;
#define CLK(v)
  CLK(c_a);
  if (wi == 14) {
    if (elect_one()) { init_barriers<0, NBAR1>(bars); asm volatile("fence.mbarrier_init.release.cluster;" ::: "memory"); }
    __syncwarp();
  } else if (wi >= 12) prefetch_map(wi == 12 ? &P.mB : &P.mA[umap]);
  else if (wg == 2) xb_prefetch<1>(H, blockIdx.x + H.base, tid, 0);
  else if (P.role[blockIdx.x].w) return;
  CLK(c_b);
  asm volatile("barrier.cluster.arrive.relaxed.aligned;" ::: "memory");
  CLK(c_c);
  Role R;
  { const uint4 r = P.role[blockIdx.x]; R.v = r.x; R.c = r.y; R.p = r.z; }
  const int id = R.c & 255;
  const int tb = R.tb(), cb = R.cb(), b = R.b(), tb2 = b >> 3, db = b & 7, rank = R.rank();
  const bool has1 = tb <= 12, has2 = b < 128, full = tb < 12;
  Scratch* const S = H.s;
  unsigned* const epoch_p = &S->epoch[id * 8];
  const long long t_start = 0;
  if (wg < 2) {
    if (threadIdx.x == 0) PROF(50);
    asm volatile("griddepcontrol.launch_dependents;");
    bar_sync(6, 448);
    asm volatile("setmaxnreg.inc.sync.aligned.u32 176;");
    float xr[40];
#pragma unroll
    for (int i = 0; i < 40; i++) xr[i] = 0.f;
#pragma unroll 1
    for (int ly = 0; ly < 2; ly++) {
      if (has1) g1_phase(ly, H, sb, wg, tid, R, xr, t_start);
      if (ly == 0) {
        conv_loop<false>(sb, R.c, wg, tid, t_start);
        if (tid == 0 && wg == 0) PROF(9);
      }
      if (has2) g2_phase(ly, P, S, sb, wg, tid, R, xr, t_start);
    }
    if (tid == 0 && wg == 0) st_rlx(epoch_p, lds32(sb + MISC_OFF));
  } else if (wg == 2) {
    bar_sync(6, 448);
    if (has1) aux_prep(H, P, sb, R, tid, t_start);
    asm volatile("setmaxnreg.inc.sync.aligned.u32 136;");
    conv_loop<true>(sb, R.c, wg, tid, t_start);
    if (tid == 0) PROF(44);
  } else {
    if (threadIdx.x == 384) PROF(354);
    asm volatile("setmaxnreg.dec.sync.aligned.u32 24;");
    const int wlo = R.wlo(), whi = R.whi();
    const uint32_t wmask = R.wmask(), umask = R.umask(), f1bytes = full ? 36864 : 32768;
    if (wi < 14) {
      if (threadIdx.x == 384) PROF(340);
      asm volatile("barrier.cluster.wait.aligned;" ::: "memory");
      if (has1 && elect_one()) {
        uint64_t tab = wi == 12 ? WTAB0 : XTAB0;
        PROF(329 + wi);
#pragma unroll 1
        for (int kb = 0; kb < 6; kb++, tab >>= 6) {
          const uint32_t dst = sb + ((uint32_t)tab & 63) * 4096;
          if (wi == 12) {
#pragma unroll 1
            for (int h = wlo; h <= whi; h++) tma4d_mc(dst + h * 8192, &P.mB, kb * 64, 0, 0, 8 * cb + 4 * h, BAR(B_F1 + kb), wmask);
          } else {
            tma4d_mc(dst + R.uj() * 1024, &P.mA[umap], kb * 64, 0, 0, 80 * tb + R.uj(), BAR(B_F1 + kb), umask);
            mbar_expect_tx(BAR(B_F1 + kb), f1bytes);
          }
        }
      }
      if (!has1 && wi == 13) bar_sync(7, 64);
    } else {
      if (wi == 15 && elect_one()) { init_barriers<NBAR1, NBAR>(bars); asm volatile("fence.mbarrier_init.release.cluster;" ::: "memory"); }
      bar_sync(6, 448);
      if (!has1 && wi == 14) bar_sync(7, 64);
    }
    const unsigned e1 = ld_rlx(epoch_p) + 1;
    if (wi == 12) {
      if (elect_one()) {
#pragma unroll 1
        for (int ly = 0; ly < 2; ly++) {
#pragma unroll 1
          for (int kb = ly ? 0 : 6; kb < 10 && has1; kb++) {
            if (ly == 0) { mbar_wait(BAR(B_E1 + ((DEP0 >> (4 * kb - 24)) & 15))); mbar_wait(BAR(B_AX + (kb == 9))); }
            else if (has2) {
              if (kb < 6) mbar_wait(BAR(B_E2 + ((0x988765u >> (4 * kb)) & 15)));
              else { mbar_wait(BAR(B_GE)); mbar_wait(BAR(B_F1 + kb - 6), 1); }
            } else if (kb == 0) { mbar_wait(BAR(B_E1 + 9)); mbar_wait(BAR(B_CD + 1)); }
            const uint32_t dst = sb + ((uint32_t)((ly ? WTAB1 : WTAB0) >> (6 * kb)) & 63) * 4096;
#pragma unroll 1
            for (int h = wlo; h <= whi; h++) tma4d_mc(dst + h * 8192, &P.mB, kb * 64, 0, 0, 8 * cb + 4 * h, BAR(B_F1 + kb), wmask);
          }
          if (has2) {
            if (ly == 0) {
              mbar_wait(BAR(B_E1 + XRAT));
              mbar_expect_tx(BAR(B_XR), 20480 + 160 + 1024);
              tma4d(sb + XR_OFF, &P.mX, 80 * db, tb2, BAR(B_XR));
              bulk_g2s(sb + XR_OFF + 20480, P.dskip + 80 * db, 160, BAR(B_XR));
              bulk_g2s(sb + XR_OFF + 20480 + 256, S->S + 128 * tb2, 1024, BAR(B_XR));
              if (CWAIT) mbar_wait(BAR(CWAIT == 1 ? B_KF + 2 : CWAIT == 2 ? B_KF + R.nch() - 1 : CWAIT == 3 ? B_KF + R.nch() - 2 : B_HD));
            }
#pragma unroll 1
            for (int kp = 0; kp < 10; kp++) {
              const uint32_t dst = sb + (kp < 5 ? kp : kp - 5) * 20480;
              mbar_wait(BAR(kp >= 5 ? B_E2 + kp - 5 : ly ? B_E1 + ((0x84321u >> (4 * kp)) & 15) : kp < 3 ? B_SH : kp < 4 ? B_HD : B_CD), ly);
              mbar_expect_tx(BAR(B_F2 + kp), 20480 + 32768);
              tma5d(dst, &P.mC[0], g2_cb(kp) * 64, db * 5, BAR(B_F2 + kp));
              tma5d(dst + 10240, &P.mC[1], g2_cb(kp) * 64, db * 5, BAR(B_F2 + kp));
              if (kp == (ly ? 4 : 9)) {
                mbar_wait(BAR(ly ? B_E1 + 9 : B_CD + 1), ly);
                wait_cnt(&S->cnt[(C_G + db) * 32], e1 * 80);
                if (!ly) PROF(47);
                mbar_expect_tx(BAR(B_GF), 20480);
                tma2d(sb + G_OFF, &P.mGT, tb2 * 128, db * 80, BAR(B_GF));
                tma2d(sb + G_OFF + 10240, &P.mGT, tb2 * 128 + 64, db * 80, BAR(B_GF));
              }
            }
          }
        }
      }
    } else if (wi == 13) {
      const int h0 = R.cs() == 8 ? rank : 4 * rank;
#pragma unroll 1
      for (int ly = 0; ly < 2; ly++) {
        int lane = lane_id();
        if (has1) {
          const unsigned* fp = &S->flag[(F_U3 + 8 * ((160 * tb) >> 7) + (lane & (full ? 15 : 7))) * 32];
          uint32_t ready = ly ? __ballot_sync(0xffffffff, ld_rlx(fp) == e1) : ~0u;
          if (ly) mbar_wait(BAR(has2 ? B_SG : B_RF1));
#pragma unroll 1
          for (int kb = ly ? 0 : 6; kb < 10; kb++) {
            wait_flags(fp, e1, 0x101u * ((1u << (64 * kb / 80)) | (1u << ((64 * kb + 63) / 80))), ready);
            if (kb >= 3) mbar_wait(BAR(B_E1 + (ly ? kb - 3 : (DEP0 >> (4 * kb - 24)) & 15)), ly);
            mbar_wait(BAR(B_AX + (kb == 9)));
            if (elect_one()) {
              if (ly && kb == 0) PROF(34);
              tma4d_mc(sb + ((uint32_t)((ly ? XTAB1 : XTAB0) >> (6 * kb)) & 63) * 4096 + R.uj() * 1024, &P.mA[2 * ly + umap], kb * 64, 0, 0, 80 * tb + R.uj(),
                       BAR(B_F1 + kb), umask);
              mbar_expect_tx(BAR(B_F1 + kb), f1bytes);
            }
            __syncwarp();
          }
        }
        if (ly == 0) {
          if (has1) mbar_wait(BAR(B_E1 + KPF));
          if (elect_one()) {
#pragma unroll 1
            for (int s = 0; s < R.nch(); s++) prefetch_l2(P.ssmk + (size_t)R.ch(s) * SEQ, 4096);
          }
          lane = lane_id();
#pragma unroll
          for (int s = 0; s < 5; s++) {
            asm volatile("st.shared.v4.u32 [%0],{%1,%1,%1,%1};" ::"r"(conv_buf(sb, s) + 16 * lane), "r"(0) : "memory");
            asm volatile("st.shared.u8 [%0],%1;" ::"r"(conv_buf(sb, s) + KC_OFS + lane), "r"(0) : "memory");
          }
          fence_async();
          __syncwarp();
          const unsigned* cp = &S->cnt[(C_KV + (R.ch(min(lane, R.nch() - 1)) >> 6)) * 32];
          uint32_t ready = 0;
#pragma unroll 1
          for (int s = 0, sk = 0; s < R.nch(); s++) {
#pragma unroll 1
            for (; sk < (s ? R.nch() : KUP); sk++)
              if (elect_one()) { mbar_expect_tx(BAR(B_KF + sk), 8192); bulk_g2s(conv_buf(sb, sk) + KC_OFS + 32, P.ssmk + (size_t)R.ch(sk) * SEQ, 4096, BAR(B_KF + sk)); }
            PROFC(s == 0, 329);
#pragma unroll 1
            for (int it = 0; !((ready >> s) & 1) && it < SPIN; it++) ready = __ballot_sync(0xffffffff, (int)(ld_rlx(cp) - e1 * 32) >= 0);
            PROFC(s == 0, 30);
            if (elect_one()) {
              bulk_g2s(conv_buf(sb, s) + KV_PAD, S->kv + (size_t)R.ch(s) * SEQ, 4096, BAR(B_KF + s));
              if (s == 0 && has2) { prefetch_l2(P.cre + (size_t)5 * b * DM, 5 * DM * 2); prefetch_l2(P.cim + (size_t)5 * b * DM, 5 * DM * 2); }
            }
            __syncwarp();
          }
          PROF(31);
          if (!has1) return;
        }
        lane = lane_id();
        const int s0 = 128 * min(tb2, 15) / 160;
        const bool two = (128 * tb2 + 127) / 160 != s0;
        const unsigned* fp = &S->flag[(F_H + (ly * 13 + s0) * 10 + min(lane & 15, 9) + (two && lane >= 16 ? 10 : 0)) * 32];
        uint32_t ready = __ballot_sync(0xffffffff, ld_rlx(fp) == e1), st = 0;
        if (ly == 0 && !has2) {
          mbar_wait(BAR(B_HD));
          if (lane < 8) mbar_arrive_cl(BAR(B_RF1), lane & 1);
        }
        if (has2) {
          mbar_wait(BAR(B_RF0), ly);
#pragma unroll 1
          for (int kp = 0; kp < 10; kp++) {
            if (kp == 2) { mbar_wait(BAR(B_HD), ly); if (lane < 8) mbar_arrive_cl(BAR(B_RF1), lane & (R.cs() - 1)); }
            wait_flags(fp, e1, 0x10001u << g2_cb(kp), ready);
            if (kp == 2) mbar_wait(BAR(B_RF1), ly);
            if (kp >= 3) mbar_wait(BAR(B_E2 + kp - 3), ly);
            if (elect_one()) {
              if (kp == 0) PROF(33 + 2 * ly);
#pragma unroll
              for (int hf = 0; hf < 2; hf++)
                tma4d_mc(sb + H_OFF + st * 32768 + hf * 16384 + h0 * 2048, &P.mH, g2_cb(kp) * 128 + hf * 64, 0, 2 * h0,
                         ly * 16 + tb2, BAR(B_F2 + kp), (1u << R.cs()) - 1);
            }
            __syncwarp();
            st = st == 2 ? 0 : st + 1;
          }
        }
      }
    } else if (wi == 14) {
      if (!has1) return;
      prefetch_if(P.dskip + 64 * (tid & 31), (tid & 31) < 10);
      if (elect_one()) { prefetch_map(&P.sK); prefetch_map(&P.mX); prefetch_map(&P.sH); prefetch_map(&P.sU); prefetch_map(&P.sO); prefetch_map(&P.mC[0]); prefetch_map(&P.mC[1]); prefetch_map(&P.mH); prefetch_map(&P.mGT); prefetch_map(&P.mA[2 + umap]); }
      __syncwarp();
#pragma unroll 1
      for (int ly = 0; ly < 2; ly++) {
        const int lane = lane_id();
        mbar_wait(BAR(B_E1 + STAT_AT), ly);
        PROFC(lane == 0 && ly == 0, 36);
        {
          const int l = lane - (full ? 0 : 16);
          const uint2* p = S->S + ly * SEQ + 160 * tb + 2 * l;
          uint4 v[3];
#pragma unroll 1
          for (int it = 0; it < SPIN; it++) {
            v[0] = ld_rlx4(p); v[1] = ld_rlx4(p + 64); v[2] = ld_rlx4(p + 96);
            const bool miss = __any_sync(0xffffffff, untagged(v[0], e1 & 1) | untagged(v[1], e1 & 1) | untagged(v[2], e1 & 1));
            PROFC(lane == 0 && ly == 0 && it == 0, 37);
            if (!miss) break;
          }
          PROFC(lane == 0 && ly == 0, 38);
#pragma unroll
          for (int i = 0; i < 3; i++) {
            const int pr = l + (i == 2 ? 48 : 32 * i);
            if (pr >= 0) asm volatile("st.shared.v4.u32 [%0],{%1,%2,%3,%4};" ::"r"(sb + SSM_OFF + 16 * (pr + ((pr * (full ? 205 : 256)) >> 12))), "r"(v[i].x & ~1u),
                                      "r"(v[i].y & ~1u), "r"(v[i].z & ~1u), "r"(v[i].w & ~1u) : "memory");
          }
          __syncwarp();
        }
        if (lane == 0) mbar_arrive(BAR(B_ST));
        if (ly && has2) {
          mbar_wait(BAR(B_E1 + 9), 1);
          if (lane < 8) mbar_arrive_cl(BAR(B_RF0), lane & (R.cs() - 1));
        }
        if (lane == 0) {
#pragma unroll 1
          for (int pc = 0; pc < (full ? 5 : 4); pc++) {
            mbar_wait(BAR(B_SH + pc), ly);
            if (pc == 0 && (cb & 1)) delay(ly ? HDLY : HDLY0);
            fence_async();
#pragma unroll
            for (int i = 0; i < 2; i++) tma4d_store(&P.sH, sb + (pc < 4 ? R_OFF + i * 16384 + pc * 4096 : (ly ? R4_OFF1 : R4_OFF0) + i * 4096), 128 * cb + 64 * i, 0, 0, ly * 1024 + 80 * tb + 4 * pc);
          }
          bulk_commit(); bulk_wait();
          PROF(ly ? 17 : 16);
          mbar_arrive(BAR(B_HD));
          release<1>();
          signal_flag(&S->flag[(F_H + (ly * 13 + tb) * 10 + cb) * 32], e1);
          PROF(ly ? 24 : 8);
        }
        if (lane == 0 && has2 && !(ODIR && ly)) {
          mbar_wait(BAR(B_SG), ly);
          if (!(ly ? ODIR : UDIR)) {
          fence_async();
          tma4d_store(ly ? &P.sO : &P.sU, sb + (ly ? OS_OFF : US_OFF), 80 * db, 0, 0, tb2);
          bulk_commit(); bulk_wait();
          }
          if (ly == 0) { PROF(18); mbar_arrive(BAR(B_GE)); mbar_arrive_cl(BAR(B_GE), R.wpart()); release<2>(); signal_flag(&S->flag[(F_U3 + b) * 32], e1); }
          PROF(ly ? 29 : 14);
        }
        __syncwarp();
      }
    } else {
      discretise(H, P, sb, R, tid & 31, e1);
      if (elect_one()) {
        mbar_arrive(BAR(B_LM));
        PROF(348);
        if (b < R.nprep()) {
#pragma unroll 1
          for (int task = b, r = 0; task < 320; task += R.nprep(), r++) {
            mbar_wait(BAR(B_PS + r));
            PROF(320 + 3 * r);
            fence_async();
            tma2d_store(&P.sK, sb + KS_OFF + r * 8192, 64 * (task & 31), 64 * (task >> 5));
            bulk_commit(); bulk_wait();
            PROF(321 + 3 * r);
            release<4>();
            signal_cnt(&S->cnt[(C_KV + (task >> 5)) * 32], 1);
            PROF(322 + 3 * r);
          }
          PROF(41);
        }
        if (has2) {
          mbar_wait(BAR(B_SH));
#pragma unroll 1
          for (int i = 0; i < 8; i++) mbar_arrive_cl(BAR(B_RF0), i & (R.cs() - 1));
        }
#pragma unroll 1
        for (int s = 0, s0 = 0; s < R.nch(); s++) {
          mbar_wait(BAR(B_GS + s));
          fence_async();
          bulk_s2g(S->gt + (size_t)R.ch(s) * SEQ, conv_buf(sb, s) + KC_OFS, 4096); bulk_commit();
          if (s == 1 || s >= R.nch() - GSPL) bulk_wait();
          if (s == 1 || s == R.nch() - 1) mbar_arrive(BAR(B_CD + (s > 1)));
          if (s >= R.nch() - GSPL) {
            PROF(45);
            release<8>();
#pragma unroll 1
            for (; s0 <= s; s0++) signal_cnt(&S->cnt[(C_G + R.ch(s0) / 80) * 32], 1);
          }
        }
        PROF(46);
      }
    }
  }
}

typedef CUresult (*EncFn)(CUtensorMap*, CUtensorMapDataType, cuuint32_t, void*, const cuuint64_t*, const cuuint64_t*, const cuuint32_t*,
                          const cuuint32_t*, CUtensorMapInterleave, CUtensorMapSwizzle, CUtensorMapL2promotion, CUtensorMapFloatOOBfill);
bool enc(EncFn f, CUtensorMap* m, const void* base, int rank, const cuuint64_t* dims, const cuuint64_t* strides, const cuuint32_t* box, bool swz,
         bool f32 = false) {
  const cuuint32_t es[5] = {1, 1, 1, 1, 1};
  return f(m, f32 ? CU_TENSOR_MAP_DATA_TYPE_FLOAT32 : CU_TENSOR_MAP_DATA_TYPE_BFLOAT16, rank, const_cast<void*>(base), dims, strides, box, es,
           CU_TENSOR_MAP_INTERLEAVE_NONE, swz ? CU_TENSOR_MAP_SWIZZLE_128B : CU_TENSOR_MAP_SWIZZLE_NONE, CU_TENSOR_MAP_L2_PROMOTION_L2_256B,
           CU_TENSOR_MAP_FLOAT_OOB_FILL_NONE) == CUDA_SUCCESS;
}
void make_roles(Params& P, bool big) {
  for (uint32_t bx = 0; bx < (big ? 120u : 12u); bx++) {
    const uint32_t c = bx >> 3, r = bx & 7, id = big ? bx : 120 + bx;
    const uint32_t vA = c < 12 ? (2 * (c >> 1) + (r >> 2)) | (4 * (c & 1) + (r & 3)) << 4 | (r & 4) << 16 | 4 << 19 | (r ^ 4) << 22
                               : (4 * (c - 12) + (r >> 1)) | (8 + (r & 1)) << 4 | (r & 6) << 16 | 2 << 19 | (r ^ 2) << 22;
    const uint32_t vB = (bx < 10 ? 12 : 13) | bx << 4 | 2 << 19 | (bx & 1) << 22 | (bx & 1) << 26;
    P.role[bx].x = (big ? vA | r << 26 | 1u << 29 : vB) | (id < 128 ? (id & ~7u) | (r >> 1) | (r & 1) << 2 : id) << 8;
    P.role[bx].y = id | (big ? 5 : bx < 8 ? 3 : 4) << 10 | 120 << 13 | 132 << 21 | (big ? 4u : 3u) << 29;
    const uint32_t v = P.role[bx].x, cb = (v >> 4) & 15, rank = (v >> 26) & 7, ubase = (v >> 16) & 7, ugs = (v >> 19) & 7, wp = (v >> 22) & 7;
    const uint32_t wlo = rank > wp, whi = wp != rank ? wlo : 1, wmask = 1u << rank | 1u << wp;
    const uint32_t uj = (rank - ubase) * (!big ? 8 : ugs == 4 ? 5 : 10), sm = big ? (0x7296418530ull >> (4 * cb)) & 15 : bx < 8 ? 4 * (bx & 1) + (bx >> 1) : 15;
    P.role[bx].z = wlo | whi << 1 | wmask << 2 | ((1u << ugs) - 1) << (10 + ubase) | uj << 20 | sm << 25;
    P.role[bx].w = 0;
  }
}
void launch(const Head& H, const Params& P, int grid, int cs, bool dependent) {
  cudaLaunchConfig_t cfg = {};
  cfg.gridDim = grid; cfg.blockDim = 512; cfg.dynamicSmemBytes = SMEM_BYTES; cfg.stream = cudaStreamPerThread;
  cudaLaunchAttribute at[2];
  at[0].id = cudaLaunchAttributeClusterDimension; at[0].val.clusterDim.x = cs; at[0].val.clusterDim.y = 1; at[0].val.clusterDim.z = 1;
  at[1].id = cudaLaunchAttributeProgrammaticStreamSerialization; at[1].val.programmaticStreamSerializationAllowed = 1;
  cfg.attrs = at; cfg.numAttrs = dependent ? 2 : 1;
  cudaLaunchKernelEx(&cfg, fused_kernel, H, P);
}

}

extern "C" void kernel_launch(void* const* d_in, const int* in_sizes, int n_in, void* d_out, int out_size) {
  (void)in_sizes; (void)n_in; (void)out_size;
  typedef const __nv_bfloat16* cb;
  void* fp = nullptr; cudaDriverEntryPointQueryResult qr;
  cudaGetDriverEntryPoint("cuTensorMapEncodeTiled", &fp, cudaEnableDefault, &qr);
  EncFn f = (EncFn)fp;
  Scratch* sp = nullptr;
  cudaGetSymbolAddress((void**)&sp, g_scr);
  void *pu = sp->u, *ph = sp->h, *pgt = sp->gt;
  Params P;
  Head H;
  H.s = sp; H.x = (cb)d_in[0]; H.swap = (uintptr_t)d_in[4] < (uintptr_t)d_in[3] ? 0 : 0x80000000u; H.b0 = (cb)d_in[H.swap ? 3 : 4]; H.b1 = (cb)d_in[H.swap ? 4 : 3];
  for (int i = 0; i < 2; i++) {
    const cuuint64_t d[4] = {640, 8, 2, 80}, s[3] = {1280, (cuuint64_t)((uintptr_t)H.b1 - (uintptr_t)H.b0), 8 * 1280}; const cuuint32_t bx[4] = {64, 8, 2, 4};
    if (enc(f, &P.mB, H.b0, 4, d, s, bx, true)) break;
    cudaMemcpyAsync(sp->bcopy, H.b0, DM * DM * 2, cudaMemcpyDeviceToDevice, cudaStreamPerThread);
    cudaMemcpyAsync(sp->bcopy + DM * DM, H.b1, DM * DM * 2, cudaMemcpyDeviceToDevice, cudaStreamPerThread);
    H.b0 = sp->bcopy; H.b1 = sp->bcopy + DM * DM;
  }
  {
    const cuuint64_t d[5] = {640, 2, 4, 2, 40}, s[4] = {1280, 4 * 1280, 2 * 1280, 16 * 1280}; const cuuint32_t bx[5] = {64, 2, 4, 2, 5};
    enc(f, &P.mC[0], d_in[5], 5, d, s, bx, true); enc(f, &P.mC[1], d_in[6], 5, d, s, bx, true); }
  { const cuuint64_t d[2] = {2048, 640}, s[1] = {4096}; const cuuint32_t bx[2] = {64, 80}; enc(f, &P.mGT, pgt, 2, d, s, bx, true); }
  { const cuuint64_t d[4] = {640, 8, 16, 16}, s[3] = {16 * 1280, 1280, 128 * 1280}, so[3] = {16 * 2560, 2560, 128 * 2560}; const cuuint32_t bx[4] = {80, 8, 16, 1};
    enc(f, &P.sU, pu, 4, d, s, bx, false); enc(f, &P.mX, d_in[0], 4, d, s, bx, false); enc(f, &P.sO, d_out, 4, d, so, bx, false, true); }
  { const cuuint64_t d[2] = {2048, 640}, s[1] = {4096}; const cuuint32_t bx[2] = {64, 64}; enc(f, &P.sK, sp->kv, 2, d, s, bx, true); }
  P.lre = (cb)d_in[1]; P.lim = (cb)d_in[2]; P.cre = (cb)d_in[5]; P.cim = (cb)d_in[6]; P.ldt = (cb)d_in[7]; P.dskip = (cb)d_in[8];
  P.out = (float*)d_out;
  P.k = (cb)d_in[10]; P.v = (cb)d_in[11]; P.shk = (cb)d_in[12]; P.ssmk = (cb)d_in[13]; P.ssmd = (cb)d_in[14];
  cudaFuncSetAttribute(fused_kernel, cudaFuncAttributeMaxDynamicSharedMemorySize, SMEM_BYTES);
  for (int big = 1; big >= 0; big--) {
    const cuuint64_t seg = big ? 40 : 32;
    for (int i = 0; i < 4; i++) {
      const cuuint64_t d[4] = {640, 2, 4, 1024}, s[3] = {1280, seg * 1280, 2 * 1280}; const cuuint32_t bx[4] = {64, 2, 4, !big ? 8u : (i & 1) ? 10u : 5u};
      enc(f, &P.mA[i], i < 2 ? d_in[0] : pu, 4, d, s, bx, true);
    }
    {
      const cuuint64_t d[4] = {1280, 8, 16, 32}, s[3] = {16 * 2560, 2560, 128 * 2560}; const cuuint32_t bx[4] = {64, 8, big ? 2u : 8u, 1};
      enc(f, &P.mH, ph, 4, d, s, bx, true); }
    { const cuuint64_t d[4] = {1280, 2, 4, 2048}, s[3] = {2560, seg * 2560, 2 * 2560}; const cuuint32_t bx[4] = {64, 2, 4, 4};
      enc(f, &P.sH, ph, 4, d, s, bx, true); }
    make_roles(P, big);
    H.base = big ? 0 : 120;
    launch(H, P, big ? 120 : 12, big ? 8 : 2, !big);
  }
}
```

```cpp
#include <cuda_runtime.h>
#include <cuda.h>
#include <cuda_bf16.h>
#include <stdint.h>

namespace {

constexpr int SEQ = 2048, DM = 640;
constexpr int SPIN = 1 << 20;
#define PFAT 99
#define KVDLY 500
#define PFD 1
#define XPFAT 9
#define STAT_AT 6
#define KPFAT 3
#define KPFAT2 5
#define KPF 7
#define ODIR 1
#define UDIR 0
#define HDLY 1900
#define GSPL 2
#define CWAIT 0
#define HDLY0 1900
#define CTAB1 0x96543u
#define NSAT 0
#define SKW 1
#define RIAT 2
#define MIAT 5
#define FPAT 1
#define UPAT 7
#define STAT_AT1 4
#define W4AT 0
#define MBAR 1
#define NSDB 4
#define GLATE 6
#define KUP 1
#define XRAT 9
#define ORD 1

struct Scratch {
  uint2 E[2 * 13 * 10 * 8 * 16];
  uint32_t M[3 * 16 * 8 * 256];
  uint2 S[3 * SEQ];
  uint2 RS[80 * 16];
  unsigned flag[512 * 32];
  unsigned cnt[32 * 32];
  unsigned epoch[132 * 8];
  unsigned zero[128];
  unsigned prof[132 * 512];
  __align__(1024)
  __nv_bfloat16 u[SEQ * DM];
  __nv_bfloat16 h[2 * SEQ * 1280];
  __nv_bfloat16 kv[DM * SEQ];
  __nv_bfloat16 gt[DM * SEQ];
  __nv_bfloat16 bcopy[2 * DM * DM];
};
__device__ __align__(1024) Scratch g_scr;
#define PROF(i) do {} while (0)
#define PROFC(c, i) do {} while (0)

constexpr int C_KV = 0, C_G = 10;
constexpr int F_U3 = 0, F_H = 128;

constexpr int R_OFF = 196608, R4_OFF0 = 73728, R4_OFF1 = 122880, H_OFF = 131072, KS_OFF = 131072, CV_OFF = 86272, G_OFF0 = 40960, G_OFF1 = 102400, US_OFF = 98304, OS_OFF = US_OFF + 20480, XR_OFF = 163840;
constexpr int LAM_OFF = 229376, SSM_OFF = LAM_OFF + 1024, BAR_OFF = SSM_OFF + 1344;
constexpr int B_F1 = 0, B_E1 = 10, B_RF0 = 20, B_RF1 = 21, NBAR1 = 22;
constexpr int B_F2 = 22, B_KF = 32, B_GF = 37, B_CD = 38, B_XR = 40, B_ST = 41, B_HD = 42, B_LM = 43, B_E2 = 44, B_GS = 54, B_PS = 59, B_AX = 62, B_SH = 64, B_SG = 69, B_GE = 70, B_EA = 71, B_F3 = 74, NBAR = 84;
__host__ __device__ constexpr int bar_count(int i) { return i < B_E1 ? 1 : i < B_RF0 ? 9 : i < B_F2 ? 8 : i < B_E2 ? 1 : i < B_GS ? 12 : i < B_SH ? 4 : i < B_GE ? 8 : i < B_EA ? 2 : i < B_F3 ? 8 : 1; }
constexpr int MISC_OFF = BAR_OFF + NBAR * 8, SMEM_BYTES = MISC_OFF + 32;
constexpr int KV_PAD = 512, KC_OFS = KV_PAD + 4096, CH_STRIDE = 8960;
__device__ __forceinline__ uint32_t conv_buf(uint32_t sb, int slot) { return sb + CV_OFF + slot * CH_STRIDE; }
constexpr uint64_t tab6(int a, int b, int c, int d, int e, int f, int g, int h, int i, int j) {
  return (uint64_t)a | (uint64_t)b << 6 | (uint64_t)c << 12 | (uint64_t)d << 18 | (uint64_t)e << 24 | (uint64_t)f << 30 | (uint64_t)g << 36 | (uint64_t)h << 42 |
         (uint64_t)i << 48 | (uint64_t)j << 54;
}
constexpr uint64_t WTAB0 = tab6(0, 4, 8, 30, 12, 26, 0, 4, 8, 12), XTAB0 = tab6(40, 45, 50, 34, 16, 21, 40, 45, 50, 16);
constexpr uint64_t WTAB1 = tab6(16, 20, 0, 4, 8, 12, 16, 20, 24, 28), XTAB1 = tab6(40, 45, 50, 32, 40, 45, 50, 32, 40, 45);
constexpr uint32_t DEP0 = 0x4210;

struct Head {
  Scratch* s;
  const __nv_bfloat16 *x, *b0, *b1;
  uint32_t base, swap;
};
struct Params {
  const __nv_bfloat16 *lre, *lim, *ldt, *k, *v, *shk, *cre, *cim, *ssmk, *ssmd, *dskip;
  float* out;
  uint4 role[120];
  CUtensorMap mB, mA[4], mH, mC[2], mGT, mX, sH, sU, sO, sK;
};

__device__ __forceinline__ uint32_t smem_u32(const void* p) { return (uint32_t)__cvta_generic_to_shared(p); }
__device__ __forceinline__ uint32_t opaque(uint32_t x) { uint32_t y; asm volatile("mov.u32 %0, %1;" : "=r"(y) : "r"(x)); return y; }
__device__ __forceinline__ int lane_id() { int y; asm volatile("mov.u32 %0, %%laneid;" : "=r"(y)); return y; }
__device__ __forceinline__ void delay(uint32_t n) {
  asm volatile("{ .reg .pred p; .reg .u32 a, b; mov.u32 a, %%clock; L: mov.u32 b, %%clock; sub.u32 b, b, a; setp.lt.u32 p, b, %0; @p bra.uni L; }" ::"r"(n) : "memory");
}
__device__ __forceinline__ void mbar_init(uint32_t bar, uint32_t cnt) { asm volatile("mbarrier.init.shared::cta.b64 [%0], %1;" ::"r"(bar), "r"(cnt) : "memory"); }
__device__ __forceinline__ void mbar_expect_tx(uint32_t bar, uint32_t bytes) { asm volatile("mbarrier.arrive.expect_tx.shared::cta.b64 _, [%0], %1;" ::"r"(bar), "r"(bytes) : "memory"); }
__device__ __forceinline__ void mbar_arrive(uint32_t bar) { asm volatile("mbarrier.arrive.shared::cta.b64 _, [%0];" ::"r"(bar) : "memory"); }
__device__ __forceinline__ void mbar_arrive_if(uint32_t bar, bool c) {
  asm volatile("{ .reg .pred p; setp.ne.u32 p, %1, 0; @p mbarrier.arrive.shared::cta.b64 _, [%0]; }" ::"r"(bar), "r"((uint32_t)c) : "memory");
}
__device__ __forceinline__ void prefetch_if(const void* p, bool c) { asm volatile("{ .reg .pred p; setp.ne.u32 p, %1, 0; @p prefetch.global.L2 [%0]; }" ::"l"(p), "r"((uint32_t)c)); }
__device__ __forceinline__ void mbar_arrive_cl(uint32_t bar, uint32_t cta) {
  asm volatile("{ .reg .b32 ra; mapa.shared::cluster.u32 ra, %0, %1; mbarrier.arrive.shared::cluster.b64 _, [ra]; }" ::"r"(bar), "r"(cta) : "memory");
}
__device__ __forceinline__ uint32_t mapa(uint32_t a, uint32_t cta) { uint32_t r; asm("mapa.shared::cluster.u32 %0, %1, %2;" : "=r"(r) : "r"(a), "r"(cta)); return r; }
__device__ __forceinline__ void mbar_arrive_at(uint32_t ra) { asm volatile("mbarrier.arrive.shared::cluster.b64 _, [%0];" ::"r"(ra) : "memory"); }
__device__ __forceinline__ void mbar_wait(uint32_t bar, uint32_t parity = 0) {
  asm volatile("{ .reg .pred p; .reg .u32 c; mov.u32 c, 0;\n"
               "W: mbarrier.try_wait.parity.shared::cta.b64 p, [%0], %1; @p bra.uni D;\n"
               "add.u32 c, c, 1; setp.lt.u32 p, c, 0x100000; @p bra.uni W;\nD: }" ::"r"(bar), "r"(parity) : "memory");
}
__device__ __forceinline__ bool elect_one() { uint32_t p; asm volatile("{ .reg .pred P; elect.sync _|P, 0xffffffff; selp.u32 %0,1,0,P; }" : "=r"(p)); return p; }
__device__ __forceinline__ void bar_sync(int id, int n) { __syncwarp(); asm volatile("bar.sync %0, %1;" ::"r"(id), "r"(n) : "memory"); }
__device__ __forceinline__ void tma2d(uint32_t dst, const CUtensorMap* m, int c0, int c1, uint32_t bar) {
  asm volatile("cp.async.bulk.tensor.2d.shared::cluster.global.mbarrier::complete_tx::bytes [%0], [%1, {%3,%4}], [%2];"
               ::"r"(dst), "l"(m), "r"(bar), "r"(c0), "r"(c1) : "memory");
}
__device__ __forceinline__ void tma5d(uint32_t dst, const CUtensorMap* m, int c0, int c4, uint32_t bar) {
  asm volatile("cp.async.bulk.tensor.5d.shared::cluster.global.mbarrier::complete_tx::bytes [%0], [%1, {%3,%5,%5,%5,%4}], [%2];"
               ::"r"(dst), "l"(m), "r"(bar), "r"(c0), "r"(c4), "r"(0) : "memory");
}
__device__ __forceinline__ void tma4d(uint32_t dst, const CUtensorMap* m, int c0, int c3, uint32_t bar) {
  asm volatile("cp.async.bulk.tensor.4d.shared::cluster.global.mbarrier::complete_tx::bytes [%0], [%1, {%3,%5,%5,%4}], [%2];"
               ::"r"(dst), "l"(m), "r"(bar), "r"(c0), "r"(c3), "r"(0) : "memory");
}
__device__ __forceinline__ void tma4d_mc(uint32_t dst, const CUtensorMap* m, int c0, int c1, int c2, int c3, uint32_t bar, uint32_t mask) {
  asm volatile("cp.async.bulk.tensor.4d.shared::cluster.global.mbarrier::complete_tx::bytes.multicast::cluster [%0], [%1, {%3,%4,%5,%6}], [%2], %7;"
               ::"r"(dst), "l"(m), "r"(bar), "r"(c0), "r"(c1), "r"(c2), "r"(c3), "h"((uint16_t)mask) : "memory");
}
__device__ __forceinline__ void bulk_g2s(uint32_t dst, const void* src, uint32_t bytes, uint32_t bar) {
  asm volatile("cp.async.bulk.shared::cluster.global.mbarrier::complete_tx::bytes [%0], [%1], %2, [%3];" ::"r"(dst), "l"(src), "r"(bytes), "r"(bar) : "memory");
}
__device__ __forceinline__ void tma4d_store(const CUtensorMap* m, uint32_t src, int c0, int c1, int c2, int c3) {
  asm volatile("cp.async.bulk.tensor.4d.global.shared::cta.bulk_group [%0, {%2,%3,%4,%5}], [%1];" ::"l"(m), "r"(src), "r"(c0), "r"(c1), "r"(c2), "r"(c3) : "memory");
}
__device__ __forceinline__ void tma2d_store(const CUtensorMap* m, uint32_t src, int c0, int c1) {
  asm volatile("cp.async.bulk.tensor.2d.global.shared::cta.bulk_group [%0, {%2,%3}], [%1];" ::"l"(m), "r"(src), "r"(c0), "r"(c1) : "memory");
}
__device__ __forceinline__ void bulk_s2g(void* dst, uint32_t src, uint32_t bytes) {
  asm volatile("cp.async.bulk.global.shared::cta.bulk_group [%0], [%1], %2;" ::"l"(dst), "r"(src), "r"(bytes) : "memory");
}
__device__ __forceinline__ void bulk_commit() { asm volatile("cp.async.bulk.commit_group;" ::: "memory"); }
__device__ __forceinline__ void bulk_wait() { asm volatile("cp.async.bulk.wait_group 0;" ::: "memory"); }
__device__ __forceinline__ void fence_async() { asm volatile("fence.proxy.async.shared::cta;" ::: "memory"); }
__device__ __forceinline__ void prefetch_l2(const void* src, uint32_t bytes) { asm volatile("cp.async.bulk.prefetch.L2.global [%0], %1;" ::"l"(src), "r"(bytes) : "memory"); }
__device__ __forceinline__ void prefetch_map(const CUtensorMap* m) { asm volatile("prefetch.tensormap [%0];" ::"l"(m) : "memory"); }
__device__ __forceinline__ void wg_fence() { __syncwarp(); asm volatile("wgmma.fence.sync.aligned;" ::: "memory"); }
__device__ __forceinline__ void wg_commit() { asm volatile("wgmma.commit_group.sync.aligned;" ::: "memory"); }
template <int N> __device__ __forceinline__ void wg_wait() { asm volatile("wgmma.wait_group.sync.aligned %0;" ::"n"(N) : "memory"); }
template <int N> __device__ __forceinline__ void fence_regs(float (&d)[N]) {
#pragma unroll
  for (int i = 0; i < N; i++) asm volatile("" : "+f"(d[i])::"memory");
}
__device__ __forceinline__ uint64_t make_desc(uint32_t addr, uint32_t lbo, uint32_t sbo, uint32_t swz) {
  return (uint64_t)((addr & 0x3FFFF) >> 4) | ((uint64_t)(lbo >> 4) << 16) | ((uint64_t)(sbo >> 4) << 32) | ((uint64_t)swz << 62);
}
__device__ __forceinline__ uint32_t ldg1(const void* p) { uint32_t v; asm volatile("ld.global.nc.u32 %0,[%1];" : "=r"(v) : "l"(p)); return v; }
__device__ __forceinline__ uint32_t lds32(uint32_t a) { uint32_t v; asm volatile("ld.shared.u32 %0,[%1];" : "=r"(v) : "r"(a)); return v; }
__device__ __forceinline__ unsigned ld_rlx(const unsigned* p) { unsigned v; asm volatile("ld.relaxed.gpu.global.u32 %0,[%1];" : "=r"(v) : "l"(p) : "memory"); return v; }
__device__ __forceinline__ uint4 ld_rlx4(const void* p) {
  uint4 v; asm volatile("ld.relaxed.gpu.global.v4.u32 {%0,%1,%2,%3},[%4];" : "=r"(v.x), "=r"(v.y), "=r"(v.z), "=r"(v.w) : "l"(p) : "memory"); return v;
}
__device__ __forceinline__ uint2 ld_rlx2(const void* p) { uint2 v; asm volatile("ld.relaxed.gpu.global.v2.u32 {%0,%1},[%2];" : "=r"(v.x), "=r"(v.y) : "l"(p) : "memory"); return v; }
__device__ __forceinline__ void st_rlx2(void* p, uint32_t a, uint32_t b) { asm volatile("st.relaxed.gpu.global.v2.u32 [%0],{%1,%2};" ::"l"(p), "r"(a), "r"(b) : "memory"); }
__device__ __forceinline__ void st_rlx(void* p, uint32_t a) { asm volatile("st.relaxed.gpu.global.u32 [%0],%1;" ::"l"(p), "r"(a) : "memory"); }
#define PUB 15
template <int SITE> __device__ __forceinline__ void release() { if (PUB & SITE) asm volatile("fence.acq_rel.gpu;" ::: "memory"); }
__device__ __forceinline__ void signal_flag(unsigned* p, unsigned val) { asm volatile("st.relaxed.gpu.global.u32 [%0],%1;" ::"l"(p), "r"(val) : "memory"); }
__device__ __forceinline__ void signal_cnt(unsigned* p, unsigned n) { asm volatile("red.relaxed.gpu.global.add.u32 [%0],%1;" ::"l"(p), "r"(n) : "memory"); }
__device__ __forceinline__ void wait_flags(const unsigned* p, unsigned val, uint32_t need, uint32_t& ready) {
#pragma unroll 1
  for (int it = 0; (ready & need) != need && it < SPIN; it++) ready = __ballot_sync(0xffffffff, ld_rlx(p) == val);
}
__device__ __forceinline__ void wait_cnt(const unsigned* p, unsigned tgt) {
  asm volatile("{ .reg .pred p; .reg .u32 c; .reg .s32 v; mov.u32 c, 0;\n"
               "W: ld.relaxed.gpu.global.u32 v, [%0]; sub.s32 v, v, %1; setp.ge.s32 p, v, 0; @p bra.uni D;\n"
               "add.u32 c, c, 1; setp.lt.u32 p, c, 0x100000; @p bra.uni W;\nD: }" ::"l"(p), "r"(tgt) : "memory");
}
__device__ __forceinline__ uint32_t pack_bf(float lo, float hi) { uint32_t r; asm("cvt.rn.bf16x2.f32 %0, %1, %2;" : "=r"(r) : "f"(hi), "f"(lo)); return r; }
__device__ __forceinline__ float bf_lo(uint32_t v) { return __uint_as_float(v << 16); }
__device__ __forceinline__ float bf_hi(uint32_t v) { return __uint_as_float(v & 0xffff0000u); }
__device__ __forceinline__ float bf_rn(float x) { return __bfloat162float(__float2bfloat16_rn(x)); }
__device__ __forceinline__ float frcp(float x) { float r; asm("rcp.approx.ftz.f32 %0,%1;" : "=f"(r) : "f"(x)); return r; }
__device__ __forceinline__ float fsqrt(float x) { float r; asm("sqrt.approx.ftz.f32 %0,%1;" : "=f"(r) : "f"(x)); return r; }
__device__ __forceinline__ float frsqrt(float x) { float r; asm("rsqrt.approx.ftz.f32 %0,%1;" : "=f"(r) : "f"(x)); return r; }
__device__ __forceinline__ uint32_t hmul2(uint32_t a, uint32_t b) { uint32_t r; asm("mul.rn.bf16x2 %0,%1,%2;" : "=r"(r) : "r"(a), "r"(b)); return r; }
__device__ __forceinline__ uint32_t hfma2(uint32_t a, uint32_t b, uint32_t c) { uint32_t r; asm("fma.rn.bf16x2 %0,%1,%2,%3;" : "=r"(r) : "r"(a), "r"(b), "r"(c)); return r; }
__device__ __forceinline__ float2 cmul(float2 a, float2 b) { return make_float2(a.x * b.x - a.y * b.y, a.x * b.y + a.y * b.x); }
__device__ __forceinline__ float2 cfma(float2 a, float2 b, float2 c) {
  return make_float2(fmaf(a.x, b.x, fmaf(-a.y, b.y, c.x)), fmaf(a.x, b.y, fmaf(a.y, b.x, c.y)));
}
__device__ __forceinline__ uint32_t tagf(float v, uint32_t tag) { return (__float_as_uint(v) & ~1u) | tag; }
__device__ __forceinline__ float untag(uint32_t v) { return __uint_as_float(v & ~1u); }
__device__ __forceinline__ bool untagged(const uint4& v, uint32_t tag) { return (((v.x ^ tag) | (v.y ^ tag) | (v.z ^ tag) | (v.w ^ tag)) & 1) != 0; }
__device__ __forceinline__ bool untagged(const uint2& v, uint32_t tag) { return (((v.x ^ tag) | (v.y ^ tag)) & 1) != 0; }
__device__ __forceinline__ float2 lam_bar(float lr, float li, float ldt) {
  float dt = bf_rn(expf(ldt)); float e = expf(dt * lr), s, c; sincospif(dt * li * 0.31830988618379067f, &s, &c); return make_float2(e * c, e * s);
}

__device__ __forceinline__ int conv_ch(uint32_t c, int s) { return s * ((c >> 21) & 255) + (c & 255) - (s >= (int)(c >> 29) ? 8 : 0); }
struct Role {
  uint32_t v, c, p;
  __device__ __forceinline__ int tb() const { return v & 15; }
  __device__ __forceinline__ int cb() const { return (v >> 4) & 15; }
  __device__ __forceinline__ int b() const { return (v >> 8) & 255; }
  __device__ __forceinline__ int ubase() const { return (v >> 16) & 7; }
  __device__ __forceinline__ int ugs() const { return (v >> 19) & 7; }
  __device__ __forceinline__ int wpart() const { return (v >> 22) & 7; }
  __device__ __forceinline__ int rank() const { return (v >> 26) & 7; }
  __device__ __forceinline__ int cs() const { return (v >> 29) ? 8 : 2; }
  __device__ __forceinline__ int ch(int s) const { return conv_ch(c, s); }
  __device__ __forceinline__ int wlo() const { return p & 1; }
  __device__ __forceinline__ int whi() const { return (p >> 1) & 1; }
  __device__ __forceinline__ uint32_t wmask() const { return (p >> 2) & 255; }
  __device__ __forceinline__ uint32_t umask() const { return (p >> 10) & 255; }
  __device__ __forceinline__ int uj() const { return (p >> 20) & 31; }
  __device__ __forceinline__ int sm() const { return (p >> 25) & 15; }
  __device__ __forceinline__ int nch() const { return (c >> 10) & 7; }
  __device__ __forceinline__ int nprep() const { return (c >> 13) & 255; }
};

__device__ __forceinline__ void wgmma_ss80(float (&d)[40], uint64_t da, uint64_t db, int sd){
  asm volatile("{ .reg .pred p; setp.ne.b32 p, %42, 0;\n"
   "wgmma.mma_async.sync.aligned.m64n80k16.f32.bf16.bf16 {%0, %1, %2, %3, %4, %5, %6, %7, %8, %9, %10, %11, %12, %13, %14, %15, %16, %17, %18, %19, %20, %21, %22, %23, %24, %25, %26, %27, %28, %29, %30, %31, %32, %33, %34, %35, %36, %37, %38, %39}, %40, %41, p, 1, 1, 0, 0; }\n"
   : "+f"(d[0]), "+f"(d[1]), "+f"(d[2]), "+f"(d[3]), "+f"(d[4]), "+f"(d[5]), "+f"(d[6]), "+f"(d[7]), "+f"(d[8]), "+f"(d[9]), "+f"(d[10]), "+f"(d[11]), "+f"(d[12]), "+f"(d[13]), "+f"(d[14]), "+f"(d[15]), "+f"(d[16]), "+f"(d[17]), "+f"(d[18]), "+f"(d[19]), "+f"(d[20]), "+f"(d[21]), "+f"(d[22]), "+f"(d[23]), "+f"(d[24]), "+f"(d[25]), "+f"(d[26]), "+f"(d[27]), "+f"(d[28]), "+f"(d[29]), "+f"(d[30]), "+f"(d[31]), "+f"(d[32]), "+f"(d[33]), "+f"(d[34]), "+f"(d[35]), "+f"(d[36]), "+f"(d[37]), "+f"(d[38]), "+f"(d[39]) : "l"(da), "l"(db), "r"(sd));
}
__device__ __forceinline__ void wgmma_ss160(float (&d)[80], uint64_t da, uint64_t db, int sd){
  asm volatile("{ .reg .pred p; setp.ne.b32 p, %82, 0;\n"
   "wgmma.mma_async.sync.aligned.m64n160k16.f32.bf16.bf16 {%0, %1, %2, %3, %4, %5, %6, %7, %8, %9, %10, %11, %12, %13, %14, %15, %16, %17, %18, %19, %20, %21, %22, %23, %24, %25, %26, %27, %28, %29, %30, %31, %32, %33, %34, %35, %36, %37, %38, %39, %40, %41, %42, %43, %44, %45, %46, %47, %48, %49, %50, %51, %52, %53, %54, %55, %56, %57, %58, %59, %60, %61, %62, %63, %64, %65, %66, %67, %68, %69, %70, %71, %72, %73, %74, %75, %76, %77, %78, %79}, %80, %81, p, 1, 1, 0, 0; }\n"
   : "+f"(d[0]), "+f"(d[1]), "+f"(d[2]), "+f"(d[3]), "+f"(d[4]), "+f"(d[5]), "+f"(d[6]), "+f"(d[7]), "+f"(d[8]), "+f"(d[9]), "+f"(d[10]), "+f"(d[11]), "+f"(d[12]), "+f"(d[13]), "+f"(d[14]), "+f"(d[15]), "+f"(d[16]), "+f"(d[17]), "+f"(d[18]), "+f"(d[19]), "+f"(d[20]), "+f"(d[21]), "+f"(d[22]), "+f"(d[23]), "+f"(d[24]), "+f"(d[25]), "+f"(d[26]), "+f"(d[27]), "+f"(d[28]), "+f"(d[29]), "+f"(d[30]), "+f"(d[31]), "+f"(d[32]), "+f"(d[33]), "+f"(d[34]), "+f"(d[35]), "+f"(d[36]), "+f"(d[37]), "+f"(d[38]), "+f"(d[39]), "+f"(d[40]), "+f"(d[41]), "+f"(d[42]), "+f"(d[43]), "+f"(d[44]), "+f"(d[45]), "+f"(d[46]), "+f"(d[47]), "+f"(d[48]), "+f"(d[49]), "+f"(d[50]), "+f"(d[51]), "+f"(d[52]), "+f"(d[53]), "+f"(d[54]), "+f"(d[55]), "+f"(d[56]), "+f"(d[57]), "+f"(d[58]), "+f"(d[59]), "+f"(d[60]), "+f"(d[61]), "+f"(d[62]), "+f"(d[63]), "+f"(d[64]), "+f"(d[65]), "+f"(d[66]), "+f"(d[67]), "+f"(d[68]), "+f"(d[69]), "+f"(d[70]), "+f"(d[71]), "+f"(d[72]), "+f"(d[73]), "+f"(d[74]), "+f"(d[75]), "+f"(d[76]), "+f"(d[77]), "+f"(d[78]), "+f"(d[79]) : "l"(da), "l"(db), "r"(sd));
}
template<int N> __device__ __forceinline__ void wgmma_rs(float (&d)[N/2], uint32_t a0, uint32_t a1, uint32_t a2, uint32_t a3, uint64_t db, int sd);
template<> __device__ __forceinline__ void wgmma_rs<16>(float (&d)[8], uint32_t a0, uint32_t a1, uint32_t a2, uint32_t a3, uint64_t db, int sd){
  asm volatile("{ .reg .pred p; setp.ne.b32 p, %13, 0;\n"
   "wgmma.mma_async.sync.aligned.m64n16k16.f32.bf16.bf16 {%0, %1, %2, %3, %4, %5, %6, %7}, {%8,%9,%10,%11}, %12, p, 1, 1, 0; }\n"
   : "+f"(d[0]), "+f"(d[1]), "+f"(d[2]), "+f"(d[3]), "+f"(d[4]), "+f"(d[5]), "+f"(d[6]), "+f"(d[7]) : "r"(a0), "r"(a1), "r"(a2), "r"(a3), "l"(db), "r"(sd));
}
template<> __device__ __forceinline__ void wgmma_rs<32>(float (&d)[16], uint32_t a0, uint32_t a1, uint32_t a2, uint32_t a3, uint64_t db, int sd){
  asm volatile("{ .reg .pred p; setp.ne.b32 p, %21, 0;\n"
   "wgmma.mma_async.sync.aligned.m64n32k16.f32.bf16.bf16 {%0, %1, %2, %3, %4, %5, %6, %7, %8, %9, %10, %11, %12, %13, %14, %15}, {%16,%17,%18,%19}, %20, p, 1, 1, 0; }\n"
   : "+f"(d[0]), "+f"(d[1]), "+f"(d[2]), "+f"(d[3]), "+f"(d[4]), "+f"(d[5]), "+f"(d[6]), "+f"(d[7]), "+f"(d[8]), "+f"(d[9]), "+f"(d[10]), "+f"(d[11]), "+f"(d[12]), "+f"(d[13]), "+f"(d[14]), "+f"(d[15]) : "r"(a0), "r"(a1), "r"(a2), "r"(a3), "l"(db), "r"(sd));
}
template<> __device__ __forceinline__ void wgmma_rs<48>(float (&d)[24], uint32_t a0, uint32_t a1, uint32_t a2, uint32_t a3, uint64_t db, int sd){
  asm volatile("{ .reg .pred p; setp.ne.b32 p, %29, 0;\n"
   "wgmma.mma_async.sync.aligned.m64n48k16.f32.bf16.bf16 {%0, %1, %2, %3, %4, %5, %6, %7, %8, %9, %10, %11, %12, %13, %14, %15, %16, %17, %18, %19, %20, %21, %22, %23}, {%24,%25,%26,%27}, %28, p, 1, 1, 0; }\n"
   : "+f"(d[0]), "+f"(d[1]), "+f"(d[2]), "+f"(d[3]), "+f"(d[4]), "+f"(d[5]), "+f"(d[6]), "+f"(d[7]), "+f"(d[8]), "+f"(d[9]), "+f"(d[10]), "+f"(d[11]), "+f"(d[12]), "+f"(d[13]), "+f"(d[14]), "+f"(d[15]), "+f"(d[16]), "+f"(d[17]), "+f"(d[18]), "+f"(d[19]), "+f"(d[20]), "+f"(d[21]), "+f"(d[22]), "+f"(d[23]) : "r"(a0), "r"(a1), "r"(a2), "r"(a3), "l"(db), "r"(sd));
}
template<> __device__ __forceinline__ void wgmma_rs<64>(float (&d)[32], uint32_t a0, uint32_t a1, uint32_t a2, uint32_t a3, uint64_t db, int sd){
  asm volatile("{ .reg .pred p; setp.ne.b32 p, %37, 0;\n"
   "wgmma.mma_async.sync.aligned.m64n64k16.f32.bf16.bf16 {%0, %1, %2, %3, %4, %5, %6, %7, %8, %9, %10, %11, %12, %13, %14, %15, %16, %17, %18, %19, %20, %21, %22, %23, %24, %25, %26, %27, %28, %29, %30, %31}, {%32,%33,%34,%35}, %36, p, 1, 1, 0; }\n"
   : "+f"(d[0]), "+f"(d[1]), "+f"(d[2]), "+f"(d[3]), "+f"(d[4]), "+f"(d[5]), "+f"(d[6]), "+f"(d[7]), "+f"(d[8]), "+f"(d[9]), "+f"(d[10]), "+f"(d[11]), "+f"(d[12]), "+f"(d[13]), "+f"(d[14]), "+f"(d[15]), "+f"(d[16]), "+f"(d[17]), "+f"(d[18]), "+f"(d[19]), "+f"(d[20]), "+f"(d[21]), "+f"(d[22]), "+f"(d[23]), "+f"(d[24]), "+f"(d[25]), "+f"(d[26]), "+f"(d[27]), "+f"(d[28]), "+f"(d[29]), "+f"(d[30]), "+f"(d[31]) : "r"(a0), "r"(a1), "r"(a2), "r"(a3), "l"(db), "r"(sd));
}
template<> __device__ __forceinline__ void wgmma_rs<80>(float (&d)[40], uint32_t a0, uint32_t a1, uint32_t a2, uint32_t a3, uint64_t db, int sd){
  asm volatile("{ .reg .pred p; setp.ne.b32 p, %45, 0;\n"
   "wgmma.mma_async.sync.aligned.m64n80k16.f32.bf16.bf16 {%0, %1, %2, %3, %4, %5, %6, %7, %8, %9, %10, %11, %12, %13, %14, %15, %16, %17, %18, %19, %20, %21, %22, %23, %24, %25, %26, %27, %28, %29, %30, %31, %32, %33, %34, %35, %36, %37, %38, %39}, {%40,%41,%42,%43}, %44, p, 1, 1, 0; }\n"
   : "+f"(d[0]), "+f"(d[1]), "+f"(d[2]), "+f"(d[3]), "+f"(d[4]), "+f"(d[5]), "+f"(d[6]), "+f"(d[7]), "+f"(d[8]), "+f"(d[9]), "+f"(d[10]), "+f"(d[11]), "+f"(d[12]), "+f"(d[13]), "+f"(d[14]), "+f"(d[15]), "+f"(d[16]), "+f"(d[17]), "+f"(d[18]), "+f"(d[19]), "+f"(d[20]), "+f"(d[21]), "+f"(d[22]), "+f"(d[23]), "+f"(d[24]), "+f"(d[25]), "+f"(d[26]), "+f"(d[27]), "+f"(d[28]), "+f"(d[29]), "+f"(d[30]), "+f"(d[31]), "+f"(d[32]), "+f"(d[33]), "+f"(d[34]), "+f"(d[35]), "+f"(d[36]), "+f"(d[37]), "+f"(d[38]), "+f"(d[39]) : "r"(a0), "r"(a1), "r"(a2), "r"(a3), "l"(db), "r"(sd));
}
template<> __device__ __forceinline__ void wgmma_rs<96>(float (&d)[48], uint32_t a0, uint32_t a1, uint32_t a2, uint32_t a3, uint64_t db, int sd){
  asm volatile("{ .reg .pred p; setp.ne.b32 p, %53, 0;\n"
   "wgmma.mma_async.sync.aligned.m64n96k16.f32.bf16.bf16 {%0, %1, %2, %3, %4, %5, %6, %7, %8, %9, %10, %11, %12, %13, %14, %15, %16, %17, %18, %19, %20, %21, %22, %23, %24, %25, %26, %27, %28, %29, %30, %31, %32, %33, %34, %35, %36, %37, %38, %39, %40, %41, %42, %43, %44, %45, %46, %47}, {%48,%49,%50,%51}, %52, p, 1, 1, 0; }\n"
   : "+f"(d[0]), "+f"(d[1]), "+f"(d[2]), "+f"(d[3]), "+f"(d[4]), "+f"(d[5]), "+f"(d[6]), "+f"(d[7]), "+f"(d[8]), "+f"(d[9]), "+f"(d[10]), "+f"(d[11]), "+f"(d[12]), "+f"(d[13]), "+f"(d[14]), "+f"(d[15]), "+f"(d[16]), "+f"(d[17]), "+f"(d[18]), "+f"(d[19]), "+f"(d[20]), "+f"(d[21]), "+f"(d[22]), "+f"(d[23]), "+f"(d[24]), "+f"(d[25]), "+f"(d[26]), "+f"(d[27]), "+f"(d[28]), "+f"(d[29]), "+f"(d[30]), "+f"(d[31]), "+f"(d[32]), "+f"(d[33]), "+f"(d[34]), "+f"(d[35]), "+f"(d[36]), "+f"(d[37]), "+f"(d[38]), "+f"(d[39]), "+f"(d[40]), "+f"(d[41]), "+f"(d[42]), "+f"(d[43]), "+f"(d[44]), "+f"(d[45]), "+f"(d[46]), "+f"(d[47]) : "r"(a0), "r"(a1), "r"(a2), "r"(a3), "l"(db), "r"(sd));
}
template<> __device__ __forceinline__ void wgmma_rs<112>(float (&d)[56], uint32_t a0, uint32_t a1, uint32_t a2, uint32_t a3, uint64_t db, int sd){
  asm volatile("{ .reg .pred p; setp.ne.b32 p, %61, 0;\n"
   "wgmma.mma_async.sync.aligned.m64n112k16.f32.bf16.bf16 {%0, %1, %2, %3, %4, %5, %6, %7, %8, %9, %10, %11, %12, %13, %14, %15, %16, %17, %18, %19, %20, %21, %22, %23, %24, %25, %26, %27, %28, %29, %30, %31, %32, %33, %34, %35, %36, %37, %38, %39, %40, %41, %42, %43, %44, %45, %46, %47, %48, %49, %50, %51, %52, %53, %54, %55}, {%56,%57,%58,%59}, %60, p, 1, 1, 0; }\n"
   : "+f"(d[0]), "+f"(d[1]), "+f"(d[2]), "+f"(d[3]), "+f"(d[4]), "+f"(d[5]), "+f"(d[6]), "+f"(d[7]), "+f"(d[8]), "+f"(d[9]), "+f"(d[10]), "+f"(d[11]), "+f"(d[12]), "+f"(d[13]), "+f"(d[14]), "+f"(d[15]), "+f"(d[16]), "+f"(d[17]), "+f"(d[18]), "+f"(d[19]), "+f"(d[20]), "+f"(d[21]), "+f"(d[22]), "+f"(d[23]), "+f"(d[24]), "+f"(d[25]), "+f"(d[26]), "+f"(d[27]), "+f"(d[28]), "+f"(d[29]), "+f"(d[30]), "+f"(d[31]), "+f"(d[32]), "+f"(d[33]), "+f"(d[34]), "+f"(d[35]), "+f"(d[36]), "+f"(d[37]), "+f"(d[38]), "+f"(d[39]), "+f"(d[40]), "+f"(d[41]), "+f"(d[42]), "+f"(d[43]), "+f"(d[44]), "+f"(d[45]), "+f"(d[46]), "+f"(d[47]), "+f"(d[48]), "+f"(d[49]), "+f"(d[50]), "+f"(d[51]), "+f"(d[52]), "+f"(d[53]), "+f"(d[54]), "+f"(d[55]) : "r"(a0), "r"(a1), "r"(a2), "r"(a3), "l"(db), "r"(sd));
}
template<> __device__ __forceinline__ void wgmma_rs<128>(float (&d)[64], uint32_t a0, uint32_t a1, uint32_t a2, uint32_t a3, uint64_t db, int sd){
  asm volatile("{ .reg .pred p; setp.ne.b32 p, %69, 0;\n"
   "wgmma.mma_async.sync.aligned.m64n128k16.f32.bf16.bf16 {%0, %1, %2, %3, %4, %5, %6, %7, %8, %9, %10, %11, %12, %13, %14, %15, %16, %17, %18, %19, %20, %21, %22, %23, %24, %25, %26, %27, %28, %29, %30, %31, %32, %33, %34, %35, %36, %37, %38, %39, %40, %41, %42, %43, %44, %45, %46, %47, %48, %49, %50, %51, %52, %53, %54, %55, %56, %57, %58, %59, %60, %61, %62, %63}, {%64,%65,%66,%67}, %68, p, 1, 1, 0; }\n"
   : "+f"(d[0]), "+f"(d[1]), "+f"(d[2]), "+f"(d[3]), "+f"(d[4]), "+f"(d[5]), "+f"(d[6]), "+f"(d[7]), "+f"(d[8]), "+f"(d[9]), "+f"(d[10]), "+f"(d[11]), "+f"(d[12]), "+f"(d[13]), "+f"(d[14]), "+f"(d[15]), "+f"(d[16]), "+f"(d[17]), "+f"(d[18]), "+f"(d[19]), "+f"(d[20]), "+f"(d[21]), "+f"(d[22]), "+f"(d[23]), "+f"(d[24]), "+f"(d[25]), "+f"(d[26]), "+f"(d[27]), "+f"(d[28]), "+f"(d[29]), "+f"(d[30]), "+f"(d[31]), "+f"(d[32]), "+f"(d[33]), "+f"(d[34]), "+f"(d[35]), "+f"(d[36]), "+f"(d[37]), "+f"(d[38]), "+f"(d[39]), "+f"(d[40]), "+f"(d[41]), "+f"(d[42]), "+f"(d[43]), "+f"(d[44]), "+f"(d[45]), "+f"(d[46]), "+f"(d[47]), "+f"(d[48]), "+f"(d[49]), "+f"(d[50]), "+f"(d[51]), "+f"(d[52]), "+f"(d[53]), "+f"(d[54]), "+f"(d[55]), "+f"(d[56]), "+f"(d[57]), "+f"(d[58]), "+f"(d[59]), "+f"(d[60]), "+f"(d[61]), "+f"(d[62]), "+f"(d[63]) : "r"(a0), "r"(a1), "r"(a2), "r"(a3), "l"(db), "r"(sd));
}

#define BAR(i) (bars + 8u * (uint32_t)(i))

template <int G> __device__ __forceinline__ void conv_frags(uint32_t (&a)[12], uint32_t abase) {
#pragma unroll
  for (int i = 0; i < 12; i++) a[i] = lds32(abase + (G * 4 + i / 3) * 128 + (i % 3) * 4);
}
__device__ __forceinline__ void kv_prefetch(const __nv_bfloat16* pf, int task) { prefetch_if(pf + 64 * (task & 31) * DM + 64 * (task >> 5), task < 320); }
__device__ __forceinline__ void kv_load(const Params& P, Scratch* S, int task, int tid, uint32_t (&k_)[19], uint32_t (&v_)[16], uint4& sk) {
  const int row = 64 * (task & 31) + 16 * (tid >> 5), ch = 64 * (task >> 5) + 2 * (tid & 31);
  const uint32_t* kp = (const uint32_t*)(P.k + (size_t)row * DM + ch);
  const uint32_t* vp = (const uint32_t*)(P.v + (size_t)row * DM + ch);
  const uint32_t* hp = row > 0 ? kp - 3 * (DM / 2) : S->zero;
  const int hs = row > 0 ? DM / 2 : 0;
  asm volatile("ld.global.nc.v4.u32 {%0,%1,%2,%3},[%4];" : "=r"(sk.x), "=r"(sk.y), "=r"(sk.z), "=r"(sk.w) : "l"(P.shk + ch * 4));
#pragma unroll
  for (int i = 0; i < 3; i++) k_[i] = ldg1(hp + i * hs);
#pragma unroll
  for (int i = 0; i < 16; i++) { k_[i + 3] = ldg1(kp + i * (DM / 2)); v_[i] = ldg1(vp + i * (DM / 2)); }
}
template <int SH> __device__ __forceinline__ void xb_prefetch(const Head& H, int id, int tid, int c0) {
  const int ri = tid >> SH, rr = 11 * id + ri - 16;
  const __nv_bfloat16* p = ri < 16 ? H.x + (size_t)(16 * min(id, 127) + ri) * DM : (rr < DM ? H.b0 : H.b1 - DM * DM) + (size_t)rr * DM;
  prefetch_if(p + c0 + 64 * (tid & ((1 << SH) - 1)), ri < 16 || (ri < 27 && rr < 2 * DM));
}
__device__ __forceinline__ uint4 ldg4(const void* p) { uint4 v; asm volatile("ld.global.nc.v4.u32 {%0,%1,%2,%3},[%4];" : "=r"(v.x), "=r"(v.y), "=r"(v.z), "=r"(v.w) : "l"(p)); return v; }
__device__ __forceinline__ uint4 lds4(uint32_t a) { uint4 v; asm volatile("ld.shared.v4.u32 {%0,%1,%2,%3},[%4];" : "=r"(v.x), "=r"(v.y), "=r"(v.z), "=r"(v.w) : "r"(a) : "memory"); return v; }
__device__ __forceinline__ void discretise(const Head& H, const Params& P, uint32_t sb, Role R, int lane, uint32_t e1) {
  const uint32_t dn = __ldg((const unsigned short*)P.ssmd + min(conv_ch(R.c, (lane + 7) & 7), DM - 1));
  const int c = 32 * min(R.cb(), 9) + lane;
  const uint32_t lr2 = ldg1(P.lre + 2 * c), li2 = ldg1(P.lim + 2 * c), ld2 = ldg1(P.ldt + 2 * c);
  asm volatile("st.shared.u32 [%0],%1;" ::"r"(sb + MISC_OFF + 4 * (lane & 7)), "r"((lane & 7) ? dn : e1) : "memory");
#pragma unroll 1
  for (int i = 0; i < 2; i++) {
    const float lr = bf_hi(lr2 << (16 - 16 * i)), li = bf_hi(li2 << (16 - 16 * i));
    const float2 lb = lam_bar(lr, li, bf_hi(ld2 << (16 - 16 * i)));
    const float nx = lb.x - 1.f, ny = lb.y, inv = 2.f * frcp(lr * lr + li * li), cx = (nx * lr + ny * li) * inv, cy = (ny * lr - nx * li) * inv;
    const bool sw = !H.swap;
    asm volatile("st.shared.v4.f32 [%0],{%1,%2,%3,%4};" ::"r"(sb + LAM_OFF + 32 * lane + 16 * i), "f"(lb.x), "f"(sw ? -lb.y : lb.y), "f"(sw ? -cy : cx), "f"(sw ? cx : -cy) : "memory");
  }
  __syncwarp();
}
__device__ __forceinline__ void aux_prep(const Head& H, const Params& P, uint32_t sb, Role R, int tid, long long t_start) {
  Scratch* const S = H.s;
  const uint32_t bars = sb + BAR_OFF;
  tid = opaque(tid);
  const int w = tid >> 5, lane = tid & 31, tb = R.tb(), cb = R.cb();
  uint32_t k_[19], v_[16];
  uint4 sk;
  int task = R.b() < R.nprep() ? R.b() : 320;
  delay(KVDLY);
  PROFC(tid == 0, 345);
  kv_load(P, S, min(task, 319), tid, k_, v_, sk);
  const __nv_bfloat16* pf = (tid < 64 ? P.k : P.v) + (tid & 63) * DM;
  const int j = lane >> 3, sm = min(R.sm(), 9), trow = 160 * tb + 4 * sm + (tb < 12 ? 40 : 32) * w + j;
  const uint32_t so = sb + (2 * w + (j & 1) + 8 * (j >> 1)) * 128 + 16 * (lane & 7), xo = so + sm * 2048, wo = so + (tb & 1) * 8192 + (tb & 6) * 1024;
  const __nv_bfloat16* xp = H.x + (size_t)min(trow, SEQ - 1) * DM + 384 + 8 * (lane & 7);
  const __nv_bfloat16* bp = (j < 2 ? H.b0 : H.b1) + (size_t)(64 * cb + 32 * (tb & 1) + 4 * (tb & 6) + 2 * w + (j & 1)) * DM + 384 + 8 * (lane & 7);
  float s = 0.f, s2 = 0.f, sr = 0.f;
#define STAT(m, n) { const uint32_t xw[4] = {m.x, m.y, m.z, m.w}, bw[4] = {n.x, n.y, n.z, n.w}; \
  _Pragma("unroll") for (int i = 0; i < 4; i++) { const float u = bf_lo(xw[i]), v = bf_hi(xw[i]); s += u + v; s2 = fmaf(u, u, fmaf(v, v, s2)); sr += bf_lo(bw[i]) + bf_hi(bw[i]); } }
#define STATS(K0, K1) _Pragma("unroll 1") for (int kb = K0; kb < K1; kb++) { \
    mbar_wait(BAR(B_F1 + kb)); \
    const uint4 a = lds4(xo + ((uint32_t)(XTAB0 >> (6 * kb)) & 63) * 4096), c = lds4(wo + ((uint32_t)(WTAB0 >> (6 * kb)) & 63) * 4096); \
    STAT(a, c) \
    asm volatile("" : "+f"(s), "+f"(s2), "+f"(sr)); \
    if (XPFAT >= K0 && XPFAT < K1) prefetch_if(((lane & 4) ? bp : xp) + 64 * (lane & 3), kb == XPFAT); \
    kv_prefetch(pf, kb == KPFAT ? task + R.nprep() : kb == KPFAT2 ? task + 2 * R.nprep() : 320); \
  } \
  __syncwarp(); mbar_arrive_if(BAR(B_AX + K0 / 3), lane == 0);
  STATS(0, 3)
  PROFC(tid == 0, 349);
    {
      uint4 m[4], n[4];
#pragma unroll
      for (int i = 0; i < 4; i++) { m[i] = ldg4(xp + 64 * i); n[i] = ldg4(bp + 64 * i); }
      STATS(3, 6)
      PROFC(tid == 0, 346);
      mbar_wait(BAR(B_LM));
      const uint32_t tag = lds32(sb + MISC_OFF) & 1;
#pragma unroll
      for (int i = 0; i < 4; i++) { const uint4 a = m[i], c = n[i]; STAT(a, c) }
      PROFC(tid == 0 && s2 != 1.2345f, 347);
#pragma unroll
      for (int o = 1; o <= 4; o <<= 1) { s += __shfl_xor_sync(0xffffffff, s, o); s2 += __shfl_xor_sync(0xffffffff, s2, o); sr += __shfl_xor_sync(0xffffffff, sr, o); }
      const float mn = s * (1.f / DM), rs = frcp(bf_rn(fsqrt(bf_rn(bf_rn(fmaxf(s2 * (1.f / DM) - mn * mn, 0.f)) + 1e-5f))));
      asm volatile("{ .reg .pred p; setp.ne.u32 p, %2, 0; @p st.relaxed.gpu.global.u32 [%0],%1; }"
                   ::"l"((uint32_t*)(S->RS + (8 * cb + 4 * (tb & 1) + (tb >> 1)) * 16 + 4 * w + (j & 1)) + (lane & 4) + (j >> 1)), "r"(tagf(sr, tag)),
                   "r"((uint32_t)(tb < 8 && (lane & 3) == 0)) : "memory");
      asm volatile("{ .reg .pred p; setp.ne.u32 p, %3, 0; @p st.relaxed.gpu.global.v2.u32 [%0],{%1,%2}; }"
                   ::"l"(S->S + trow), "r"(tagf(rs, tag)), "r"(tagf(-bf_rn(mn) * rs, tag)), "r"((uint32_t)(R.sm() < 10 && (lane & 7) == 0)) : "memory");
      PROFC(tid == 0, 3);
    }
#pragma unroll 1
  for (int r = 0; task < 320; r++) {
    {
      const uint32_t T0 = __byte_perm(sk.x, sk.z, 0x5410), T1 = __byte_perm(sk.x, sk.z, 0x7632);
      const uint32_t T2 = __byte_perm(sk.y, sk.w, 0x5410), T3 = __byte_perm(sk.y, sk.w, 0x7632);
      PROFC(tid == 0 && v_[15] != 0x12345, 336 + r);
      uint32_t o[16];
#pragma unroll
      for (int t = 0; t < 16; t += 2) {
        const uint32_t a = hmul2(hfma2(k_[t + 3], T0, hfma2(k_[t + 2], T1, hfma2(k_[t + 1], T2, hmul2(k_[t], T3)))), v_[t]);
        const uint32_t c = hmul2(hfma2(k_[t + 4], T0, hfma2(k_[t + 3], T1, hfma2(k_[t + 2], T2, hmul2(k_[t + 1], T3)))), v_[t + 1]);
        const int wd = ((7 - t / 2) >> 1) + 4 * ((7 - t / 2) & 1);
        o[wd] = __byte_perm(c, a, 0x5410); o[8 + wd] = __byte_perm(c, a, 0x7632);
        asm volatile("" : "+r"(o[wd]), "+r"(o[8 + wd]));
        if (t == PFAT) kv_prefetch(pf, task + (1 + PFD) * R.nprep());
      }
      PROFC(tid == 0, 330 + 2 * r);
      const int ph = task & 1;
      task += R.nprep();
      if (ORD == 0 && task < 320) kv_load(P, S, task, tid, k_, v_, sk);
      mbar_wait(BAR(B_E1 + 3)); mbar_wait(BAR(B_AX + 1));
#pragma unroll
      for (int i = 0; i < 4; i++) {
        const int row = 2 * lane + (i >> 1);
        asm volatile("st.shared.v4.u32 [%0],{%1,%2,%3,%4};" ::"r"(sb + KS_OFF + r * 8192 + row * 128 + (((2 * w + ((i & 1) ^ ph)) ^ (row & 7)) << 4)),
                     "r"(o[4 * i]), "r"(o[4 * i + 1]), "r"(o[4 * i + 2]), "r"(o[4 * i + 3]) : "memory");
      }
      __syncwarp();
      mbar_arrive_if(BAR(B_PS + r), lane == 0);
      PROFC(tid == 0, 331 + 2 * r);
      if (ORD == 1 && task < 320) kv_load(P, S, task, tid, k_, v_, sk);
    }
  }
#undef STAT
#undef STATS
  PROFC(tid == 0, 40);
}
#define SPLIT(G) asm volatile("{ .reg .pred p; .reg .u32 r; L: mov.u32 r, %%clock; setp.eq.u32 p, r, %0; @p bra.uni L; }" ::"n"(G) : "memory")
template <bool AUX>
__device__ __forceinline__ void conv_loop(uint32_t sb, uint32_t rc, int wg, int tid, long long t_start) {
  sb = opaque(sb); rc = opaque(rc);
  const uint32_t bars = sb + BAR_OFF;
  int slot = AUX ? 0 : wg + 1;
  mbar_wait(BAR(B_LM));
#pragma unroll 1
  while (slot < (int)((rc >> 10) & 7)) {
    tid = opaque(tid);
    const int w = tid >> 5, lane = tid & 31, g = lane >> 2, q = lane & 3;
    const uint32_t Dn = lds32(sb + MISC_OFF + 4 + 4 * slot);
    const uint32_t d0 = (g == 1 && q == 3 - w) ? Dn : 0, d1 = (g == 0 && q == 3 - w) ? Dn : 0;
    const uint32_t cb_ = conv_buf(sb, slot), c0 = cb_ + KC_OFS;
    const uint32_t abase = c0 + 2 * (2 * (g & 1) + 4 * w + 16 * (g >> 1) + 4 * q);
    const uint64_t bd = make_desc(cb_ + KV_PAD, 16, 256, 3);
    const bool hi = lane & 16, s1 = lane & 8;
    const int qo = hi ? (q + 1) & 3 : q;
    const int srcA = hi ? (lane & 12) | ((q + 1) & 3) : (lane & 12) | 16 | ((q + 3) & 3);
    const bool h3 = hi && q == 3, wrap = s1 && qo == 3, back = wrap && hi;
    const bool chi = wrap ? !hi : hi;
    const int cq = s1 ? (qo + 1) & 3 : qo;
    const int srcB = (lane & 4) | (s1 ? 0 : 8) | (chi ? 16 | ((cq + 3) & 3) : cq);
    const uint32_t gp = c0 + 16 * (2 * (g & 1) + 4 * w) + (chi ? 256 : 0) + 2 * (2 * cq + (s1 ? 0 : 1));
    uint32_t a[12], f[16], o[8];
    float S[4], T[4], U[2], keep[2], pv[2] = {0.f, 0.f}, pr[4] = {0.f, 0.f, 0.f, 0.f};
    float e0[64], e1[56], e2[48], e3[40], e4[32], e5[24], e6[16], e7[8];
#define UNR _Pragma("unroll")
#define PERM() UNR for (int i = 0; i < 4; i++) { f[4 * i] = __byte_perm(a[3 * i], a[3 * i + 1], 0x5432); f[4 * i + 1] = a[3 * i + 1]; \
                                                 f[4 * i + 2] = __byte_perm(a[3 * i + 1], a[3 * i + 2], 0x5432); f[4 * i + 3] = a[3 * i + 2]; }
#define MMA(N, E) UNR for (int i = 0; i < 4; i++) wgmma_rs<N>(E, f[4 * i], f[4 * i + 1], f[4 * i + 2], f[4 * i + 3], bd - 8 * i, 1); wg_commit();
#define L1(c) UNR for (int i = 0; i < 4; i++) { const float ev = c[i], od = c[4 + i]; S[i] = hi ? (h3 ? ev : od) : ev; \
                                                T[i] = __shfl_sync(0xffffffff, hi ? (h3 ? pr[i] : ev) : od, srcA); pr[i] = od; }
#define L1E() UNR for (int i = 0; i < 4; i++) S[i] += T[i];
#define L2() UNR for (int h = 0; h < 2; h++) { keep[h] = back ? pv[h] : S[2 * h + 1]; pv[h] = S[2 * h + 1]; U[h] = __shfl_sync(0xffffffff, S[2 * h], srcB); }
#define L2E(j) o[j] = pack_bf(keep[0] + U[0], keep[1] + U[1]);
#define GRP(G, N, P, E) UNR for (int i = 0; i < N / 2; i++) asm volatile("mov.b32 %0,%1;" : "=f"(E[i]) : "f"(P[i + 8])); \
    wg_fence(); if (G < 7) conv_frags<(G + 1) & 7>(a, abase); if (G >= 2) { L2() } L1(P) MMA(N, E) SPLIT(G); \
    if (G < 7) { PERM() } if (G >= 2) { L2E((G + 6) & 7) } L1E() wg_wait<0>(); fence_regs(E);
    PROFC(tid == 0, 300 + 4 * slot);
    mbar_wait(BAR(B_KF + slot));
    PROFC(tid == 0, 301 + 4 * slot);
    conv_frags<0>(a, abase);
    wg_fence();
    wgmma_rs<128>(e0, d0 << 16, d0, d1 << 16, d1, bd, 0);
    PERM() conv_frags<1>(a, abase); wg_fence(); MMA(128, e0) SPLIT(0); PERM() wg_wait<0>(); fence_regs(e0);
    GRP(1, 112, e0, e1) GRP(2, 96, e1, e2) GRP(3, 80, e2, e3) GRP(4, 64, e3, e4) GRP(5, 48, e4, e5) GRP(6, 32, e5, e6) GRP(7, 16, e6, e7)
    PROFC(tid == 0, 302 + 4 * slot);
    L2() L1(e7) L2E(6) L1E() L2() L2E(7)
    bar_sync(wg + 1, 128);
#pragma unroll
    for (int jj = 0; jj < 8; jj++)
      asm volatile("st.shared.u16 [%0],%1; st.shared.u16 [%0+16],%2;" ::"r"(gp + jj * 512), "h"((uint16_t)o[jj]), "h"((uint16_t)(o[jj] >> 16)) : "memory");
#undef PERM
#undef MMA
#undef L1
#undef L1E
#undef L2
#undef L2E
#undef GRP
    PROFC(tid == 0, 303 + 4 * slot);
    __syncwarp();
    if (lane == 0) mbar_arrive(BAR(B_GS + slot));
    if (!AUX) break;
    slot = slot ? slot + 1 : 3;
  }
}

#define IDX(J, c, h) (8 * (J) + 4 * ((c) >> 1) + 2 * (h) + ((c) & 1))
__device__ __forceinline__ uint2 lds2(uint32_t a) { uint2 v; asm volatile("ld.shared.v2.u32 {%0,%1},[%2];" : "=r"(v.x), "=r"(v.y) : "r"(a) : "memory"); return v; }
__device__ __forceinline__ void resid_load(float (&r)[40], uint32_t sb, int wg, int tid, const uint4& s) {
  const uint32_t dp = sb + XR_OFF + 8 * (tid & 3), xp = dp + (64 * wg + 16 * (tid >> 5) + ((tid & 31) >> 2)) * 160;
#pragma unroll
  for (int J = 0; J < 5; J++) {
    const uint2 u = lds2(xp + 32 * J), v = lds2(xp + 32 * J + 1280), d = lds2(dp + 20480 + 32 * J);
    r[8 * J] = __uint_as_float(u.x); r[8 * J + 1] = __uint_as_float(u.y); r[8 * J + 2] = __uint_as_float(v.x); r[8 * J + 3] = __uint_as_float(v.y);
    r[8 * J + 4] = __uint_as_float(d.x); r[8 * J + 5] = __uint_as_float(d.y);
  }
  r[30] = untag(s.x); r[31] = untag(s.y); r[38] = untag(s.z); r[39] = untag(s.w);
}
__device__ __forceinline__ void resid_init(float (&r)[40]) {
  const float s[4] = {r[30], r[31], r[38], r[39]};
#pragma unroll
  for (int J = 0; J < 5; J++) {
    uint32_t w[6];
#pragma unroll
    for (int i = 0; i < 6; i++) w[i] = __float_as_uint(r[8 * J + i]);
#pragma unroll
    for (int i = 0; i < 4; i++) {
      const int h = i >> 1, c = 2 * (i & 1);
      const float rs = s[2 * h], nm = s[2 * h + 1], x0 = bf_lo(w[i]), x1 = bf_hi(w[i]);
      const uint32_t t = hmul2(pack_bf(fmaf(x0, rs, nm), fmaf(x1, rs, nm)), w[4 + (i & 1)]);
      r[IDX(J, c, h)] = x0 + bf_lo(t); r[IDX(J, c + 1, h)] = x1 + bf_hi(t);
    }
  }
}

__device__ __forceinline__ float flip(float v, uint32_t m) { return __uint_as_float(__float_as_uint(v) ^ m); }
__device__ __forceinline__ void g1_phase(const int LY, const Head& H, uint32_t sb, int wg, int tid, Role R, float (&xr)[40], long long t_start) {
  Scratch* const S = H.s;
  tid = opaque(tid); sb = opaque(sb); R.v = opaque(R.v);
  const uint32_t bars = sb + BAR_OFF;
  const int cb = R.cb(), tb = R.tb();
  const int w = tid >> 5, lane = tid & 31, g = lane >> 2, q = lane & 3;
  const bool full = tb < 12;
  uint2* Eb = S->E + ((LY * 130 + cb) * 8 + 4 * wg + w) * 16 + g;
  float a[80];
#pragma unroll
  for (int i = 0; i < 80; i++) a[i] = 0.f;
  uint32_t rel = mapa(BAR(B_E1), lane ? R.wpart() : R.ubase() + (w & (R.ugs() - 1)));
  const bool rels = lane == 0 || (tid == 1 && wg != R.wlo());
  {
    uint64_t tw = LY ? WTAB1 : WTAB0, tx = LY ? XTAB1 : XTAB0;
    uint32_t bf = BAR(B_F1);
    if (tid == 0 && wg == 0 && !LY) PROF(351);
    fence_regs(a);
    mbar_wait(bf, LY);
    if (tid == 0 && wg == 0) PROF(LY ? 20 : 4);
#pragma unroll 1
    for (int kb = 0; kb < 10; kb++) {
      const uint64_t da = make_desc(sb + ((uint32_t)tw & 63) * 4096 + wg * 8192, 16, 1024, 1);
      const uint64_t db = make_desc(sb + ((uint32_t)tx & 63) * 4096, 16, 1024, 1);
      wg_fence();
#pragma unroll
      for (int kk = 0; kk < 4; kk++) wgmma_ss160(a, da + 2 * kk, db + 2 * kk, 1);
      wg_commit();
      wg_wait<1>();
      if (kb > 0) { if (rels) mbar_arrive_at(rel); rel += 8; }
      bf += 8; tw >>= 6; tx >>= 6;
      if (kb < 9) mbar_wait(bf, LY);
    }
  }
  if (tid == 0 && wg == 0) PROF(LY ? 19 : 2);
  mbar_wait(BAR(B_LM));
  const uint32_t tag = lds32(sb + MISC_OFF) & 1;
  if (q == 3) st_rlx2(Eb + tb * 1280, tag ^ 1, tag ^ 1);
  float2 lam, mu, mu2;
  float rs0, rs1;
  const uint32_t lamp = sb + LAM_OFF + 16 * (32 * wg + 8 * w + g);
  {
    const uint2* rp = S->RS + (8 * cb + 4 * wg + w) * 16 + 2 * g - (g & 1);
    uint2 v = ld_rlx2(rp);
    asm volatile("ld.shared.v2.f32 {%0,%1},[%2];" : "=f"(lam.x), "=f"(lam.y) : "r"(lamp));
    const float2 l2 = cmul(lam, lam), l4 = cmul(l2, l2), l8 = cmul(l4, l4), l16 = cmul(l8, l8), l32 = cmul(l16, l16);
    mu = full ? cmul(l32, l8) : l32; mu2 = cmul(mu, mu);
#pragma unroll 1
    for (int it = 0; it < SPIN && __any_sync(0xffffffff, untagged(v, tag)); it++) v = ld_rlx2(rp);
    rs0 = untag(v.x); rs1 = untag(v.y);
  }
  if (tid == 0 && wg == 0 && !LY) PROF(39);
  mbar_wait(BAR(B_ST), LY);
  const uint32_t ssm = sb + SSM_OFF + q * (full ? 336 : 272);
  wg_wait<0>(); fence_regs(a);
  if (rels) mbar_arrive_at(rel);
  if (tid == 0 && wg == 0) PROF(LY ? 21 : 5);
  float2 p = make_float2(0.f, 0.f);
#pragma unroll
  for (int j = 0; j < 20; j++) {
    if (j < 16 || full) {
      float4 sv;
      asm volatile("ld.shared.v4.f32 {%0,%1,%2,%3},[%4];" : "=f"(sv.x), "=f"(sv.y), "=f"(sv.z), "=f"(sv.w) : "r"(ssm + 16 * j));
#pragma unroll
      for (int e = 0; e < 2; e++) {
        const int o = 4 * j + e;
        const float r = e ? sv.z : sv.x, nm = e ? sv.w : sv.y;
        a[o] = fmaf(a[o], r, nm * rs0); a[o + 2] = fmaf(a[o + 2], r, nm * rs1);
        p = cfma(lam, p, make_float2(a[o], a[o + 2]));
      }
    }
  }
  {
    float2 t = make_float2(__shfl_up_sync(0xffffffff, p.x, 1, 4), __shfl_up_sync(0xffffffff, p.y, 1, 4));
    if (q >= 1) p = cfma(mu, t, p);
    t = make_float2(__shfl_up_sync(0xffffffff, p.x, 2, 4), __shfl_up_sync(0xffffffff, p.y, 2, 4));
    if (q >= 2) p = cfma(mu2, t, p);
  }
  if (q == 3 && full) st_rlx2(Eb + tb * 1280, tagf(p.x, tag), tagf(p.y, tag));
  if (tid == 0 && wg == 1) PROF(96 + 64 * LY);
  uint2 ev[3];
#pragma unroll
  for (int i = 0; i < 3; i++) { const int j = tb - 1 - q - 4 * i; ev[i] = j >= 0 ? ld_rlx2(Eb + j * 1280) : make_uint2(tag, tag); }
  float2 x = make_float2(__shfl_up_sync(0xffffffff, p.x, 1, 4), __shfl_up_sync(0xffffffff, p.y, 1, 4));
  if (q == 0) x = make_float2(0.f, 0.f);
  float c0, c1;
  asm volatile("ld.shared.v2.f32 {%0,%1},[%2+8];" : "=f"(c0), "=f"(c1) : "r"(lamp));
  const float c2 = -flip(c1, H.swap), c3 = flip(c0, H.swap);
#pragma unroll
  for (int i = 0; i < 40; i++) {
    const int o = 4 * (i >> 1) + (i & 1);
    const float u = a[o], v = a[o + 2];
    a[o] = fmaf(c0, u, c1 * v); a[o + 2] = fmaf(c2, u, c3 * v);
  }
  fence_regs(a);
  if (LY == 0 && R.b() < 128) {
    const int t0 = 16 * g + 8 * wg + 2 * w;
    mbar_wait(BAR(B_XR));
    uint4 s = lds4(sb + XR_OFF + 20480 + 256 + 8 * t0);
    if (__any_sync(0xffffffff, untagged(s, tag))) {
#pragma unroll 1
      for (int it = 0; it < SPIN; it++) { s = ld_rlx4(S->S + 128 * (R.b() >> 3) + t0); if (!__any_sync(0xffffffff, untagged(s, tag))) break; }
    }
    resid_load(xr, sb, wg, tid, s);
  }
  float2 mq, om4, fq;
  {
    asm volatile("" : "+f"(lam.x), "+f"(lam.y));
    const float2 one = make_float2(1.f, 0.f), l2 = cmul(lam, lam), l4 = cmul(l2, l2), l8 = cmul(l4, l4), l16 = cmul(l8, l8);
    const float2 l80 = full ? mu2 : cmul(mu2, l16), om = cmul(l80, l80), om2 = cmul(om, om);
    mq = cmul((q & 1) ? mu : one, (q & 2) ? mu2 : one);
    om4 = cmul(om2, om2); fq = cmul((q & 1) ? om : one, (q & 2) ? om2 : one);
  }
  mbar_wait(BAR(B_E1 + 9), LY);
#pragma unroll 1
  for (int it = 0; it < SPIN; it++) {
    const bool m0 = untagged(ev[0], tag), m1 = untagged(ev[1], tag), m2 = untagged(ev[2], tag);
    if (!__any_sync(0xffffffff, m0 || m1 || m2)) break;
    if (m0) ev[0] = ld_rlx2(Eb + (tb - 1 - q) * 1280);
    if (m1) ev[1] = ld_rlx2(Eb + (tb - 5 - q) * 1280);
    if (m2) ev[2] = ld_rlx2(Eb + (tb - 9 - q) * 1280);
  }
  if (tid == 0 && wg == 1) PROF(97 + 64 * LY);
  float2 c = make_float2(untag(ev[2].x), untag(ev[2].y));
#pragma unroll
  for (int i = 1; i >= 0; i--) c = cfma(om4, c, make_float2(untag(ev[i].x), untag(ev[i].y)));
  c = cmul(fq, c);
#pragma unroll
  for (int s = 1; s <= 2; s <<= 1) { c.x += __shfl_xor_sync(0xffffffff, c.x, s); c.y += __shfl_xor_sync(0xffffffff, c.y, s); }
  c = cfma(mq, c, x);
  float2 z = make_float2(fmaf(c0, c.x, c1 * c.y), fmaf(c2, c.x, c3 * c.y));
  if (tid == 0 && wg == 0) PROF(LY ? 22 : 6);
  const float2 lc = make_float2(lam.x, flip(lam.y, H.swap));
  const uint32_t hq = sb + (lane >> 4) * 1024 + (lane & 7) * 128 + (((4 * wg + w) ^ (lane & 7)) << 4);
  const uint32_t hp = hq + R_OFF + (lane & 8) * 2048, hp4 = hq + (LY ? R4_OFF1 : R4_OFF0) + (lane & 8) * 512;
#pragma unroll
  for (int j = 0; j < 20; j += 2) {
    if (j < 16 || full) {
      uint32_t o[4];
#pragma unroll
      for (int i = 0; i < 2; i++) {
        const float2 z0 = cfma(lc, z, make_float2(a[4 * (j + i)], a[4 * (j + i) + 2]));
        z = cfma(lc, z0, make_float2(a[4 * (j + i) + 1], a[4 * (j + i) + 3]));
        o[2 * i] = pack_bf(z0.x, z.x); o[2 * i + 1] = pack_bf(z0.y, z.y);
      }
      asm volatile("stmatrix.sync.aligned.m8n8.x4.trans.shared.b16 [%0], {%1,%2,%3,%4};" ::"r"(j < 16 ? hp + j * 1024 : hp4 + (j - 16) * 1024), "r"(o[0]), "r"(o[1]), "r"(o[2]), "r"(o[3]) : "memory");
      if (j & 2) { __syncwarp(); if (lane == 0) mbar_arrive(BAR(B_SH + j / 4)); }
    }
  }
  if (tid == 0 && wg == 0) PROF(LY ? 23 : 7);
}

__device__ __forceinline__ void gate_load(uint32_t (&G)[20], uint32_t sb, int LY, int wg, int tid) {
  const uint32_t bars = sb + BAR_OFF;
  const int lane = tid & 31, w = tid >> 5;
  mbar_wait(BAR(B_GF), LY);
  __syncwarp();
  {
    const uint32_t gb = sb + (LY ? G_OFF1 : G_OFF0) + wg * 10240;
    const int dr = 4 * ((lane & 7) >> 1) + (lane & 1) + 2 * ((lane >> 3) & 1), ck = 2 * w + (lane >> 4);
#pragma unroll
    for (int J = 0; J < 5; J++) {
      const int dd = 16 * J + dr;
      asm volatile("ldmatrix.sync.aligned.m8n8.x4.trans.shared.b16 {%0,%1,%2,%3},[%4];"
                   : "=r"(G[4 * J]), "=r"(G[4 * J + 1]), "=r"(G[4 * J + 2]), "=r"(G[4 * J + 3]) : "r"(gb + dd * 128 + ((ck ^ (dd & 7)) << 4)) : "memory");
    }
  }
}
__device__ __forceinline__ void g2_phase(const int LY, const Params& P, Scratch* S, uint32_t sb, int wg, int tid, Role R, float (&xr)[40], long long t_start) {
  sb = opaque(sb);
  const uint32_t bars = sb + BAR_OFF;
  if (LY) {
    const int td = opaque(tid), b = (opaque(R.v) >> 8) & 255;
    const uint32_t tag = lds32(sb + MISC_OFF) & 1;
    const uint2* sp = S->S + 2 * SEQ + 128 * (b >> 3) + 4 * (td & 28) + 8 * wg + 2 * (td >> 5);
    if (!(R.cb() & 1)) mbar_wait(BAR(B_HD), 1);
    uint2 dl[5];
#pragma unroll
    for (int J = 0; J < 5; J++) dl[J] = __ldg((const uint2*)(P.dskip + 80 * (b & 7) + 4 * (td & 3) + 16 * J));
    uint4 sv;
#pragma unroll 1
    for (int it = 0; it < SPIN; it++) { sv = ld_rlx4(sp); if (!__any_sync(0xffffffff, untagged(sv, tag))) break; }
#pragma unroll
    for (int h = 0; h < 2; h++)
#pragma unroll
      for (int J = 0; J < 5; J++)
#pragma unroll
        for (int c = 0; c < 4; c++) {
          const float x2 = xr[IDX(J, c, h)];
          const uint32_t dw = (c & 2) ? dl[J].y : dl[J].x;
          xr[IDX(J, c, h)] = fmaf(fmaf(x2, untag(h ? sv.z : sv.x), untag(h ? sv.w : sv.y)), (c & 1) ? bf_hi(dw) : bf_lo(dw), x2);
        }
    fence_regs(xr);
  }
  float acc[40];
#pragma unroll
  for (int i = 0; i < 40; i++) acc[i] = RIAT == 1 ? 0.f : xr[i];
  fence_regs(acc);
#define G2_STEP(st, cs, hf) { \
    const uint64_t da = make_desc(sb + H_OFF + (st) * 32768 + (hf) * 16384 + wg * 8192, 16, 1024, 1), db = make_desc(sb + (cs) * 20480 + (hf) * 10240, 16, 1024, 1); \
    wg_fence(); \
    _Pragma("unroll") for (int kk = 0; kk < 4; kk++) wgmma_ss80(acc, da + 2 * kk, db + 2 * kk, 1); \
    wg_commit(); }
  mbar_wait(BAR(B_F2), LY);
  if (tid == 0 && wg == 0) PROF(LY ? 25 : 10);
  G2_STEP(0, 0, 0)
  mbar_wait(BAR(B_F3), LY);
  G2_STEP(0, 0, 1)
  tid = opaque(tid); R.v = opaque(R.v);
  const uint32_t tag = lds32(sb + MISC_OFF) & 1;
  const int b = R.b(), tb2 = b >> 3, db_ = b & 7;
  const int w = tid >> 5, lane = tid & 31, g = lane >> 2, q = lane & 3;
  const int t0 = 128 * tb2 + 16 * g + 8 * wg + 2 * w;
  const int d0 = 80 * db_ + 4 * q, mrow = 64 * wg + 16 * w + g;
#define GATE(J, c, h) (((c) & 1) ? bf_hi(G[4 * (J) + 2 * (h) + ((c) >> 1)]) : bf_lo(G[4 * (J) + 2 * (h) + ((c) >> 1)]))
  uint32_t rel = mapa(BAR(B_E2), lane ? ((w & 1) ? R.wpart() : R.rank()) : R.cs() == 8 ? 4 * wg + w : wg);
  const bool rels = lane == 0 || (lane == 1 && w < 2);
  uint32_t* Mb = S->M + ((2 * LY * 16 + tb2) * 8) * 256 + (wg * 4 + w) * 32 + (2 * g + (q & 1)) * 2 + (q >> 1);
  {
    uint32_t bf = BAR(B_F2 + 1), st = 1, ra = rel + 8 * (B_EA - B_E2);
#pragma unroll 1
    for (int kp = 1; kp < 10; kp++) {
      const bool more = LY == 0 || kp < 8;
      wg_wait<1>();
      if (lane == 0 && more) mbar_arrive_at(ra + 8 * (st ? st - 1 : 2));
      mbar_wait(bf, LY);
      G2_STEP(st, kp < 5 ? kp : kp - 5, 0)
      wg_wait<1>();
      if (rels && more) mbar_arrive_at(rel);
      rel += 8;
      mbar_wait(bf + 8 * (B_F3 - B_F2), LY);
      G2_STEP(st, kp < 5 ? kp : kp - 5, 1)
      if (kp == MIAT) {
        st_rlx(Mb + db_ * 256, tag ^ 1);
        if (LY == 0) st_rlx(Mb + (16 * 8 + db_) * 256, tag ^ 1);
      }
      bf += 8; st = st == 2 ? 0 : st + 1;
    }
  }
  wg_wait<0>(); fence_regs(acc);
  if (LY == 0 && rels) mbar_arrive_at(rel);
  if (tid == 0 && wg == 0) PROF(LY ? 26 : 11);
  if (lane == 0) PROF(116 + 64 * LY + wg * 4 + w);

  float mm[2] = {0.f, 0.f}, rr[2];
#pragma unroll 1
  for (int rep = 0;; rep++) {
    float m[2][2];
#pragma unroll
    for (int h = 0; h < 2; h++) {
      m[h][0] = m[h][1] = 0.f;
#pragma unroll
      for (int J = 0; J < 5; J++)
#pragma unroll
        for (int c = 0; c < 4; c++) { const float xv = acc[IDX(J, c, h)]; m[h][0] += xv; m[h][1] = fmaf(xv, xv, m[h][1]); }
    }
    float r1[2];
#pragma unroll
    for (int i = 0; i < 2; i++) { const float snd = (q & 1) ? m[0][i] : m[1][i], kp = (q & 1) ? m[1][i] : m[0][i]; r1[i] = kp + __shfl_xor_sync(0xffffffff, snd, 1); }
    const float r2 = ((q & 2) ? r1[1] : r1[0]) + __shfl_xor_sync(0xffffffff, (q & 2) ? r1[0] : r1[1], 2);
    st_rlx(Mb + db_ * 256, tagf(r2, tag));
    if (rep) break;
    if (lane == 0) PROF(100 + 64 * LY + wg * 4 + w);
    uint32_t G[20];
    const bool late = LY == 0 && db_ >= GLATE;
#pragma unroll
    for (int i = 0; i < 20; i++) G[i] = 0;
    if (!late) gate_load(G, sb, LY, wg, tid);
    mbar_wait(BAR(B_CD + 1));
    uint32_t mv[8];
#pragma unroll
    for (int i = 0; i < 8; i++) mv[i] = ld_rlx(Mb + i * 256);
#pragma unroll 1
    for (int it = 0; it < SPIN; it++) {
      uint32_t miss = 0;
#pragma unroll
      for (int i = 0; i < 8; i++) miss |= ((mv[i] ^ tag) & 1) << i;
      if (!__any_sync(0xffffffff, miss)) break;
#pragma unroll
      for (int i = 0; i < 8; i++) if ((miss >> i) & 1) mv[i] = ld_rlx(Mb + i * 256);
    }
    if (lane == 0) PROF(108 + 64 * LY + wg * 4 + w);
    const float s = ((untag(mv[0]) + untag(mv[1])) + (untag(mv[2]) + untag(mv[3]))) + ((untag(mv[4]) + untag(mv[5])) + (untag(mv[6]) + untag(mv[7])));
    const float o = __shfl_xor_sync(0xffffffff, s, 2);
    const float S1 = (q & 2) ? o : s, S2 = (q & 2) ? s : o;
    const float mean = S1 * (1.f / DM), rs = frsqrt(fmaxf(S2 * (1.f / DM) - mean * mean, 0.f) + 1e-5f);
    const float mo = __shfl_xor_sync(0xffffffff, mean, 1), ro = __shfl_xor_sync(0xffffffff, rs, 1);
    mm[0] = (q & 1) ? mo : mean; mm[1] = (q & 1) ? mean : mo; rr[0] = (q & 1) ? ro : rs; rr[1] = (q & 1) ? rs : ro;
    bar_sync(4, 256);
    if (late) gate_load(G, sb, LY, wg, tid);
    if (tid == 0 && wg == 0) PROF(LY ? 27 : 12);
    const float nm[2] = {-mm[0] * rr[0], -mm[1] * rr[1]};
    if (LY) mm[0] = mm[1] = 0.f;
#pragma unroll
    for (int h = 0; h < 2; h++)
#pragma unroll
      for (int J = 0; J < 5; J++)
#pragma unroll
        for (int c = 0; c < 4; c++) { const float xv = acc[IDX(J, c, h)]; acc[IDX(J, c, h)] = fmaf(fmaf(xv, rr[h], nm[h]), GATE(J, c, h), xv - mm[h]); }
    if (LY) break;
#pragma unroll
    for (int i = 0; i < 10; i++) {
      const int J = i >> 1, h = i & 1;
      const uint32_t u0 = pack_bf(acc[IDX(J, 0, h)], acc[IDX(J, 1, h)]), u1 = pack_bf(acc[IDX(J, 2, h)], acc[IDX(J, 3, h)]);
      asm volatile("st.shared.v2.u32 [%0],{%1,%2};" ::"r"(sb + US_OFF + (mrow + 8 * h) * 160 + 32 * J + 8 * q), "r"(u0), "r"(u1) : "memory");
    }
    __syncwarp();
    if (lane == 0) mbar_arrive(BAR(B_SG));
    if (tid == 0 && wg == 0) PROF(13);
    Mb += 16 * 8 * 256;
  }
  if (LY == 0) {
#pragma unroll
    for (int i = 0; i < 40; i++) xr[i] = acc[i] + mm[(i >> 1) & 1];
    if (tid == 0 && wg == 0) PROF(15);
  }
  else {
    float* op = P.out + (size_t)t0 * DM + d0;
#pragma unroll
    for (int i = 0; i < 10; i++) {
      const int J = i >> 1, h = i & 1;
      asm volatile("st.global.v4.f32 [%0],{%1,%2,%3,%4};" ::"l"(op + h * DM + 16 * J),
                   "f"(acc[IDX(J, 0, h)]), "f"(acc[IDX(J, 1, h)]), "f"(acc[IDX(J, 2, h)]), "f"(acc[IDX(J, 3, h)]) : "memory");
    }
  }
  if (tid == 0 && wg == 0 && LY) PROF(28);
#undef IDX
#undef GATE
}

__device__ __forceinline__ void next_stats(Scratch* S, uint32_t sb, int tb2, int tid) {
  const uint32_t bars = sb + BAR_OFF, tag = lds32(sb + MISC_OFF) & 1;
  const uint32_t* Mb = S->M + tb2 * 8 * 256 + 2 * tid;
  mbar_wait(BAR(B_F1 + NSAT), 1);
  float m1, s1, s2;
#pragma unroll 1
  for (int it = 0; it < SPIN; it++) {
    uint32_t a[8], miss = 0;
    uint2 v[8];
#pragma unroll
    for (int i = 0; i < 8; i++) { a[i] = ld_rlx(Mb + i * 256); v[i] = ld_rlx2((const uint2*)(Mb + (16 * 8 + i) * 256)); }
#pragma unroll
    for (int i = 0; i < 8; i++) miss |= (a[i] ^ tag) | (v[i].x ^ tag) | (v[i].y ^ tag);
#define SUM8(F) ((untag(F(0)) + untag(F(1))) + (untag(F(2)) + untag(F(3)))) + ((untag(F(4)) + untag(F(5))) + (untag(F(6)) + untag(F(7))))
#define FA(i) a[i]
#define FX(i) v[i].x
#define FY(i) v[i].y
    m1 = SUM8(FA); s1 = SUM8(FX); s2 = SUM8(FY);
    if (!__any_sync(0xffffffff, miss & 1)) break;
  }
  const float mean = s1 * (1.f / DM), rs = frsqrt(fmaxf(s2 * (1.f / DM) - mean * mean, 0.f) + 1e-5f);
  uint2* sp = S->S + SEQ + 128 * tb2 + 8 * (tid & 14) + 2 * (tid >> 4) + (tid & 1);
  st_rlx2(sp, tagf(rs, tag), tagf(-mean * rs, tag));
  st_rlx2(sp + SEQ, tagf(rs, tag), tagf(-(mean + m1 * (1.f / DM)) * rs, tag));
}
template <int I0, int I1> __device__ __forceinline__ void init_barriers(uint32_t bars) {
#pragma unroll
  for (int i = I0; i < I1; i++) mbar_init(BAR(i), bar_count(i));
}
__device__ __forceinline__ int g2_cb(int kp) { return kp < 5 ? 2 * kp : 2 * kp - 9; }
__device__ __forceinline__ const unsigned* h_flag(Scratch* S, int ly, int tb2, int lane) {
  const int s0 = 128 * min(tb2, 15) / 160;
  const bool two = (128 * tb2 + 127) / 160 != s0;
  return &S->flag[(F_H + (ly * 13 + s0) * 10 + min(lane & 15, 9) + (two && lane >= 16 ? 10 : 0)) * 32];
}
__device__ __forceinline__ void gate_tile(const Params& P, uint32_t dst, uint32_t bar, int tb2, int db) {
  mbar_expect_tx(bar, 20480);
  tma2d(dst, &P.mGT, tb2 * 128, db * 80, bar);
  tma2d(dst + 10240, &P.mGT, tb2 * 128 + 64, db * 80, bar);
}
__global__ void __cluster_dims__() __launch_bounds__(512, 1) fused_kernel(const Head H, const __grid_constant__ Params P) {
  extern __shared__ __align__(1024) uint8_t smem[];
  const uint32_t sb = opaque(smem_u32(smem)), bars = sb + BAR_OFF;
  const int wi = __shfl_sync(0xffffffff, threadIdx.x >> 5, 0), wg = wi >> 2, tid = threadIdx.x & 127;
  const int umap = blockIdx.x >= 96;
#define CLK(v)
  CLK(c_a);
  if (wi == 14) {
    if (elect_one()) { init_barriers<0, NBAR1>(bars); asm volatile("fence.mbarrier_init.release.cluster;" ::: "memory"); }
    __syncwarp();
  } else if (wi >= 12) prefetch_map(wi == 12 ? &P.mB : &P.mA[umap]);
  else if (wg == 2) xb_prefetch<1>(H, blockIdx.x + H.base, tid, 0);
  else if (P.role[blockIdx.x].w) return;
  CLK(c_b);
  asm volatile("barrier.cluster.arrive.relaxed.aligned;" ::: "memory");
  CLK(c_c);
  Role R;
  { const uint4 r = P.role[blockIdx.x]; R.v = r.x; R.c = r.y; R.p = r.z; }
  const int id = R.c & 255;
  const int tb = R.tb(), cb = R.cb(), b = R.b(), tb2 = b >> 3, db = b & 7, rank = R.rank();
  const bool has1 = tb <= 12, has2 = b < 128, full = tb < 12;
  Scratch* const S = H.s;
  unsigned* const epoch_p = &S->epoch[id * 8];
  const long long t_start = 0;
  if (wg < 2) {
    if (threadIdx.x == 0) PROF(50);
    asm volatile("griddepcontrol.launch_dependents;");
    bar_sync(6, 448);
    asm volatile("setmaxnreg.inc.sync.aligned.u32 176;");
    float xr[40];
#pragma unroll
    for (int i = 0; i < 40; i++) xr[i] = 0.f;
#pragma unroll 1
    for (int ly = 0; ly < 2; ly++) {
      if (has1) g1_phase(ly, H, sb, wg, tid, R, xr, t_start);
      if (ly == 0) {
        resid_init(xr); fence_regs(xr);
        conv_loop<false>(sb, R.c, wg, tid, t_start);
        if (tid == 0 && wg == 0) PROF(9);
      }
      if (has2) g2_phase(ly, P, S, sb, wg, tid, R, xr, t_start);
    }
    if (tid == 0 && wg == 0) st_rlx(epoch_p, lds32(sb + MISC_OFF));
  } else if (wg == 2) {
    bar_sync(6, 448);
    if (has1) aux_prep(H, P, sb, R, tid, t_start);
    asm volatile("setmaxnreg.inc.sync.aligned.u32 136;");
    conv_loop<true>(sb, R.c, wg, tid, t_start);
    if (tid == 0) PROF(44);
    {
      const uint32_t bb = (P.role[blockIdx.x].x >> 8) & 255;
      if ((bb & 132) == NSDB && tid < 32) next_stats(H.s, sb, bb >> 3, 32 * (bb & 3) + tid);
    }
  } else {
    if (threadIdx.x == 384) PROF(354);
    asm volatile("setmaxnreg.dec.sync.aligned.u32 24;");
    const int wlo = R.wlo(), whi = R.whi();
    const uint32_t wmask = R.wmask(), umask = R.umask(), f1bytes = full ? 36864 : 32768;
    if (wi < 14) {
      if (threadIdx.x == 384) PROF(340);
      asm volatile("barrier.cluster.wait.aligned;" ::: "memory");
      if (has1 && elect_one()) {
        uint64_t tab = wi == 12 ? WTAB0 : XTAB0;
        PROF(329 + wi);
#pragma unroll 1
        for (int kb = 0; kb < 6; kb++, tab >>= 6) {
          const uint32_t dst = sb + ((uint32_t)tab & 63) * 4096;
          if (wi == 12) {
#pragma unroll 1
            for (int h = wlo; h <= whi; h++) tma4d_mc(dst + h * 8192, &P.mB, kb * 64, 0, 0, 8 * cb + 4 * h, BAR(B_F1 + kb), wmask);
          } else {
            tma4d_mc(dst + R.uj() * 1024, &P.mA[umap], kb * 64, 0, 0, 80 * tb + R.uj(), BAR(B_F1 + kb), umask);
            mbar_expect_tx(BAR(B_F1 + kb), f1bytes);
          }
        }
      }
      if (!has1 && wi == 13) bar_sync(7, 64);
    } else {
      if (wi == 15 && elect_one()) { init_barriers<NBAR1, NBAR>(bars); asm volatile("fence.mbarrier_init.release.cluster;" ::: "memory"); }
      bar_sync(6, 448);
      if (!has1 && wi == 14) bar_sync(7, 64);
    }
    const unsigned e1 = ld_rlx(epoch_p) + 1;
    if (wi == 12) {
      if (elect_one()) {
#pragma unroll 1
        for (int ly = 0; ly < 2; ly++) {
#pragma unroll 1
          for (int i = ly ? 0 : 6; i < 10 && has1; i++) {
            const int kb = (0x9876541032ull >> (4 * i)) & 15;
            if (ly == 0) { mbar_wait(BAR(B_E1 + ((DEP0 >> (4 * kb - 24)) & 15))); mbar_wait(BAR(B_AX + (kb == 9))); }
            else {
              if (has2 && i == (db >= GLATE ? 4 : 2)) {
                wait_cnt(&S->cnt[(C_G + db) * 32], e1 * 80);
                mbar_wait(BAR(B_E2 + 7));
                PROF(47);
                gate_tile(P, sb + G_OFF0, BAR(B_GF), tb2, db);
              }
              if (has2) mbar_wait(BAR(i < 4 ? B_E2 + ((0x9865u >> (4 * i)) & 15) : B_GE));
              else if (i == 0) { mbar_wait(BAR(B_E1 + 9)); mbar_wait(BAR(B_CD + 1)); }
              if (i >= 4) mbar_wait(BAR(i < 6 ? B_F1 + W4AT : B_E1 + i - 6), 1);
            }
            const uint32_t dst = sb + ((uint32_t)((ly ? WTAB1 : WTAB0) >> (6 * kb)) & 63) * 4096;
#pragma unroll 1
            for (int h = wlo; h <= whi; h++) tma4d_mc(dst + h * 8192, &P.mB, kb * 64, 0, 0, 8 * cb + 4 * h, BAR(B_F1 + kb), wmask);
          }
          if (has2) {
            if (ly == 0) {
              mbar_wait(BAR(B_E1 + XRAT));
              mbar_expect_tx(BAR(B_XR), 20480 + 160 + 1024);
              tma4d(sb + XR_OFF, &P.mX, 80 * db, tb2, BAR(B_XR));
              bulk_g2s(sb + XR_OFF + 20480, P.dskip + 80 * db, 160, BAR(B_XR));
              bulk_g2s(sb + XR_OFF + 20480 + 256, S->S + 128 * tb2, 1024, BAR(B_XR));
              if (CWAIT) mbar_wait(BAR(CWAIT == 1 ? B_KF + 2 : CWAIT == 2 ? B_KF + R.nch() - 1 : CWAIT == 3 ? B_KF + R.nch() - 2 : B_HD));
            }
#pragma unroll 1
            for (int kp = 0; kp < 10; kp++) {
              const uint32_t dst = sb + (kp < 5 ? kp : kp - 5) * 20480;
              mbar_wait(BAR(kp >= 5 ? B_E2 + kp - 5 : ly ? B_E1 + ((CTAB1 >> (4 * kp)) & 15) : kp < 3 ? B_SH : kp < 4 ? B_HD : B_CD), ly);
              mbar_expect_tx(BAR(B_F2 + kp), 10240 + 16384);
              tma5d(dst, &P.mC[0], g2_cb(kp) * 64, db * 5, BAR(B_F2 + kp));
              mbar_expect_tx(BAR(B_F3 + kp), 10240 + 16384);
              tma5d(dst + 10240, &P.mC[1], g2_cb(kp) * 64, db * 5, BAR(B_F3 + kp));
              if (ly && kp == 4) { mbar_wait(BAR(B_E1 + 9), 1); gate_tile(P, sb + G_OFF1, BAR(B_GF), tb2, db); }
            }
          }
        }
      }
    } else if (wi == 13) {
      const int h0 = R.cs() == 8 ? rank : 4 * rank;
#pragma unroll 1
      for (int ly = 0; ly < 2; ly++) {
        int lane = lane_id();
        if (has1) {
          const unsigned* fp = &S->flag[(F_U3 + 8 * ((160 * tb) >> 7) + (lane & (full ? 15 : 7))) * 32];
          uint32_t ready = ly ? __ballot_sync(0xffffffff, ld_rlx(fp) == e1) : ~0u;
          if (ly) mbar_wait(BAR(has2 ? B_SG : B_RF1));
#pragma unroll 1
          for (int kb = ly ? 0 : 6; kb < 10; kb++) {
            if (ly && kb == UPAT) { mbar_wait(BAR(B_XR)); ready = ~0u; }
            wait_flags(fp, e1, 0x101u * ((1u << (64 * kb / 80)) | (1u << ((64 * kb + 63) / 80))), ready);
            if (kb >= 4) mbar_wait(BAR(B_E1 + (ly ? kb - 4 : (DEP0 >> (4 * kb - 24)) & 15)), ly);
            mbar_wait(BAR(B_AX + (kb == 9)));
            if (elect_one()) {
              if (ly && kb == 0) PROF(34);
              tma4d_mc(sb + ((uint32_t)((ly ? XTAB1 : XTAB0) >> (6 * kb)) & 63) * 4096 + R.uj() * 1024, &P.mA[2 * ly + umap], kb * 64, 0, 0, 80 * tb + R.uj(),
                       BAR(B_F1 + kb), umask);
              mbar_expect_tx(BAR(B_F1 + kb), f1bytes);
            }
            __syncwarp();
          }
        }
        if (ly == 0) {
          if (has1) mbar_wait(BAR(B_E1 + KPF));
          if (elect_one()) {
#pragma unroll 1
            for (int s = 0; s < R.nch(); s++) prefetch_l2(P.ssmk + (size_t)R.ch(s) * SEQ, 4096);
          }
          lane = lane_id();
#pragma unroll
          for (int s = 0; s < 5; s++) {
            asm volatile("st.shared.v4.u32 [%0],{%1,%1,%1,%1};" ::"r"(conv_buf(sb, s) + 16 * lane), "r"(0) : "memory");
            asm volatile("st.shared.u8 [%0],%1;" ::"r"(conv_buf(sb, s) + KC_OFS + lane), "r"(0) : "memory");
          }
          fence_async();
          __syncwarp();
          const unsigned* cp = &S->cnt[(C_KV + (R.ch(min(lane, R.nch() - 1)) >> 6)) * 32];
          uint32_t ready = 0;
#pragma unroll 1
          for (int s = 0, sk = 0; s < R.nch(); s++) {
#pragma unroll 1
            for (; sk < (s ? R.nch() : KUP); sk++)
              if (elect_one()) { mbar_expect_tx(BAR(B_KF + sk), 8192); bulk_g2s(conv_buf(sb, sk) + KC_OFS + 32, P.ssmk + (size_t)R.ch(sk) * SEQ, 4096, BAR(B_KF + sk)); }
            PROFC(s == 0, 329);
#pragma unroll 1
            for (int it = 0; !((ready >> s) & 1) && it < SPIN; it++) ready = __ballot_sync(0xffffffff, (int)(ld_rlx(cp) - e1 * 32) >= 0);
            PROFC(s == 0, 30);
            if (elect_one()) {
              bulk_g2s(conv_buf(sb, s) + KV_PAD, S->kv + (size_t)R.ch(s) * SEQ, 4096, BAR(B_KF + s));
              if (s == 0 && has2) { prefetch_l2(P.cre + (size_t)5 * b * DM, 5 * DM * 2); prefetch_l2(P.cim + (size_t)5 * b * DM, 5 * DM * 2); }
            }
            __syncwarp();
          }
          PROF(31);
          if (!has1) return;
        }
        lane = lane_id();
        const unsigned* fp = h_flag(S, ly, tb2, lane);
        uint32_t ready = __ballot_sync(0xffffffff, ld_rlx(fp) == e1), st = 0;
        if (ly == 0 && !has2) {
          mbar_wait(BAR(B_HD));
          if (lane < 8) mbar_arrive_cl(BAR(B_RF1), lane & 1);
        }
        if (has2) {
          mbar_wait(BAR(B_RF0), ly);
#pragma unroll 1
          for (int kp = 0; kp < 10; kp++) {
            if (kp == 5) { mbar_wait(BAR(B_XR), 1); ready = ~0u; }
            if (kp == 2) { mbar_wait(BAR(B_HD), ly); if (lane < 8) mbar_arrive_cl(BAR(B_RF1), lane & (R.cs() - 1)); }
            wait_flags(fp, e1, 0x10001u << g2_cb(kp), ready);
            if (kp == 2) mbar_wait(BAR(B_RF1), ly);
#pragma unroll
            for (int hf = 0; hf < 2; hf++) {
              if (kp >= 3) { if (hf) mbar_wait(BAR(B_E2 + kp - 3), ly); else mbar_wait(BAR(B_EA + st), ly ^ (kp >= 6 && kp < 9)); }
              if (elect_one()) {
                if (kp == 0 && !hf) PROF(33 + 2 * ly);
                tma4d_mc(sb + H_OFF + st * 32768 + hf * 16384 + h0 * 2048, &P.mH, g2_cb(kp) * 128 + hf * 64, 0, 2 * h0,
                         ly * 16 + tb2, BAR((hf ? B_F3 : B_F2) + kp), (1u << R.cs()) - 1);
              }
              __syncwarp();
            }
            st = st == 2 ? 0 : st + 1;
          }
        }
      }
    } else if (wi == 14) {
      if (!has1) return;
      prefetch_if(P.dskip + 64 * (tid & 31), (tid & 31) < 10);
      if (elect_one()) { prefetch_map(&P.sK); prefetch_map(&P.mX); prefetch_map(&P.sH); prefetch_map(&P.sU); prefetch_map(&P.sO); prefetch_map(&P.mC[0]); prefetch_map(&P.mC[1]); prefetch_map(&P.mH); prefetch_map(&P.mGT); prefetch_map(&P.mA[2 + umap]); }
      __syncwarp();
#pragma unroll 1
      for (int ly = 0; ly < 2; ly++) {
        if (ly) {
          mbar_wait(BAR(B_F1 + 1), 1);
          uint32_t ready = 0;
          wait_flags(&S->flag[(F_U3 + 8 * ((160 * tb) >> 7) + ((lane_id() + ly) & (full ? 15 : 7))) * 32], e1, ~0u, ready);
          if (elect_one()) mbar_arrive(BAR(B_XR));
        }
        const int lane = lane_id();
        mbar_wait(BAR(B_E1 + (ly ? STAT_AT1 : STAT_AT)), ly);
        PROFC(lane == 0 && ly == 0, 36);
        {
          const int l = lane - (full ? 0 : 16);
          const uint2* p = S->S + ly * SEQ + 160 * tb + 2 * l;
          uint4 v[3];
#pragma unroll 1
          for (int it = 0; it < SPIN; it++) {
            v[0] = ld_rlx4(p); v[1] = ld_rlx4(p + 64); v[2] = ld_rlx4(p + 96);
            const bool miss = __any_sync(0xffffffff, untagged(v[0], e1 & 1) | untagged(v[1], e1 & 1) | untagged(v[2], e1 & 1));
            PROFC(lane == 0 && ly == 0 && it == 0, 37);
            if (!miss) break;
          }
          PROFC(lane == 0 && ly == 0, 38);
#pragma unroll
          for (int i = 0; i < 3; i++) {
            const int pr = l + (i == 2 ? 48 : 32 * i);
            if (pr >= 0) asm volatile("st.shared.v4.u32 [%0],{%1,%2,%3,%4};" ::"r"(sb + SSM_OFF + 16 * (pr + ((pr * (full ? 205 : 256)) >> 12))), "r"(v[i].x & ~1u),
                                      "r"(v[i].y & ~1u), "r"(v[i].z & ~1u), "r"(v[i].w & ~1u) : "memory");
          }
          __syncwarp();
        }
        if (lane == 0) mbar_arrive(BAR(B_ST));
        if (ly && has2) {
          mbar_wait(BAR(B_E1 + 9), 1);
          if (lane < 8) mbar_arrive_cl(BAR(B_RF0), lane & (R.cs() - 1));
        }
        if (lane == 0) {
#pragma unroll 1
          for (int pc = 0; pc < (full ? 5 : 4); pc++) {
            mbar_wait(BAR(B_SH + pc), ly);
            if (pc == 0 && (cb & 1)) delay(ly ? HDLY : HDLY0);
            fence_async();
#pragma unroll
            for (int i = 0; i < 2; i++) tma4d_store(&P.sH, sb + (pc < 4 ? R_OFF + i * 16384 + pc * 4096 : (ly ? R4_OFF1 : R4_OFF0) + i * 4096), 128 * cb + 64 * i, 0, 0, ly * 1024 + 80 * tb + 4 * pc);
          }
          bulk_commit(); bulk_wait();
          PROF(ly ? 17 : 16);
          mbar_arrive(BAR(B_HD));
          release<1>();
          signal_flag(&S->flag[(F_H + (ly * 13 + tb) * 10 + cb) * 32], e1);
          PROF(ly ? 24 : 8);
        }
        __syncwarp();
        if (has2) {
          mbar_wait(BAR(B_F2 + FPAT), ly);
          uint32_t ready = 0;
          wait_flags(h_flag(S, ly, tb2, lane_id() | 1), e1, ~0u, ready);
          if (elect_one()) mbar_arrive(BAR(B_XR));
        }
        if (lane == 0 && has2 && !(ODIR && ly)) {
          mbar_wait(BAR(B_SG), ly);
          if (!(ly ? ODIR : UDIR)) {
          fence_async();
          tma4d_store(ly ? &P.sO : &P.sU, sb + (ly ? OS_OFF : US_OFF), 80 * db, 0, 0, tb2);
          bulk_commit(); bulk_wait();
          }
          if (ly == 0) { PROF(18); mbar_arrive(BAR(B_GE)); mbar_arrive_cl(BAR(B_GE), R.wpart()); release<2>(); signal_flag(&S->flag[(F_U3 + b) * 32], e1); }
          PROF(ly ? 29 : 14);
        }
        __syncwarp();
      }
    } else {
      discretise(H, P, sb, R, tid & 31, e1);
      if (elect_one()) {
        mbar_arrive(BAR(B_LM));
        PROF(348);
        if (b < R.nprep()) {
#pragma unroll 1
          for (int task = b, r = 0; task < 320; task += R.nprep(), r++) {
            mbar_wait(BAR(B_PS + r));
            PROF(320 + 3 * r);
            fence_async();
            tma2d_store(&P.sK, sb + KS_OFF + r * 8192, 64 * (task & 31), 64 * (task >> 5));
            bulk_commit(); bulk_wait();
            PROF(321 + 3 * r);
            release<4>();
            signal_cnt(&S->cnt[(C_KV + (task >> 5)) * 32], 1);
            PROF(322 + 3 * r);
          }
          PROF(41);
        }
        if (has2) {
          mbar_wait(BAR(B_SH));
#pragma unroll 1
          for (int i = 0; i < 8; i++) mbar_arrive_cl(BAR(B_RF0), i & (R.cs() - 1));
        }
#pragma unroll 1
        for (int s = 0, s0 = 0; s < R.nch(); s++) {
          mbar_wait(BAR(B_GS + s));
          fence_async();
          bulk_s2g(S->gt + (size_t)R.ch(s) * SEQ, conv_buf(sb, s) + KC_OFS, 4096); bulk_commit();
          if (s == 1 || s >= R.nch() - GSPL) bulk_wait();
          if (s == 1 || s == R.nch() - 1) mbar_arrive(BAR(B_CD + (s > 1)));
          if (s >= R.nch() - GSPL) {
            PROF(45);
            release<8>();
#pragma unroll 1
            for (; s0 <= s; s0++) signal_cnt(&S->cnt[(C_G + R.ch(s0) / 80) * 32], 1);
          }
        }
        PROF(46);
      }
    }
  }
}

typedef CUresult (*EncFn)(CUtensorMap*, CUtensorMapDataType, cuuint32_t, void*, const cuuint64_t*, const cuuint64_t*, const cuuint32_t*,
                          const cuuint32_t*, CUtensorMapInterleave, CUtensorMapSwizzle, CUtensorMapL2promotion, CUtensorMapFloatOOBfill);
bool enc(EncFn f, CUtensorMap* m, const void* base, int rank, const cuuint64_t* dims, const cuuint64_t* strides, const cuuint32_t* box, bool swz,
         bool f32 = false) {
  const cuuint32_t es[5] = {1, 1, 1, 1, 1};
  return f(m, f32 ? CU_TENSOR_MAP_DATA_TYPE_FLOAT32 : CU_TENSOR_MAP_DATA_TYPE_BFLOAT16, rank, const_cast<void*>(base), dims, strides, box, es,
           CU_TENSOR_MAP_INTERLEAVE_NONE, swz ? CU_TENSOR_MAP_SWIZZLE_128B : CU_TENSOR_MAP_SWIZZLE_NONE, CU_TENSOR_MAP_L2_PROMOTION_L2_256B,
           CU_TENSOR_MAP_FLOAT_OOB_FILL_NONE) == CUDA_SUCCESS;
}
void make_roles(Params& P, bool big) {
  for (uint32_t bx = 0; bx < (big ? 120u : 12u); bx++) {
    const uint32_t c = bx >> 3, r = bx & 7, id = big ? bx : 120 + bx;
    const uint32_t vA = c < 12 ? (2 * (c >> 1) + (r >> 2)) | (4 * (c & 1) + (r & 3)) << 4 | (r & 4) << 16 | 4 << 19 | (r ^ 4) << 22
                               : (4 * (c - 12) + (r >> 1)) | (8 + (r & 1)) << 4 | (r & 6) << 16 | 2 << 19 | (r ^ 2) << 22;
    const uint32_t vB = (bx < 10 ? 12 : 13) | bx << 4 | 2 << 19 | (bx & 1) << 22 | (bx & 1) << 26;
    P.role[bx].x = (big ? vA | r << 26 | 1u << 29 : vB) | (id < 128 ? (id & ~7u) | (r >> 1) | (r & 1) << 2 : id) << 8;
    P.role[bx].y = id | (big ? 5 : bx < 8 ? 3 : 4) << 10 | 120 << 13 | 132 << 21 | (big ? 4u : 3u) << 29;
    const uint32_t v = P.role[bx].x, cb = (v >> 4) & 15, rank = (v >> 26) & 7, ubase = (v >> 16) & 7, ugs = (v >> 19) & 7, wp = (v >> 22) & 7;
    const uint32_t wlo = rank > wp, whi = wp != rank ? wlo : 1, wmask = 1u << rank | 1u << wp;
    const uint32_t uj = (rank - ubase) * (!big ? 8 : ugs == 4 ? 5 : 10), sm = big ? (0x7296418530ull >> (4 * cb)) & 15 : bx < 8 ? 4 * (bx & 1) + (bx >> 1) : 15;
    P.role[bx].z = wlo | whi << 1 | wmask << 2 | ((1u << ugs) - 1) << (10 + ubase) | uj << 20 | sm << 25;
    P.role[bx].w = 0;
  }
}
void launch(const Head& H, const Params& P, int grid, int cs, bool dependent) {
  cudaLaunchConfig_t cfg = {};
  cfg.gridDim = grid; cfg.blockDim = 512; cfg.dynamicSmemBytes = SMEM_BYTES; cfg.stream = cudaStreamPerThread;
  cudaLaunchAttribute at[2];
  at[0].id = cudaLaunchAttributeClusterDimension; at[0].val.clusterDim.x = cs; at[0].val.clusterDim.y = 1; at[0].val.clusterDim.z = 1;
  at[1].id = cudaLaunchAttributeProgrammaticStreamSerialization; at[1].val.programmaticStreamSerializationAllowed = 1;
  cfg.attrs = at; cfg.numAttrs = dependent ? 2 : 1;
  cudaLaunchKernelEx(&cfg, fused_kernel, H, P);
}

}

extern "C" void kernel_launch(void* const* d_in, const int* in_sizes, int n_in, void* d_out, int out_size) {
  (void)in_sizes; (void)n_in; (void)out_size;
  typedef const __nv_bfloat16* cb;
  void* fp = nullptr; cudaDriverEntryPointQueryResult qr;
  cudaGetDriverEntryPoint("cuTensorMapEncodeTiled", &fp, cudaEnableDefault, &qr);
  EncFn f = (EncFn)fp;
  Scratch* sp = nullptr;
  cudaGetSymbolAddress((void**)&sp, g_scr);
  void *pu = sp->u, *ph = sp->h, *pgt = sp->gt;
  Params P;
  Head H;
  H.s = sp; H.x = (cb)d_in[0]; H.swap = (uintptr_t)d_in[4] < (uintptr_t)d_in[3] ? 0 : 0x80000000u; H.b0 = (cb)d_in[H.swap ? 3 : 4]; H.b1 = (cb)d_in[H.swap ? 4 : 3];
  for (int i = 0; i < 2; i++) {
    const cuuint64_t d[4] = {640, 8, 2, 80}, s[3] = {1280, (cuuint64_t)((uintptr_t)H.b1 - (uintptr_t)H.b0), 8 * 1280}; const cuuint32_t bx[4] = {64, 8, 2, 4};
    if (enc(f, &P.mB, H.b0, 4, d, s, bx, true)) break;
    cudaMemcpyAsync(sp->bcopy, H.b0, DM * DM * 2, cudaMemcpyDeviceToDevice, cudaStreamPerThread);
    cudaMemcpyAsync(sp->bcopy + DM * DM, H.b1, DM * DM * 2, cudaMemcpyDeviceToDevice, cudaStreamPerThread);
    H.b0 = sp->bcopy; H.b1 = sp->bcopy + DM * DM;
  }
  {
    const cuuint64_t d[5] = {640, 2, 4, 2, 40}, s[4] = {1280, 4 * 1280, 2 * 1280, 16 * 1280}; const cuuint32_t bx[5] = {64, 2, 4, 2, 5};
    enc(f, &P.mC[0], d_in[5], 5, d, s, bx, true); enc(f, &P.mC[1], d_in[6], 5, d, s, bx, true); }
  { const cuuint64_t d[2] = {2048, 640}, s[1] = {4096}; const cuuint32_t bx[2] = {64, 80}; enc(f, &P.mGT, pgt, 2, d, s, bx, true); }
  { const cuuint64_t d[4] = {640, 8, 16, 16}, s[3] = {16 * 1280, 1280, 128 * 1280}, so[3] = {16 * 2560, 2560, 128 * 2560}; const cuuint32_t bx[4] = {80, 8, 16, 1};
    enc(f, &P.sU, pu, 4, d, s, bx, false); enc(f, &P.mX, d_in[0], 4, d, s, bx, false); enc(f, &P.sO, d_out, 4, d, so, bx, false, true); }
  { const cuuint64_t d[2] = {2048, 640}, s[1] = {4096}; const cuuint32_t bx[2] = {64, 64}; enc(f, &P.sK, sp->kv, 2, d, s, bx, true); }
  P.lre = (cb)d_in[1]; P.lim = (cb)d_in[2]; P.cre = (cb)d_in[5]; P.cim = (cb)d_in[6]; P.ldt = (cb)d_in[7]; P.dskip = (cb)d_in[8];
  P.out = (float*)d_out;
  P.k = (cb)d_in[10]; P.v = (cb)d_in[11]; P.shk = (cb)d_in[12]; P.ssmk = (cb)d_in[13]; P.ssmd = (cb)d_in[14];
  cudaFuncSetAttribute(fused_kernel, cudaFuncAttributeMaxDynamicSharedMemorySize, SMEM_BYTES);
  for (int big = 1; big >= 0; big--) {
    const cuuint64_t seg = big ? 40 : 32;
    for (int i = 0; i < 4; i++) {
      const cuuint64_t d[4] = {640, 2, 4, 1024}, s[3] = {1280, seg * 1280, 2 * 1280}; const cuuint32_t bx[4] = {64, 2, 4, !big ? 8u : (i & 1) ? 10u : 5u};
      enc(f, &P.mA[i], i < 2 ? d_in[0] : pu, 4, d, s, bx, true);
    }
    {
      const cuuint64_t d[4] = {1280, 8, 16, 32}, s[3] = {16 * 2560, 2560, 128 * 2560}; const cuuint32_t bx[4] = {64, 8, big ? 2u : 8u, 1};
      enc(f, &P.mH, ph, 4, d, s, bx, true); }
    { const cuuint64_t d[4] = {1280, 2, 4, 2048}, s[3] = {2560, seg * 2560, 2 * 2560}; const cuuint32_t bx[4] = {64, 2, 4, 4};
      enc(f, &P.sH, ph, 4, d, s, bx, true); }
    make_roles(P, big);
    H.base = big ? 0 : 120;
    launch(H, P, big ? 120 : 12, big ? 8 : 2, !big);
  }
}
```

```cpp
#include <cuda_runtime.h>
#include <cuda.h>
#include <cuda_bf16.h>
#include <stdint.h>

namespace {

constexpr int SEQ = 2048, DM = 640;
constexpr int SPIN = 1 << 20;
#define PFAT 99
#define KVDLY 500
#define PFD 1
#define XPFAT 9
#define STAT_AT 6
#define KPFAT 3
#define KPFAT2 5
#define KPF 7
#define ODIR 1
#define UDIR 0
#define HDLY 1900
#define GSPL 2
#define CWAIT 0
#define HDLY0 1900
#define CTAB1 0x96543u
#define NSAT 0
#define SKW 1
#define RIAT 2
#define MIAT 5
#define FPAT 1
#define UPAT 7
#define STAT_AT1 4
#define W4AT 0
#define MBAR 1
#define XEARLY 1
#define PWG 1
#define DSM 1
#define HWM 0xc09
#define REL 1
#define NSDB 4
#define GLATE 6
#define KUP 1
#define XRAT 9
#define ORD 1

struct Scratch {
  uint2 E[2 * 13 * 10 * 8 * 16];
  uint32_t M[3 * 16 * 8 * 256];
  uint2 S[3 * SEQ];
  uint2 RS[80 * 16];
  unsigned flag[512 * 32];
  unsigned cnt[32 * 32];
  unsigned epoch[132 * 8];
  unsigned zero[128];
  unsigned prof[132 * 512];
  __align__(1024)
  __nv_bfloat16 u[SEQ * DM];
  __nv_bfloat16 h[2 * SEQ * 1280];
  __nv_bfloat16 kv[DM * SEQ];
  __nv_bfloat16 gt[DM * SEQ];
  __nv_bfloat16 bcopy[2 * DM * DM];
};
__device__ __align__(1024) Scratch g_scr;
#define PROFC(c, i) do {} while (0)
#define PSEL 1
#define PROF(i) do {} while (0)

constexpr int C_KV = 0, C_G = 10;
constexpr int F_U3 = 0, F_H = 128;

constexpr int R_OFF = 196608, R4_OFF0 = 73728, R4_OFF1 = 122880, H_OFF = 131072, KS_OFF = 131072, CV_OFF = 86272, G_OFF0 = 40960, G_OFF1 = 102400, US_OFF = 98304, OS_OFF = US_OFF + 20480, XR_OFF = 163840, MX_OFF = 32768;
constexpr int LAM_OFF = 229376, SSM_OFF = LAM_OFF + 1024, BAR_OFF = SSM_OFF + 1344;
constexpr int B_F1 = 0, B_E1 = 10, B_RF0 = 20, B_RF1 = 21, NBAR1 = 22;
constexpr int B_F2 = 22, B_KF = 32, B_GF = 37, B_CD = 38, B_XR = 40, B_ST = 41, B_HD = 42, B_LM = 43, B_E2 = 44, B_GS = 54, B_PS = 59, B_AX = 62, B_SH = 64, B_SG = 69, B_GE = 70, B_EA = 71, B_F3 = 74, NBAR = 84;
__host__ __device__ constexpr int bar_count(int i) { return i < B_E1 ? 1 : i < B_RF0 ? 9 : i < B_F2 ? 8 : i < B_E2 ? 1 : i < B_GS ? 12 : i < B_SH ? 4 : i < B_GE ? 8 : i < B_EA ? 2 : i < B_F3 ? 8 : 1; }
constexpr int MISC_OFF = BAR_OFF + NBAR * 8, SMEM_BYTES = MISC_OFF + 32;
constexpr int KV_PAD = 512, KC_OFS = KV_PAD + 4096, CH_STRIDE = 8960;
__device__ __forceinline__ uint32_t conv_buf(uint32_t sb, int slot) { return sb + CV_OFF + slot * CH_STRIDE; }
constexpr uint64_t tab6(int a, int b, int c, int d, int e, int f, int g, int h, int i, int j) {
  return (uint64_t)a | (uint64_t)b << 6 | (uint64_t)c << 12 | (uint64_t)d << 18 | (uint64_t)e << 24 | (uint64_t)f << 30 | (uint64_t)g << 36 | (uint64_t)h << 42 |
         (uint64_t)i << 48 | (uint64_t)j << 54;
}
constexpr uint64_t WTAB0 = tab6(0, 4, 8, 30, 12, 26, 0, 4, 8, 12), XTAB0 = tab6(40, 45, 50, 34, 16, 21, 40, 45, 50, 16);
constexpr uint64_t WTAB1 = tab6(16, 20, 0, 4, 8, 12, 16, 20, 24, 28), XTAB1 = tab6(40, 45, 50, 32, 40, 45, 50, 32, 40, 45);
constexpr uint32_t DEP0 = 0x4210;

struct Head {
  Scratch* s;
  const __nv_bfloat16 *x, *b0, *b1;
  uint32_t base, swap;
};
struct Params {
  const __nv_bfloat16 *lre, *lim, *ldt, *k, *v, *shk, *cre, *cim, *ssmk, *ssmd, *dskip;
  float* out;
  uint4 role[120];
  CUtensorMap mB, mA[4], mH, mC[2], mGT, mX, sH, sU, sO, sK;
};

__device__ __forceinline__ uint32_t smem_u32(const void* p) { return (uint32_t)__cvta_generic_to_shared(p); }
__device__ __forceinline__ uint32_t opaque(uint32_t x) { uint32_t y; asm volatile("mov.u32 %0, %1;" : "=r"(y) : "r"(x)); return y; }
__device__ __forceinline__ int lane_id() { int y; asm volatile("mov.u32 %0, %%laneid;" : "=r"(y)); return y; }
__device__ __forceinline__ void delay(uint32_t n) {
  asm volatile("{ .reg .pred p; .reg .u32 a, b; mov.u32 a, %%clock; L: mov.u32 b, %%clock; sub.u32 b, b, a; setp.lt.u32 p, b, %0; @p bra.uni L; }" ::"r"(n) : "memory");
}
__device__ __forceinline__ void mbar_init(uint32_t bar, uint32_t cnt) { asm volatile("mbarrier.init.shared::cta.b64 [%0], %1;" ::"r"(bar), "r"(cnt) : "memory"); }
__device__ __forceinline__ void mbar_expect_tx(uint32_t bar, uint32_t bytes) { asm volatile("mbarrier.arrive.expect_tx.shared::cta.b64 _, [%0], %1;" ::"r"(bar), "r"(bytes) : "memory"); }
__device__ __forceinline__ void mbar_arrive(uint32_t bar) { asm volatile("mbarrier.arrive.shared::cta.b64 _, [%0];" ::"r"(bar) : "memory"); }
__device__ __forceinline__ void mbar_arrive_if(uint32_t bar, bool c) {
  asm volatile("{ .reg .pred p; setp.ne.u32 p, %1, 0; @p mbarrier.arrive.shared::cta.b64 _, [%0]; }" ::"r"(bar), "r"((uint32_t)c) : "memory");
}
__device__ __forceinline__ void prefetch_if(const void* p, bool c) { asm volatile("{ .reg .pred p; setp.ne.u32 p, %1, 0; @p prefetch.global.L2 [%0]; }" ::"l"(p), "r"((uint32_t)c)); }
__device__ __forceinline__ void mbar_arrive_cl(uint32_t bar, uint32_t cta) {
  asm volatile("{ .reg .b32 ra; mapa.shared::cluster.u32 ra, %0, %1; mbarrier.arrive.shared::cluster.b64 _, [ra]; }" ::"r"(bar), "r"(cta) : "memory");
}
__device__ __forceinline__ uint32_t mapa(uint32_t a, uint32_t cta) { uint32_t r; asm("mapa.shared::cluster.u32 %0, %1, %2;" : "=r"(r) : "r"(a), "r"(cta)); return r; }
__device__ __forceinline__ void mbar_arrive_at(uint32_t ra) { asm volatile("mbarrier.arrive.shared::cluster.b64 _, [%0];" ::"r"(ra) : "memory"); }
__device__ __forceinline__ void mbar_wait(uint32_t bar, uint32_t parity = 0) {
  asm volatile("{ .reg .pred p; .reg .u32 c; mov.u32 c, 0;\n"
               "W: mbarrier.try_wait.parity.shared::cta.b64 p, [%0], %1; @p bra.uni D;\n"
               "add.u32 c, c, 1; setp.lt.u32 p, c, 0x100000; @p bra.uni W;\nD: }" ::"r"(bar), "r"(parity) : "memory");
}
__device__ __forceinline__ bool elect_one() { uint32_t p; asm volatile("{ .reg .pred P; elect.sync _|P, 0xffffffff; selp.u32 %0,1,0,P; }" : "=r"(p)); return p; }
__device__ __forceinline__ void bar_sync(int id, int n) { __syncwarp(); asm volatile("bar.sync %0, %1;" ::"r"(id), "r"(n) : "memory"); }
__device__ __forceinline__ void tma2d(uint32_t dst, const CUtensorMap* m, int c0, int c1, uint32_t bar) {
  asm volatile("cp.async.bulk.tensor.2d.shared::cluster.global.mbarrier::complete_tx::bytes [%0], [%1, {%3,%4}], [%2];"
               ::"r"(dst), "l"(m), "r"(bar), "r"(c0), "r"(c1) : "memory");
}
__device__ __forceinline__ void tma5d(uint32_t dst, const CUtensorMap* m, int c0, int c4, uint32_t bar) {
  asm volatile("cp.async.bulk.tensor.5d.shared::cluster.global.mbarrier::complete_tx::bytes [%0], [%1, {%3,%5,%5,%5,%4}], [%2];"
               ::"r"(dst), "l"(m), "r"(bar), "r"(c0), "r"(c4), "r"(0) : "memory");
}
__device__ __forceinline__ void tma4d(uint32_t dst, const CUtensorMap* m, int c0, int c3, uint32_t bar) {
  asm volatile("cp.async.bulk.tensor.4d.shared::cluster.global.mbarrier::complete_tx::bytes [%0], [%1, {%3,%5,%5,%4}], [%2];"
               ::"r"(dst), "l"(m), "r"(bar), "r"(c0), "r"(c3), "r"(0) : "memory");
}
__device__ __forceinline__ void tma4d_mc(uint32_t dst, const CUtensorMap* m, int c0, int c1, int c2, int c3, uint32_t bar, uint32_t mask) {
  asm volatile("cp.async.bulk.tensor.4d.shared::cluster.global.mbarrier::complete_tx::bytes.multicast::cluster [%0], [%1, {%3,%4,%5,%6}], [%2], %7;"
               ::"r"(dst), "l"(m), "r"(bar), "r"(c0), "r"(c1), "r"(c2), "r"(c3), "h"((uint16_t)mask) : "memory");
}
__device__ __forceinline__ void bulk_g2s(uint32_t dst, const void* src, uint32_t bytes, uint32_t bar) {
  asm volatile("cp.async.bulk.shared::cluster.global.mbarrier::complete_tx::bytes [%0], [%1], %2, [%3];" ::"r"(dst), "l"(src), "r"(bytes), "r"(bar) : "memory");
}
__device__ __forceinline__ void tma4d_store(const CUtensorMap* m, uint32_t src, int c0, int c1, int c2, int c3) {
  asm volatile("cp.async.bulk.tensor.4d.global.shared::cta.bulk_group [%0, {%2,%3,%4,%5}], [%1];" ::"l"(m), "r"(src), "r"(c0), "r"(c1), "r"(c2), "r"(c3) : "memory");
}
__device__ __forceinline__ void tma2d_store(const CUtensorMap* m, uint32_t src, int c0, int c1) {
  asm volatile("cp.async.bulk.tensor.2d.global.shared::cta.bulk_group [%0, {%2,%3}], [%1];" ::"l"(m), "r"(src), "r"(c0), "r"(c1) : "memory");
}
__device__ __forceinline__ void bulk_s2g(void* dst, uint32_t src, uint32_t bytes) {
  asm volatile("cp.async.bulk.global.shared::cta.bulk_group [%0], [%1], %2;" ::"l"(dst), "r"(src), "r"(bytes) : "memory");
}
__device__ __forceinline__ void bulk_commit() { asm volatile("cp.async.bulk.commit_group;" ::: "memory"); }
__device__ __forceinline__ void bulk_wait() { asm volatile("cp.async.bulk.wait_group 0;" ::: "memory"); }
__device__ __forceinline__ void fence_async() { asm volatile("fence.proxy.async.shared::cta;" ::: "memory"); }
__device__ __forceinline__ void prefetch_l2(const void* src, uint32_t bytes) { asm volatile("cp.async.bulk.prefetch.L2.global [%0], %1;" ::"l"(src), "r"(bytes) : "memory"); }
__device__ __forceinline__ void prefetch_map(const CUtensorMap* m) { asm volatile("prefetch.tensormap [%0];" ::"l"(m) : "memory"); }
__device__ __forceinline__ void wg_fence() { __syncwarp(); asm volatile("wgmma.fence.sync.aligned;" ::: "memory"); }
__device__ __forceinline__ void wg_commit() { asm volatile("wgmma.commit_group.sync.aligned;" ::: "memory"); }
template <int N> __device__ __forceinline__ void wg_wait() { asm volatile("wgmma.wait_group.sync.aligned %0;" ::"n"(N) : "memory"); }
template <int N> __device__ __forceinline__ void fence_regs(float (&d)[N]) {
#pragma unroll
  for (int i = 0; i < N; i++) asm volatile("" : "+f"(d[i])::"memory");
}
__device__ __forceinline__ uint64_t make_desc(uint32_t addr, uint32_t lbo, uint32_t sbo, uint32_t swz) {
  return (uint64_t)((addr & 0x3FFFF) >> 4) | ((uint64_t)(lbo >> 4) << 16) | ((uint64_t)(sbo >> 4) << 32) | ((uint64_t)swz << 62);
}
__device__ __forceinline__ uint32_t ldg1(const void* p) { uint32_t v; asm volatile("ld.global.nc.u32 %0,[%1];" : "=r"(v) : "l"(p)); return v; }
__device__ __forceinline__ uint32_t lds32(uint32_t a) { uint32_t v; asm volatile("ld.shared.u32 %0,[%1];" : "=r"(v) : "r"(a)); return v; }
__device__ __forceinline__ unsigned ld_rlx(const unsigned* p) { unsigned v; asm volatile("ld.relaxed.gpu.global.u32 %0,[%1];" : "=r"(v) : "l"(p) : "memory"); return v; }
__device__ __forceinline__ uint4 ld_rlx4(const void* p) {
  uint4 v; asm volatile("ld.relaxed.gpu.global.v4.u32 {%0,%1,%2,%3},[%4];" : "=r"(v.x), "=r"(v.y), "=r"(v.z), "=r"(v.w) : "l"(p) : "memory"); return v;
}
__device__ __forceinline__ uint2 ld_rlx2(const void* p) { uint2 v; asm volatile("ld.relaxed.gpu.global.v2.u32 {%0,%1},[%2];" : "=r"(v.x), "=r"(v.y) : "l"(p) : "memory"); return v; }
__device__ __forceinline__ void st_rlx2(void* p, uint32_t a, uint32_t b) { asm volatile("st.relaxed.gpu.global.v2.u32 [%0],{%1,%2};" ::"l"(p), "r"(a), "r"(b) : "memory"); }
__device__ __forceinline__ void st_rlx(void* p, uint32_t a) { asm volatile("st.relaxed.gpu.global.u32 [%0],%1;" ::"l"(p), "r"(a) : "memory"); }
#define PUB 15
template <int SITE> __device__ __forceinline__ void release() { if (PUB & SITE) { if (REL) asm volatile("fence.release.gpu;" ::: "memory"); else asm volatile("fence.acq_rel.gpu;" ::: "memory"); } }
__device__ __forceinline__ void signal_flag(unsigned* p, unsigned val) { asm volatile("st.relaxed.gpu.global.u32 [%0],%1;" ::"l"(p), "r"(val) : "memory"); }
__device__ __forceinline__ void signal_cnt(unsigned* p, unsigned n) { asm volatile("red.relaxed.gpu.global.add.u32 [%0],%1;" ::"l"(p), "r"(n) : "memory"); }
__device__ __forceinline__ void wait_flags(const unsigned* p, unsigned val, uint32_t need, uint32_t& ready) {
#pragma unroll 1
  for (int it = 0; (ready & need) != need && it < SPIN; it++) ready = __ballot_sync(0xffffffff, ld_rlx(p) == val);
}
__device__ __forceinline__ void wait_cnt(const unsigned* p, unsigned tgt) {
  asm volatile("{ .reg .pred p; .reg .u32 c; .reg .s32 v; mov.u32 c, 0;\n"
               "W: ld.relaxed.gpu.global.u32 v, [%0]; sub.s32 v, v, %1; setp.ge.s32 p, v, 0; @p bra.uni D;\n"
               "add.u32 c, c, 1; setp.lt.u32 p, c, 0x100000; @p bra.uni W;\nD: }" ::"l"(p), "r"(tgt) : "memory");
}
__device__ __forceinline__ uint32_t pack_bf(float lo, float hi) { uint32_t r; asm("cvt.rn.bf16x2.f32 %0, %1, %2;" : "=r"(r) : "f"(hi), "f"(lo)); return r; }
__device__ __forceinline__ float bf_lo(uint32_t v) { return __uint_as_float(v << 16); }
__device__ __forceinline__ float bf_hi(uint32_t v) { return __uint_as_float(v & 0xffff0000u); }
__device__ __forceinline__ float bf_rn(float x) { return __bfloat162float(__float2bfloat16_rn(x)); }
__device__ __forceinline__ float frcp(float x) { float r; asm("rcp.approx.ftz.f32 %0,%1;" : "=f"(r) : "f"(x)); return r; }
__device__ __forceinline__ float fsqrt(float x) { float r; asm("sqrt.approx.ftz.f32 %0,%1;" : "=f"(r) : "f"(x)); return r; }
__device__ __forceinline__ float frsqrt(float x) { float r; asm("rsqrt.approx.ftz.f32 %0,%1;" : "=f"(r) : "f"(x)); return r; }
__device__ __forceinline__ uint32_t hmul2(uint32_t a, uint32_t b) { uint32_t r; asm("mul.rn.bf16x2 %0,%1,%2;" : "=r"(r) : "r"(a), "r"(b)); return r; }
__device__ __forceinline__ uint32_t hfma2(uint32_t a, uint32_t b, uint32_t c) { uint32_t r; asm("fma.rn.bf16x2 %0,%1,%2,%3;" : "=r"(r) : "r"(a), "r"(b), "r"(c)); return r; }
__device__ __forceinline__ float2 cmul(float2 a, float2 b) { return make_float2(a.x * b.x - a.y * b.y, a.x * b.y + a.y * b.x); }
__device__ __forceinline__ float2 cfma(float2 a, float2 b, float2 c) {
  return make_float2(fmaf(a.x, b.x, fmaf(-a.y, b.y, c.x)), fmaf(a.x, b.y, fmaf(a.y, b.x, c.y)));
}
__device__ __forceinline__ uint32_t tagf(float v, uint32_t tag) { return (__float_as_uint(v) & ~1u) | tag; }
__device__ __forceinline__ float untag(uint32_t v) { return __uint_as_float(v & ~1u); }
__device__ __forceinline__ bool untagged(const uint4& v, uint32_t tag) { return (((v.x ^ tag) | (v.y ^ tag) | (v.z ^ tag) | (v.w ^ tag)) & 1) != 0; }
__device__ __forceinline__ bool untagged(const uint2& v, uint32_t tag) { return (((v.x ^ tag) | (v.y ^ tag)) & 1) != 0; }
__device__ __forceinline__ float2 lam_bar(float lr, float li, float ldt) {
  float dt = bf_rn(expf(ldt)); float e = expf(dt * lr), s, c; sincospif(dt * li * 0.31830988618379067f, &s, &c); return make_float2(e * c, e * s);
}

__device__ __forceinline__ int conv_ch(uint32_t c, int s) { return s * ((c >> 21) & 255) + (c & 255) - (s >= (int)(c >> 29) ? 8 : 0); }
struct Role {
  uint32_t v, c, p;
  __device__ __forceinline__ int tb() const { return v & 15; }
  __device__ __forceinline__ int cb() const { return (v >> 4) & 15; }
  __device__ __forceinline__ int b() const { return (v >> 8) & 255; }
  __device__ __forceinline__ int ubase() const { return (v >> 16) & 7; }
  __device__ __forceinline__ int ugs() const { return (v >> 19) & 7; }
  __device__ __forceinline__ int wpart() const { return (v >> 22) & 7; }
  __device__ __forceinline__ int rank() const { return (v >> 26) & 7; }
  __device__ __forceinline__ int cs() const { return (v >> 29) ? 8 : 2; }
  __device__ __forceinline__ int ch(int s) const { return conv_ch(c, s); }
  __device__ __forceinline__ int wlo() const { return p & 1; }
  __device__ __forceinline__ int whi() const { return (p >> 1) & 1; }
  __device__ __forceinline__ uint32_t wmask() const { return (p >> 2) & 255; }
  __device__ __forceinline__ uint32_t umask() const { return (p >> 10) & 255; }
  __device__ __forceinline__ int uj() const { return (p >> 20) & 31; }
  __device__ __forceinline__ int sm() const { return (p >> 25) & 15; }
  __device__ __forceinline__ int nch() const { return (c >> 10) & 7; }
  __device__ __forceinline__ int nprep() const { return (c >> 13) & 255; }
};

__device__ __forceinline__ void wgmma_ss80(float (&d)[40], uint64_t da, uint64_t db, int sd){
  asm volatile("{ .reg .pred p; setp.ne.b32 p, %42, 0;\n"
   "wgmma.mma_async.sync.aligned.m64n80k16.f32.bf16.bf16 {%0, %1, %2, %3, %4, %5, %6, %7, %8, %9, %10, %11, %12, %13, %14, %15, %16, %17, %18, %19, %20, %21, %22, %23, %24, %25, %26, %27, %28, %29, %30, %31, %32, %33, %34, %35, %36, %37, %38, %39}, %40, %41, p, 1, 1, 0, 0; }\n"
   : "+f"(d[0]), "+f"(d[1]), "+f"(d[2]), "+f"(d[3]), "+f"(d[4]), "+f"(d[5]), "+f"(d[6]), "+f"(d[7]), "+f"(d[8]), "+f"(d[9]), "+f"(d[10]), "+f"(d[11]), "+f"(d[12]), "+f"(d[13]), "+f"(d[14]), "+f"(d[15]), "+f"(d[16]), "+f"(d[17]), "+f"(d[18]), "+f"(d[19]), "+f"(d[20]), "+f"(d[21]), "+f"(d[22]), "+f"(d[23]), "+f"(d[24]), "+f"(d[25]), "+f"(d[26]), "+f"(d[27]), "+f"(d[28]), "+f"(d[29]), "+f"(d[30]), "+f"(d[31]), "+f"(d[32]), "+f"(d[33]), "+f"(d[34]), "+f"(d[35]), "+f"(d[36]), "+f"(d[37]), "+f"(d[38]), "+f"(d[39]) : "l"(da), "l"(db), "r"(sd));
}
__device__ __forceinline__ void wgmma_ss160(float (&d)[80], uint64_t da, uint64_t db, int sd){
  asm volatile("{ .reg .pred p; setp.ne.b32 p, %82, 0;\n"
   "wgmma.mma_async.sync.aligned.m64n160k16.f32.bf16.bf16 {%0, %1, %2, %3, %4, %5, %6, %7, %8, %9, %10, %11, %12, %13, %14, %15, %16, %17, %18, %19, %20, %21, %22, %23, %24, %25, %26, %27, %28, %29, %30, %31, %32, %33, %34, %35, %36, %37, %38, %39, %40, %41, %42, %43, %44, %45, %46, %47, %48, %49, %50, %51, %52, %53, %54, %55, %56, %57, %58, %59, %60, %61, %62, %63, %64, %65, %66, %67, %68, %69, %70, %71, %72, %73, %74, %75, %76, %77, %78, %79}, %80, %81, p, 1, 1, 0, 0; }\n"
   : "+f"(d[0]), "+f"(d[1]), "+f"(d[2]), "+f"(d[3]), "+f"(d[4]), "+f"(d[5]), "+f"(d[6]), "+f"(d[7]), "+f"(d[8]), "+f"(d[9]), "+f"(d[10]), "+f"(d[11]), "+f"(d[12]), "+f"(d[13]), "+f"(d[14]), "+f"(d[15]), "+f"(d[16]), "+f"(d[17]), "+f"(d[18]), "+f"(d[19]), "+f"(d[20]), "+f"(d[21]), "+f"(d[22]), "+f"(d[23]), "+f"(d[24]), "+f"(d[25]), "+f"(d[26]), "+f"(d[27]), "+f"(d[28]), "+f"(d[29]), "+f"(d[30]), "+f"(d[31]), "+f"(d[32]), "+f"(d[33]), "+f"(d[34]), "+f"(d[35]), "+f"(d[36]), "+f"(d[37]), "+f"(d[38]), "+f"(d[39]), "+f"(d[40]), "+f"(d[41]), "+f"(d[42]), "+f"(d[43]), "+f"(d[44]), "+f"(d[45]), "+f"(d[46]), "+f"(d[47]), "+f"(d[48]), "+f"(d[49]), "+f"(d[50]), "+f"(d[51]), "+f"(d[52]), "+f"(d[53]), "+f"(d[54]), "+f"(d[55]), "+f"(d[56]), "+f"(d[57]), "+f"(d[58]), "+f"(d[59]), "+f"(d[60]), "+f"(d[61]), "+f"(d[62]), "+f"(d[63]), "+f"(d[64]), "+f"(d[65]), "+f"(d[66]), "+f"(d[67]), "+f"(d[68]), "+f"(d[69]), "+f"(d[70]), "+f"(d[71]), "+f"(d[72]), "+f"(d[73]), "+f"(d[74]), "+f"(d[75]), "+f"(d[76]), "+f"(d[77]), "+f"(d[78]), "+f"(d[79]) : "l"(da), "l"(db), "r"(sd));
}
template<int N> __device__ __forceinline__ void wgmma_rs(float (&d)[N/2], uint32_t a0, uint32_t a1, uint32_t a2, uint32_t a3, uint64_t db, int sd);
template<> __device__ __forceinline__ void wgmma_rs<16>(float (&d)[8], uint32_t a0, uint32_t a1, uint32_t a2, uint32_t a3, uint64_t db, int sd){
  asm volatile("{ .reg .pred p; setp.ne.b32 p, %13, 0;\n"
   "wgmma.mma_async.sync.aligned.m64n16k16.f32.bf16.bf16 {%0, %1, %2, %3, %4, %5, %6, %7}, {%8,%9,%10,%11}, %12, p, 1, 1, 0; }\n"
   : "+f"(d[0]), "+f"(d[1]), "+f"(d[2]), "+f"(d[3]), "+f"(d[4]), "+f"(d[5]), "+f"(d[6]), "+f"(d[7]) : "r"(a0), "r"(a1), "r"(a2), "r"(a3), "l"(db), "r"(sd));
}
template<> __device__ __forceinline__ void wgmma_rs<32>(float (&d)[16], uint32_t a0, uint32_t a1, uint32_t a2, uint32_t a3, uint64_t db, int sd){
  asm volatile("{ .reg .pred p; setp.ne.b32 p, %21, 0;\n"
   "wgmma.mma_async.sync.aligned.m64n32k16.f32.bf16.bf16 {%0, %1, %2, %3, %4, %5, %6, %7, %8, %9, %10, %11, %12, %13, %14, %15}, {%16,%17,%18,%19}, %20, p, 1, 1, 0; }\n"
   : "+f"(d[0]), "+f"(d[1]), "+f"(d[2]), "+f"(d[3]), "+f"(d[4]), "+f"(d[5]), "+f"(d[6]), "+f"(d[7]), "+f"(d[8]), "+f"(d[9]), "+f"(d[10]), "+f"(d[11]), "+f"(d[12]), "+f"(d[13]), "+f"(d[14]), "+f"(d[15]) : "r"(a0), "r"(a1), "r"(a2), "r"(a3), "l"(db), "r"(sd));
}
template<> __device__ __forceinline__ void wgmma_rs<48>(float (&d)[24], uint32_t a0, uint32_t a1, uint32_t a2, uint32_t a3, uint64_t db, int sd){
  asm volatile("{ .reg .pred p; setp.ne.b32 p, %29, 0;\n"
   "wgmma.mma_async.sync.aligned.m64n48k16.f32.bf16.bf16 {%0, %1, %2, %3, %4, %5, %6, %7, %8, %9, %10, %11, %12, %13, %14, %15, %16, %17, %18, %19, %20, %21, %22, %23}, {%24,%25,%26,%27}, %28, p, 1, 1, 0; }\n"
   : "+f"(d[0]), "+f"(d[1]), "+f"(d[2]), "+f"(d[3]), "+f"(d[4]), "+f"(d[5]), "+f"(d[6]), "+f"(d[7]), "+f"(d[8]), "+f"(d[9]), "+f"(d[10]), "+f"(d[11]), "+f"(d[12]), "+f"(d[13]), "+f"(d[14]), "+f"(d[15]), "+f"(d[16]), "+f"(d[17]), "+f"(d[18]), "+f"(d[19]), "+f"(d[20]), "+f"(d[21]), "+f"(d[22]), "+f"(d[23]) : "r"(a0), "r"(a1), "r"(a2), "r"(a3), "l"(db), "r"(sd));
}
template<> __device__ __forceinline__ void wgmma_rs<64>(float (&d)[32], uint32_t a0, uint32_t a1, uint32_t a2, uint32_t a3, uint64_t db, int sd){
  asm volatile("{ .reg .pred p; setp.ne.b32 p, %37, 0;\n"
   "wgmma.mma_async.sync.aligned.m64n64k16.f32.bf16.bf16 {%0, %1, %2, %3, %4, %5, %6, %7, %8, %9, %10, %11, %12, %13, %14, %15, %16, %17, %18, %19, %20, %21, %22, %23, %24, %25, %26, %27, %28, %29, %30, %31}, {%32,%33,%34,%35}, %36, p, 1, 1, 0; }\n"
   : "+f"(d[0]), "+f"(d[1]), "+f"(d[2]), "+f"(d[3]), "+f"(d[4]), "+f"(d[5]), "+f"(d[6]), "+f"(d[7]), "+f"(d[8]), "+f"(d[9]), "+f"(d[10]), "+f"(d[11]), "+f"(d[12]), "+f"(d[13]), "+f"(d[14]), "+f"(d[15]), "+f"(d[16]), "+f"(d[17]), "+f"(d[18]), "+f"(d[19]), "+f"(d[20]), "+f"(d[21]), "+f"(d[22]), "+f"(d[23]), "+f"(d[24]), "+f"(d[25]), "+f"(d[26]), "+f"(d[27]), "+f"(d[28]), "+f"(d[29]), "+f"(d[30]), "+f"(d[31]) : "r"(a0), "r"(a1), "r"(a2), "r"(a3), "l"(db), "r"(sd));
}
template<> __device__ __forceinline__ void wgmma_rs<80>(float (&d)[40], uint32_t a0, uint32_t a1, uint32_t a2, uint32_t a3, uint64_t db, int sd){
  asm volatile("{ .reg .pred p; setp.ne.b32 p, %45, 0;\n"
   "wgmma.mma_async.sync.aligned.m64n80k16.f32.bf16.bf16 {%0, %1, %2, %3, %4, %5, %6, %7, %8, %9, %10, %11, %12, %13, %14, %15, %16, %17, %18, %19, %20, %21, %22, %23, %24, %25, %26, %27, %28, %29, %30, %31, %32, %33, %34, %35, %36, %37, %38, %39}, {%40,%41,%42,%43}, %44, p, 1, 1, 0; }\n"
   : "+f"(d[0]), "+f"(d[1]), "+f"(d[2]), "+f"(d[3]), "+f"(d[4]), "+f"(d[5]), "+f"(d[6]), "+f"(d[7]), "+f"(d[8]), "+f"(d[9]), "+f"(d[10]), "+f"(d[11]), "+f"(d[12]), "+f"(d[13]), "+f"(d[14]), "+f"(d[15]), "+f"(d[16]), "+f"(d[17]), "+f"(d[18]), "+f"(d[19]), "+f"(d[20]), "+f"(d[21]), "+f"(d[22]), "+f"(d[23]), "+f"(d[24]), "+f"(d[25]), "+f"(d[26]), "+f"(d[27]), "+f"(d[28]), "+f"(d[29]), "+f"(d[30]), "+f"(d[31]), "+f"(d[32]), "+f"(d[33]), "+f"(d[34]), "+f"(d[35]), "+f"(d[36]), "+f"(d[37]), "+f"(d[38]), "+f"(d[39]) : "r"(a0), "r"(a1), "r"(a2), "r"(a3), "l"(db), "r"(sd));
}
template<> __device__ __forceinline__ void wgmma_rs<96>(float (&d)[48], uint32_t a0, uint32_t a1, uint32_t a2, uint32_t a3, uint64_t db, int sd){
  asm volatile("{ .reg .pred p; setp.ne.b32 p, %53, 0;\n"
   "wgmma.mma_async.sync.aligned.m64n96k16.f32.bf16.bf16 {%0, %1, %2, %3, %4, %5, %6, %7, %8, %9, %10, %11, %12, %13, %14, %15, %16, %17, %18, %19, %20, %21, %22, %23, %24, %25, %26, %27, %28, %29, %30, %31, %32, %33, %34, %35, %36, %37, %38, %39, %40, %41, %42, %43, %44, %45, %46, %47}, {%48,%49,%50,%51}, %52, p, 1, 1, 0; }\n"
   : "+f"(d[0]), "+f"(d[1]), "+f"(d[2]), "+f"(d[3]), "+f"(d[4]), "+f"(d[5]), "+f"(d[6]), "+f"(d[7]), "+f"(d[8]), "+f"(d[9]), "+f"(d[10]), "+f"(d[11]), "+f"(d[12]), "+f"(d[13]), "+f"(d[14]), "+f"(d[15]), "+f"(d[16]), "+f"(d[17]), "+f"(d[18]), "+f"(d[19]), "+f"(d[20]), "+f"(d[21]), "+f"(d[22]), "+f"(d[23]), "+f"(d[24]), "+f"(d[25]), "+f"(d[26]), "+f"(d[27]), "+f"(d[28]), "+f"(d[29]), "+f"(d[30]), "+f"(d[31]), "+f"(d[32]), "+f"(d[33]), "+f"(d[34]), "+f"(d[35]), "+f"(d[36]), "+f"(d[37]), "+f"(d[38]), "+f"(d[39]), "+f"(d[40]), "+f"(d[41]), "+f"(d[42]), "+f"(d[43]), "+f"(d[44]), "+f"(d[45]), "+f"(d[46]), "+f"(d[47]) : "r"(a0), "r"(a1), "r"(a2), "r"(a3), "l"(db), "r"(sd));
}
template<> __device__ __forceinline__ void wgmma_rs<112>(float (&d)[56], uint32_t a0, uint32_t a1, uint32_t a2, uint32_t a3, uint64_t db, int sd){
  asm volatile("{ .reg .pred p; setp.ne.b32 p, %61, 0;\n"
   "wgmma.mma_async.sync.aligned.m64n112k16.f32.bf16.bf16 {%0, %1, %2, %3, %4, %5, %6, %7, %8, %9, %10, %11, %12, %13, %14, %15, %16, %17, %18, %19, %20, %21, %22, %23, %24, %25, %26, %27, %28, %29, %30, %31, %32, %33, %34, %35, %36, %37, %38, %39, %40, %41, %42, %43, %44, %45, %46, %47, %48, %49, %50, %51, %52, %53, %54, %55}, {%56,%57,%58,%59}, %60, p, 1, 1, 0; }\n"
   : "+f"(d[0]), "+f"(d[1]), "+f"(d[2]), "+f"(d[3]), "+f"(d[4]), "+f"(d[5]), "+f"(d[6]), "+f"(d[7]), "+f"(d[8]), "+f"(d[9]), "+f"(d[10]), "+f"(d[11]), "+f"(d[12]), "+f"(d[13]), "+f"(d[14]), "+f"(d[15]), "+f"(d[16]), "+f"(d[17]), "+f"(d[18]), "+f"(d[19]), "+f"(d[20]), "+f"(d[21]), "+f"(d[22]), "+f"(d[23]), "+f"(d[24]), "+f"(d[25]), "+f"(d[26]), "+f"(d[27]), "+f"(d[28]), "+f"(d[29]), "+f"(d[30]), "+f"(d[31]), "+f"(d[32]), "+f"(d[33]), "+f"(d[34]), "+f"(d[35]), "+f"(d[36]), "+f"(d[37]), "+f"(d[38]), "+f"(d[39]), "+f"(d[40]), "+f"(d[41]), "+f"(d[42]), "+f"(d[43]), "+f"(d[44]), "+f"(d[45]), "+f"(d[46]), "+f"(d[47]), "+f"(d[48]), "+f"(d[49]), "+f"(d[50]), "+f"(d[51]), "+f"(d[52]), "+f"(d[53]), "+f"(d[54]), "+f"(d[55]) : "r"(a0), "r"(a1), "r"(a2), "r"(a3), "l"(db), "r"(sd));
}
template<> __device__ __forceinline__ void wgmma_rs<128>(float (&d)[64], uint32_t a0, uint32_t a1, uint32_t a2, uint32_t a3, uint64_t db, int sd){
  asm volatile("{ .reg .pred p; setp.ne.b32 p, %69, 0;\n"
   "wgmma.mma_async.sync.aligned.m64n128k16.f32.bf16.bf16 {%0, %1, %2, %3, %4, %5, %6, %7, %8, %9, %10, %11, %12, %13, %14, %15, %16, %17, %18, %19, %20, %21, %22, %23, %24, %25, %26, %27, %28, %29, %30, %31, %32, %33, %34, %35, %36, %37, %38, %39, %40, %41, %42, %43, %44, %45, %46, %47, %48, %49, %50, %51, %52, %53, %54, %55, %56, %57, %58, %59, %60, %61, %62, %63}, {%64,%65,%66,%67}, %68, p, 1, 1, 0; }\n"
   : "+f"(d[0]), "+f"(d[1]), "+f"(d[2]), "+f"(d[3]), "+f"(d[4]), "+f"(d[5]), "+f"(d[6]), "+f"(d[7]), "+f"(d[8]), "+f"(d[9]), "+f"(d[10]), "+f"(d[11]), "+f"(d[12]), "+f"(d[13]), "+f"(d[14]), "+f"(d[15]), "+f"(d[16]), "+f"(d[17]), "+f"(d[18]), "+f"(d[19]), "+f"(d[20]), "+f"(d[21]), "+f"(d[22]), "+f"(d[23]), "+f"(d[24]), "+f"(d[25]), "+f"(d[26]), "+f"(d[27]), "+f"(d[28]), "+f"(d[29]), "+f"(d[30]), "+f"(d[31]), "+f"(d[32]), "+f"(d[33]), "+f"(d[34]), "+f"(d[35]), "+f"(d[36]), "+f"(d[37]), "+f"(d[38]), "+f"(d[39]), "+f"(d[40]), "+f"(d[41]), "+f"(d[42]), "+f"(d[43]), "+f"(d[44]), "+f"(d[45]), "+f"(d[46]), "+f"(d[47]), "+f"(d[48]), "+f"(d[49]), "+f"(d[50]), "+f"(d[51]), "+f"(d[52]), "+f"(d[53]), "+f"(d[54]), "+f"(d[55]), "+f"(d[56]), "+f"(d[57]), "+f"(d[58]), "+f"(d[59]), "+f"(d[60]), "+f"(d[61]), "+f"(d[62]), "+f"(d[63]) : "r"(a0), "r"(a1), "r"(a2), "r"(a3), "l"(db), "r"(sd));
}

#define BAR(i) (bars + 8u * (uint32_t)(i))

template <int G> __device__ __forceinline__ void conv_frags(uint32_t (&a)[12], uint32_t abase) {
#pragma unroll
  for (int i = 0; i < 12; i++) a[i] = lds32(abase + (G * 4 + i / 3) * 128 + (i % 3) * 4);
}
__device__ __forceinline__ void kv_prefetch(const __nv_bfloat16* pf, int task) { prefetch_if(pf + 64 * (task & 31) * DM + 64 * (task >> 5), task < 320); }
__device__ __forceinline__ void kv_load(const Params& P, Scratch* S, int task, int tid, uint32_t (&k_)[19], uint32_t (&v_)[16], uint4& sk) {
  const int row = 64 * (task & 31) + 16 * (tid >> 5), ch = 64 * (task >> 5) + 2 * (tid & 31);
  const uint32_t* kp = (const uint32_t*)(P.k + (size_t)row * DM + ch);
  const uint32_t* vp = (const uint32_t*)(P.v + (size_t)row * DM + ch);
  const uint32_t* hp = row > 0 ? kp - 3 * (DM / 2) : S->zero;
  const int hs = row > 0 ? DM / 2 : 0;
  asm volatile("ld.global.nc.v4.u32 {%0,%1,%2,%3},[%4];" : "=r"(sk.x), "=r"(sk.y), "=r"(sk.z), "=r"(sk.w) : "l"(P.shk + ch * 4));
#pragma unroll
  for (int i = 0; i < 3; i++) k_[i] = ldg1(hp + i * hs);
#pragma unroll
  for (int i = 0; i < 16; i++) { k_[i + 3] = ldg1(kp + i * (DM / 2)); v_[i] = ldg1(vp + i * (DM / 2)); }
}
template <int SH> __device__ __forceinline__ void xb_prefetch(const Head& H, int id, int tid, int c0) {
  const int ri = tid >> SH, rr = 11 * id + ri - 16;
  const __nv_bfloat16* p = ri < 16 ? H.x + (size_t)(16 * min(id, 127) + ri) * DM : (rr < DM ? H.b0 : H.b1 - DM * DM) + (size_t)rr * DM;
  prefetch_if(p + c0 + 64 * (tid & ((1 << SH) - 1)), ri < 16 || (ri < 27 && rr < 2 * DM));
}
__device__ __forceinline__ uint4 ldg4(const void* p) { uint4 v; asm volatile("ld.global.nc.v4.u32 {%0,%1,%2,%3},[%4];" : "=r"(v.x), "=r"(v.y), "=r"(v.z), "=r"(v.w) : "l"(p)); return v; }
__device__ __forceinline__ uint4 lds4(uint32_t a) { uint4 v; asm volatile("ld.shared.v4.u32 {%0,%1,%2,%3},[%4];" : "=r"(v.x), "=r"(v.y), "=r"(v.z), "=r"(v.w) : "r"(a) : "memory"); return v; }
__device__ __forceinline__ void discretise(const Head& H, const Params& P, uint32_t sb, Role R, int lane, uint32_t e1) {
  const uint32_t dn = __ldg((const unsigned short*)P.ssmd + min(conv_ch(R.c, (lane + 7) & 7), DM - 1));
  const int c = 32 * min(R.cb(), 9) + lane;
  const uint32_t lr2 = ldg1(P.lre + 2 * c), li2 = ldg1(P.lim + 2 * c), ld2 = ldg1(P.ldt + 2 * c);
  asm volatile("st.shared.u32 [%0],%1;" ::"r"(sb + MISC_OFF + 4 * (lane & 7)), "r"((lane & 7) ? dn : e1) : "memory");
#pragma unroll 1
  for (int i = 0; i < 2; i++) {
    const float lr = bf_hi(lr2 << (16 - 16 * i)), li = bf_hi(li2 << (16 - 16 * i));
    const float2 lb = lam_bar(lr, li, bf_hi(ld2 << (16 - 16 * i)));
    const float nx = lb.x - 1.f, ny = lb.y, inv = 2.f * frcp(lr * lr + li * li), cx = (nx * lr + ny * li) * inv, cy = (ny * lr - nx * li) * inv;
    const bool sw = !H.swap;
    asm volatile("st.shared.v4.f32 [%0],{%1,%2,%3,%4};" ::"r"(sb + LAM_OFF + 32 * lane + 16 * i), "f"(lb.x), "f"(sw ? -lb.y : lb.y), "f"(sw ? -cy : cx), "f"(sw ? cx : -cy) : "memory");
  }
  __syncwarp();
}
__device__ __forceinline__ void aux_prep(const Head& H, const Params& P, uint32_t sb, Role R, int tid, long long t_start) {
  Scratch* const S = H.s;
  const uint32_t bars = sb + BAR_OFF;
  tid = opaque(tid);
  const int w = tid >> 5, lane = tid & 31, tb = R.tb(), cb = R.cb();
  uint32_t k_[19], v_[16];
  uint4 sk;
  int task = R.b() < R.nprep() ? R.b() : 320;
  delay(KVDLY);
  PROFC(tid == 0, 345);
  kv_load(P, S, min(task, 319), tid, k_, v_, sk);
  const __nv_bfloat16* pf = (tid < 64 ? P.k : P.v) + (tid & 63) * DM;
  const int j = lane >> 3, sm = min(R.sm(), 9), trow = 160 * tb + 4 * sm + (tb < 12 ? 40 : 32) * w + j;
  const uint32_t so = sb + (2 * w + (j & 1) + 8 * (j >> 1)) * 128 + 16 * (lane & 7), xo = so + sm * 2048, wo = so + (tb & 1) * 8192 + (tb & 6) * 1024;
  const __nv_bfloat16* xp = H.x + (size_t)min(trow, SEQ - 1) * DM + 384 + 8 * (lane & 7);
  const __nv_bfloat16* bp = (j < 2 ? H.b0 : H.b1) + (size_t)(64 * cb + 32 * (tb & 1) + 4 * (tb & 6) + 2 * w + (j & 1)) * DM + 384 + 8 * (lane & 7);
  float s = 0.f, s2 = 0.f, sr = 0.f;
#define STAT(m, n) { const uint32_t xw[4] = {m.x, m.y, m.z, m.w}, bw[4] = {n.x, n.y, n.z, n.w}; \
  _Pragma("unroll") for (int i = 0; i < 4; i++) { const float u = bf_lo(xw[i]), v = bf_hi(xw[i]); s += u + v; s2 = fmaf(u, u, fmaf(v, v, s2)); sr += bf_lo(bw[i]) + bf_hi(bw[i]); } }
#define STATS(K0, K1) _Pragma("unroll 1") for (int kb = K0; kb < K1; kb++) { \
    mbar_wait(BAR(B_F1 + kb)); \
    const uint4 a = lds4(xo + ((uint32_t)(XTAB0 >> (6 * kb)) & 63) * 4096), c = lds4(wo + ((uint32_t)(WTAB0 >> (6 * kb)) & 63) * 4096); \
    STAT(a, c) \
    asm volatile("" : "+f"(s), "+f"(s2), "+f"(sr)); \
    if (XPFAT >= K0 && XPFAT < K1) prefetch_if(((lane & 4) ? bp : xp) + 64 * (lane & 3), kb == XPFAT); \
    kv_prefetch(pf, kb == KPFAT ? task + R.nprep() : kb == KPFAT2 ? task + 2 * R.nprep() : 320); \
  } \
  __syncwarp(); mbar_arrive_if(BAR(B_AX + K0 / 3), lane == 0);
  STATS(0, 3)
  PROFC(tid == 0, 349);
    {
      uint4 m[4], n[4];
#pragma unroll
      for (int i = 0; i < 4; i++) { m[i] = ldg4(xp + 64 * i); n[i] = ldg4(bp + 64 * i); }
      STATS(3, 6)
      PROFC(tid == 0, 346);
      mbar_wait(BAR(B_LM));
      const uint32_t tag = lds32(sb + MISC_OFF) & 1;
#pragma unroll
      for (int i = 0; i < 4; i++) { const uint4 a = m[i], c = n[i]; STAT(a, c) }
      PROFC(tid == 0 && s2 != 1.2345f, 347);
#pragma unroll
      for (int o = 1; o <= 4; o <<= 1) { s += __shfl_xor_sync(0xffffffff, s, o); s2 += __shfl_xor_sync(0xffffffff, s2, o); sr += __shfl_xor_sync(0xffffffff, sr, o); }
      const float mn = s * (1.f / DM), rs = frcp(bf_rn(fsqrt(bf_rn(bf_rn(fmaxf(s2 * (1.f / DM) - mn * mn, 0.f)) + 1e-5f))));
      asm volatile("{ .reg .pred p; setp.ne.u32 p, %2, 0; @p st.relaxed.gpu.global.u32 [%0],%1; }"
                   ::"l"((uint32_t*)(S->RS + (8 * cb + 4 * (tb & 1) + (tb >> 1)) * 16 + 4 * w + (j & 1)) + (lane & 4) + (j >> 1)), "r"(tagf(sr, tag)),
                   "r"((uint32_t)(tb < 8 && (lane & 3) == 0)) : "memory");
      asm volatile("{ .reg .pred p; setp.ne.u32 p, %3, 0; @p st.relaxed.gpu.global.v2.u32 [%0],{%1,%2}; }"
                   ::"l"(S->S + trow), "r"(tagf(rs, tag)), "r"(tagf(-bf_rn(mn) * rs, tag)), "r"((uint32_t)(R.sm() < 10 && (lane & 7) == 0)) : "memory");
      PROFC(tid == 0, 3);
    }
#pragma unroll 1
  for (int r = 0; task < 320; r++) {
    {
      const uint32_t T0 = __byte_perm(sk.x, sk.z, 0x5410), T1 = __byte_perm(sk.x, sk.z, 0x7632);
      const uint32_t T2 = __byte_perm(sk.y, sk.w, 0x5410), T3 = __byte_perm(sk.y, sk.w, 0x7632);
      PROFC(tid == 0 && v_[15] != 0x12345, 336 + r);
      uint32_t o[16];
#pragma unroll
      for (int t = 0; t < 16; t += 2) {
        const uint32_t a = hmul2(hfma2(k_[t + 3], T0, hfma2(k_[t + 2], T1, hfma2(k_[t + 1], T2, hmul2(k_[t], T3)))), v_[t]);
        const uint32_t c = hmul2(hfma2(k_[t + 4], T0, hfma2(k_[t + 3], T1, hfma2(k_[t + 2], T2, hmul2(k_[t + 1], T3)))), v_[t + 1]);
        const int wd = ((7 - t / 2) >> 1) + 4 * ((7 - t / 2) & 1);
        o[wd] = __byte_perm(c, a, 0x5410); o[8 + wd] = __byte_perm(c, a, 0x7632);
        asm volatile("" : "+r"(o[wd]), "+r"(o[8 + wd]));
        if (t == PFAT) kv_prefetch(pf, task + (1 + PFD) * R.nprep());
      }
      PROFC(tid == 0, 330 + 2 * r);
      const int ph = task & 1;
      task += R.nprep();
      if (ORD == 0 && task < 320) kv_load(P, S, task, tid, k_, v_, sk);
      mbar_wait(BAR(B_E1 + 3)); mbar_wait(BAR(B_AX + 1));
#pragma unroll
      for (int i = 0; i < 4; i++) {
        const int row = 2 * lane + (i >> 1);
        asm volatile("st.shared.v4.u32 [%0],{%1,%2,%3,%4};" ::"r"(sb + KS_OFF + r * 8192 + row * 128 + (((2 * w + ((i & 1) ^ ph)) ^ (row & 7)) << 4)),
                     "r"(o[4 * i]), "r"(o[4 * i + 1]), "r"(o[4 * i + 2]), "r"(o[4 * i + 3]) : "memory");
      }
      __syncwarp();
      mbar_arrive_if(BAR(B_PS + r), lane == 0);
      PROFC(tid == 0, 331 + 2 * r);
      if (ORD == 1 && task < 320) kv_load(P, S, task, tid, k_, v_, sk);
    }
  }
#undef STAT
#undef STATS
  PROFC(tid == 0, 40);
}
#define SPLIT(G) asm volatile("{ .reg .pred p; .reg .u32 r; L: mov.u32 r, %%clock; setp.eq.u32 p, r, %0; @p bra.uni L; }" ::"n"(G) : "memory")
template <bool AUX>
__device__ __forceinline__ void conv_loop(uint32_t sb, uint32_t rc, int wg, int tid, long long t_start) {
  sb = opaque(sb); rc = opaque(rc);
  const uint32_t bars = sb + BAR_OFF;
  int slot = AUX ? 0 : wg + 1;
  mbar_wait(BAR(B_LM));
#pragma unroll 1
  while (slot < (int)((rc >> 10) & 7)) {
    tid = opaque(tid);
    const int w = tid >> 5, lane = tid & 31, g = lane >> 2, q = lane & 3;
    const uint32_t Dn = lds32(sb + MISC_OFF + 4 + 4 * slot);
    const uint32_t d0 = (g == 1 && q == 3 - w) ? Dn : 0, d1 = (g == 0 && q == 3 - w) ? Dn : 0;
    const uint32_t cb_ = conv_buf(sb, slot), c0 = cb_ + KC_OFS;
    const uint32_t abase = c0 + 2 * (2 * (g & 1) + 4 * w + 16 * (g >> 1) + 4 * q);
    const uint64_t bd = make_desc(cb_ + KV_PAD, 16, 256, 3);
    const bool hi = lane & 16, s1 = lane & 8;
    const int qo = hi ? (q + 1) & 3 : q;
    const int srcA = hi ? (lane & 12) | ((q + 1) & 3) : (lane & 12) | 16 | ((q + 3) & 3);
    const bool h3 = hi && q == 3, wrap = s1 && qo == 3, back = wrap && hi;
    const bool chi = wrap ? !hi : hi;
    const int cq = s1 ? (qo + 1) & 3 : qo;
    const int srcB = (lane & 4) | (s1 ? 0 : 8) | (chi ? 16 | ((cq + 3) & 3) : cq);
    const uint32_t gp = c0 + 16 * (2 * (g & 1) + 4 * w) + (chi ? 256 : 0) + 2 * (2 * cq + (s1 ? 0 : 1));
    uint32_t a[12], f[16], o[8];
    float S[4], T[4], U[2], keep[2], pv[2] = {0.f, 0.f}, pr[4] = {0.f, 0.f, 0.f, 0.f};
    float e0[64], e1[56], e2[48], e3[40], e4[32], e5[24], e6[16], e7[8];
#define UNR _Pragma("unroll")
#define PERM() UNR for (int i = 0; i < 4; i++) { f[4 * i] = __byte_perm(a[3 * i], a[3 * i + 1], 0x5432); f[4 * i + 1] = a[3 * i + 1]; \
                                                 f[4 * i + 2] = __byte_perm(a[3 * i + 1], a[3 * i + 2], 0x5432); f[4 * i + 3] = a[3 * i + 2]; }
#define MMA(N, E) UNR for (int i = 0; i < 4; i++) wgmma_rs<N>(E, f[4 * i], f[4 * i + 1], f[4 * i + 2], f[4 * i + 3], bd - 8 * i, 1); wg_commit();
#define L1(c) UNR for (int i = 0; i < 4; i++) { const float ev = c[i], od = c[4 + i]; S[i] = hi ? (h3 ? ev : od) : ev; \
                                                T[i] = __shfl_sync(0xffffffff, hi ? (h3 ? pr[i] : ev) : od, srcA); pr[i] = od; }
#define L1E() UNR for (int i = 0; i < 4; i++) S[i] += T[i];
#define L2() UNR for (int h = 0; h < 2; h++) { keep[h] = back ? pv[h] : S[2 * h + 1]; pv[h] = S[2 * h + 1]; U[h] = __shfl_sync(0xffffffff, S[2 * h], srcB); }
#define L2E(j) o[j] = pack_bf(keep[0] + U[0], keep[1] + U[1]);
#define GRP(G, N, P, E) UNR for (int i = 0; i < N / 2; i++) asm volatile("mov.b32 %0,%1;" : "=f"(E[i]) : "f"(P[i + 8])); \
    wg_fence(); if (G < 7) conv_frags<(G + 1) & 7>(a, abase); if (G >= 2) { L2() } L1(P) MMA(N, E) SPLIT(G); \
    if (G < 7) { PERM() } if (G >= 2) { L2E((G + 6) & 7) } L1E() wg_wait<0>(); fence_regs(E);
    PROFC(tid == 0, 300 + 4 * slot);
    mbar_wait(BAR(B_KF + slot));
    if (tid == 0) PROF(361 + slot);
    PROFC(tid == 0, 301 + 4 * slot);
    conv_frags<0>(a, abase);
    wg_fence();
    wgmma_rs<128>(e0, d0 << 16, d0, d1 << 16, d1, bd, 0);
    PERM() conv_frags<1>(a, abase); wg_fence(); MMA(128, e0) SPLIT(0); PERM() wg_wait<0>(); fence_regs(e0);
    GRP(1, 112, e0, e1) GRP(2, 96, e1, e2) GRP(3, 80, e2, e3) GRP(4, 64, e3, e4) GRP(5, 48, e4, e5) GRP(6, 32, e5, e6) GRP(7, 16, e6, e7)
    PROFC(tid == 0, 302 + 4 * slot);
    L2() L1(e7) L2E(6) L1E() L2() L2E(7)
    bar_sync(wg + 1, 128);
#pragma unroll
    for (int jj = 0; jj < 8; jj++)
      asm volatile("st.shared.u16 [%0],%1; st.shared.u16 [%0+16],%2;" ::"r"(gp + jj * 512), "h"((uint16_t)o[jj]), "h"((uint16_t)(o[jj] >> 16)) : "memory");
#undef PERM
#undef MMA
#undef L1
#undef L1E
#undef L2
#undef L2E
#undef GRP
    PROFC(tid == 0, 303 + 4 * slot);
    __syncwarp();
    if (lane == 0) mbar_arrive(BAR(B_GS + slot));
    if (!AUX) break;
    slot = slot ? slot + 1 : 3;
  }
}

#define IDX(J, c, h) (8 * (J) + 4 * ((c) >> 1) + 2 * (h) + ((c) & 1))
__device__ __forceinline__ uint2 lds2(uint32_t a) { uint2 v; asm volatile("ld.shared.v2.u32 {%0,%1},[%2];" : "=r"(v.x), "=r"(v.y) : "r"(a) : "memory"); return v; }
__device__ __forceinline__ void resid_load(float (&r)[40], uint32_t sb, int wg, int tid, const uint4& s) {
  const uint32_t dp = sb + XR_OFF + 8 * (tid & 3), xp = dp + (64 * wg + 16 * (tid >> 5) + ((tid & 31) >> 2)) * 160;
#pragma unroll
  for (int J = 0; J < 5; J++) {
    const uint2 u = lds2(xp + 32 * J), v = lds2(xp + 32 * J + 1280), d = lds2(dp + 20480 + 32 * J);
    r[8 * J] = __uint_as_float(u.x); r[8 * J + 1] = __uint_as_float(u.y); r[8 * J + 2] = __uint_as_float(v.x); r[8 * J + 3] = __uint_as_float(v.y);
    r[8 * J + 4] = __uint_as_float(d.x); r[8 * J + 5] = __uint_as_float(d.y);
  }
  r[30] = untag(s.x); r[31] = untag(s.y); r[38] = untag(s.z); r[39] = untag(s.w);
}
__device__ __forceinline__ void resid_init(float (&r)[40]) {
  const float s[4] = {r[30], r[31], r[38], r[39]};
#pragma unroll
  for (int J = 0; J < 5; J++) {
    uint32_t w[6];
#pragma unroll
    for (int i = 0; i < 6; i++) w[i] = __float_as_uint(r[8 * J + i]);
#pragma unroll
    for (int i = 0; i < 4; i++) {
      const int h = i >> 1, c = 2 * (i & 1);
      const float rs = s[2 * h], nm = s[2 * h + 1], x0 = bf_lo(w[i]), x1 = bf_hi(w[i]);
      const uint32_t t = hmul2(pack_bf(fmaf(x0, rs, nm), fmaf(x1, rs, nm)), w[4 + (i & 1)]);
      r[IDX(J, c, h)] = x0 + bf_lo(t); r[IDX(J, c + 1, h)] = x1 + bf_hi(t);
    }
  }
}

__device__ __forceinline__ float flip(float v, uint32_t m) { return __uint_as_float(__float_as_uint(v) ^ m); }
__device__ __forceinline__ void g1_phase(const int LY, const Head& H, uint32_t sb, int wg, int tid, Role R, float (&xr)[40], long long t_start) {
  Scratch* const S = H.s;
  tid = opaque(tid); sb = opaque(sb); R.v = opaque(R.v);
  const uint32_t bars = sb + BAR_OFF;
  const int cb = R.cb(), tb = R.tb();
  const int w = tid >> 5, lane = tid & 31, g = lane >> 2, q = lane & 3;
  const bool full = tb < 12;
  uint2* Eb = S->E + ((LY * 130 + cb) * 8 + 4 * wg + w) * 16 + g;
  float a[80];
#pragma unroll
  for (int i = 0; i < 80; i++) a[i] = 0.f;
  uint32_t rel = mapa(BAR(B_E1), lane ? R.wpart() : R.ubase() + (w & (R.ugs() - 1)));
  const bool rels = lane == 0 || (tid == 1 && wg != R.wlo());
  {
    uint64_t tw = LY ? WTAB1 : WTAB0, tx = LY ? XTAB1 : XTAB0;
    uint32_t bf = BAR(B_F1);
    if (tid == 0 && wg == 0 && !LY) PROF(351);
    fence_regs(a);
    mbar_wait(bf, LY);
    if (tid == 0 && wg == 0) PROF(LY ? 20 : 4);
#pragma unroll 1
    for (int kb = 0; kb < 10; kb++) {
      const uint64_t da = make_desc(sb + ((uint32_t)tw & 63) * 4096 + wg * 8192, 16, 1024, 1);
      const uint64_t db = make_desc(sb + ((uint32_t)tx & 63) * 4096, 16, 1024, 1);
      wg_fence();
#pragma unroll
      for (int kk = 0; kk < 4; kk++) wgmma_ss160(a, da + 2 * kk, db + 2 * kk, 1);
      wg_commit();
      wg_wait<1>();
      if (kb > 0) { if (rels) mbar_arrive_at(rel); rel += 8; }
      bf += 8; tw >>= 6; tx >>= 6;
      if (kb < 9) mbar_wait(bf, LY);
    }
  }
  if (tid == 0 && wg == 0) PROF(LY ? 19 : 2);
  mbar_wait(BAR(B_LM));
  const uint32_t tag = lds32(sb + MISC_OFF) & 1;
  if (q == 3) st_rlx2(Eb + tb * 1280, tag ^ 1, tag ^ 1);
  float2 lam, mu, mu2;
  float rs0, rs1;
  const uint32_t lamp = sb + LAM_OFF + 16 * (32 * wg + 8 * w + g);
  {
    const uint2* rp = S->RS + (8 * cb + 4 * wg + w) * 16 + 2 * g - (g & 1);
    uint2 v = ld_rlx2(rp);
    asm volatile("ld.shared.v2.f32 {%0,%1},[%2];" : "=f"(lam.x), "=f"(lam.y) : "r"(lamp));
    const float2 l2 = cmul(lam, lam), l4 = cmul(l2, l2), l8 = cmul(l4, l4), l16 = cmul(l8, l8), l32 = cmul(l16, l16);
    mu = full ? cmul(l32, l8) : l32; mu2 = cmul(mu, mu);
#pragma unroll 1
    for (int it = 0; it < SPIN && __any_sync(0xffffffff, untagged(v, tag)); it++) v = ld_rlx2(rp);
    rs0 = untag(v.x); rs1 = untag(v.y);
  }
  if (tid == 0 && wg == 0 && !LY) PROF(39);
  mbar_wait(BAR(B_ST), LY);
  const uint32_t ssm = sb + SSM_OFF + q * (full ? 336 : 272);
  wg_wait<0>(); fence_regs(a);
  if (rels) mbar_arrive_at(rel);
  if (tid == 0 && wg == 0) PROF(LY ? 21 : 5);
  float2 p = make_float2(0.f, 0.f);
#pragma unroll
  for (int j = 0; j < 20; j++) {
    if (j < 16 || full) {
      float4 sv;
      asm volatile("ld.shared.v4.f32 {%0,%1,%2,%3},[%4];" : "=f"(sv.x), "=f"(sv.y), "=f"(sv.z), "=f"(sv.w) : "r"(ssm + 16 * j));
#pragma unroll
      for (int e = 0; e < 2; e++) {
        const int o = 4 * j + e;
        const float r = e ? sv.z : sv.x, nm = e ? sv.w : sv.y;
        a[o] = fmaf(a[o], r, nm * rs0); a[o + 2] = fmaf(a[o + 2], r, nm * rs1);
        p = cfma(lam, p, make_float2(a[o], a[o + 2]));
      }
    }
  }
  {
    float2 t = make_float2(__shfl_up_sync(0xffffffff, p.x, 1, 4), __shfl_up_sync(0xffffffff, p.y, 1, 4));
    if (q >= 1) p = cfma(mu, t, p);
    t = make_float2(__shfl_up_sync(0xffffffff, p.x, 2, 4), __shfl_up_sync(0xffffffff, p.y, 2, 4));
    if (q >= 2) p = cfma(mu2, t, p);
  }
  if (q == 3 && full) st_rlx2(Eb + tb * 1280, tagf(p.x, tag), tagf(p.y, tag));
  if (tid == 0 && wg == 1) PROF(96 + 64 * LY);
  uint2 ev[3];
#pragma unroll
  for (int i = 0; i < 3; i++) { const int j = tb - 1 - q - 4 * i; ev[i] = j >= 0 ? ld_rlx2(Eb + j * 1280) : make_uint2(tag, tag); }
  float2 x = make_float2(__shfl_up_sync(0xffffffff, p.x, 1, 4), __shfl_up_sync(0xffffffff, p.y, 1, 4));
  if (q == 0) x = make_float2(0.f, 0.f);
  float c0, c1;
  asm volatile("ld.shared.v2.f32 {%0,%1},[%2+8];" : "=f"(c0), "=f"(c1) : "r"(lamp));
  const float c2 = -flip(c1, H.swap), c3 = flip(c0, H.swap);
#pragma unroll
  for (int i = 0; i < 40; i++) {
    const int o = 4 * (i >> 1) + (i & 1);
    const float u = a[o], v = a[o + 2];
    a[o] = fmaf(c0, u, c1 * v); a[o + 2] = fmaf(c2, u, c3 * v);
  }
  fence_regs(a);
  if (LY == 0 && R.b() < 128) {
    const int t0 = 16 * g + 8 * wg + 2 * w;
    if (tid == 0 && wg == 1) PROF(366);
    mbar_wait(BAR(B_XR));
    if (tid == 0 && wg == 1) PROF(367);
    uint4 s = lds4(sb + XR_OFF + 20480 + 256 + 8 * t0);
    if (__any_sync(0xffffffff, untagged(s, tag))) {
#pragma unroll 1
      for (int it = 0; it < SPIN; it++) { s = ld_rlx4(S->S + 128 * (R.b() >> 3) + t0); if (!__any_sync(0xffffffff, untagged(s, tag))) break; }
    }
    resid_load(xr, sb, wg, tid, s);
  }
  float2 mq, om4, fq;
  {
    asm volatile("" : "+f"(lam.x), "+f"(lam.y));
    const float2 one = make_float2(1.f, 0.f), l2 = cmul(lam, lam), l4 = cmul(l2, l2), l8 = cmul(l4, l4), l16 = cmul(l8, l8);
    const float2 l80 = full ? mu2 : cmul(mu2, l16), om = cmul(l80, l80), om2 = cmul(om, om);
    mq = cmul((q & 1) ? mu : one, (q & 2) ? mu2 : one);
    om4 = cmul(om2, om2); fq = cmul((q & 1) ? om : one, (q & 2) ? om2 : one);
  }
  mbar_wait(BAR(B_E1 + 9), LY);
  if (tid == 0 && wg == 1) PROF(368 + LY);
#pragma unroll 1
  for (int it = 0; it < SPIN; it++) {
    const bool m0 = untagged(ev[0], tag), m1 = untagged(ev[1], tag), m2 = untagged(ev[2], tag);
    if (!__any_sync(0xffffffff, m0 || m1 || m2)) break;
    if (m0) ev[0] = ld_rlx2(Eb + (tb - 1 - q) * 1280);
    if (m1) ev[1] = ld_rlx2(Eb + (tb - 5 - q) * 1280);
    if (m2) ev[2] = ld_rlx2(Eb + (tb - 9 - q) * 1280);
  }
  if (tid == 0 && wg == 1) PROF(97 + 64 * LY);
  float2 c = make_float2(untag(ev[2].x), untag(ev[2].y));
#pragma unroll
  for (int i = 1; i >= 0; i--) c = cfma(om4, c, make_float2(untag(ev[i].x), untag(ev[i].y)));
  c = cmul(fq, c);
#pragma unroll
  for (int s = 1; s <= 2; s <<= 1) { c.x += __shfl_xor_sync(0xffffffff, c.x, s); c.y += __shfl_xor_sync(0xffffffff, c.y, s); }
  c = cfma(mq, c, x);
  float2 z = make_float2(fmaf(c0, c.x, c1 * c.y), fmaf(c2, c.x, c3 * c.y));
  if (tid == 0 && wg == 0) PROF(LY ? 22 : 6);
  const float2 lc = make_float2(lam.x, flip(lam.y, H.swap));
  const uint32_t hq = sb + (lane >> 4) * 1024 + (lane & 7) * 128 + (((4 * wg + w) ^ (lane & 7)) << 4);
  const uint32_t hp = hq + R_OFF + (lane & 8) * 2048, hp4 = hq + (LY ? R4_OFF1 : R4_OFF0) + (lane & 8) * 512;
#pragma unroll
  for (int j = 0; j < 20; j += 2) {
    if (j < 16 || full) {
      uint32_t o[4];
#pragma unroll
      for (int i = 0; i < 2; i++) {
        const float2 z0 = cfma(lc, z, make_float2(a[4 * (j + i)], a[4 * (j + i) + 2]));
        z = cfma(lc, z0, make_float2(a[4 * (j + i) + 1], a[4 * (j + i) + 3]));
        o[2 * i] = pack_bf(z0.x, z.x); o[2 * i + 1] = pack_bf(z0.y, z.y);
      }
      asm volatile("stmatrix.sync.aligned.m8n8.x4.trans.shared.b16 [%0], {%1,%2,%3,%4};" ::"r"(j < 16 ? hp + j * 1024 : hp4 + (j - 16) * 1024), "r"(o[0]), "r"(o[1]), "r"(o[2]), "r"(o[3]) : "memory");
      if (j & 2) { __syncwarp(); if (lane == 0) mbar_arrive(BAR(B_SH + j / 4)); }
    }
  }
  if (tid == 0 && wg == 0) PROF(LY ? 23 : 7);
  if (lane == 0) PROF(390 + 4 * wg + w);
}

__device__ __forceinline__ void gate_load(uint32_t (&G)[20], uint32_t sb, int LY, int wg, int tid) {
  const uint32_t bars = sb + BAR_OFF;
  const int lane = tid & 31, w = tid >> 5;
  mbar_wait(BAR(B_GF), LY);
  __syncwarp();
  {
    const uint32_t gb = sb + (LY ? G_OFF1 : G_OFF0) + wg * 10240;
    const int dr = 4 * ((lane & 7) >> 1) + (lane & 1) + 2 * ((lane >> 3) & 1), ck = 2 * w + (lane >> 4);
#pragma unroll
    for (int J = 0; J < 5; J++) {
      const int dd = 16 * J + dr;
      asm volatile("ldmatrix.sync.aligned.m8n8.x4.trans.shared.b16 {%0,%1,%2,%3},[%4];"
                   : "=r"(G[4 * J]), "=r"(G[4 * J + 1]), "=r"(G[4 * J + 2]), "=r"(G[4 * J + 3]) : "r"(gb + dd * 128 + ((ck ^ (dd & 7)) << 4)) : "memory");
    }
  }
}
__device__ __forceinline__ void g2_phase(const int LY, const Params& P, Scratch* S, uint32_t sb, int wg, int tid, Role R, float (&xr)[40], long long t_start) {
  sb = opaque(sb);
  const uint32_t bars = sb + BAR_OFF;
  if (LY) {
    const int td = opaque(tid), b = (opaque(R.v) >> 8) & 255;
    const uint32_t tag = lds32(sb + MISC_OFF) & 1;
    const uint2* sp = S->S + 2 * SEQ + 128 * (b >> 3) + 4 * (td & 28) + 8 * wg + 2 * (td >> 5);
    if (!(R.cb() & 1)) mbar_wait(BAR(B_HD), 1);
    uint2 dl[5];
#pragma unroll
    for (int J = 0; J < 5; J++) dl[J] = __ldg((const uint2*)(P.dskip + 80 * (b & 7) + 4 * (td & 3) + 16 * J));
    uint4 sv;
#pragma unroll 1
    for (int it = 0; it < SPIN; it++) { sv = ld_rlx4(sp); if (!__any_sync(0xffffffff, untagged(sv, tag))) break; }
#pragma unroll
    for (int h = 0; h < 2; h++)
#pragma unroll
      for (int J = 0; J < 5; J++)
#pragma unroll
        for (int c = 0; c < 4; c++) {
          const float x2 = xr[IDX(J, c, h)];
          const uint32_t dw = (c & 2) ? dl[J].y : dl[J].x;
          xr[IDX(J, c, h)] = fmaf(fmaf(x2, untag(h ? sv.z : sv.x), untag(h ? sv.w : sv.y)), (c & 1) ? bf_hi(dw) : bf_lo(dw), x2);
        }
    fence_regs(xr);
  }
  float acc[40];
#pragma unroll
  for (int i = 0; i < 40; i++) acc[i] = RIAT == 1 ? 0.f : xr[i];
  fence_regs(acc);
#define G2_STEP(st, cs, hf) { \
    const uint64_t da = make_desc(sb + H_OFF + (st) * 32768 + (hf) * 16384 + wg * 8192, 16, 1024, 1), db = make_desc(sb + (cs) * 20480 + (hf) * 10240, 16, 1024, 1); \
    wg_fence(); \
    _Pragma("unroll") for (int kk = 0; kk < 4; kk++) wgmma_ss80(acc, da + 2 * kk, db + 2 * kk, 1); \
    wg_commit(); }
  mbar_wait(BAR(B_F2), LY);
  if (tid == 0 && wg == 0) PROF(LY ? 25 : 10);
  G2_STEP(0, 0, 0)
  mbar_wait(BAR(B_F3), LY);
  G2_STEP(0, 0, 1)
  tid = opaque(tid); R.v = opaque(R.v);
  const uint32_t tag = lds32(sb + MISC_OFF) & 1;
  const int b = R.b(), tb2 = b >> 3, db_ = b & 7;
  const int w = tid >> 5, lane = tid & 31, g = lane >> 2, q = lane & 3;
  const int t0 = 128 * tb2 + 16 * g + 8 * wg + 2 * w;
  const int d0 = 80 * db_ + 4 * q, mrow = 64 * wg + 16 * w + g;
#define GATE(J, c, h) (((c) & 1) ? bf_hi(G[4 * (J) + 2 * (h) + ((c) >> 1)]) : bf_lo(G[4 * (J) + 2 * (h) + ((c) >> 1)]))
  uint32_t rel = mapa(BAR(B_E2), lane ? ((w & 1) ? R.wpart() : R.rank()) : R.cs() == 8 ? 4 * wg + w : wg);
  const bool rels = lane == 0 || (lane == 1 && w < 2);
  uint32_t* Mb = S->M + ((2 * LY * 16 + tb2) * 8) * 256 + (wg * 4 + w) * 32 + (2 * g + (q & 1)) * 2 + (q >> 1);
  {
    uint32_t bf = BAR(B_F2 + 1), st = 1, ra = rel + 8 * (B_EA - B_E2);
#pragma unroll 1
    for (int kp = 1; kp < 10; kp++) {
      const bool more = LY == 0 || kp < 8;
      wg_wait<1>();
      if (lane == 0 && more) mbar_arrive_at(ra + 8 * (st ? st - 1 : 2));
      mbar_wait(bf, LY);
      G2_STEP(st, kp < 5 ? kp : kp - 5, 0)
      wg_wait<1>();
      if (rels && more) mbar_arrive_at(rel);
      rel += 8;
      mbar_wait(bf + 8 * (B_F3 - B_F2), LY);
      G2_STEP(st, kp < 5 ? kp : kp - 5, 1)
      if (kp == MIAT) {
        st_rlx(Mb + db_ * 256, tag ^ 1);
        if (LY == 0) st_rlx(Mb + (16 * 8 + db_) * 256, tag ^ 1);
      }
      bf += 8; st = st == 2 ? 0 : st + 1;
    }
  }
  wg_wait<0>(); fence_regs(acc);
  if (LY == 0 && rels) mbar_arrive_at(rel);
  if (tid == 0 && wg == 0) PROF(LY ? 26 : 11);
  if (lane == 0) PROF(116 + 64 * LY + wg * 4 + w);

  float mm[2] = {0.f, 0.f}, rr[2];
#pragma unroll 1
  for (int rep = 0;; rep++) {
    float m[2][2];
#pragma unroll
    for (int h = 0; h < 2; h++) {
      m[h][0] = m[h][1] = 0.f;
#pragma unroll
      for (int J = 0; J < 5; J++)
#pragma unroll
        for (int c = 0; c < 4; c++) { const float xv = acc[IDX(J, c, h)]; m[h][0] += xv; m[h][1] = fmaf(xv, xv, m[h][1]); }
    }
    float r1[2];
#pragma unroll
    for (int i = 0; i < 2; i++) { const float snd = (q & 1) ? m[0][i] : m[1][i], kp = (q & 1) ? m[1][i] : m[0][i]; r1[i] = kp + __shfl_xor_sync(0xffffffff, snd, 1); }
    const float r2 = ((q & 2) ? r1[1] : r1[0]) + __shfl_xor_sync(0xffffffff, (q & 2) ? r1[0] : r1[1], 2);
    const uint32_t mx = sb + MX_OFF + 512 * wg + 4 * tid, bx = BAR(B_KF + 1 + (PWG ? 2 * LY + wg : LY));
    if (R.cs() == 8 && !rep) {
      float v[4];
#pragma unroll
      for (int i = 0; i < 4; i++) v[i] = __shfl_sync(0xffffffff, r2, i, 4);
#pragma unroll
      for (int i = 0; i < 2; i++)
        asm volatile("st.async.weak.shared::cluster.mbarrier::complete_tx::bytes.v4.f32 [%0],{%1,%2,%3,%4},[%5];" ::"r"(mapa(mx - 4 * q + 1024 * db_, (q + 4 * i) ^ db_)),
                     "f"(v[0]), "f"(v[1]), "f"(v[2]), "f"(v[3]), "r"(mapa(bx, (q + 4 * i) ^ db_)) : "memory");
      if (tid == 0 && (PWG || wg == 0)) mbar_expect_tx(bx, PWG ? 4096 : 8192);
    }
    st_rlx(Mb + db_ * 256, tagf(r2, tag));
    if (rep) break;
    if (lane == 0) PROF(100 + 64 * LY + wg * 4 + w);
    uint32_t G[20];
    const bool late = LY == 0 && db_ >= GLATE;
#pragma unroll
    for (int i = 0; i < 20; i++) G[i] = 0;
    if (!late) gate_load(G, sb, LY, wg, tid);
    mbar_wait(BAR(B_CD + 1));
    uint32_t mv[8];
    if (R.cs() == 8) {
      mbar_wait(bx, 1);
#pragma unroll
      for (int i = 0; i < 8; i++) mv[i] = lds32(mx + 1024 * i);
    } else {
#pragma unroll
    for (int i = 0; i < 8; i++) mv[i] = ld_rlx(Mb + i * 256);
#pragma unroll 1
    for (int it = 0; it < SPIN; it++) {
      uint32_t miss = 0;
#pragma unroll
      for (int i = 0; i < 8; i++) miss |= ((mv[i] ^ tag) & 1) << i;
      if (!__any_sync(0xffffffff, miss)) break;
#pragma unroll
      for (int i = 0; i < 8; i++) if ((miss >> i) & 1) mv[i] = ld_rlx(Mb + i * 256);
    }
      bar_sync(4, 256);
    }
    if (lane == 0) PROF(108 + 64 * LY + wg * 4 + w);
    const float s = ((untag(mv[0]) + untag(mv[1])) + (untag(mv[2]) + untag(mv[3]))) + ((untag(mv[4]) + untag(mv[5])) + (untag(mv[6]) + untag(mv[7])));
    const float o = __shfl_xor_sync(0xffffffff, s, 2);
    const float S1 = (q & 2) ? o : s, S2 = (q & 2) ? s : o;
    const float mean = S1 * (1.f / DM), rs = frsqrt(fmaxf(S2 * (1.f / DM) - mean * mean, 0.f) + 1e-5f);
    const float mo = __shfl_xor_sync(0xffffffff, mean, 1), ro = __shfl_xor_sync(0xffffffff, rs, 1);
    mm[0] = (q & 1) ? mo : mean; mm[1] = (q & 1) ? mean : mo; rr[0] = (q & 1) ? ro : rs; rr[1] = (q & 1) ? rs : ro;
    if (late) gate_load(G, sb, LY, wg, tid);
    if (tid == 0 && wg == 0) PROF(LY ? 27 : 12);
    const float nm[2] = {-mm[0] * rr[0], -mm[1] * rr[1]};
    if (LY) mm[0] = mm[1] = 0.f;
#pragma unroll
    for (int h = 0; h < 2; h++)
#pragma unroll
      for (int J = 0; J < 5; J++)
#pragma unroll
        for (int c = 0; c < 4; c++) { const float xv = acc[IDX(J, c, h)]; acc[IDX(J, c, h)] = fmaf(fmaf(xv, rr[h], nm[h]), GATE(J, c, h), xv - mm[h]); }
    if (LY) break;
    if (PWG && R.cs() == 8) mbar_wait(BAR(B_KF + 2 - wg), 1);
#pragma unroll
    for (int i = 0; i < 10; i++) {
      const int J = i >> 1, h = i & 1;
      const uint32_t u0 = pack_bf(acc[IDX(J, 0, h)], acc[IDX(J, 1, h)]), u1 = pack_bf(acc[IDX(J, 2, h)], acc[IDX(J, 3, h)]);
      asm volatile("st.shared.v2.u32 [%0],{%1,%2};" ::"r"(sb + US_OFF + (mrow + 8 * h) * 160 + 32 * J + 8 * q), "r"(u0), "r"(u1) : "memory");
    }
    __syncwarp();
    if (lane == 0) mbar_arrive(BAR(B_SG));
    if (tid == 0 && wg == 0) PROF(13);
    Mb += 16 * 8 * 256;
  }
  if (LY == 0) {
#pragma unroll
    for (int i = 0; i < 40; i++) xr[i] = acc[i] + mm[(i >> 1) & 1];
    if (tid == 0 && wg == 0) PROF(15);
  }
  else {
    float* op = P.out + (size_t)t0 * DM + d0;
#pragma unroll
    for (int i = 0; i < 10; i++) {
      const int J = i >> 1, h = i & 1;
      asm volatile("st.global.v4.f32 [%0],{%1,%2,%3,%4};" ::"l"(op + h * DM + 16 * J),
                   "f"(acc[IDX(J, 0, h)]), "f"(acc[IDX(J, 1, h)]), "f"(acc[IDX(J, 2, h)]), "f"(acc[IDX(J, 3, h)]) : "memory");
    }
  }
  if (tid == 0 && wg == 0 && LY) PROF(28);
#undef IDX
#undef GATE
}

__device__ __forceinline__ void next_stats(Scratch* S, uint32_t sb, int tb2, int tid) {
  const uint32_t bars = sb + BAR_OFF, tag = lds32(sb + MISC_OFF) & 1;
  const uint32_t* Mb = S->M + tb2 * 8 * 256 + 2 * tid;
  mbar_wait(BAR(B_F1 + NSAT), 1);
  float m1, s1, s2;
#pragma unroll 1
  for (int it = 0; it < SPIN; it++) {
    uint32_t a[8], miss = 0;
    uint2 v[8];
#pragma unroll
    for (int i = 0; i < 8; i++) { a[i] = ld_rlx(Mb + i * 256); v[i] = ld_rlx2((const uint2*)(Mb + (16 * 8 + i) * 256)); }
#pragma unroll
    for (int i = 0; i < 8; i++) miss |= (a[i] ^ tag) | (v[i].x ^ tag) | (v[i].y ^ tag);
#define SUM8(F) ((untag(F(0)) + untag(F(1))) + (untag(F(2)) + untag(F(3)))) + ((untag(F(4)) + untag(F(5))) + (untag(F(6)) + untag(F(7))))
#define FA(i) a[i]
#define FX(i) v[i].x
#define FY(i) v[i].y
    m1 = SUM8(FA); s1 = SUM8(FX); s2 = SUM8(FY);
    if (!__any_sync(0xffffffff, miss & 1)) break;
  }
  const float mean = s1 * (1.f / DM), rs = frsqrt(fmaxf(s2 * (1.f / DM) - mean * mean, 0.f) + 1e-5f);
  uint2* sp = S->S + SEQ + 128 * tb2 + 8 * (tid & 14) + 2 * (tid >> 4) + (tid & 1);
  st_rlx2(sp, tagf(rs, tag), tagf(-mean * rs, tag));
  st_rlx2(sp + SEQ, tagf(rs, tag), tagf(-(mean + m1 * (1.f / DM)) * rs, tag));
}
template <int I0, int I1> __device__ __forceinline__ void init_barriers(uint32_t bars) {
#pragma unroll
  for (int i = I0; i < I1; i++) mbar_init(BAR(i), bar_count(i));
}
__device__ __forceinline__ int g2_cb(int kp) { return kp < 5 ? 2 * kp : 2 * kp - 9; }
__device__ __forceinline__ const unsigned* h_flag(Scratch* S, int ly, int tb2, int lane) {
  const int s0 = 128 * min(tb2, 15) / 160;
  const bool two = (128 * tb2 + 127) / 160 != s0;
  return &S->flag[(F_H + (ly * 13 + s0) * 10 + min(lane & 15, 9) + (two && lane >= 16 ? 10 : 0)) * 32];
}
__device__ __forceinline__ void gate_tile(const Params& P, uint32_t dst, uint32_t bar, int tb2, int db) {
  mbar_expect_tx(bar, 20480);
  tma2d(dst, &P.mGT, tb2 * 128, db * 80, bar);
  tma2d(dst + 10240, &P.mGT, tb2 * 128 + 64, db * 80, bar);
}
__global__ void __cluster_dims__() __launch_bounds__(512, 1) fused_kernel(const Head H, const __grid_constant__ Params P) {
  extern __shared__ __align__(1024) uint8_t smem[];
  const uint32_t sb = opaque(smem_u32(smem)), bars = sb + BAR_OFF;
  const int wi = __shfl_sync(0xffffffff, threadIdx.x >> 5, 0), wg = wi >> 2, tid = threadIdx.x & 127;
  const int umap = blockIdx.x >= 96;
#define CLK(v)
  CLK(c_a);
  if (wi == 14) {
    if (elect_one()) { init_barriers<0, NBAR1>(bars); asm volatile("fence.mbarrier_init.release.cluster;" ::: "memory"); }
    __syncwarp();
  } else if (wi >= 12) prefetch_map(wi == 12 ? &P.mB : &P.mA[umap]);
  else if (wg == 2) xb_prefetch<1>(H, blockIdx.x + H.base, tid, 0);
  else if (P.role[blockIdx.x].w) return;
  CLK(c_b);
  asm volatile("barrier.cluster.arrive.relaxed.aligned;" ::: "memory");
  CLK(c_c);
  Role R;
  { const uint4 r = P.role[blockIdx.x]; R.v = r.x; R.c = r.y; R.p = r.z; }
  const int id = R.c & 255;
  const int tb = R.tb(), cb = R.cb(), b = R.b(), tb2 = b >> 3, db = b & 7, rank = R.rank();
  const bool has1 = tb <= 12, has2 = b < 128, full = tb < 12;
  Scratch* const S = H.s;
  unsigned* const epoch_p = &S->epoch[id * 8];
  const long long t_start = 0;
  if (wg < 2) {
    if (threadIdx.x == 0) PROF(50);
    asm volatile("griddepcontrol.launch_dependents;");
    bar_sync(6, 448);
    asm volatile("setmaxnreg.inc.sync.aligned.u32 176;");
    float xr[40];
#pragma unroll
    for (int i = 0; i < 40; i++) xr[i] = 0.f;
#pragma unroll 1
    for (int ly = 0; ly < 2; ly++) {
      if (has1) g1_phase(ly, H, sb, wg, tid, R, xr, t_start);
      if (ly == 0) {
        resid_init(xr); fence_regs(xr);
        conv_loop<false>(sb, R.c, wg, tid, t_start);
        if (tid == 0 && wg == 0) PROF(9);
      }
      if (has2) g2_phase(ly, P, S, sb, wg, tid, R, xr, t_start);
    }
    if (tid == 0 && wg == 0) st_rlx(epoch_p, lds32(sb + MISC_OFF));
  } else if (wg == 2) {
    bar_sync(6, 448);
    if (has1) aux_prep(H, P, sb, R, tid, t_start);
    asm volatile("setmaxnreg.inc.sync.aligned.u32 136;");
    conv_loop<true>(sb, R.c, wg, tid, t_start);
    if (tid == 0) PROF(44);
    {
      const uint32_t bb = (P.role[blockIdx.x].x >> 8) & 255;
      if ((bb & 132) == NSDB && tid < 32) next_stats(H.s, sb, bb >> 3, 32 * (bb & 3) + tid);
    }
  } else {
    if (threadIdx.x == 384) PROF(354);
    asm volatile("setmaxnreg.dec.sync.aligned.u32 24;");
    const int wlo = R.wlo(), whi = R.whi();
    const uint32_t wmask = R.wmask(), umask = R.umask(), f1bytes = full ? 36864 : 32768;
    if (wi < 14) {
      if (threadIdx.x == 384) PROF(340);
      asm volatile("barrier.cluster.wait.aligned;" ::: "memory");
      if (has1 && elect_one()) {
        uint64_t tab = wi == 12 ? WTAB0 : XTAB0;
        PROF(329 + wi);
#pragma unroll 1
        for (int kb = 0; kb < 6; kb++, tab >>= 6) {
          const uint32_t dst = sb + ((uint32_t)tab & 63) * 4096;
          if (wi == 12) {
#pragma unroll 1
            for (int h = wlo; h <= whi; h++) tma4d_mc(dst + h * 8192, &P.mB, kb * 64, 0, 0, 8 * cb + 4 * h, BAR(B_F1 + kb), wmask);
          } else {
            tma4d_mc(dst + R.uj() * 1024, &P.mA[umap], kb * 64, 0, 0, 80 * tb + R.uj(), BAR(B_F1 + kb), umask);
            mbar_expect_tx(BAR(B_F1 + kb), f1bytes);
          }
        }
      }
      if (!has1 && wi == 13) bar_sync(7, 64);
    } else {
      if (wi == 15 && elect_one()) { init_barriers<NBAR1, NBAR>(bars); asm volatile("fence.mbarrier_init.release.cluster;" ::: "memory"); }
      bar_sync(6, 448);
      if (!has1 && wi == 14) bar_sync(7, 64);
    }
    const unsigned e1 = ld_rlx(epoch_p) + 1;
    if (wi == 12) {
      if (elect_one()) {
#pragma unroll 1
        for (int ly = 0; ly < 2; ly++) {
#pragma unroll 1
          for (int i = ly ? 0 : 6; i < 10 && has1; i++) {
            const int kb = (0x9876541032ull >> (4 * i)) & 15;
            if (ly == 0) { mbar_wait(BAR(B_E1 + ((DEP0 >> (4 * kb - 24)) & 15))); mbar_wait(BAR(B_AX + (kb == 9))); }
            else {
              if (has2 && i == (db >= GLATE ? 4 : 2)) {
                wait_cnt(&S->cnt[(C_G + db) * 32], e1 * 80);
                mbar_wait(BAR(B_E2 + 7));
                PROF(47);
                gate_tile(P, sb + G_OFF0, BAR(B_GF), tb2, db);
              }
              if (has2) mbar_wait(BAR(i < 4 ? B_E2 + ((0x9865u >> (4 * i)) & 15) : B_GE));
              else if (i == 0) { mbar_wait(BAR(B_E1 + 9)); mbar_wait(BAR(B_CD + 1)); }
              if (i >= 4) mbar_wait(BAR(i < 6 ? B_F1 + W4AT : B_E1 + i - 6), 1);
            }
            const uint32_t dst = sb + ((uint32_t)((ly ? WTAB1 : WTAB0) >> (6 * kb)) & 63) * 4096;
#pragma unroll 1
            for (int h = wlo; h <= whi; h++) tma4d_mc(dst + h * 8192, &P.mB, kb * 64, 0, 0, 8 * cb + 4 * h, BAR(B_F1 + kb), wmask);
          }
          if (has2) {
            if (ly == 0) {
              mbar_wait(BAR(B_E1 + XRAT));
              mbar_expect_tx(BAR(B_XR), 20480 + 160 + 1024);
              tma4d(sb + XR_OFF, &P.mX, 80 * db, tb2, BAR(B_XR));
              bulk_g2s(sb + XR_OFF + 20480, P.dskip + 80 * db, 160, BAR(B_XR));
              bulk_g2s(sb + XR_OFF + 20480 + 256, S->S + 128 * tb2, 1024, BAR(B_XR));
              if (CWAIT) mbar_wait(BAR(CWAIT == 1 ? B_KF + 2 : CWAIT == 2 ? B_KF + R.nch() - 1 : CWAIT == 3 ? B_KF + R.nch() - 2 : B_HD));
            }
#pragma unroll 1
            for (int kp = 0; kp < 10; kp++) {
              const uint32_t dst = sb + (kp < 5 ? kp : kp - 5) * 20480;
              mbar_wait(BAR(kp >= 5 ? B_E2 + kp - 5 : ly ? B_E1 + ((CTAB1 >> (4 * kp)) & 15) : kp < 3 ? B_SH : kp < 4 ? B_HD : B_CD), ly);
              mbar_expect_tx(BAR(B_F2 + kp), 10240 + 16384);
              tma5d(dst, &P.mC[0], g2_cb(kp) * 64, db * 5, BAR(B_F2 + kp));
              mbar_expect_tx(BAR(B_F3 + kp), 10240 + 16384);
              tma5d(dst + 10240, &P.mC[1], g2_cb(kp) * 64, db * 5, BAR(B_F3 + kp));
              if (ly && kp == 4) { mbar_wait(BAR(B_E1 + 9), 1); gate_tile(P, sb + G_OFF1, BAR(B_GF), tb2, db); }
            }
          }
        }
      }
    } else if (wi == 13) {
      const int h0 = R.cs() == 8 ? rank : 4 * rank;
#pragma unroll 1
      for (int ly = 0; ly < 2; ly++) {
        int lane = lane_id();
        if (has1) {
          const unsigned* fp = &S->flag[(F_U3 + 8 * ((160 * tb) >> 7) + (lane & (full ? 15 : 7))) * 32];
          uint32_t ready = ly ? __ballot_sync(0xffffffff, ld_rlx(fp) == e1) : ~0u;
          if (ly) mbar_wait(BAR(XEARLY && full ? B_KF + 1 : has2 ? B_SG : B_RF1), XEARLY && full);
          if (PWG && XEARLY && ly && full) mbar_wait(BAR(B_KF + 2), 1);
#pragma unroll 1
          for (int kb = ly ? 0 : 6; kb < 10; kb++) {
            if (ly && kb == UPAT) { mbar_wait(BAR(B_XR)); ready = ~0u; }
            wait_flags(fp, e1, 0x101u * ((1u << (64 * kb / 80)) | (1u << ((64 * kb + 63) / 80))), ready);
            if (kb >= 4) mbar_wait(BAR(B_E1 + (ly ? kb - 4 : (DEP0 >> (4 * kb - 24)) & 15)), ly);
            mbar_wait(BAR(B_AX + (kb == 9)));
            if (elect_one()) {
              if (ly && kb == 0) PROF(34);
              tma4d_mc(sb + ((uint32_t)((ly ? XTAB1 : XTAB0) >> (6 * kb)) & 63) * 4096 + R.uj() * 1024, &P.mA[2 * ly + umap], kb * 64, 0, 0, 80 * tb + R.uj(),
                       BAR(B_F1 + kb), umask);
              mbar_expect_tx(BAR(B_F1 + kb), f1bytes);
            }
            __syncwarp();
          }
        }
        if (ly == 0) {
          if (has1) mbar_wait(BAR(B_E1 + KPF));
          if (elect_one()) {
#pragma unroll 1
            for (int s = 0; s < R.nch(); s++) prefetch_l2(P.ssmk + (size_t)R.ch(s) * SEQ, 4096);
          }
          lane = lane_id();
#pragma unroll
          for (int s = 0; s < 5; s++) {
            asm volatile("st.shared.v4.u32 [%0],{%1,%1,%1,%1};" ::"r"(conv_buf(sb, s) + 16 * lane), "r"(0) : "memory");
            asm volatile("st.shared.u8 [%0],%1;" ::"r"(conv_buf(sb, s) + KC_OFS + lane), "r"(0) : "memory");
          }
          fence_async();
          __syncwarp();
          const unsigned* cp = &S->cnt[(C_KV + (R.ch(min(lane, R.nch() - 1)) >> 6)) * 32];
          uint32_t ready = 0;
#pragma unroll 1
          for (int s = 0, sk = 0; s < R.nch(); s++) {
#pragma unroll 1
            for (; sk < (s ? R.nch() : KUP); sk++)
              if (elect_one()) { mbar_expect_tx(BAR(B_KF + sk), 8192); bulk_g2s(conv_buf(sb, sk) + KC_OFS + 32, P.ssmk + (size_t)R.ch(sk) * SEQ, 4096, BAR(B_KF + sk)); }
            PROFC(s == 0, 329);
#pragma unroll 1
            for (int it = 0; !((ready >> s) & 1) && it < SPIN; it++) ready = __ballot_sync(0xffffffff, (int)(ld_rlx(cp) - e1 * 32) >= 0);
            PROFC(s == 0, 30);
            if (elect_one()) {
              bulk_g2s(conv_buf(sb, s) + KV_PAD, S->kv + (size_t)R.ch(s) * SEQ, 4096, BAR(B_KF + s));
              if (s == 0 && has2) { prefetch_l2(P.cre + (size_t)5 * b * DM, 5 * DM * 2); prefetch_l2(P.cim + (size_t)5 * b * DM, 5 * DM * 2); }
            }
            __syncwarp();
          }
          PROF(31);
          if (!has1) return;
        }
        lane = lane_id();
        const unsigned* fp = h_flag(S, ly, tb2, lane);
        uint32_t ready = __ballot_sync(0xffffffff, ld_rlx(fp) == e1), st = 0;
        if (ly == 0 && !has2) {
          mbar_wait(BAR(B_HD));
          if (lane < 8) mbar_arrive_cl(BAR(B_RF1), lane & 1);
        }
        if (has2) {
          mbar_wait(BAR(B_RF0), ly);
#pragma unroll 1
          for (int kp = 0; kp < 10; kp++) {
            if (kp == 5) { mbar_wait(BAR(B_XR), 1); ready = ~0u; }
            if (kp == 2) { mbar_wait(BAR(B_HD), ly); if (lane < 8) mbar_arrive_cl(BAR(B_RF1), lane & (R.cs() - 1)); }
            wait_flags(fp, e1, 0x10001u << g2_cb(kp), ready);
            if (kp == 2) mbar_wait(BAR(B_RF1), ly);
#pragma unroll
            for (int hf = 0; hf < 2; hf++) {
              if (kp >= 3) { if (hf) mbar_wait(BAR(B_E2 + kp - 3), ly); else mbar_wait(BAR(B_EA + st), ly ^ (kp >= 6 && kp < 9)); }
              if (elect_one()) {
                if (kp == 0 && !hf) PROF(33 + 2 * ly);
                tma4d_mc(sb + H_OFF + st * 32768 + hf * 16384 + h0 * 2048, &P.mH, g2_cb(kp) * 128 + hf * 64, 0, 2 * h0,
                         ly * 16 + tb2, BAR((hf ? B_F3 : B_F2) + kp), (1u << R.cs()) - 1);
              }
              __syncwarp();
            }
            st = st == 2 ? 0 : st + 1;
          }
        }
      }
    } else if (wi == 14) {
      if (!has1) return;
      prefetch_if(P.dskip + 64 * (tid & 31), (tid & 31) < 10);
      if (elect_one()) { prefetch_map(&P.sK); prefetch_map(&P.mX); prefetch_map(&P.sH); prefetch_map(&P.sU); prefetch_map(&P.sO); prefetch_map(&P.mC[0]); prefetch_map(&P.mC[1]); prefetch_map(&P.mH); prefetch_map(&P.mGT); prefetch_map(&P.mA[2 + umap]); }
      __syncwarp();
#pragma unroll 1
      for (int ly = 0; ly < 2; ly++) {
        if (ly) {
          mbar_wait(BAR(B_F1 + 1), 1);
          uint32_t ready = 0;
          wait_flags(&S->flag[(F_U3 + 8 * ((160 * tb) >> 7) + ((lane_id() + ly) & (full ? 15 : 7))) * 32], e1, ~0u, ready);
          if (elect_one()) mbar_arrive(BAR(B_XR));
        }
        const int lane = lane_id();
        mbar_wait(BAR(B_E1 + (ly ? STAT_AT1 : STAT_AT)), ly);
        PROFC(lane == 0 && ly == 0, 36);
        {
          const int l = lane - (full ? 0 : 16);
          const uint2* p = S->S + ly * SEQ + 160 * tb + 2 * l;
          uint4 v[3];
#pragma unroll 1
          for (int it = 0; it < SPIN; it++) {
            v[0] = ld_rlx4(p); v[1] = ld_rlx4(p + 64); v[2] = ld_rlx4(p + 96);
            const bool miss = __any_sync(0xffffffff, untagged(v[0], e1 & 1) | untagged(v[1], e1 & 1) | untagged(v[2], e1 & 1));
            PROFC(lane == 0 && ly == 0 && it == 0, 37);
            if (!miss) break;
          }
          PROFC(lane == 0 && ly == 0, 38);
#pragma unroll
          for (int i = 0; i < 3; i++) {
            const int pr = l + (i == 2 ? 48 : 32 * i);
            if (pr >= 0) asm volatile("st.shared.v4.u32 [%0],{%1,%2,%3,%4};" ::"r"(sb + SSM_OFF + 16 * (pr + ((pr * (full ? 205 : 256)) >> 12))), "r"(v[i].x & ~1u),
                                      "r"(v[i].y & ~1u), "r"(v[i].z & ~1u), "r"(v[i].w & ~1u) : "memory");
          }
          __syncwarp();
        }
        if (lane == 0) mbar_arrive(BAR(B_ST));
        if (ly && has2) {
          mbar_wait(BAR(B_E1 + 9), 1);
          if (lane < 8) mbar_arrive_cl(BAR(B_RF0), lane & (R.cs() - 1));
        }
        if (lane == 0) {
#pragma unroll 1
          for (int pc = 0; pc < (full ? 5 : 4); pc++) {
            if ((HWM >> (4 * pc)) & 8) {
              mbar_wait(BAR(B_SH + min((HWM >> (4 * pc)) & 7, full ? 4 : 3)), ly);
              PROF(380 + 5 * ly + pc);
              if (pc == 0 && (cb & 1)) delay(ly ? HDLY : HDLY0);
              fence_async();
            }
#pragma unroll
            for (int i = 0; i < 2; i++) tma4d_store(&P.sH, sb + (pc < 4 ? R_OFF + i * 16384 + pc * 4096 : (ly ? R4_OFF1 : R4_OFF0) + i * 4096), 128 * cb + 64 * i, 0, 0, ly * 1024 + 80 * tb + 4 * pc);
          }
          bulk_commit(); bulk_wait();
          PROF(ly ? 17 : 16);
          mbar_arrive(BAR(B_HD));
          release<1>();
          signal_flag(&S->flag[(F_H + (ly * 13 + tb) * 10 + cb) * 32], e1);
          PROF(ly ? 24 : 8);
        }
        __syncwarp();
        if (has2) {
          mbar_wait(BAR(B_F2 + FPAT), ly);
          uint32_t ready = 0;
          wait_flags(h_flag(S, ly, tb2, lane_id() | 1), e1, ~0u, ready);
          if (elect_one()) mbar_arrive(BAR(B_XR));
        }
        if (lane == 0 && has2 && !(ODIR && ly)) {
          mbar_wait(BAR(B_SG), ly);
          if (!(ly ? ODIR : UDIR)) {
          fence_async();
          tma4d_store(ly ? &P.sO : &P.sU, sb + (ly ? OS_OFF : US_OFF), 80 * db, 0, 0, tb2);
          bulk_commit(); bulk_wait();
          }
          if (ly == 0) { PROF(18); mbar_arrive(BAR(B_GE)); mbar_arrive_cl(BAR(B_GE), R.wpart()); release<2>(); signal_flag(&S->flag[(F_U3 + b) * 32], e1); }
          PROF(ly ? 29 : 14);
        }
        __syncwarp();
      }
    } else {
      discretise(H, P, sb, R, tid & 31, e1);
      if (elect_one()) {
        mbar_arrive(BAR(B_LM));
        PROF(348);
        if (b < R.nprep()) {
#pragma unroll 1
          for (int task = b, r = 0; task < 320; task += R.nprep(), r++) {
            mbar_wait(BAR(B_PS + r));
            PROF(320 + 3 * r);
            fence_async();
            tma2d_store(&P.sK, sb + KS_OFF + r * 8192, 64 * (task & 31), 64 * (task >> 5));
            bulk_commit(); bulk_wait();
            PROF(321 + 3 * r);
            release<4>();
            signal_cnt(&S->cnt[(C_KV + (task >> 5)) * 32], 1);
            PROF(322 + 3 * r);
          }
          PROF(41);
        }
        if (has2) {
          mbar_wait(BAR(B_SH));
#pragma unroll 1
          for (int i = 0; i < 8; i++) mbar_arrive_cl(BAR(B_RF0), i & (R.cs() - 1));
        }
#pragma unroll 1
        for (int s = 0, s0 = 0; s < R.nch(); s++) {
          mbar_wait(BAR(B_GS + s));
          fence_async();
          bulk_s2g(S->gt + (size_t)R.ch(s) * SEQ, conv_buf(sb, s) + KC_OFS, 4096); bulk_commit();
          if (s == 1 || s >= R.nch() - GSPL) bulk_wait();
          if (s == 1 || s == R.nch() - 1) mbar_arrive(BAR(B_CD + (s > 1)));
          if (s >= R.nch() - GSPL) {
            PROF(45);
            release<8>();
#pragma unroll 1
            for (; s0 <= s; s0++) signal_cnt(&S->cnt[(C_G + R.ch(s0) / 80) * 32], 1);
          }
        }
        PROF(46);
      }
    }
  }
}

typedef CUresult (*EncFn)(CUtensorMap*, CUtensorMapDataType, cuuint32_t, void*, const cuuint64_t*, const cuuint64_t*, const cuuint32_t*,
                          const cuuint32_t*, CUtensorMapInterleave, CUtensorMapSwizzle, CUtensorMapL2promotion, CUtensorMapFloatOOBfill);
bool enc(EncFn f, CUtensorMap* m, const void* base, int rank, const cuuint64_t* dims, const cuuint64_t* strides, const cuuint32_t* box, bool swz,
         bool f32 = false) {
  const cuuint32_t es[5] = {1, 1, 1, 1, 1};
  return f(m, f32 ? CU_TENSOR_MAP_DATA_TYPE_FLOAT32 : CU_TENSOR_MAP_DATA_TYPE_BFLOAT16, rank, const_cast<void*>(base), dims, strides, box, es,
           CU_TENSOR_MAP_INTERLEAVE_NONE, swz ? CU_TENSOR_MAP_SWIZZLE_128B : CU_TENSOR_MAP_SWIZZLE_NONE, CU_TENSOR_MAP_L2_PROMOTION_L2_256B,
           CU_TENSOR_MAP_FLOAT_OOB_FILL_NONE) == CUDA_SUCCESS;
}
void make_roles(Params& P, bool big) {
  for (uint32_t bx = 0; bx < (big ? 120u : 12u); bx++) {
    const uint32_t c = bx >> 3, r = bx & 7, id = big ? bx : 120 + bx;
    const uint32_t vA = c < 12 ? (2 * (c >> 1) + (r >> 2)) | (4 * (c & 1) + (r & 3)) << 4 | (r & 4) << 16 | 4 << 19 | (r ^ 4) << 22
                               : (4 * (c - 12) + (r >> 1)) | (8 + (r & 1)) << 4 | (r & 6) << 16 | 2 << 19 | (r ^ 2) << 22;
    const uint32_t vB = (bx < 10 ? 12 : 13) | bx << 4 | 2 << 19 | (bx & 1) << 22 | (bx & 1) << 26;
    P.role[bx].x = (big ? vA | r << 26 | 1u << 29 : vB) | (id < 128 ? (id & ~7u) | (r >> 1) | (r & 1) << 2 : id) << 8;
    P.role[bx].y = id | (big ? 5 : bx < 8 ? 3 : 4) << 10 | 120 << 13 | 132 << 21 | (big ? 4u : 3u) << 29;
    const uint32_t v = P.role[bx].x, cb = (v >> 4) & 15, rank = (v >> 26) & 7, ubase = (v >> 16) & 7, ugs = (v >> 19) & 7, wp = (v >> 22) & 7;
    const uint32_t wlo = rank > wp, whi = wp != rank ? wlo : 1, wmask = 1u << rank | 1u << wp;
    const uint32_t uj = (rank - ubase) * (!big ? 8 : ugs == 4 ? 5 : 10), sm = big ? (0x7296418530ull >> (4 * cb)) & 15 : bx < 8 ? 4 * (bx & 1) + (bx >> 1) : 15;
    P.role[bx].z = wlo | whi << 1 | wmask << 2 | ((1u << ugs) - 1) << (10 + ubase) | uj << 20 | sm << 25;
    P.role[bx].w = 0;
  }
}
void launch(const Head& H, const Params& P, int grid, int cs, bool dependent) {
  cudaLaunchConfig_t cfg = {};
  cfg.gridDim = grid; cfg.blockDim = 512; cfg.dynamicSmemBytes = SMEM_BYTES; cfg.stream = cudaStreamPerThread;
  cudaLaunchAttribute at[2];
  at[0].id = cudaLaunchAttributeClusterDimension; at[0].val.clusterDim.x = cs; at[0].val.clusterDim.y = 1; at[0].val.clusterDim.z = 1;
  at[1].id = cudaLaunchAttributeProgrammaticStreamSerialization; at[1].val.programmaticStreamSerializationAllowed = 1;
  cfg.attrs = at; cfg.numAttrs = dependent ? 2 : 1;
  cudaLaunchKernelEx(&cfg, fused_kernel, H, P);
}

}

extern "C" void kernel_launch(void* const* d_in, const int* in_sizes, int n_in, void* d_out, int out_size) {
  (void)in_sizes; (void)n_in; (void)out_size;
  typedef const __nv_bfloat16* cb;
  void* fp = nullptr; cudaDriverEntryPointQueryResult qr;
  cudaGetDriverEntryPoint("cuTensorMapEncodeTiled", &fp, cudaEnableDefault, &qr);
  EncFn f = (EncFn)fp;
  Scratch* sp = nullptr;
  cudaGetSymbolAddress((void**)&sp, g_scr);
  void *pu = sp->u, *ph = sp->h, *pgt = sp->gt;
  Params P;
  Head H;
  H.s = sp; H.x = (cb)d_in[0]; H.swap = (uintptr_t)d_in[4] < (uintptr_t)d_in[3] ? 0 : 0x80000000u; H.b0 = (cb)d_in[H.swap ? 3 : 4]; H.b1 = (cb)d_in[H.swap ? 4 : 3];
  for (int i = 0; i < 2; i++) {
    const cuuint64_t d[4] = {640, 8, 2, 80}, s[3] = {1280, (cuuint64_t)((uintptr_t)H.b1 - (uintptr_t)H.b0), 8 * 1280}; const cuuint32_t bx[4] = {64, 8, 2, 4};
    if (enc(f, &P.mB, H.b0, 4, d, s, bx, true)) break;
    cudaMemcpyAsync(sp->bcopy, H.b0, DM * DM * 2, cudaMemcpyDeviceToDevice, cudaStreamPerThread);
    cudaMemcpyAsync(sp->bcopy + DM * DM, H.b1, DM * DM * 2, cudaMemcpyDeviceToDevice, cudaStreamPerThread);
    H.b0 = sp->bcopy; H.b1 = sp->bcopy + DM * DM;
  }
  {
    const cuuint64_t d[5] = {640, 2, 4, 2, 40}, s[4] = {1280, 4 * 1280, 2 * 1280, 16 * 1280}; const cuuint32_t bx[5] = {64, 2, 4, 2, 5};
    enc(f, &P.mC[0], d_in[5], 5, d, s, bx, true); enc(f, &P.mC[1], d_in[6], 5, d, s, bx, true); }
  { const cuuint64_t d[2] = {2048, 640}, s[1] = {4096}; const cuuint32_t bx[2] = {64, 80}; enc(f, &P.mGT, pgt, 2, d, s, bx, true); }
  { const cuuint64_t d[4] = {640, 8, 16, 16}, s[3] = {16 * 1280, 1280, 128 * 1280}, so[3] = {16 * 2560, 2560, 128 * 2560}; const cuuint32_t bx[4] = {80, 8, 16, 1};
    enc(f, &P.sU, pu, 4, d, s, bx, false); enc(f, &P.mX, d_in[0], 4, d, s, bx, false); enc(f, &P.sO, d_out, 4, d, so, bx, false, true); }
  { const cuuint64_t d[2] = {2048, 640}, s[1] = {4096}; const cuuint32_t bx[2] = {64, 64}; enc(f, &P.sK, sp->kv, 2, d, s, bx, true); }
  P.lre = (cb)d_in[1]; P.lim = (cb)d_in[2]; P.cre = (cb)d_in[5]; P.cim = (cb)d_in[6]; P.ldt = (cb)d_in[7]; P.dskip = (cb)d_in[8];
  P.out = (float*)d_out;
  P.k = (cb)d_in[10]; P.v = (cb)d_in[11]; P.shk = (cb)d_in[12]; P.ssmk = (cb)d_in[13]; P.ssmd = (cb)d_in[14];
  cudaFuncSetAttribute(fused_kernel, cudaFuncAttributeMaxDynamicSharedMemorySize, SMEM_BYTES);
  for (int big = 1; big >= 0; big--) {
    const cuuint64_t seg = big ? 40 : 32;
    for (int i = 0; i < 4; i++) {
      const cuuint64_t d[4] = {640, 2, 4, 1024}, s[3] = {1280, seg * 1280, 2 * 1280}; const cuuint32_t bx[4] = {64, 2, 4, !big ? 8u : (i & 1) ? 10u : 5u};
      enc(f, &P.mA[i], i < 2 ? d_in[0] : pu, 4, d, s, bx, true);
    }
    {
      const cuuint64_t d[4] = {1280, 8, 16, 32}, s[3] = {16 * 2560, 2560, 128 * 2560}; const cuuint32_t bx[4] = {64, 8, big ? 2u : 8u, 1};
      enc(f, &P.mH, ph, 4, d, s, bx, true); }
    { const cuuint64_t d[4] = {1280, 2, 4, 2048}, s[3] = {2560, seg * 2560, 2 * 2560}; const cuuint32_t bx[4] = {64, 2, 4, 4};
      enc(f, &P.sH, ph, 4, d, s, bx, true); }
    make_roles(P, big);
    H.base = big ? 0 : 120;
    launch(H, P, big ? 120 : 12, big ? 8 : 2, !big);
  }
}
```

```cpp
#include <cuda_runtime.h>
#include <cuda.h>
#include <cuda_bf16.h>
#include <stdint.h>

namespace {

constexpr int SEQ = 2048, DM = 640;
constexpr int SPIN = 1 << 20;
#define PFAT 99
#define KVDLY 500
#define PFD 1
#define XPFAT 9
#define STAT_AT 6
#define KPFAT 3
#define KPFAT2 5
#define KPF 7
#define ODIR 1
#define UDIR 0
#define HDLY 1900
#define GSPL 2
#define CWAIT 0
#define HDLY0 1900
#define CTAB1 0x96543u
#define NSAT 0
#define SKW 1
#define RIAT 2
#define MIAT 5
#define FPAT 1
#define UPAT 7
#define STAT_AT1 4
#define W4AT 0
#define MBAR 1
#define XEARLY 1
#define PWG 1
#define STG 17
#define STG0 0
#define S1G 0
#define S1G0 0
#define DSM 2
#define HWM 0xc09
#define REL 1
#define NSDB 4
#define GLATE 6
#define KUP 1
#define XRAT 9
#define ORD 1

struct Scratch {
  uint2 E[2 * 13 * 10 * 8 * 16];
  uint32_t M[3 * 16 * 8 * 256];
  uint2 S[3 * SEQ];
  uint2 RS[80 * 16];
  unsigned flag[512 * 32];
  unsigned cnt[32 * 32];
  unsigned epoch[132 * 8];
  unsigned zero[128];
  unsigned prof[132 * 512];
  __align__(1024)
  __nv_bfloat16 u[SEQ * DM];
  __nv_bfloat16 h[2 * SEQ * 1280];
  __nv_bfloat16 kv[DM * SEQ];
  __nv_bfloat16 gt[DM * SEQ];
  __nv_bfloat16 bcopy[2 * DM * DM];
};
__device__ __align__(1024) Scratch g_scr;
#define PROFC(c, i) do {} while (0)
#define PSEL 1
#define PROF(i) do {} while (0)

constexpr int C_KV = 0, C_G = 10;
constexpr int F_U3 = 0, F_H = 128;

constexpr int R_OFF = 196608, R4_OFF0 = 73728, R4_OFF1 = 122880, H_OFF = 131072, KS_OFF = 131072, CV_OFF = 86272, G_OFF0 = 40960, G_OFF1 = 102400, US_OFF = 98304, OS_OFF = US_OFF + 20480, XR_OFF = 163840, MX_OFF = 32768;
constexpr int LAM_OFF = 229376, SSM_OFF = LAM_OFF + 1024, BAR_OFF = SSM_OFF + 1344;
constexpr int B_F1 = 0, B_E1 = 10, B_RF0 = 20, B_RF1 = 21, NBAR1 = 22;
constexpr int B_F2 = 22, B_KF = 32, B_GF = 37, B_CD = 38, B_XR = 40, B_ST = 41, B_HD = 42, B_LM = 43, B_E2 = 44, B_GS = 54, B_PS = 59, B_AX = 62, B_SH = 64, B_SG = 69, B_GE = 70, B_EA = 71, B_F3 = 74, NBAR = 84;
__host__ __device__ constexpr int bar_count(int i) { return i < B_E1 ? 1 : i < B_RF0 ? 9 : i < B_F2 ? 8 : i < B_E2 ? 1 : i < B_GS ? 12 : i < B_SH ? 4 : i < B_GE ? 8 : i < B_EA ? 2 : i < B_F3 ? 8 : 1; }
constexpr int MISC_OFF = BAR_OFF + NBAR * 8, SMEM_BYTES = MISC_OFF + 32;
constexpr int KV_PAD = 512, KC_OFS = KV_PAD + 4096, CH_STRIDE = 8960;
__device__ __forceinline__ uint32_t conv_buf(uint32_t sb, int slot) { return sb + CV_OFF + slot * CH_STRIDE; }
constexpr uint64_t tab6(int a, int b, int c, int d, int e, int f, int g, int h, int i, int j) {
  return (uint64_t)a | (uint64_t)b << 6 | (uint64_t)c << 12 | (uint64_t)d << 18 | (uint64_t)e << 24 | (uint64_t)f << 30 | (uint64_t)g << 36 | (uint64_t)h << 42 |
         (uint64_t)i << 48 | (uint64_t)j << 54;
}
constexpr uint64_t WTAB0 = tab6(0, 4, 8, 30, 12, 26, 0, 4, 8, 12), XTAB0 = tab6(40, 45, 50, 34, 16, 21, 40, 45, 50, 16);
constexpr uint64_t WTAB1 = tab6(16, 20, 0, 4, 8, 12, 16, 20, 24, 28), XTAB1 = tab6(40, 45, 50, 32, 40, 45, 50, 32, 40, 45);
constexpr uint32_t DEP0 = 0x4210;

struct Head {
  Scratch* s;
  const __nv_bfloat16 *x, *b0, *b1;
  uint32_t base, swap;
};
struct Params {
  const __nv_bfloat16 *lre, *lim, *ldt, *k, *v, *shk, *cre, *cim, *ssmk, *ssmd, *dskip;
  float* out;
  uint4 role[120];
  CUtensorMap mB, mA[4], mH, mC[2], mGT, mX, sH, sU, sO, sK;
};

__device__ __forceinline__ uint32_t smem_u32(const void* p) { return (uint32_t)__cvta_generic_to_shared(p); }
__device__ __forceinline__ uint32_t opaque(uint32_t x) { uint32_t y; asm volatile("mov.u32 %0, %1;" : "=r"(y) : "r"(x)); return y; }
__device__ __forceinline__ int lane_id() { int y; asm volatile("mov.u32 %0, %%laneid;" : "=r"(y)); return y; }
__device__ __forceinline__ void delay(uint32_t n) {
  asm volatile("{ .reg .pred p; .reg .u32 a, b; mov.u32 a, %%clock; L: mov.u32 b, %%clock; sub.u32 b, b, a; setp.lt.u32 p, b, %0; @p bra.uni L; }" ::"r"(n) : "memory");
}
__device__ __forceinline__ void mbar_init(uint32_t bar, uint32_t cnt) { asm volatile("mbarrier.init.shared::cta.b64 [%0], %1;" ::"r"(bar), "r"(cnt) : "memory"); }
__device__ __forceinline__ void mbar_expect_tx(uint32_t bar, uint32_t bytes) { asm volatile("mbarrier.arrive.expect_tx.shared::cta.b64 _, [%0], %1;" ::"r"(bar), "r"(bytes) : "memory"); }
__device__ __forceinline__ void mbar_arrive(uint32_t bar) { asm volatile("mbarrier.arrive.shared::cta.b64 _, [%0];" ::"r"(bar) : "memory"); }
__device__ __forceinline__ void mbar_arrive_if(uint32_t bar, bool c) {
  asm volatile("{ .reg .pred p; setp.ne.u32 p, %1, 0; @p mbarrier.arrive.shared::cta.b64 _, [%0]; }" ::"r"(bar), "r"((uint32_t)c) : "memory");
}
__device__ __forceinline__ void prefetch_if(const void* p, bool c) { asm volatile("{ .reg .pred p; setp.ne.u32 p, %1, 0; @p prefetch.global.L2 [%0]; }" ::"l"(p), "r"((uint32_t)c)); }
__device__ __forceinline__ void mbar_arrive_cl(uint32_t bar, uint32_t cta) {
  asm volatile("{ .reg .b32 ra; mapa.shared::cluster.u32 ra, %0, %1; mbarrier.arrive.shared::cluster.b64 _, [ra]; }" ::"r"(bar), "r"(cta) : "memory");
}
__device__ __forceinline__ uint32_t mapa(uint32_t a, uint32_t cta) { uint32_t r; asm("mapa.shared::cluster.u32 %0, %1, %2;" : "=r"(r) : "r"(a), "r"(cta)); return r; }
__device__ __forceinline__ void mbar_arrive_at(uint32_t ra) { asm volatile("mbarrier.arrive.shared::cluster.b64 _, [%0];" ::"r"(ra) : "memory"); }
__device__ __forceinline__ void mbar_wait(uint32_t bar, uint32_t parity = 0) {
  asm volatile("{ .reg .pred p; .reg .u32 c; mov.u32 c, 0;\n"
               "W: mbarrier.try_wait.parity.shared::cta.b64 p, [%0], %1; @p bra.uni D;\n"
               "add.u32 c, c, 1; setp.lt.u32 p, c, 0x100000; @p bra.uni W;\nD: }" ::"r"(bar), "r"(parity) : "memory");
}
__device__ __forceinline__ bool elect_one() { uint32_t p; asm volatile("{ .reg .pred P; elect.sync _|P, 0xffffffff; selp.u32 %0,1,0,P; }" : "=r"(p)); return p; }
__device__ __forceinline__ void bar_sync(int id, int n) { __syncwarp(); asm volatile("bar.sync %0, %1;" ::"r"(id), "r"(n) : "memory"); }
__device__ __forceinline__ void tma2d(uint32_t dst, const CUtensorMap* m, int c0, int c1, uint32_t bar) {
  asm volatile("cp.async.bulk.tensor.2d.shared::cluster.global.mbarrier::complete_tx::bytes [%0], [%1, {%3,%4}], [%2];"
               ::"r"(dst), "l"(m), "r"(bar), "r"(c0), "r"(c1) : "memory");
}
__device__ __forceinline__ void tma5d(uint32_t dst, const CUtensorMap* m, int c0, int c4, uint32_t bar) {
  asm volatile("cp.async.bulk.tensor.5d.shared::cluster.global.mbarrier::complete_tx::bytes [%0], [%1, {%3,%5,%5,%5,%4}], [%2];"
               ::"r"(dst), "l"(m), "r"(bar), "r"(c0), "r"(c4), "r"(0) : "memory");
}
__device__ __forceinline__ void tma4d(uint32_t dst, const CUtensorMap* m, int c0, int c3, uint32_t bar) {
  asm volatile("cp.async.bulk.tensor.4d.shared::cluster.global.mbarrier::complete_tx::bytes [%0], [%1, {%3,%5,%5,%4}], [%2];"
               ::"r"(dst), "l"(m), "r"(bar), "r"(c0), "r"(c3), "r"(0) : "memory");
}
__device__ __forceinline__ void tma4d_mc(uint32_t dst, const CUtensorMap* m, int c0, int c1, int c2, int c3, uint32_t bar, uint32_t mask) {
  asm volatile("cp.async.bulk.tensor.4d.shared::cluster.global.mbarrier::complete_tx::bytes.multicast::cluster [%0], [%1, {%3,%4,%5,%6}], [%2], %7;"
               ::"r"(dst), "l"(m), "r"(bar), "r"(c0), "r"(c1), "r"(c2), "r"(c3), "h"((uint16_t)mask) : "memory");
}
__device__ __forceinline__ void bulk_g2s(uint32_t dst, const void* src, uint32_t bytes, uint32_t bar) {
  asm volatile("cp.async.bulk.shared::cluster.global.mbarrier::complete_tx::bytes [%0], [%1], %2, [%3];" ::"r"(dst), "l"(src), "r"(bytes), "r"(bar) : "memory");
}
__device__ __forceinline__ void tma4d_store(const CUtensorMap* m, uint32_t src, int c0, int c1, int c2, int c3) {
  asm volatile("cp.async.bulk.tensor.4d.global.shared::cta.bulk_group [%0, {%2,%3,%4,%5}], [%1];" ::"l"(m), "r"(src), "r"(c0), "r"(c1), "r"(c2), "r"(c3) : "memory");
}
__device__ __forceinline__ void tma2d_store(const CUtensorMap* m, uint32_t src, int c0, int c1) {
  asm volatile("cp.async.bulk.tensor.2d.global.shared::cta.bulk_group [%0, {%2,%3}], [%1];" ::"l"(m), "r"(src), "r"(c0), "r"(c1) : "memory");
}
__device__ __forceinline__ void bulk_s2g(void* dst, uint32_t src, uint32_t bytes) {
  asm volatile("cp.async.bulk.global.shared::cta.bulk_group [%0], [%1], %2;" ::"l"(dst), "r"(src), "r"(bytes) : "memory");
}
__device__ __forceinline__ void bulk_commit() { asm volatile("cp.async.bulk.commit_group;" ::: "memory"); }
__device__ __forceinline__ void bulk_wait() { asm volatile("cp.async.bulk.wait_group 0;" ::: "memory"); }
__device__ __forceinline__ void fence_async() { asm volatile("fence.proxy.async.shared::cta;" ::: "memory"); }
__device__ __forceinline__ void prefetch_l2(const void* src, uint32_t bytes) { asm volatile("cp.async.bulk.prefetch.L2.global [%0], %1;" ::"l"(src), "r"(bytes) : "memory"); }
__device__ __forceinline__ void prefetch_map(const CUtensorMap* m) { asm volatile("prefetch.tensormap [%0];" ::"l"(m) : "memory"); }
__device__ __forceinline__ void wg_fence() { __syncwarp(); asm volatile("wgmma.fence.sync.aligned;" ::: "memory"); }
__device__ __forceinline__ void wg_commit() { asm volatile("wgmma.commit_group.sync.aligned;" ::: "memory"); }
template <int N> __device__ __forceinline__ void wg_wait() { asm volatile("wgmma.wait_group.sync.aligned %0;" ::"n"(N) : "memory"); }
template <int N> __device__ __forceinline__ void fence_regs(float (&d)[N]) {
#pragma unroll
  for (int i = 0; i < N; i++) asm volatile("" : "+f"(d[i])::"memory");
}
__device__ __forceinline__ uint64_t make_desc(uint32_t addr, uint32_t lbo, uint32_t sbo, uint32_t swz) {
  return (uint64_t)((addr & 0x3FFFF) >> 4) | ((uint64_t)(lbo >> 4) << 16) | ((uint64_t)(sbo >> 4) << 32) | ((uint64_t)swz << 62);
}
__device__ __forceinline__ uint32_t ldg1(const void* p) { uint32_t v; asm volatile("ld.global.nc.u32 %0,[%1];" : "=r"(v) : "l"(p)); return v; }
__device__ __forceinline__ uint32_t lds32(uint32_t a) { uint32_t v; asm volatile("ld.shared.u32 %0,[%1];" : "=r"(v) : "r"(a)); return v; }
__device__ __forceinline__ unsigned ld_rlx(const unsigned* p) { unsigned v; asm volatile("ld.relaxed.gpu.global.u32 %0,[%1];" : "=r"(v) : "l"(p) : "memory"); return v; }
__device__ __forceinline__ uint4 ld_rlx4(const void* p) {
  uint4 v; asm volatile("ld.relaxed.gpu.global.v4.u32 {%0,%1,%2,%3},[%4];" : "=r"(v.x), "=r"(v.y), "=r"(v.z), "=r"(v.w) : "l"(p) : "memory"); return v;
}
__device__ __forceinline__ uint2 ld_rlx2(const void* p) { uint2 v; asm volatile("ld.relaxed.gpu.global.v2.u32 {%0,%1},[%2];" : "=r"(v.x), "=r"(v.y) : "l"(p) : "memory"); return v; }
__device__ __forceinline__ void st_rlx2(void* p, uint32_t a, uint32_t b) { asm volatile("st.relaxed.gpu.global.v2.u32 [%0],{%1,%2};" ::"l"(p), "r"(a), "r"(b) : "memory"); }
__device__ __forceinline__ void st_rlx(void* p, uint32_t a) { asm volatile("st.relaxed.gpu.global.u32 [%0],%1;" ::"l"(p), "r"(a) : "memory"); }
#define PUB 15
template <int SITE> __device__ __forceinline__ void release() { if (PUB & SITE) { if (REL) asm volatile("fence.release.gpu;" ::: "memory"); else asm volatile("fence.acq_rel.gpu;" ::: "memory"); } }
__device__ __forceinline__ void signal_flag(unsigned* p, unsigned val) { asm volatile("st.relaxed.gpu.global.u32 [%0],%1;" ::"l"(p), "r"(val) : "memory"); }
__device__ __forceinline__ void signal_cnt(unsigned* p, unsigned n) { asm volatile("red.relaxed.gpu.global.add.u32 [%0],%1;" ::"l"(p), "r"(n) : "memory"); }
__device__ __forceinline__ void wait_flags(const unsigned* p, unsigned val, uint32_t need, uint32_t& ready) {
#pragma unroll 1
  for (int it = 0; (ready & need) != need && it < SPIN; it++) ready = __ballot_sync(0xffffffff, ld_rlx(p) == val);
}
__device__ __forceinline__ void wait_cnt(const unsigned* p, unsigned tgt) {
  asm volatile("{ .reg .pred p; .reg .u32 c; .reg .s32 v; mov.u32 c, 0;\n"
               "W: ld.relaxed.gpu.global.u32 v, [%0]; sub.s32 v, v, %1; setp.ge.s32 p, v, 0; @p bra.uni D;\n"
               "add.u32 c, c, 1; setp.lt.u32 p, c, 0x100000; @p bra.uni W;\nD: }" ::"l"(p), "r"(tgt) : "memory");
}
__device__ __forceinline__ uint32_t pack_bf(float lo, float hi) { uint32_t r; asm("cvt.rn.bf16x2.f32 %0, %1, %2;" : "=r"(r) : "f"(hi), "f"(lo)); return r; }
__device__ __forceinline__ float bf_lo(uint32_t v) { return __uint_as_float(v << 16); }
__device__ __forceinline__ float bf_hi(uint32_t v) { return __uint_as_float(v & 0xffff0000u); }
__device__ __forceinline__ float bf_rn(float x) { return __bfloat162float(__float2bfloat16_rn(x)); }
__device__ __forceinline__ float frcp(float x) { float r; asm("rcp.approx.ftz.f32 %0,%1;" : "=f"(r) : "f"(x)); return r; }
__device__ __forceinline__ float fsqrt(float x) { float r; asm("sqrt.approx.ftz.f32 %0,%1;" : "=f"(r) : "f"(x)); return r; }
__device__ __forceinline__ float frsqrt(float x) { float r; asm("rsqrt.approx.ftz.f32 %0,%1;" : "=f"(r) : "f"(x)); return r; }
__device__ __forceinline__ uint32_t hmul2(uint32_t a, uint32_t b) { uint32_t r; asm("mul.rn.bf16x2 %0,%1,%2;" : "=r"(r) : "r"(a), "r"(b)); return r; }
__device__ __forceinline__ uint32_t hfma2(uint32_t a, uint32_t b, uint32_t c) { uint32_t r; asm("fma.rn.bf16x2 %0,%1,%2,%3;" : "=r"(r) : "r"(a), "r"(b), "r"(c)); return r; }
__device__ __forceinline__ float2 cmul(float2 a, float2 b) { return make_float2(a.x * b.x - a.y * b.y, a.x * b.y + a.y * b.x); }
__device__ __forceinline__ float2 cfma(float2 a, float2 b, float2 c) {
  return make_float2(fmaf(a.x, b.x, fmaf(-a.y, b.y, c.x)), fmaf(a.x, b.y, fmaf(a.y, b.x, c.y)));
}
__device__ __forceinline__ uint32_t tagf(float v, uint32_t tag) { return (__float_as_uint(v) & ~1u) | tag; }
__device__ __forceinline__ float untag(uint32_t v) { return __uint_as_float(v & ~1u); }
__device__ __forceinline__ bool untagged(const uint4& v, uint32_t tag) { return (((v.x ^ tag) | (v.y ^ tag) | (v.z ^ tag) | (v.w ^ tag)) & 1) != 0; }
__device__ __forceinline__ bool untagged(const uint2& v, uint32_t tag) { return (((v.x ^ tag) | (v.y ^ tag)) & 1) != 0; }
__device__ __forceinline__ float2 lam_bar(float lr, float li, float ldt) {
  float dt = bf_rn(expf(ldt)); float e = expf(dt * lr), s, c; sincospif(dt * li * 0.31830988618379067f, &s, &c); return make_float2(e * c, e * s);
}

__device__ __forceinline__ int conv_ch(uint32_t c, int s) { return s * ((c >> 21) & 255) + (c & 255) - (s >= (int)(c >> 29) ? 8 : 0); }
struct Role {
  uint32_t v, c, p;
  __device__ __forceinline__ int tb() const { return v & 15; }
  __device__ __forceinline__ int cb() const { return (v >> 4) & 15; }
  __device__ __forceinline__ int b() const { return (v >> 8) & 255; }
  __device__ __forceinline__ int ubase() const { return (v >> 16) & 7; }
  __device__ __forceinline__ int ugs() const { return (v >> 19) & 7; }
  __device__ __forceinline__ int wpart() const { return (v >> 22) & 7; }
  __device__ __forceinline__ int rank() const { return (v >> 26) & 7; }
  __device__ __forceinline__ int cs() const { return (v >> 29) ? 8 : 2; }
  __device__ __forceinline__ int ch(int s) const { return conv_ch(c, s); }
  __device__ __forceinline__ int wlo() const { return p & 1; }
  __device__ __forceinline__ int whi() const { return (p >> 1) & 1; }
  __device__ __forceinline__ uint32_t wmask() const { return (p >> 2) & 255; }
  __device__ __forceinline__ uint32_t umask() const { return (p >> 10) & 255; }
  __device__ __forceinline__ int uj() const { return (p >> 20) & 31; }
  __device__ __forceinline__ int sm() const { return (p >> 25) & 15; }
  __device__ __forceinline__ int nch() const { return (c >> 10) & 7; }
  __device__ __forceinline__ int nprep() const { return (c >> 13) & 255; }
};

__device__ __forceinline__ void wgmma_ss80(float (&d)[40], uint64_t da, uint64_t db, int sd){
  asm volatile("{ .reg .pred p; setp.ne.b32 p, %42, 0;\n"
   "wgmma.mma_async.sync.aligned.m64n80k16.f32.bf16.bf16 {%0, %1, %2, %3, %4, %5, %6, %7, %8, %9, %10, %11, %12, %13, %14, %15, %16, %17, %18, %19, %20, %21, %22, %23, %24, %25, %26, %27, %28, %29, %30, %31, %32, %33, %34, %35, %36, %37, %38, %39}, %40, %41, p, 1, 1, 0, 0; }\n"
   : "+f"(d[0]), "+f"(d[1]), "+f"(d[2]), "+f"(d[3]), "+f"(d[4]), "+f"(d[5]), "+f"(d[6]), "+f"(d[7]), "+f"(d[8]), "+f"(d[9]), "+f"(d[10]), "+f"(d[11]), "+f"(d[12]), "+f"(d[13]), "+f"(d[14]), "+f"(d[15]), "+f"(d[16]), "+f"(d[17]), "+f"(d[18]), "+f"(d[19]), "+f"(d[20]), "+f"(d[21]), "+f"(d[22]), "+f"(d[23]), "+f"(d[24]), "+f"(d[25]), "+f"(d[26]), "+f"(d[27]), "+f"(d[28]), "+f"(d[29]), "+f"(d[30]), "+f"(d[31]), "+f"(d[32]), "+f"(d[33]), "+f"(d[34]), "+f"(d[35]), "+f"(d[36]), "+f"(d[37]), "+f"(d[38]), "+f"(d[39]) : "l"(da), "l"(db), "r"(sd));
}
__device__ __forceinline__ void wgmma_ss160(float (&d)[80], uint64_t da, uint64_t db, int sd){
  asm volatile("{ .reg .pred p; setp.ne.b32 p, %82, 0;\n"
   "wgmma.mma_async.sync.aligned.m64n160k16.f32.bf16.bf16 {%0, %1, %2, %3, %4, %5, %6, %7, %8, %9, %10, %11, %12, %13, %14, %15, %16, %17, %18, %19, %20, %21, %22, %23, %24, %25, %26, %27, %28, %29, %30, %31, %32, %33, %34, %35, %36, %37, %38, %39, %40, %41, %42, %43, %44, %45, %46, %47, %48, %49, %50, %51, %52, %53, %54, %55, %56, %57, %58, %59, %60, %61, %62, %63, %64, %65, %66, %67, %68, %69, %70, %71, %72, %73, %74, %75, %76, %77, %78, %79}, %80, %81, p, 1, 1, 0, 0; }\n"
   : "+f"(d[0]), "+f"(d[1]), "+f"(d[2]), "+f"(d[3]), "+f"(d[4]), "+f"(d[5]), "+f"(d[6]), "+f"(d[7]), "+f"(d[8]), "+f"(d[9]), "+f"(d[10]), "+f"(d[11]), "+f"(d[12]), "+f"(d[13]), "+f"(d[14]), "+f"(d[15]), "+f"(d[16]), "+f"(d[17]), "+f"(d[18]), "+f"(d[19]), "+f"(d[20]), "+f"(d[21]), "+f"(d[22]), "+f"(d[23]), "+f"(d[24]), "+f"(d[25]), "+f"(d[26]), "+f"(d[27]), "+f"(d[28]), "+f"(d[29]), "+f"(d[30]), "+f"(d[31]), "+f"(d[32]), "+f"(d[33]), "+f"(d[34]), "+f"(d[35]), "+f"(d[36]), "+f"(d[37]), "+f"(d[38]), "+f"(d[39]), "+f"(d[40]), "+f"(d[41]), "+f"(d[42]), "+f"(d[43]), "+f"(d[44]), "+f"(d[45]), "+f"(d[46]), "+f"(d[47]), "+f"(d[48]), "+f"(d[49]), "+f"(d[50]), "+f"(d[51]), "+f"(d[52]), "+f"(d[53]), "+f"(d[54]), "+f"(d[55]), "+f"(d[56]), "+f"(d[57]), "+f"(d[58]), "+f"(d[59]), "+f"(d[60]), "+f"(d[61]), "+f"(d[62]), "+f"(d[63]), "+f"(d[64]), "+f"(d[65]), "+f"(d[66]), "+f"(d[67]), "+f"(d[68]), "+f"(d[69]), "+f"(d[70]), "+f"(d[71]), "+f"(d[72]), "+f"(d[73]), "+f"(d[74]), "+f"(d[75]), "+f"(d[76]), "+f"(d[77]), "+f"(d[78]), "+f"(d[79]) : "l"(da), "l"(db), "r"(sd));
}
template<int N> __device__ __forceinline__ void wgmma_rs(float (&d)[N/2], uint32_t a0, uint32_t a1, uint32_t a2, uint32_t a3, uint64_t db, int sd);
template<> __device__ __forceinline__ void wgmma_rs<16>(float (&d)[8], uint32_t a0, uint32_t a1, uint32_t a2, uint32_t a3, uint64_t db, int sd){
  asm volatile("{ .reg .pred p; setp.ne.b32 p, %13, 0;\n"
   "wgmma.mma_async.sync.aligned.m64n16k16.f32.bf16.bf16 {%0, %1, %2, %3, %4, %5, %6, %7}, {%8,%9,%10,%11}, %12, p, 1, 1, 0; }\n"
   : "+f"(d[0]), "+f"(d[1]), "+f"(d[2]), "+f"(d[3]), "+f"(d[4]), "+f"(d[5]), "+f"(d[6]), "+f"(d[7]) : "r"(a0), "r"(a1), "r"(a2), "r"(a3), "l"(db), "r"(sd));
}
template<> __device__ __forceinline__ void wgmma_rs<32>(float (&d)[16], uint32_t a0, uint32_t a1, uint32_t a2, uint32_t a3, uint64_t db, int sd){
  asm volatile("{ .reg .pred p; setp.ne.b32 p, %21, 0;\n"
   "wgmma.mma_async.sync.aligned.m64n32k16.f32.bf16.bf16 {%0, %1, %2, %3, %4, %5, %6, %7, %8, %9, %10, %11, %12, %13, %14, %15}, {%16,%17,%18,%19}, %20, p, 1, 1, 0; }\n"
   : "+f"(d[0]), "+f"(d[1]), "+f"(d[2]), "+f"(d[3]), "+f"(d[4]), "+f"(d[5]), "+f"(d[6]), "+f"(d[7]), "+f"(d[8]), "+f"(d[9]), "+f"(d[10]), "+f"(d[11]), "+f"(d[12]), "+f"(d[13]), "+f"(d[14]), "+f"(d[15]) : "r"(a0), "r"(a1), "r"(a2), "r"(a3), "l"(db), "r"(sd));
}
template<> __device__ __forceinline__ void wgmma_rs<48>(float (&d)[24], uint32_t a0, uint32_t a1, uint32_t a2, uint32_t a3, uint64_t db, int sd){
  asm volatile("{ .reg .pred p; setp.ne.b32 p, %29, 0;\n"
   "wgmma.mma_async.sync.aligned.m64n48k16.f32.bf16.bf16 {%0, %1, %2, %3, %4, %5, %6, %7, %8, %9, %10, %11, %12, %13, %14, %15, %16, %17, %18, %19, %20, %21, %22, %23}, {%24,%25,%26,%27}, %28, p, 1, 1, 0; }\n"
   : "+f"(d[0]), "+f"(d[1]), "+f"(d[2]), "+f"(d[3]), "+f"(d[4]), "+f"(d[5]), "+f"(d[6]), "+f"(d[7]), "+f"(d[8]), "+f"(d[9]), "+f"(d[10]), "+f"(d[11]), "+f"(d[12]), "+f"(d[13]), "+f"(d[14]), "+f"(d[15]), "+f"(d[16]), "+f"(d[17]), "+f"(d[18]), "+f"(d[19]), "+f"(d[20]), "+f"(d[21]), "+f"(d[22]), "+f"(d[23]) : "r"(a0), "r"(a1), "r"(a2), "r"(a3), "l"(db), "r"(sd));
}
template<> __device__ __forceinline__ void wgmma_rs<64>(float (&d)[32], uint32_t a0, uint32_t a1, uint32_t a2, uint32_t a3, uint64_t db, int sd){
  asm volatile("{ .reg .pred p; setp.ne.b32 p, %37, 0;\n"
   "wgmma.mma_async.sync.aligned.m64n64k16.f32.bf16.bf16 {%0, %1, %2, %3, %4, %5, %6, %7, %8, %9, %10, %11, %12, %13, %14, %15, %16, %17, %18, %19, %20, %21, %22, %23, %24, %25, %26, %27, %28, %29, %30, %31}, {%32,%33,%34,%35}, %36, p, 1, 1, 0; }\n"
   : "+f"(d[0]), "+f"(d[1]), "+f"(d[2]), "+f"(d[3]), "+f"(d[4]), "+f"(d[5]), "+f"(d[6]), "+f"(d[7]), "+f"(d[8]), "+f"(d[9]), "+f"(d[10]), "+f"(d[11]), "+f"(d[12]), "+f"(d[13]), "+f"(d[14]), "+f"(d[15]), "+f"(d[16]), "+f"(d[17]), "+f"(d[18]), "+f"(d[19]), "+f"(d[20]), "+f"(d[21]), "+f"(d[22]), "+f"(d[23]), "+f"(d[24]), "+f"(d[25]), "+f"(d[26]), "+f"(d[27]), "+f"(d[28]), "+f"(d[29]), "+f"(d[30]), "+f"(d[31]) : "r"(a0), "r"(a1), "r"(a2), "r"(a3), "l"(db), "r"(sd));
}
template<> __device__ __forceinline__ void wgmma_rs<80>(float (&d)[40], uint32_t a0, uint32_t a1, uint32_t a2, uint32_t a3, uint64_t db, int sd){
  asm volatile("{ .reg .pred p; setp.ne.b32 p, %45, 0;\n"
   "wgmma.mma_async.sync.aligned.m64n80k16.f32.bf16.bf16 {%0, %1, %2, %3, %4, %5, %6, %7, %8, %9, %10, %11, %12, %13, %14, %15, %16, %17, %18, %19, %20, %21, %22, %23, %24, %25, %26, %27, %28, %29, %30, %31, %32, %33, %34, %35, %36, %37, %38, %39}, {%40,%41,%42,%43}, %44, p, 1, 1, 0; }\n"
   : "+f"(d[0]), "+f"(d[1]), "+f"(d[2]), "+f"(d[3]), "+f"(d[4]), "+f"(d[5]), "+f"(d[6]), "+f"(d[7]), "+f"(d[8]), "+f"(d[9]), "+f"(d[10]), "+f"(d[11]), "+f"(d[12]), "+f"(d[13]), "+f"(d[14]), "+f"(d[15]), "+f"(d[16]), "+f"(d[17]), "+f"(d[18]), "+f"(d[19]), "+f"(d[20]), "+f"(d[21]), "+f"(d[22]), "+f"(d[23]), "+f"(d[24]), "+f"(d[25]), "+f"(d[26]), "+f"(d[27]), "+f"(d[28]), "+f"(d[29]), "+f"(d[30]), "+f"(d[31]), "+f"(d[32]), "+f"(d[33]), "+f"(d[34]), "+f"(d[35]), "+f"(d[36]), "+f"(d[37]), "+f"(d[38]), "+f"(d[39]) : "r"(a0), "r"(a1), "r"(a2), "r"(a3), "l"(db), "r"(sd));
}
template<> __device__ __forceinline__ void wgmma_rs<96>(float (&d)[48], uint32_t a0, uint32_t a1, uint32_t a2, uint32_t a3, uint64_t db, int sd){
  asm volatile("{ .reg .pred p; setp.ne.b32 p, %53, 0;\n"
   "wgmma.mma_async.sync.aligned.m64n96k16.f32.bf16.bf16 {%0, %1, %2, %3, %4, %5, %6, %7, %8, %9, %10, %11, %12, %13, %14, %15, %16, %17, %18, %19, %20, %21, %22, %23, %24, %25, %26, %27, %28, %29, %30, %31, %32, %33, %34, %35, %36, %37, %38, %39, %40, %41, %42, %43, %44, %45, %46, %47}, {%48,%49,%50,%51}, %52, p, 1, 1, 0; }\n"
   : "+f"(d[0]), "+f"(d[1]), "+f"(d[2]), "+f"(d[3]), "+f"(d[4]), "+f"(d[5]), "+f"(d[6]), "+f"(d[7]), "+f"(d[8]), "+f"(d[9]), "+f"(d[10]), "+f"(d[11]), "+f"(d[12]), "+f"(d[13]), "+f"(d[14]), "+f"(d[15]), "+f"(d[16]), "+f"(d[17]), "+f"(d[18]), "+f"(d[19]), "+f"(d[20]), "+f"(d[21]), "+f"(d[22]), "+f"(d[23]), "+f"(d[24]), "+f"(d[25]), "+f"(d[26]), "+f"(d[27]), "+f"(d[28]), "+f"(d[29]), "+f"(d[30]), "+f"(d[31]), "+f"(d[32]), "+f"(d[33]), "+f"(d[34]), "+f"(d[35]), "+f"(d[36]), "+f"(d[37]), "+f"(d[38]), "+f"(d[39]), "+f"(d[40]), "+f"(d[41]), "+f"(d[42]), "+f"(d[43]), "+f"(d[44]), "+f"(d[45]), "+f"(d[46]), "+f"(d[47]) : "r"(a0), "r"(a1), "r"(a2), "r"(a3), "l"(db), "r"(sd));
}
template<> __device__ __forceinline__ void wgmma_rs<112>(float (&d)[56], uint32_t a0, uint32_t a1, uint32_t a2, uint32_t a3, uint64_t db, int sd){
  asm volatile("{ .reg .pred p; setp.ne.b32 p, %61, 0;\n"
   "wgmma.mma_async.sync.aligned.m64n112k16.f32.bf16.bf16 {%0, %1, %2, %3, %4, %5, %6, %7, %8, %9, %10, %11, %12, %13, %14, %15, %16, %17, %18, %19, %20, %21, %22, %23, %24, %25, %26, %27, %28, %29, %30, %31, %32, %33, %34, %35, %36, %37, %38, %39, %40, %41, %42, %43, %44, %45, %46, %47, %48, %49, %50, %51, %52, %53, %54, %55}, {%56,%57,%58,%59}, %60, p, 1, 1, 0; }\n"
   : "+f"(d[0]), "+f"(d[1]), "+f"(d[2]), "+f"(d[3]), "+f"(d[4]), "+f"(d[5]), "+f"(d[6]), "+f"(d[7]), "+f"(d[8]), "+f"(d[9]), "+f"(d[10]), "+f"(d[11]), "+f"(d[12]), "+f"(d[13]), "+f"(d[14]), "+f"(d[15]), "+f"(d[16]), "+f"(d[17]), "+f"(d[18]), "+f"(d[19]), "+f"(d[20]), "+f"(d[21]), "+f"(d[22]), "+f"(d[23]), "+f"(d[24]), "+f"(d[25]), "+f"(d[26]), "+f"(d[27]), "+f"(d[28]), "+f"(d[29]), "+f"(d[30]), "+f"(d[31]), "+f"(d[32]), "+f"(d[33]), "+f"(d[34]), "+f"(d[35]), "+f"(d[36]), "+f"(d[37]), "+f"(d[38]), "+f"(d[39]), "+f"(d[40]), "+f"(d[41]), "+f"(d[42]), "+f"(d[43]), "+f"(d[44]), "+f"(d[45]), "+f"(d[46]), "+f"(d[47]), "+f"(d[48]), "+f"(d[49]), "+f"(d[50]), "+f"(d[51]), "+f"(d[52]), "+f"(d[53]), "+f"(d[54]), "+f"(d[55]) : "r"(a0), "r"(a1), "r"(a2), "r"(a3), "l"(db), "r"(sd));
}
template<> __device__ __forceinline__ void wgmma_rs<128>(float (&d)[64], uint32_t a0, uint32_t a1, uint32_t a2, uint32_t a3, uint64_t db, int sd){
  asm volatile("{ .reg .pred p; setp.ne.b32 p, %69, 0;\n"
   "wgmma.mma_async.sync.aligned.m64n128k16.f32.bf16.bf16 {%0, %1, %2, %3, %4, %5, %6, %7, %8, %9, %10, %11, %12, %13, %14, %15, %16, %17, %18, %19, %20, %21, %22, %23, %24, %25, %26, %27, %28, %29, %30, %31, %32, %33, %34, %35, %36, %37, %38, %39, %40, %41, %42, %43, %44, %45, %46, %47, %48, %49, %50, %51, %52, %53, %54, %55, %56, %57, %58, %59, %60, %61, %62, %63}, {%64,%65,%66,%67}, %68, p, 1, 1, 0; }\n"
   : "+f"(d[0]), "+f"(d[1]), "+f"(d[2]), "+f"(d[3]), "+f"(d[4]), "+f"(d[5]), "+f"(d[6]), "+f"(d[7]), "+f"(d[8]), "+f"(d[9]), "+f"(d[10]), "+f"(d[11]), "+f"(d[12]), "+f"(d[13]), "+f"(d[14]), "+f"(d[15]), "+f"(d[16]), "+f"(d[17]), "+f"(d[18]), "+f"(d[19]), "+f"(d[20]), "+f"(d[21]), "+f"(d[22]), "+f"(d[23]), "+f"(d[24]), "+f"(d[25]), "+f"(d[26]), "+f"(d[27]), "+f"(d[28]), "+f"(d[29]), "+f"(d[30]), "+f"(d[31]), "+f"(d[32]), "+f"(d[33]), "+f"(d[34]), "+f"(d[35]), "+f"(d[36]), "+f"(d[37]), "+f"(d[38]), "+f"(d[39]), "+f"(d[40]), "+f"(d[41]), "+f"(d[42]), "+f"(d[43]), "+f"(d[44]), "+f"(d[45]), "+f"(d[46]), "+f"(d[47]), "+f"(d[48]), "+f"(d[49]), "+f"(d[50]), "+f"(d[51]), "+f"(d[52]), "+f"(d[53]), "+f"(d[54]), "+f"(d[55]), "+f"(d[56]), "+f"(d[57]), "+f"(d[58]), "+f"(d[59]), "+f"(d[60]), "+f"(d[61]), "+f"(d[62]), "+f"(d[63]) : "r"(a0), "r"(a1), "r"(a2), "r"(a3), "l"(db), "r"(sd));
}

#define BAR(i) (bars + 8u * (uint32_t)(i))

template <int G> __device__ __forceinline__ void conv_frags(uint32_t (&a)[12], uint32_t abase) {
#pragma unroll
  for (int i = 0; i < 12; i++) a[i] = lds32(abase + (G * 4 + i / 3) * 128 + (i % 3) * 4);
}
__device__ __forceinline__ void kv_prefetch(const __nv_bfloat16* pf, int task) { prefetch_if(pf + 64 * (task & 31) * DM + 64 * (task >> 5), task < 320); }
__device__ __forceinline__ void kv_load(const Params& P, Scratch* S, int task, int tid, uint32_t (&k_)[19], uint32_t (&v_)[16], uint4& sk) {
  const int row = 64 * (task & 31) + 16 * (tid >> 5), ch = 64 * (task >> 5) + 2 * (tid & 31);
  const uint32_t* kp = (const uint32_t*)(P.k + (size_t)row * DM + ch);
  const uint32_t* vp = (const uint32_t*)(P.v + (size_t)row * DM + ch);
  const uint32_t* hp = row > 0 ? kp - 3 * (DM / 2) : S->zero;
  const int hs = row > 0 ? DM / 2 : 0;
  asm volatile("ld.global.nc.v4.u32 {%0,%1,%2,%3},[%4];" : "=r"(sk.x), "=r"(sk.y), "=r"(sk.z), "=r"(sk.w) : "l"(P.shk + ch * 4));
#pragma unroll
  for (int i = 0; i < 3; i++) k_[i] = ldg1(hp + i * hs);
#pragma unroll
  for (int i = 0; i < 16; i++) { k_[i + 3] = ldg1(kp + i * (DM / 2)); v_[i] = ldg1(vp + i * (DM / 2)); }
}
template <int SH> __device__ __forceinline__ void xb_prefetch(const Head& H, int id, int tid, int c0) {
  const int ri = tid >> SH, rr = 11 * id + ri - 16;
  const __nv_bfloat16* p = ri < 16 ? H.x + (size_t)(16 * min(id, 127) + ri) * DM : (rr < DM ? H.b0 : H.b1 - DM * DM) + (size_t)rr * DM;
  prefetch_if(p + c0 + 64 * (tid & ((1 << SH) - 1)), ri < 16 || (ri < 27 && rr < 2 * DM));
}
__device__ __forceinline__ uint4 ldg4(const void* p) { uint4 v; asm volatile("ld.global.nc.v4.u32 {%0,%1,%2,%3},[%4];" : "=r"(v.x), "=r"(v.y), "=r"(v.z), "=r"(v.w) : "l"(p)); return v; }
__device__ __forceinline__ uint4 lds4(uint32_t a) { uint4 v; asm volatile("ld.shared.v4.u32 {%0,%1,%2,%3},[%4];" : "=r"(v.x), "=r"(v.y), "=r"(v.z), "=r"(v.w) : "r"(a) : "memory"); return v; }
__device__ __forceinline__ void discretise(const Head& H, const Params& P, uint32_t sb, Role R, int lane, uint32_t e1) {
  const uint32_t dn = __ldg((const unsigned short*)P.ssmd + min(conv_ch(R.c, (lane + 7) & 7), DM - 1));
  const int c = 32 * min(R.cb(), 9) + lane;
  const uint32_t lr2 = ldg1(P.lre + 2 * c), li2 = ldg1(P.lim + 2 * c), ld2 = ldg1(P.ldt + 2 * c);
  asm volatile("st.shared.u32 [%0],%1;" ::"r"(sb + MISC_OFF + 4 * (lane & 7)), "r"((lane & 7) ? dn : e1) : "memory");
#pragma unroll 1
  for (int i = 0; i < 2; i++) {
    const float lr = bf_hi(lr2 << (16 - 16 * i)), li = bf_hi(li2 << (16 - 16 * i));
    const float2 lb = lam_bar(lr, li, bf_hi(ld2 << (16 - 16 * i)));
    const float nx = lb.x - 1.f, ny = lb.y, inv = 2.f * frcp(lr * lr + li * li), cx = (nx * lr + ny * li) * inv, cy = (ny * lr - nx * li) * inv;
    const bool sw = !H.swap;
    asm volatile("st.shared.v4.f32 [%0],{%1,%2,%3,%4};" ::"r"(sb + LAM_OFF + 32 * lane + 16 * i), "f"(lb.x), "f"(sw ? -lb.y : lb.y), "f"(sw ? -cy : cx), "f"(sw ? cx : -cy) : "memory");
  }
  __syncwarp();
}
__device__ __forceinline__ void aux_prep(const Head& H, const Params& P, uint32_t sb, Role R, int tid, long long t_start) {
  Scratch* const S = H.s;
  const uint32_t bars = sb + BAR_OFF;
  tid = opaque(tid);
  const int w = tid >> 5, lane = tid & 31, tb = R.tb(), cb = R.cb();
  uint32_t k_[19], v_[16];
  uint4 sk;
  int task = R.b() < R.nprep() ? R.b() : 320;
  delay(KVDLY);
  PROFC(tid == 0, 345);
  kv_load(P, S, min(task, 319), tid, k_, v_, sk);
  const __nv_bfloat16* pf = (tid < 64 ? P.k : P.v) + (tid & 63) * DM;
  const int j = lane >> 3, sm = min(R.sm(), 9), trow = 160 * tb + 4 * sm + (tb < 12 ? 40 : 32) * w + j;
  const uint32_t so = sb + (2 * w + (j & 1) + 8 * (j >> 1)) * 128 + 16 * (lane & 7), xo = so + sm * 2048, wo = so + (tb & 1) * 8192 + (tb & 6) * 1024;
  const __nv_bfloat16* xp = H.x + (size_t)min(trow, SEQ - 1) * DM + 384 + 8 * (lane & 7);
  const __nv_bfloat16* bp = (j < 2 ? H.b0 : H.b1) + (size_t)(64 * cb + 32 * (tb & 1) + 4 * (tb & 6) + 2 * w + (j & 1)) * DM + 384 + 8 * (lane & 7);
  float s = 0.f, s2 = 0.f, sr = 0.f;
#define STAT(m, n) { const uint32_t xw[4] = {m.x, m.y, m.z, m.w}, bw[4] = {n.x, n.y, n.z, n.w}; \
  _Pragma("unroll") for (int i = 0; i < 4; i++) { const float u = bf_lo(xw[i]), v = bf_hi(xw[i]); s += u + v; s2 = fmaf(u, u, fmaf(v, v, s2)); sr += bf_lo(bw[i]) + bf_hi(bw[i]); } }
#define STATS(K0, K1) _Pragma("unroll 1") for (int kb = K0; kb < K1; kb++) { \
    mbar_wait(BAR(B_F1 + kb)); \
    const uint4 a = lds4(xo + ((uint32_t)(XTAB0 >> (6 * kb)) & 63) * 4096), c = lds4(wo + ((uint32_t)(WTAB0 >> (6 * kb)) & 63) * 4096); \
    STAT(a, c) \
    asm volatile("" : "+f"(s), "+f"(s2), "+f"(sr)); \
    if (XPFAT >= K0 && XPFAT < K1) prefetch_if(((lane & 4) ? bp : xp) + 64 * (lane & 3), kb == XPFAT); \
    kv_prefetch(pf, kb == KPFAT ? task + R.nprep() : kb == KPFAT2 ? task + 2 * R.nprep() : 320); \
  } \
  __syncwarp(); mbar_arrive_if(BAR(B_AX + K0 / 3), lane == 0);
  STATS(0, 3)
  PROFC(tid == 0, 349);
    {
      uint4 m[4], n[4];
#pragma unroll
      for (int i = 0; i < 4; i++) { m[i] = ldg4(xp + 64 * i); n[i] = ldg4(bp + 64 * i); }
      STATS(3, 6)
      PROFC(tid == 0, 346);
      mbar_wait(BAR(B_LM));
      const uint32_t tag = lds32(sb + MISC_OFF) & 1;
#pragma unroll
      for (int i = 0; i < 4; i++) { const uint4 a = m[i], c = n[i]; STAT(a, c) }
      PROFC(tid == 0 && s2 != 1.2345f, 347);
#pragma unroll
      for (int o = 1; o <= 4; o <<= 1) { s += __shfl_xor_sync(0xffffffff, s, o); s2 += __shfl_xor_sync(0xffffffff, s2, o); sr += __shfl_xor_sync(0xffffffff, sr, o); }
      const float mn = s * (1.f / DM), rs = frcp(bf_rn(fsqrt(bf_rn(bf_rn(fmaxf(s2 * (1.f / DM) - mn * mn, 0.f)) + 1e-5f))));
      asm volatile("{ .reg .pred p; setp.ne.u32 p, %2, 0; @p st.relaxed.gpu.global.u32 [%0],%1; }"
                   ::"l"((uint32_t*)(S->RS + (8 * cb + 4 * (tb & 1) + (tb >> 1)) * 16 + 4 * w + (j & 1)) + (lane & 4) + (j >> 1)), "r"(tagf(sr, tag)),
                   "r"((uint32_t)(tb < 8 && (lane & 3) == 0)) : "memory");
      asm volatile("{ .reg .pred p; setp.ne.u32 p, %3, 0; @p st.relaxed.gpu.global.v2.u32 [%0],{%1,%2}; }"
                   ::"l"(S->S + trow), "r"(tagf(rs, tag)), "r"(tagf(-bf_rn(mn) * rs, tag)), "r"((uint32_t)(R.sm() < 10 && (lane & 7) == 0)) : "memory");
      PROFC(tid == 0, 3);
    }
#pragma unroll 1
  for (int r = 0; task < 320; r++) {
    {
      const uint32_t T0 = __byte_perm(sk.x, sk.z, 0x5410), T1 = __byte_perm(sk.x, sk.z, 0x7632);
      const uint32_t T2 = __byte_perm(sk.y, sk.w, 0x5410), T3 = __byte_perm(sk.y, sk.w, 0x7632);
      PROFC(tid == 0 && v_[15] != 0x12345, 336 + r);
      uint32_t o[16];
#pragma unroll
      for (int t = 0; t < 16; t += 2) {
        const uint32_t a = hmul2(hfma2(k_[t + 3], T0, hfma2(k_[t + 2], T1, hfma2(k_[t + 1], T2, hmul2(k_[t], T3)))), v_[t]);
        const uint32_t c = hmul2(hfma2(k_[t + 4], T0, hfma2(k_[t + 3], T1, hfma2(k_[t + 2], T2, hmul2(k_[t + 1], T3)))), v_[t + 1]);
        const int wd = ((7 - t / 2) >> 1) + 4 * ((7 - t / 2) & 1);
        o[wd] = __byte_perm(c, a, 0x5410); o[8 + wd] = __byte_perm(c, a, 0x7632);
        asm volatile("" : "+r"(o[wd]), "+r"(o[8 + wd]));
        if (t == PFAT) kv_prefetch(pf, task + (1 + PFD) * R.nprep());
      }
      PROFC(tid == 0, 330 + 2 * r);
      const int ph = task & 1;
      task += R.nprep();
      if (ORD == 0 && task < 320) kv_load(P, S, task, tid, k_, v_, sk);
      mbar_wait(BAR(B_E1 + 3)); mbar_wait(BAR(B_AX + 1));
#pragma unroll
      for (int i = 0; i < 4; i++) {
        const int row = 2 * lane + (i >> 1);
        asm volatile("st.shared.v4.u32 [%0],{%1,%2,%3,%4};" ::"r"(sb + KS_OFF + r * 8192 + row * 128 + (((2 * w + ((i & 1) ^ ph)) ^ (row & 7)) << 4)),
                     "r"(o[4 * i]), "r"(o[4 * i + 1]), "r"(o[4 * i + 2]), "r"(o[4 * i + 3]) : "memory");
      }
      __syncwarp();
      mbar_arrive_if(BAR(B_PS + r), lane == 0);
      PROFC(tid == 0, 331 + 2 * r);
      if (ORD == 1 && task < 320) kv_load(P, S, task, tid, k_, v_, sk);
    }
  }
#undef STAT
#undef STATS
  PROFC(tid == 0, 40);
}
#define SPLIT(G) asm volatile("{ .reg .pred p; .reg .u32 r; L: mov.u32 r, %%clock; setp.eq.u32 p, r, %0; @p bra.uni L; }" ::"n"(G) : "memory")
template <bool AUX>
__device__ __forceinline__ void conv_loop(uint32_t sb, uint32_t rc, int wg, int tid, long long t_start) {
  sb = opaque(sb); rc = opaque(rc);
  const uint32_t bars = sb + BAR_OFF;
  int slot = AUX ? 0 : wg + 1;
  mbar_wait(BAR(B_LM));
#pragma unroll 1
  while (slot < (int)((rc >> 10) & 7)) {
    tid = opaque(tid);
    const int w = tid >> 5, lane = tid & 31, g = lane >> 2, q = lane & 3;
    const uint32_t Dn = lds32(sb + MISC_OFF + 4 + 4 * slot);
    const uint32_t d0 = (g == 1 && q == 3 - w) ? Dn : 0, d1 = (g == 0 && q == 3 - w) ? Dn : 0;
    const uint32_t cb_ = conv_buf(sb, slot), c0 = cb_ + KC_OFS;
    const uint32_t abase = c0 + 2 * (2 * (g & 1) + 4 * w + 16 * (g >> 1) + 4 * q);
    const uint64_t bd = make_desc(cb_ + KV_PAD, 16, 256, 3);
    const bool hi = lane & 16, s1 = lane & 8;
    const int qo = hi ? (q + 1) & 3 : q;
    const int srcA = hi ? (lane & 12) | ((q + 1) & 3) : (lane & 12) | 16 | ((q + 3) & 3);
    const bool h3 = hi && q == 3, wrap = s1 && qo == 3, back = wrap && hi;
    const bool chi = wrap ? !hi : hi;
    const int cq = s1 ? (qo + 1) & 3 : qo;
    const int srcB = (lane & 4) | (s1 ? 0 : 8) | (chi ? 16 | ((cq + 3) & 3) : cq);
    const uint32_t gp = c0 + 16 * (2 * (g & 1) + 4 * w) + (chi ? 256 : 0) + 2 * (2 * cq + (s1 ? 0 : 1));
    uint32_t a[12], f[16], o[8];
    float S[4], T[4], U[2], keep[2], pv[2] = {0.f, 0.f}, pr[4] = {0.f, 0.f, 0.f, 0.f};
    float e0[64], e1[56], e2[48], e3[40], e4[32], e5[24], e6[16], e7[8];
#define UNR _Pragma("unroll")
#define PERM() UNR for (int i = 0; i < 4; i++) { f[4 * i] = __byte_perm(a[3 * i], a[3 * i + 1], 0x5432); f[4 * i + 1] = a[3 * i + 1]; \
                                                 f[4 * i + 2] = __byte_perm(a[3 * i + 1], a[3 * i + 2], 0x5432); f[4 * i + 3] = a[3 * i + 2]; }
#define MMA(N, E) UNR for (int i = 0; i < 4; i++) wgmma_rs<N>(E, f[4 * i], f[4 * i + 1], f[4 * i + 2], f[4 * i + 3], bd - 8 * i, 1); wg_commit();
#define L1(c) UNR for (int i = 0; i < 4; i++) { const float ev = c[i], od = c[4 + i]; S[i] = hi ? (h3 ? ev : od) : ev; \
                                                T[i] = __shfl_sync(0xffffffff, hi ? (h3 ? pr[i] : ev) : od, srcA); pr[i] = od; }
#define L1E() UNR for (int i = 0; i < 4; i++) S[i] += T[i];
#define L2() UNR for (int h = 0; h < 2; h++) { keep[h] = back ? pv[h] : S[2 * h + 1]; pv[h] = S[2 * h + 1]; U[h] = __shfl_sync(0xffffffff, S[2 * h], srcB); }
#define L2E(j) o[j] = pack_bf(keep[0] + U[0], keep[1] + U[1]);
#define GRP(G, N, P, E) UNR for (int i = 0; i < N / 2; i++) asm volatile("mov.b32 %0,%1;" : "=f"(E[i]) : "f"(P[i + 8])); \
    wg_fence(); if (G < 7) conv_frags<(G + 1) & 7>(a, abase); if (G >= 2) { L2() } L1(P) MMA(N, E) SPLIT(G); \
    if (G < 7) { PERM() } if (G >= 2) { L2E((G + 6) & 7) } L1E() wg_wait<0>(); fence_regs(E);
    PROFC(tid == 0, 300 + 4 * slot);
    mbar_wait(BAR(B_KF + slot));
    if (tid == 0) PROF(361 + slot);
    PROFC(tid == 0, 301 + 4 * slot);
    conv_frags<0>(a, abase);
    wg_fence();
    wgmma_rs<128>(e0, d0 << 16, d0, d1 << 16, d1, bd, 0);
    PERM() conv_frags<1>(a, abase); wg_fence(); MMA(128, e0) SPLIT(0); PERM() wg_wait<0>(); fence_regs(e0);
    GRP(1, 112, e0, e1) GRP(2, 96, e1, e2) GRP(3, 80, e2, e3) GRP(4, 64, e3, e4) GRP(5, 48, e4, e5) GRP(6, 32, e5, e6) GRP(7, 16, e6, e7)
    PROFC(tid == 0, 302 + 4 * slot);
    L2() L1(e7) L2E(6) L1E() L2() L2E(7)
    bar_sync(wg + 1, 128);
#pragma unroll
    for (int jj = 0; jj < 8; jj++)
      asm volatile("st.shared.u16 [%0],%1; st.shared.u16 [%0+16],%2;" ::"r"(gp + jj * 512), "h"((uint16_t)o[jj]), "h"((uint16_t)(o[jj] >> 16)) : "memory");
#undef PERM
#undef MMA
#undef L1
#undef L1E
#undef L2
#undef L2E
#undef GRP
    PROFC(tid == 0, 303 + 4 * slot);
    __syncwarp();
    if (lane == 0) mbar_arrive(BAR(B_GS + slot));
    if (!AUX) break;
    slot = slot ? slot + 1 : 3;
  }
}

#define IDX(J, c, h) (8 * (J) + 4 * ((c) >> 1) + 2 * (h) + ((c) & 1))
__device__ __forceinline__ uint2 lds2(uint32_t a) { uint2 v; asm volatile("ld.shared.v2.u32 {%0,%1},[%2];" : "=r"(v.x), "=r"(v.y) : "r"(a) : "memory"); return v; }
__device__ __forceinline__ void resid_load(float (&r)[40], uint32_t sb, int wg, int tid, const uint4& s) {
  const uint32_t dp = sb + XR_OFF + 8 * (tid & 3), xp = dp + (64 * wg + 16 * (tid >> 5) + ((tid & 31) >> 2)) * 160;
#pragma unroll
  for (int J = 0; J < 5; J++) {
    const uint2 u = lds2(xp + 32 * J), v = lds2(xp + 32 * J + 1280), d = lds2(dp + 20480 + 32 * J);
    r[8 * J] = __uint_as_float(u.x); r[8 * J + 1] = __uint_as_float(u.y); r[8 * J + 2] = __uint_as_float(v.x); r[8 * J + 3] = __uint_as_float(v.y);
    r[8 * J + 4] = __uint_as_float(d.x); r[8 * J + 5] = __uint_as_float(d.y);
  }
  r[30] = untag(s.x); r[31] = untag(s.y); r[38] = untag(s.z); r[39] = untag(s.w);
}
__device__ __forceinline__ void resid_init(float (&r)[40]) {
  const float s[4] = {r[30], r[31], r[38], r[39]};
#pragma unroll
  for (int J = 0; J < 5; J++) {
    uint32_t w[6];
#pragma unroll
    for (int i = 0; i < 6; i++) w[i] = __float_as_uint(r[8 * J + i]);
#pragma unroll
    for (int i = 0; i < 4; i++) {
      const int h = i >> 1, c = 2 * (i & 1);
      const float rs = s[2 * h], nm = s[2 * h + 1], x0 = bf_lo(w[i]), x1 = bf_hi(w[i]);
      const uint32_t t = hmul2(pack_bf(fmaf(x0, rs, nm), fmaf(x1, rs, nm)), w[4 + (i & 1)]);
      r[IDX(J, c, h)] = x0 + bf_lo(t); r[IDX(J, c + 1, h)] = x1 + bf_hi(t);
    }
  }
}

__device__ __forceinline__ float flip(float v, uint32_t m) { return __uint_as_float(__float_as_uint(v) ^ m); }
__device__ __forceinline__ void g1_phase(const int LY, const Head& H, uint32_t sb, int wg, int tid, Role R, float (&xr)[40], long long t_start) {
  Scratch* const S = H.s;
  tid = opaque(tid); sb = opaque(sb); R.v = opaque(R.v);
  const uint32_t bars = sb + BAR_OFF;
  const int cb = R.cb(), tb = R.tb();
  const int w = tid >> 5, lane = tid & 31, g = lane >> 2, q = lane & 3;
  const bool full = tb < 12;
  uint2* Eb = S->E + ((LY * 130 + cb) * 8 + 4 * wg + w) * 16 + g;
  float a[80];
#pragma unroll
  for (int i = 0; i < 80; i++) a[i] = 0.f;
  uint32_t rel = mapa(BAR(B_E1), lane ? R.wpart() : R.ubase() + (w & (R.ugs() - 1)));
  const bool rels = lane == 0 || (tid == 1 && wg != R.wlo());
  {
    uint64_t tw = LY ? WTAB1 : WTAB0, tx = LY ? XTAB1 : XTAB0;
    uint32_t bf = BAR(B_F1);
    const int sg = LY ? S1G : S1G0, lag = wg && sg ? sg : -1, lead = !wg && sg ? 9 : -1;
    if (tid == 0 && wg == 0 && !LY) PROF(351);
    fence_regs(a);
    mbar_wait(bf, LY);
    if (tid == 0 && wg == 0) PROF(LY ? 20 : 4);
#pragma unroll 1
    for (int kb = 0; kb < 10; kb++) {
      const uint64_t da = make_desc(sb + ((uint32_t)tw & 63) * 4096 + wg * 8192, 16, 1024, 1);
      const uint64_t db = make_desc(sb + ((uint32_t)tx & 63) * 4096, 16, 1024, 1);
      if ((S1G || S1G0) && kb == lag) bar_sync(5, 256);
      wg_fence();
#pragma unroll
      for (int kk = 0; kk < 4; kk++) wgmma_ss160(a, da + 2 * kk, db + 2 * kk, 1);
      wg_commit();
      if ((S1G || S1G0) && kb == lead) asm volatile("bar.arrive 5, 256;" ::: "memory");
      wg_wait<1>();
      if (kb > 0) { if (rels) mbar_arrive_at(rel); rel += 8; }
      bf += 8; tw >>= 6; tx >>= 6;
      if (kb < 9) mbar_wait(bf, LY);
    }
  }
  if (tid == 0 && wg == 0) PROF(LY ? 19 : 2);
  mbar_wait(BAR(B_LM));
  const uint32_t tag = lds32(sb + MISC_OFF) & 1;
  if (q == 3) st_rlx2(Eb + tb * 1280, tag ^ 1, tag ^ 1);
  float2 lam, mu, mu2;
  float rs0, rs1;
  const uint32_t lamp = sb + LAM_OFF + 16 * (32 * wg + 8 * w + g);
  {
    const uint2* rp = S->RS + (8 * cb + 4 * wg + w) * 16 + 2 * g - (g & 1);
    uint2 v = ld_rlx2(rp);
    asm volatile("ld.shared.v2.f32 {%0,%1},[%2];" : "=f"(lam.x), "=f"(lam.y) : "r"(lamp));
    const float2 l2 = cmul(lam, lam), l4 = cmul(l2, l2), l8 = cmul(l4, l4), l16 = cmul(l8, l8), l32 = cmul(l16, l16);
    mu = full ? cmul(l32, l8) : l32; mu2 = cmul(mu, mu);
#pragma unroll 1
    for (int it = 0; it < SPIN && __any_sync(0xffffffff, untagged(v, tag)); it++) v = ld_rlx2(rp);
    rs0 = untag(v.x); rs1 = untag(v.y);
  }
  if (tid == 0 && wg == 0 && !LY) PROF(39);
  mbar_wait(BAR(B_ST), LY);
  const uint32_t ssm = sb + SSM_OFF + q * (full ? 336 : 272);
  wg_wait<0>(); fence_regs(a);
  if (rels) mbar_arrive_at(rel);
  if (tid == 0 && wg == 0) PROF(LY ? 21 : 5);
  float2 p = make_float2(0.f, 0.f);
#pragma unroll
  for (int j = 0; j < 20; j++) {
    if (j < 16 || full) {
      float4 sv;
      asm volatile("ld.shared.v4.f32 {%0,%1,%2,%3},[%4];" : "=f"(sv.x), "=f"(sv.y), "=f"(sv.z), "=f"(sv.w) : "r"(ssm + 16 * j));
#pragma unroll
      for (int e = 0; e < 2; e++) {
        const int o = 4 * j + e;
        const float r = e ? sv.z : sv.x, nm = e ? sv.w : sv.y;
        a[o] = fmaf(a[o], r, nm * rs0); a[o + 2] = fmaf(a[o + 2], r, nm * rs1);
        p = cfma(lam, p, make_float2(a[o], a[o + 2]));
      }
    }
  }
  {
    float2 t = make_float2(__shfl_up_sync(0xffffffff, p.x, 1, 4), __shfl_up_sync(0xffffffff, p.y, 1, 4));
    if (q >= 1) p = cfma(mu, t, p);
    t = make_float2(__shfl_up_sync(0xffffffff, p.x, 2, 4), __shfl_up_sync(0xffffffff, p.y, 2, 4));
    if (q >= 2) p = cfma(mu2, t, p);
  }
  if (q == 3 && full) st_rlx2(Eb + tb * 1280, tagf(p.x, tag), tagf(p.y, tag));
  if (tid == 0 && wg == 1) PROF(96 + 64 * LY);
  uint2 ev[3];
#pragma unroll
  for (int i = 0; i < 3; i++) { const int j = tb - 1 - q - 4 * i; ev[i] = j >= 0 ? ld_rlx2(Eb + j * 1280) : make_uint2(tag, tag); }
  float2 x = make_float2(__shfl_up_sync(0xffffffff, p.x, 1, 4), __shfl_up_sync(0xffffffff, p.y, 1, 4));
  if (q == 0) x = make_float2(0.f, 0.f);
  float c0, c1;
  asm volatile("ld.shared.v2.f32 {%0,%1},[%2+8];" : "=f"(c0), "=f"(c1) : "r"(lamp));
  const float c2 = -flip(c1, H.swap), c3 = flip(c0, H.swap);
#pragma unroll
  for (int i = 0; i < 40; i++) {
    const int o = 4 * (i >> 1) + (i & 1);
    const float u = a[o], v = a[o + 2];
    a[o] = fmaf(c0, u, c1 * v); a[o + 2] = fmaf(c2, u, c3 * v);
  }
  fence_regs(a);
  if (LY == 0 && R.b() < 128) {
    const int t0 = 16 * g + 8 * wg + 2 * w;
    if (tid == 0 && wg == 1) PROF(366);
    mbar_wait(BAR(B_XR));
    if (tid == 0 && wg == 1) PROF(367);
    uint4 s = lds4(sb + XR_OFF + 20480 + 256 + 8 * t0);
    if (__any_sync(0xffffffff, untagged(s, tag))) {
#pragma unroll 1
      for (int it = 0; it < SPIN; it++) { s = ld_rlx4(S->S + 128 * (R.b() >> 3) + t0); if (!__any_sync(0xffffffff, untagged(s, tag))) break; }
    }
    resid_load(xr, sb, wg, tid, s);
  }
  float2 mq, om4, fq;
  {
    asm volatile("" : "+f"(lam.x), "+f"(lam.y));
    const float2 one = make_float2(1.f, 0.f), l2 = cmul(lam, lam), l4 = cmul(l2, l2), l8 = cmul(l4, l4), l16 = cmul(l8, l8);
    const float2 l80 = full ? mu2 : cmul(mu2, l16), om = cmul(l80, l80), om2 = cmul(om, om);
    mq = cmul((q & 1) ? mu : one, (q & 2) ? mu2 : one);
    om4 = cmul(om2, om2); fq = cmul((q & 1) ? om : one, (q & 2) ? om2 : one);
  }
  mbar_wait(BAR(B_E1 + 9), LY);
  if (tid == 0 && wg == 1) PROF(368 + LY);
#pragma unroll 1
  for (int it = 0; it < SPIN; it++) {
    const bool m0 = untagged(ev[0], tag), m1 = untagged(ev[1], tag), m2 = untagged(ev[2], tag);
    if (!__any_sync(0xffffffff, m0 || m1 || m2)) break;
    if (m0) ev[0] = ld_rlx2(Eb + (tb - 1 - q) * 1280);
    if (m1) ev[1] = ld_rlx2(Eb + (tb - 5 - q) * 1280);
    if (m2) ev[2] = ld_rlx2(Eb + (tb - 9 - q) * 1280);
  }
  if (tid == 0 && wg == 1) PROF(97 + 64 * LY);
  float2 c = make_float2(untag(ev[2].x), untag(ev[2].y));
#pragma unroll
  for (int i = 1; i >= 0; i--) c = cfma(om4, c, make_float2(untag(ev[i].x), untag(ev[i].y)));
  c = cmul(fq, c);
#pragma unroll
  for (int s = 1; s <= 2; s <<= 1) { c.x += __shfl_xor_sync(0xffffffff, c.x, s); c.y += __shfl_xor_sync(0xffffffff, c.y, s); }
  c = cfma(mq, c, x);
  float2 z = make_float2(fmaf(c0, c.x, c1 * c.y), fmaf(c2, c.x, c3 * c.y));
  if (tid == 0 && wg == 0) PROF(LY ? 22 : 6);
  const float2 lc = make_float2(lam.x, flip(lam.y, H.swap));
  const uint32_t hq = sb + (lane >> 4) * 1024 + (lane & 7) * 128 + (((4 * wg + w) ^ (lane & 7)) << 4);
  const uint32_t hp = hq + R_OFF + (lane & 8) * 2048, hp4 = hq + (LY ? R4_OFF1 : R4_OFF0) + (lane & 8) * 512;
#pragma unroll
  for (int j = 0; j < 20; j += 2) {
    if (j < 16 || full) {
      uint32_t o[4];
#pragma unroll
      for (int i = 0; i < 2; i++) {
        const float2 z0 = cfma(lc, z, make_float2(a[4 * (j + i)], a[4 * (j + i) + 2]));
        z = cfma(lc, z0, make_float2(a[4 * (j + i) + 1], a[4 * (j + i) + 3]));
        o[2 * i] = pack_bf(z0.x, z.x); o[2 * i + 1] = pack_bf(z0.y, z.y);
      }
      asm volatile("stmatrix.sync.aligned.m8n8.x4.trans.shared.b16 [%0], {%1,%2,%3,%4};" ::"r"(j < 16 ? hp + j * 1024 : hp4 + (j - 16) * 1024), "r"(o[0]), "r"(o[1]), "r"(o[2]), "r"(o[3]) : "memory");
      if (j & 2) { __syncwarp(); if (lane == 0) mbar_arrive(BAR(B_SH + j / 4)); }
    }
  }
  if (tid == 0 && wg == 0) PROF(LY ? 23 : 7);
  if (lane == 0) PROF(390 + 4 * wg + w);
}

__device__ __forceinline__ void gate_load(uint32_t (&G)[20], uint32_t sb, int LY, int wg, int tid) {
  const uint32_t bars = sb + BAR_OFF;
  const int lane = tid & 31, w = tid >> 5;
  mbar_wait(BAR(B_GF), LY);
  __syncwarp();
  {
    const uint32_t gb = sb + (LY ? G_OFF1 : G_OFF0) + wg * 10240;
    const int dr = 4 * ((lane & 7) >> 1) + (lane & 1) + 2 * ((lane >> 3) & 1), ck = 2 * w + (lane >> 4);
#pragma unroll
    for (int J = 0; J < 5; J++) {
      const int dd = 16 * J + dr;
      asm volatile("ldmatrix.sync.aligned.m8n8.x4.trans.shared.b16 {%0,%1,%2,%3},[%4];"
                   : "=r"(G[4 * J]), "=r"(G[4 * J + 1]), "=r"(G[4 * J + 2]), "=r"(G[4 * J + 3]) : "r"(gb + dd * 128 + ((ck ^ (dd & 7)) << 4)) : "memory");
    }
  }
}
__device__ __forceinline__ void g2_phase(const int LY, const Params& P, Scratch* S, uint32_t sb, int wg, int tid, Role R, float (&xr)[40], long long t_start) {
  sb = opaque(sb);
  const uint32_t bars = sb + BAR_OFF;
  if (LY) {
    const int td = opaque(tid), b = (opaque(R.v) >> 8) & 255;
    const uint32_t tag = lds32(sb + MISC_OFF) & 1;
    const uint2* sp = S->S + 2 * SEQ + 128 * (b >> 3) + 4 * (td & 28) + 8 * wg + 2 * (td >> 5);
    if (!(R.cb() & 1)) mbar_wait(BAR(B_HD), 1);
    uint2 dl[5];
#pragma unroll
    for (int J = 0; J < 5; J++) dl[J] = __ldg((const uint2*)(P.dskip + 80 * (b & 7) + 4 * (td & 3) + 16 * J));
    uint4 sv;
#pragma unroll 1
    for (int it = 0; it < SPIN; it++) { sv = ld_rlx4(sp); if (!__any_sync(0xffffffff, untagged(sv, tag))) break; }
#pragma unroll
    for (int h = 0; h < 2; h++)
#pragma unroll
      for (int J = 0; J < 5; J++)
#pragma unroll
        for (int c = 0; c < 4; c++) {
          const float x2 = xr[IDX(J, c, h)];
          const uint32_t dw = (c & 2) ? dl[J].y : dl[J].x;
          xr[IDX(J, c, h)] = fmaf(fmaf(x2, untag(h ? sv.z : sv.x), untag(h ? sv.w : sv.y)), (c & 1) ? bf_hi(dw) : bf_lo(dw), x2);
        }
    fence_regs(xr);
  }
  float acc[40];
#pragma unroll
  for (int i = 0; i < 40; i++) acc[i] = RIAT == 1 ? 0.f : xr[i];
  fence_regs(acc);
#define G2_STEP(st, cs, hf) { \
    const uint64_t da = make_desc(sb + H_OFF + (st) * 32768 + (hf) * 16384 + wg * 8192, 16, 1024, 1), db = make_desc(sb + (cs) * 20480 + (hf) * 10240, 16, 1024, 1); \
    wg_fence(); \
    _Pragma("unroll") for (int kk = 0; kk < 4; kk++) wgmma_ss80(acc, da + 2 * kk, db + 2 * kk, 1); \
    wg_commit(); }
  mbar_wait(BAR(B_F2), LY);
  if (tid == 0 && wg == 0) PROF(LY ? 25 : 10);
  G2_STEP(0, 0, 0)
  mbar_wait(BAR(B_F3), LY);
  G2_STEP(0, 0, 1)
  tid = opaque(tid); R.v = opaque(R.v);
  const uint32_t tag = lds32(sb + MISC_OFF) & 1;
  const int b = R.b(), tb2 = b >> 3, db_ = b & 7;
  const int w = tid >> 5, lane = tid & 31, g = lane >> 2, q = lane & 3;
  const int t0 = 128 * tb2 + 16 * g + 8 * wg + 2 * w;
  const int d0 = 80 * db_ + 4 * q, mrow = 64 * wg + 16 * w + g;
#define GATE(J, c, h) (((c) & 1) ? bf_hi(G[4 * (J) + 2 * (h) + ((c) >> 1)]) : bf_lo(G[4 * (J) + 2 * (h) + ((c) >> 1)]))
  uint32_t rel = mapa(BAR(B_E2), lane ? ((w & 1) ? R.wpart() : R.rank()) : R.cs() == 8 ? 4 * wg + w : wg);
  const bool rels = lane == 0 || (lane == 1 && w < 2);
  uint32_t* Mb = S->M + ((2 * LY * 16 + tb2) * 8) * 256 + (wg * 4 + w) * 32 + (2 * g + (q & 1)) * 2 + (q >> 1);
  {
    uint32_t bf = BAR(B_F2 + 1), st = 1, ra = rel + 8 * (B_EA - B_E2);
    const int lag = wg ? (LY ? STG : STG0) / 2 : 0;
#pragma unroll 1
    for (int kp = 1; kp < 10; kp++) {
      const bool more = LY == 0 || kp < 8;
      wg_wait<1>();
      if (lane == 0 && more) mbar_arrive_at(ra + 8 * (st ? st - 1 : 2));
      mbar_wait(bf, LY);
      if (STG && !(STG & 1) && kp == lag) bar_sync(5, 256);
      G2_STEP(st, kp < 5 ? kp : kp - 5, 0)
      wg_wait<1>();
      if (rels && more) mbar_arrive_at(rel);
      rel += 8;
      mbar_wait(bf + 8 * (B_F3 - B_F2), LY);
      if ((STG & 1) && kp == lag) bar_sync(5, 256);
      G2_STEP(st, kp < 5 ? kp : kp - 5, 1)
      if (kp == MIAT) {
        st_rlx(Mb + db_ * 256, tag ^ 1);
        if (LY == 0) st_rlx(Mb + (16 * 8 + db_) * 256, tag ^ 1);
      }
      bf += 8; st = st == 2 ? 0 : st + 1;
    }
  }
  if (STG && (LY || STG0) && !wg) asm volatile("bar.arrive 5, 256;" ::: "memory");
  wg_wait<0>(); fence_regs(acc);
  if (LY == 0 && rels) mbar_arrive_at(rel);
  if (tid == 0 && wg == 0) PROF(LY ? 26 : 11);
  if (lane == 0) PROF(116 + 64 * LY + wg * 4 + w);

  float mm[2] = {0.f, 0.f}, rr[2];
#pragma unroll 1
  for (int rep = 0;; rep++) {
    float m[2][2];
#pragma unroll
    for (int h = 0; h < 2; h++) {
      m[h][0] = m[h][1] = 0.f;
#pragma unroll
      for (int J = 0; J < 5; J++)
#pragma unroll
        for (int c = 0; c < 4; c++) { const float xv = acc[IDX(J, c, h)]; m[h][0] += xv; m[h][1] = fmaf(xv, xv, m[h][1]); }
    }
    float r1[2];
#pragma unroll
    for (int i = 0; i < 2; i++) { const float snd = (q & 1) ? m[0][i] : m[1][i], kp = (q & 1) ? m[1][i] : m[0][i]; r1[i] = kp + __shfl_xor_sync(0xffffffff, snd, 1); }
    const float r2 = ((q & 2) ? r1[1] : r1[0]) + __shfl_xor_sync(0xffffffff, (q & 2) ? r1[0] : r1[1], 2);
    const uint32_t mx = sb + MX_OFF + 512 * wg + 4 * tid, bx = BAR(B_KF + 1 + (PWG ? 2 * LY + wg : LY));
    if (R.cs() == 8 && !rep) {
#pragma unroll
      for (int i = 0; i < 8; i++)
        asm volatile("st.async.weak.shared::cluster.mbarrier::complete_tx::bytes.b32 [%0],%1,[%2];" ::"r"(mapa(mx + 1024 * db_, i ^ db_)), "f"(r2), "r"(mapa(bx, i ^ db_)) : "memory");
      if (tid == 0 && (PWG || wg == 0)) mbar_expect_tx(bx, PWG ? 4096 : 8192);
    }
    st_rlx(Mb + db_ * 256, tagf(r2, tag));
    if (rep) break;
    if (lane == 0) PROF(100 + 64 * LY + wg * 4 + w);
    uint32_t G[20];
    const bool late = LY == 0 && db_ >= GLATE;
#pragma unroll
    for (int i = 0; i < 20; i++) G[i] = 0;
    if (!late) gate_load(G, sb, LY, wg, tid);
    mbar_wait(BAR(B_CD + 1));
    uint32_t mv[8];
    if (R.cs() == 8) {
      mbar_wait(bx, 1);
#pragma unroll
      for (int i = 0; i < 8; i++) mv[i] = lds32(mx + 1024 * i);
    } else {
#pragma unroll
    for (int i = 0; i < 8; i++) mv[i] = ld_rlx(Mb + i * 256);
#pragma unroll 1
    for (int it = 0; it < SPIN; it++) {
      uint32_t miss = 0;
#pragma unroll
      for (int i = 0; i < 8; i++) miss |= ((mv[i] ^ tag) & 1) << i;
      if (!__any_sync(0xffffffff, miss)) break;
#pragma unroll
      for (int i = 0; i < 8; i++) if ((miss >> i) & 1) mv[i] = ld_rlx(Mb + i * 256);
    }
      bar_sync(4, 256);
    }
    if (lane == 0) PROF(108 + 64 * LY + wg * 4 + w);
    const float s = ((untag(mv[0]) + untag(mv[1])) + (untag(mv[2]) + untag(mv[3]))) + ((untag(mv[4]) + untag(mv[5])) + (untag(mv[6]) + untag(mv[7])));
    const float o = __shfl_xor_sync(0xffffffff, s, 2);
    const float S1 = (q & 2) ? o : s, S2 = (q & 2) ? s : o;
    const float mean = S1 * (1.f / DM), rs = frsqrt(fmaxf(S2 * (1.f / DM) - mean * mean, 0.f) + 1e-5f);
    const float mo = __shfl_xor_sync(0xffffffff, mean, 1), ro = __shfl_xor_sync(0xffffffff, rs, 1);
    mm[0] = (q & 1) ? mo : mean; mm[1] = (q & 1) ? mean : mo; rr[0] = (q & 1) ? ro : rs; rr[1] = (q & 1) ? rs : ro;
    if (late) gate_load(G, sb, LY, wg, tid);
    if (tid == 0 && wg == 0) PROF(LY ? 27 : 12);
    const float nm[2] = {-mm[0] * rr[0], -mm[1] * rr[1]};
    if (LY) mm[0] = mm[1] = 0.f;
#pragma unroll
    for (int h = 0; h < 2; h++)
#pragma unroll
      for (int J = 0; J < 5; J++)
#pragma unroll
        for (int c = 0; c < 4; c++) { const float xv = acc[IDX(J, c, h)]; acc[IDX(J, c, h)] = fmaf(fmaf(xv, rr[h], nm[h]), GATE(J, c, h), xv - mm[h]); }
    if (LY) break;
    if (PWG && R.cs() == 8) mbar_wait(BAR(B_KF + 2 - wg), 1);
#pragma unroll
    for (int i = 0; i < 10; i++) {
      const int J = i >> 1, h = i & 1;
      const uint32_t u0 = pack_bf(acc[IDX(J, 0, h)], acc[IDX(J, 1, h)]), u1 = pack_bf(acc[IDX(J, 2, h)], acc[IDX(J, 3, h)]);
      asm volatile("st.shared.v2.u32 [%0],{%1,%2};" ::"r"(sb + US_OFF + (mrow + 8 * h) * 160 + 32 * J + 8 * q), "r"(u0), "r"(u1) : "memory");
    }
    __syncwarp();
    if (lane == 0) mbar_arrive(BAR(B_SG));
    if (tid == 0 && wg == 0) PROF(13);
    Mb += 16 * 8 * 256;
  }
  if (LY == 0) {
#pragma unroll
    for (int i = 0; i < 40; i++) xr[i] = acc[i] + mm[(i >> 1) & 1];
    if (tid == 0 && wg == 0) PROF(15);
  }
  else {
    float* op = P.out + (size_t)t0 * DM + d0;
#pragma unroll
    for (int i = 0; i < 10; i++) {
      const int J = i >> 1, h = i & 1;
      asm volatile("st.global.v4.f32 [%0],{%1,%2,%3,%4};" ::"l"(op + h * DM + 16 * J),
                   "f"(acc[IDX(J, 0, h)]), "f"(acc[IDX(J, 1, h)]), "f"(acc[IDX(J, 2, h)]), "f"(acc[IDX(J, 3, h)]) : "memory");
    }
  }
  if (tid == 0 && wg == 0 && LY) PROF(28);
#undef IDX
#undef GATE
}

__device__ __forceinline__ void next_stats(Scratch* S, uint32_t sb, int tb2, int tid) {
  const uint32_t bars = sb + BAR_OFF, tag = lds32(sb + MISC_OFF) & 1;
  const uint32_t* Mb = S->M + tb2 * 8 * 256 + 2 * tid;
  mbar_wait(BAR(B_F1 + NSAT), 1);
  float m1, s1, s2;
#pragma unroll 1
  for (int it = 0; it < SPIN; it++) {
    uint32_t a[8], miss = 0;
    uint2 v[8];
#pragma unroll
    for (int i = 0; i < 8; i++) { a[i] = ld_rlx(Mb + i * 256); v[i] = ld_rlx2((const uint2*)(Mb + (16 * 8 + i) * 256)); }
#pragma unroll
    for (int i = 0; i < 8; i++) miss |= (a[i] ^ tag) | (v[i].x ^ tag) | (v[i].y ^ tag);
#define SUM8(F) ((untag(F(0)) + untag(F(1))) + (untag(F(2)) + untag(F(3)))) + ((untag(F(4)) + untag(F(5))) + (untag(F(6)) + untag(F(7))))
#define FA(i) a[i]
#define FX(i) v[i].x
#define FY(i) v[i].y
    m1 = SUM8(FA); s1 = SUM8(FX); s2 = SUM8(FY);
    if (!__any_sync(0xffffffff, miss & 1)) break;
  }
  const float mean = s1 * (1.f / DM), rs = frsqrt(fmaxf(s2 * (1.f / DM) - mean * mean, 0.f) + 1e-5f);
  uint2* sp = S->S + SEQ + 128 * tb2 + 8 * (tid & 14) + 2 * (tid >> 4) + (tid & 1);
  st_rlx2(sp, tagf(rs, tag), tagf(-mean * rs, tag));
  st_rlx2(sp + SEQ, tagf(rs, tag), tagf(-(mean + m1 * (1.f / DM)) * rs, tag));
}
template <int I0, int I1> __device__ __forceinline__ void init_barriers(uint32_t bars) {
#pragma unroll
  for (int i = I0; i < I1; i++) mbar_init(BAR(i), bar_count(i));
}
__device__ __forceinline__ int g2_cb(int kp) { return kp < 5 ? 2 * kp : 2 * kp - 9; }
__device__ __forceinline__ const unsigned* h_flag(Scratch* S, int ly, int tb2, int lane) {
  const int s0 = 128 * min(tb2, 15) / 160;
  const bool two = (128 * tb2 + 127) / 160 != s0;
  return &S->flag[(F_H + (ly * 13 + s0) * 10 + min(lane & 15, 9) + (two && lane >= 16 ? 10 : 0)) * 32];
}
__device__ __forceinline__ void gate_tile(const Params& P, uint32_t dst, uint32_t bar, int tb2, int db) {
  mbar_expect_tx(bar, 20480);
  tma2d(dst, &P.mGT, tb2 * 128, db * 80, bar);
  tma2d(dst + 10240, &P.mGT, tb2 * 128 + 64, db * 80, bar);
}
__global__ void __cluster_dims__() __launch_bounds__(512, 1) fused_kernel(const Head H, const __grid_constant__ Params P) {
  extern __shared__ __align__(1024) uint8_t smem[];
  const uint32_t sb = opaque(smem_u32(smem)), bars = sb + BAR_OFF;
  const int wi = __shfl_sync(0xffffffff, threadIdx.x >> 5, 0), wg = wi >> 2, tid = threadIdx.x & 127;
  const int umap = blockIdx.x >= 96;
#define CLK(v)
  CLK(c_a);
  if (wi == 14) {
    if (elect_one()) { init_barriers<0, NBAR1>(bars); asm volatile("fence.mbarrier_init.release.cluster;" ::: "memory"); }
    __syncwarp();
  } else if (wi >= 12) prefetch_map(wi == 12 ? &P.mB : &P.mA[umap]);
  else if (wg == 2) xb_prefetch<1>(H, blockIdx.x + H.base, tid, 0);
  else if (P.role[blockIdx.x].w) return;
  CLK(c_b);
  asm volatile("barrier.cluster.arrive.relaxed.aligned;" ::: "memory");
  CLK(c_c);
  Role R;
  { const uint4 r = P.role[blockIdx.x]; R.v = r.x; R.c = r.y; R.p = r.z; }
  const int id = R.c & 255;
  const int tb = R.tb(), cb = R.cb(), b = R.b(), tb2 = b >> 3, db = b & 7, rank = R.rank();
  const bool has1 = tb <= 12, has2 = b < 128, full = tb < 12;
  Scratch* const S = H.s;
  unsigned* const epoch_p = &S->epoch[id * 8];
  const long long t_start = 0;
  if (wg < 2) {
    if (threadIdx.x == 0) PROF(50);
    asm volatile("griddepcontrol.launch_dependents;");
    bar_sync(6, 448);
    asm volatile("setmaxnreg.inc.sync.aligned.u32 176;");
    float xr[40];
#pragma unroll
    for (int i = 0; i < 40; i++) xr[i] = 0.f;
#pragma unroll 1
    for (int ly = 0; ly < 2; ly++) {
      if (has1) g1_phase(ly, H, sb, wg, tid, R, xr, t_start);
      if (ly == 0) {
        resid_init(xr); fence_regs(xr);
        conv_loop<false>(sb, R.c, wg, tid, t_start);
        if (tid == 0 && wg == 0) PROF(9);
      }
      if (has2) g2_phase(ly, P, S, sb, wg, tid, R, xr, t_start);
    }
    if (tid == 0 && wg == 0) st_rlx(epoch_p, lds32(sb + MISC_OFF));
  } else if (wg == 2) {
    bar_sync(6, 448);
    if (has1) aux_prep(H, P, sb, R, tid, t_start);
    asm volatile("setmaxnreg.inc.sync.aligned.u32 136;");
    conv_loop<true>(sb, R.c, wg, tid, t_start);
    if (tid == 0) PROF(44);
    {
      const uint32_t bb = (P.role[blockIdx.x].x >> 8) & 255;
      if ((bb & 132) == NSDB && tid < 32) next_stats(H.s, sb, bb >> 3, 32 * (bb & 3) + tid);
    }
  } else {
    if (threadIdx.x == 384) PROF(354);
    asm volatile("setmaxnreg.dec.sync.aligned.u32 24;");
    const int wlo = R.wlo(), whi = R.whi();
    const uint32_t wmask = R.wmask(), umask = R.umask(), f1bytes = full ? 36864 : 32768;
    if (wi < 14) {
      if (threadIdx.x == 384) PROF(340);
      asm volatile("barrier.cluster.wait.aligned;" ::: "memory");
      if (has1 && elect_one()) {
        uint64_t tab = wi == 12 ? WTAB0 : XTAB0;
        PROF(329 + wi);
#pragma unroll 1
        for (int kb = 0; kb < 6; kb++, tab >>= 6) {
          const uint32_t dst = sb + ((uint32_t)tab & 63) * 4096;
          if (wi == 12) {
#pragma unroll 1
            for (int h = wlo; h <= whi; h++) tma4d_mc(dst + h * 8192, &P.mB, kb * 64, 0, 0, 8 * cb + 4 * h, BAR(B_F1 + kb), wmask);
          } else {
            tma4d_mc(dst + R.uj() * 1024, &P.mA[umap], kb * 64, 0, 0, 80 * tb + R.uj(), BAR(B_F1 + kb), umask);
            mbar_expect_tx(BAR(B_F1 + kb), f1bytes);
          }
        }
      }
      if (!has1 && wi == 13) bar_sync(7, 64);
    } else {
      if (wi == 15 && elect_one()) { init_barriers<NBAR1, NBAR>(bars); asm volatile("fence.mbarrier_init.release.cluster;" ::: "memory"); }
      bar_sync(6, 448);
      if (!has1 && wi == 14) bar_sync(7, 64);
    }
    const unsigned e1 = ld_rlx(epoch_p) + 1;
    if (wi == 12) {
      if (elect_one()) {
#pragma unroll 1
        for (int ly = 0; ly < 2; ly++) {
#pragma unroll 1
          for (int i = ly ? 0 : 6; i < 10 && has1; i++) {
            const int kb = (0x9876541032ull >> (4 * i)) & 15;
            if (ly == 0) { mbar_wait(BAR(B_E1 + ((DEP0 >> (4 * kb - 24)) & 15))); mbar_wait(BAR(B_AX + (kb == 9))); }
            else {
              if (has2 && i == (db >= GLATE ? 4 : 2)) {
                wait_cnt(&S->cnt[(C_G + db) * 32], e1 * 80);
                mbar_wait(BAR(B_E2 + 7));
                PROF(47);
                gate_tile(P, sb + G_OFF0, BAR(B_GF), tb2, db);
              }
              if (has2) mbar_wait(BAR(i < 4 ? B_E2 + ((0x9865u >> (4 * i)) & 15) : B_GE));
              else if (i == 0) { mbar_wait(BAR(B_E1 + 9)); mbar_wait(BAR(B_CD + 1)); }
              if (i >= 4) mbar_wait(BAR(i < 6 ? B_F1 + W4AT : B_E1 + i - 6), 1);
            }
            const uint32_t dst = sb + ((uint32_t)((ly ? WTAB1 : WTAB0) >> (6 * kb)) & 63) * 4096;
#pragma unroll 1
            for (int h = wlo; h <= whi; h++) tma4d_mc(dst + h * 8192, &P.mB, kb * 64, 0, 0, 8 * cb + 4 * h, BAR(B_F1 + kb), wmask);
          }
          if (has2) {
            if (ly == 0) {
              mbar_wait(BAR(B_E1 + XRAT));
              mbar_expect_tx(BAR(B_XR), 20480 + 160 + 1024);
              tma4d(sb + XR_OFF, &P.mX, 80 * db, tb2, BAR(B_XR));
              bulk_g2s(sb + XR_OFF + 20480, P.dskip + 80 * db, 160, BAR(B_XR));
              bulk_g2s(sb + XR_OFF + 20480 + 256, S->S + 128 * tb2, 1024, BAR(B_XR));
              if (CWAIT) mbar_wait(BAR(CWAIT == 1 ? B_KF + 2 : CWAIT == 2 ? B_KF + R.nch() - 1 : CWAIT == 3 ? B_KF + R.nch() - 2 : B_HD));
            }
#pragma unroll 1
            for (int kp = 0; kp < 10; kp++) {
              const uint32_t dst = sb + (kp < 5 ? kp : kp - 5) * 20480;
              mbar_wait(BAR(kp >= 5 ? B_E2 + kp - 5 : ly ? B_E1 + ((CTAB1 >> (4 * kp)) & 15) : kp < 3 ? B_SH : kp < 4 ? B_HD : B_CD), ly);
              mbar_expect_tx(BAR(B_F2 + kp), 10240 + 16384);
              tma5d(dst, &P.mC[0], g2_cb(kp) * 64, db * 5, BAR(B_F2 + kp));
              mbar_expect_tx(BAR(B_F3 + kp), 10240 + 16384);
              tma5d(dst + 10240, &P.mC[1], g2_cb(kp) * 64, db * 5, BAR(B_F3 + kp));
              if (ly && kp == 4) { mbar_wait(BAR(B_E1 + 9), 1); gate_tile(P, sb + G_OFF1, BAR(B_GF), tb2, db); }
            }
          }
        }
      }
    } else if (wi == 13) {
      const int h0 = R.cs() == 8 ? rank : 4 * rank;
#pragma unroll 1
      for (int ly = 0; ly < 2; ly++) {
        int lane = lane_id();
        if (has1) {
          const unsigned* fp = &S->flag[(F_U3 + 8 * ((160 * tb) >> 7) + (lane & (full ? 15 : 7))) * 32];
          uint32_t ready = ly ? __ballot_sync(0xffffffff, ld_rlx(fp) == e1) : ~0u;
          if (ly) mbar_wait(BAR(XEARLY && full ? B_KF + 1 : has2 ? B_SG : B_RF1), XEARLY && full);
          if (PWG && XEARLY && ly && full) mbar_wait(BAR(B_KF + 2), 1);
#pragma unroll 1
          for (int kb = ly ? 0 : 6; kb < 10; kb++) {
            if (ly && kb == UPAT) { mbar_wait(BAR(B_XR)); ready = ~0u; }
            wait_flags(fp, e1, 0x101u * ((1u << (64 * kb / 80)) | (1u << ((64 * kb + 63) / 80))), ready);
            if (kb >= 4) mbar_wait(BAR(B_E1 + (ly ? kb - 4 : (DEP0 >> (4 * kb - 24)) & 15)), ly);
            mbar_wait(BAR(B_AX + (kb == 9)));
            if (elect_one()) {
              if (ly && kb == 0) PROF(34);
              tma4d_mc(sb + ((uint32_t)((ly ? XTAB1 : XTAB0) >> (6 * kb)) & 63) * 4096 + R.uj() * 1024, &P.mA[2 * ly + umap], kb * 64, 0, 0, 80 * tb + R.uj(),
                       BAR(B_F1 + kb), umask);
              mbar_expect_tx(BAR(B_F1 + kb), f1bytes);
            }
            __syncwarp();
          }
        }
        if (ly == 0) {
          if (has1) mbar_wait(BAR(B_E1 + KPF));
          if (elect_one()) {
#pragma unroll 1
            for (int s = 0; s < R.nch(); s++) prefetch_l2(P.ssmk + (size_t)R.ch(s) * SEQ, 4096);
          }
          lane = lane_id();
#pragma unroll
          for (int s = 0; s < 5; s++) {
            asm volatile("st.shared.v4.u32 [%0],{%1,%1,%1,%1};" ::"r"(conv_buf(sb, s) + 16 * lane), "r"(0) : "memory");
            asm volatile("st.shared.u8 [%0],%1;" ::"r"(conv_buf(sb, s) + KC_OFS + lane), "r"(0) : "memory");
          }
          fence_async();
          __syncwarp();
          const unsigned* cp = &S->cnt[(C_KV + (R.ch(min(lane, R.nch() - 1)) >> 6)) * 32];
          uint32_t ready = 0;
#pragma unroll 1
          for (int s = 0, sk = 0; s < R.nch(); s++) {
#pragma unroll 1
            for (; sk < (s ? R.nch() : KUP); sk++)
              if (elect_one()) { mbar_expect_tx(BAR(B_KF + sk), 8192); bulk_g2s(conv_buf(sb, sk) + KC_OFS + 32, P.ssmk + (size_t)R.ch(sk) * SEQ, 4096, BAR(B_KF + sk)); }
            PROFC(s == 0, 329);
#pragma unroll 1
            for (int it = 0; !((ready >> s) & 1) && it < SPIN; it++) ready = __ballot_sync(0xffffffff, (int)(ld_rlx(cp) - e1 * 32) >= 0);
            PROFC(s == 0, 30);
            if (elect_one()) {
              bulk_g2s(conv_buf(sb, s) + KV_PAD, S->kv + (size_t)R.ch(s) * SEQ, 4096, BAR(B_KF + s));
              if (s == 0 && has2) { prefetch_l2(P.cre + (size_t)5 * b * DM, 5 * DM * 2); prefetch_l2(P.cim + (size_t)5 * b * DM, 5 * DM * 2); }
            }
            __syncwarp();
          }
          PROF(31);
          if (!has1) return;
        }
        lane = lane_id();
        const unsigned* fp = h_flag(S, ly, tb2, lane);
        uint32_t ready = __ballot_sync(0xffffffff, ld_rlx(fp) == e1), st = 0;
        if (ly == 0 && !has2) {
          mbar_wait(BAR(B_HD));
          if (lane < 8) mbar_arrive_cl(BAR(B_RF1), lane & 1);
        }
        if (has2) {
          mbar_wait(BAR(B_RF0), ly);
#pragma unroll 1
          for (int kp = 0; kp < 10; kp++) {
            if (kp == 5) { mbar_wait(BAR(B_XR), 1); ready = ~0u; }
            if (kp == 2) { mbar_wait(BAR(B_HD), ly); if (lane < 8) mbar_arrive_cl(BAR(B_RF1), lane & (R.cs() - 1)); }
            wait_flags(fp, e1, 0x10001u << g2_cb(kp), ready);
            if (kp == 2) mbar_wait(BAR(B_RF1), ly);
#pragma unroll
            for (int hf = 0; hf < 2; hf++) {
              if (kp >= 3) { if (hf) mbar_wait(BAR(B_E2 + kp - 3), ly); else mbar_wait(BAR(B_EA + st), ly ^ (kp >= 6 && kp < 9)); }
              if (elect_one()) {
                if (kp == 0 && !hf) PROF(33 + 2 * ly);
                tma4d_mc(sb + H_OFF + st * 32768 + hf * 16384 + h0 * 2048, &P.mH, g2_cb(kp) * 128 + hf * 64, 0, 2 * h0,
                         ly * 16 + tb2, BAR((hf ? B_F3 : B_F2) + kp), (1u << R.cs()) - 1);
              }
              __syncwarp();
            }
            st = st == 2 ? 0 : st + 1;
          }
        }
      }
    } else if (wi == 14) {
      if (!has1) return;
      prefetch_if(P.dskip + 64 * (tid & 31), (tid & 31) < 10);
      if (elect_one()) { prefetch_map(&P.sK); prefetch_map(&P.mX); prefetch_map(&P.sH); prefetch_map(&P.sU); prefetch_map(&P.sO); prefetch_map(&P.mC[0]); prefetch_map(&P.mC[1]); prefetch_map(&P.mH); prefetch_map(&P.mGT); prefetch_map(&P.mA[2 + umap]); }
      __syncwarp();
#pragma unroll 1
      for (int ly = 0; ly < 2; ly++) {
        if (ly) {
          mbar_wait(BAR(B_F1 + 1), 1);
          uint32_t ready = 0;
          wait_flags(&S->flag[(F_U3 + 8 * ((160 * tb) >> 7) + ((lane_id() + ly) & (full ? 15 : 7))) * 32], e1, ~0u, ready);
          if (elect_one()) mbar_arrive(BAR(B_XR));
        }
        const int lane = lane_id();
        mbar_wait(BAR(B_E1 + (ly ? STAT_AT1 : STAT_AT)), ly);
        PROFC(lane == 0 && ly == 0, 36);
        {
          const int l = lane - (full ? 0 : 16);
          const uint2* p = S->S + ly * SEQ + 160 * tb + 2 * l;
          uint4 v[3];
#pragma unroll 1
          for (int it = 0; it < SPIN; it++) {
            v[0] = ld_rlx4(p); v[1] = ld_rlx4(p + 64); v[2] = ld_rlx4(p + 96);
            const bool miss = __any_sync(0xffffffff, untagged(v[0], e1 & 1) | untagged(v[1], e1 & 1) | untagged(v[2], e1 & 1));
            PROFC(lane == 0 && ly == 0 && it == 0, 37);
            if (!miss) break;
          }
          PROFC(lane == 0 && ly == 0, 38);
#pragma unroll
          for (int i = 0; i < 3; i++) {
            const int pr = l + (i == 2 ? 48 : 32 * i);
            if (pr >= 0) asm volatile("st.shared.v4.u32 [%0],{%1,%2,%3,%4};" ::"r"(sb + SSM_OFF + 16 * (pr + ((pr * (full ? 205 : 256)) >> 12))), "r"(v[i].x & ~1u),
                                      "r"(v[i].y & ~1u), "r"(v[i].z & ~1u), "r"(v[i].w & ~1u) : "memory");
          }
          __syncwarp();
        }
        if (lane == 0) mbar_arrive(BAR(B_ST));
        if (ly && has2) {
          mbar_wait(BAR(B_E1 + 9), 1);
          if (lane < 8) mbar_arrive_cl(BAR(B_RF0), lane & (R.cs() - 1));
        }
        if (lane == 0) {
#pragma unroll 1
          for (int pc = 0; pc < (full ? 5 : 4); pc++) {
            if ((HWM >> (4 * pc)) & 8) {
              mbar_wait(BAR(B_SH + min((HWM >> (4 * pc)) & 7, full ? 4 : 3)), ly);
              PROF(380 + 5 * ly + pc);
              if (pc == 0 && (cb & 1)) delay(ly ? HDLY : HDLY0);
              fence_async();
            }
#pragma unroll
            for (int i = 0; i < 2; i++) tma4d_store(&P.sH, sb + (pc < 4 ? R_OFF + i * 16384 + pc * 4096 : (ly ? R4_OFF1 : R4_OFF0) + i * 4096), 128 * cb + 64 * i, 0, 0, ly * 1024 + 80 * tb + 4 * pc);
          }
          bulk_commit(); bulk_wait();
          PROF(ly ? 17 : 16);
          mbar_arrive(BAR(B_HD));
          release<1>();
          signal_flag(&S->flag[(F_H + (ly * 13 + tb) * 10 + cb) * 32], e1);
          PROF(ly ? 24 : 8);
        }
        __syncwarp();
        if (has2) {
          mbar_wait(BAR(B_F2 + FPAT), ly);
          uint32_t ready = 0;
          wait_flags(h_flag(S, ly, tb2, lane_id() | 1), e1, ~0u, ready);
          if (elect_one()) mbar_arrive(BAR(B_XR));
        }
        if (lane == 0 && has2 && !(ODIR && ly)) {
          mbar_wait(BAR(B_SG), ly);
          if (!(ly ? ODIR : UDIR)) {
          fence_async();
          tma4d_store(ly ? &P.sO : &P.sU, sb + (ly ? OS_OFF : US_OFF), 80 * db, 0, 0, tb2);
          bulk_commit(); bulk_wait();
          }
          if (ly == 0) { PROF(18); mbar_arrive(BAR(B_GE)); mbar_arrive_cl(BAR(B_GE), R.wpart()); release<2>(); signal_flag(&S->flag[(F_U3 + b) * 32], e1); }
          PROF(ly ? 29 : 14);
        }
        __syncwarp();
      }
    } else {
      discretise(H, P, sb, R, tid & 31, e1);
      if (elect_one()) {
        mbar_arrive(BAR(B_LM));
        PROF(348);
        if (b < R.nprep()) {
#pragma unroll 1
          for (int task = b, r = 0; task < 320; task += R.nprep(), r++) {
            mbar_wait(BAR(B_PS + r));
            PROF(320 + 3 * r);
            fence_async();
            tma2d_store(&P.sK, sb + KS_OFF + r * 8192, 64 * (task & 31), 64 * (task >> 5));
            bulk_commit(); bulk_wait();
            PROF(321 + 3 * r);
            release<4>();
            signal_cnt(&S->cnt[(C_KV + (task >> 5)) * 32], 1);
            PROF(322 + 3 * r);
          }
          PROF(41);
        }
        if (has2) {
          mbar_wait(BAR(B_SH));
#pragma unroll 1
          for (int i = 0; i < 8; i++) mbar_arrive_cl(BAR(B_RF0), i & (R.cs() - 1));
        }
#pragma unroll 1
        for (int s = 0, s0 = 0; s < R.nch(); s++) {
          mbar_wait(BAR(B_GS + s));
          fence_async();
          bulk_s2g(S->gt + (size_t)R.ch(s) * SEQ, conv_buf(sb, s) + KC_OFS, 4096); bulk_commit();
          if (s == 1 || s >= R.nch() - GSPL) bulk_wait();
          if (s == 1 || s == R.nch() - 1) mbar_arrive(BAR(B_CD + (s > 1)));
          if (s >= R.nch() - GSPL) {
            PROF(45);
            release<8>();
#pragma unroll 1
            for (; s0 <= s; s0++) signal_cnt(&S->cnt[(C_G + R.ch(s0) / 80) * 32], 1);
          }
        }
        PROF(46);
      }
    }
  }
}

typedef CUresult (*EncFn)(CUtensorMap*, CUtensorMapDataType, cuuint32_t, void*, const cuuint64_t*, const cuuint64_t*, const cuuint32_t*,
                          const cuuint32_t*, CUtensorMapInterleave, CUtensorMapSwizzle, CUtensorMapL2promotion, CUtensorMapFloatOOBfill);
bool enc(EncFn f, CUtensorMap* m, const void* base, int rank, const cuuint64_t* dims, const cuuint64_t* strides, const cuuint32_t* box, bool swz,
         bool f32 = false) {
  const cuuint32_t es[5] = {1, 1, 1, 1, 1};
  return f(m, f32 ? CU_TENSOR_MAP_DATA_TYPE_FLOAT32 : CU_TENSOR_MAP_DATA_TYPE_BFLOAT16, rank, const_cast<void*>(base), dims, strides, box, es,
           CU_TENSOR_MAP_INTERLEAVE_NONE, swz ? CU_TENSOR_MAP_SWIZZLE_128B : CU_TENSOR_MAP_SWIZZLE_NONE, CU_TENSOR_MAP_L2_PROMOTION_L2_256B,
           CU_TENSOR_MAP_FLOAT_OOB_FILL_NONE) == CUDA_SUCCESS;
}
void make_roles(Params& P, bool big) {
  for (uint32_t bx = 0; bx < (big ? 120u : 12u); bx++) {
    const uint32_t c = bx >> 3, r = bx & 7, id = big ? bx : 120 + bx;
    const uint32_t vA = c < 12 ? (2 * (c >> 1) + (r >> 2)) | (4 * (c & 1) + (r & 3)) << 4 | (r & 4) << 16 | 4 << 19 | (r ^ 4) << 22
                               : (4 * (c - 12) + (r >> 1)) | (8 + (r & 1)) << 4 | (r & 6) << 16 | 2 << 19 | (r ^ 2) << 22;
    const uint32_t vB = (bx < 10 ? 12 : 13) | bx << 4 | 2 << 19 | (bx & 1) << 22 | (bx & 1) << 26;
    P.role[bx].x = (big ? vA | r << 26 | 1u << 29 : vB) | (id < 128 ? (id & ~7u) | (r >> 1) | (r & 1) << 2 : id) << 8;
    P.role[bx].y = id | (big ? 5 : bx < 8 ? 3 : 4) << 10 | 120 << 13 | 132 << 21 | (big ? 4u : 3u) << 29;
    const uint32_t v = P.role[bx].x, cb = (v >> 4) & 15, rank = (v >> 26) & 7, ubase = (v >> 16) & 7, ugs = (v >> 19) & 7, wp = (v >> 22) & 7;
    const uint32_t wlo = rank > wp, whi = wp != rank ? wlo : 1, wmask = 1u << rank | 1u << wp;
    const uint32_t uj = (rank - ubase) * (!big ? 8 : ugs == 4 ? 5 : 10), sm = big ? (0x7296418530ull >> (4 * cb)) & 15 : bx < 8 ? 4 * (bx & 1) + (bx >> 1) : 15;
    P.role[bx].z = wlo | whi << 1 | wmask << 2 | ((1u << ugs) - 1) << (10 + ubase) | uj << 20 | sm << 25;
    P.role[bx].w = 0;
  }
}
void launch(const Head& H, const Params& P, int grid, int cs, bool dependent) {
  cudaLaunchConfig_t cfg = {};
  cfg.gridDim = grid; cfg.blockDim = 512; cfg.dynamicSmemBytes = SMEM_BYTES; cfg.stream = cudaStreamPerThread;
  cudaLaunchAttribute at[2];
  at[0].id = cudaLaunchAttributeClusterDimension; at[0].val.clusterDim.x = cs; at[0].val.clusterDim.y = 1; at[0].val.clusterDim.z = 1;
  at[1].id = cudaLaunchAttributeProgrammaticStreamSerialization; at[1].val.programmaticStreamSerializationAllowed = 1;
  cfg.attrs = at; cfg.numAttrs = dependent ? 2 : 1;
  cudaLaunchKernelEx(&cfg, fused_kernel, H, P);
}

}

extern "C" void kernel_launch(void* const* d_in, const int* in_sizes, int n_in, void* d_out, int out_size) {
  (void)in_sizes; (void)n_in; (void)out_size;
  typedef const __nv_bfloat16* cb;
  void* fp = nullptr; cudaDriverEntryPointQueryResult qr;
  cudaGetDriverEntryPoint("cuTensorMapEncodeTiled", &fp, cudaEnableDefault, &qr);
  EncFn f = (EncFn)fp;
  Scratch* sp = nullptr;
  cudaGetSymbolAddress((void**)&sp, g_scr);
  void *pu = sp->u, *ph = sp->h, *pgt = sp->gt;
  Params P;
  Head H;
  H.s = sp; H.x = (cb)d_in[0]; H.swap = (uintptr_t)d_in[4] < (uintptr_t)d_in[3] ? 0 : 0x80000000u; H.b0 = (cb)d_in[H.swap ? 3 : 4]; H.b1 = (cb)d_in[H.swap ? 4 : 3];
  for (int i = 0; i < 2; i++) {
    const cuuint64_t d[4] = {640, 8, 2, 80}, s[3] = {1280, (cuuint64_t)((uintptr_t)H.b1 - (uintptr_t)H.b0), 8 * 1280}; const cuuint32_t bx[4] = {64, 8, 2, 4};
    if (enc(f, &P.mB, H.b0, 4, d, s, bx, true)) break;
    cudaMemcpyAsync(sp->bcopy, H.b0, DM * DM * 2, cudaMemcpyDeviceToDevice, cudaStreamPerThread);
    cudaMemcpyAsync(sp->bcopy + DM * DM, H.b1, DM * DM * 2, cudaMemcpyDeviceToDevice, cudaStreamPerThread);
    H.b0 = sp->bcopy; H.b1 = sp->bcopy + DM * DM;
  }
  {
    const cuuint64_t d[5] = {640, 2, 4, 2, 40}, s[4] = {1280, 4 * 1280, 2 * 1280, 16 * 1280}; const cuuint32_t bx[5] = {64, 2, 4, 2, 5};
    enc(f, &P.mC[0], d_in[5], 5, d, s, bx, true); enc(f, &P.mC[1], d_in[6], 5, d, s, bx, true); }
  { const cuuint64_t d[2] = {2048, 640}, s[1] = {4096}; const cuuint32_t bx[2] = {64, 80}; enc(f, &P.mGT, pgt, 2, d, s, bx, true); }
  { const cuuint64_t d[4] = {640, 8, 16, 16}, s[3] = {16 * 1280, 1280, 128 * 1280}, so[3] = {16 * 2560, 2560, 128 * 2560}; const cuuint32_t bx[4] = {80, 8, 16, 1};
    enc(f, &P.sU, pu, 4, d, s, bx, false); enc(f, &P.mX, d_in[0], 4, d, s, bx, false); enc(f, &P.sO, d_out, 4, d, so, bx, false, true); }
  { const cuuint64_t d[2] = {2048, 640}, s[1] = {4096}; const cuuint32_t bx[2] = {64, 64}; enc(f, &P.sK, sp->kv, 2, d, s, bx, true); }
  P.lre = (cb)d_in[1]; P.lim = (cb)d_in[2]; P.cre = (cb)d_in[5]; P.cim = (cb)d_in[6]; P.ldt = (cb)d_in[7]; P.dskip = (cb)d_in[8];
  P.out = (float*)d_out;
  P.k = (cb)d_in[10]; P.v = (cb)d_in[11]; P.shk = (cb)d_in[12]; P.ssmk = (cb)d_in[13]; P.ssmd = (cb)d_in[14];
  cudaFuncSetAttribute(fused_kernel, cudaFuncAttributeMaxDynamicSharedMemorySize, SMEM_BYTES);
  for (int big = 1; big >= 0; big--) {
    const cuuint64_t seg = big ? 40 : 32;
    for (int i = 0; i < 4; i++) {
      const cuuint64_t d[4] = {640, 2, 4, 1024}, s[3] = {1280, seg * 1280, 2 * 1280}; const cuuint32_t bx[4] = {64, 2, 4, !big ? 8u : (i & 1) ? 10u : 5u};
      enc(f, &P.mA[i], i < 2 ? d_in[0] : pu, 4, d, s, bx, true);
    }
    {
      const cuuint64_t d[4] = {1280, 8, 16, 32}, s[3] = {16 * 2560, 2560, 128 * 2560}; const cuuint32_t bx[4] = {64, 8, big ? 2u : 8u, 1};
      enc(f, &P.mH, ph, 4, d, s, bx, true); }
    { const cuuint64_t d[4] = {1280, 2, 4, 2048}, s[3] = {2560, seg * 2560, 2 * 2560}; const cuuint32_t bx[4] = {64, 2, 4, 4};
      enc(f, &P.sH, ph, 4, d, s, bx, true); }
    make_roles(P, big);
    H.base = big ? 0 : 120;
    launch(H, P, big ? 120 : 12, big ? 8 : 2, !big);
  }
}
```

```cpp
#include <cuda_runtime.h>
#include <cuda.h>
#include <cuda_bf16.h>
#include <stdint.h>

namespace {

constexpr int SEQ = 2048, DM = 640;
constexpr int SPIN = 1 << 20;
#define PFAT 99
#define KVDLY 500
#define PFD 1
#define XPFAT 9
#define STAT_AT 6
#define KPFAT 3
#define KPFAT2 5
#define KPF 7
#define ODIR 1
#define UDIR 0
#define HDLY 1900
#define GSPL 2
#define CWAIT 0
#define HDLY0 1900
#define CTAB1 0x96543u
#define NSAT 0
#define SKW 1
#define RIAT 2
#define MIAT 5
#define FPAT 1
#define UPAT 7
#define STAT_AT1 4
#define W4AT 0
#define MBAR 1
#define XEARLY 1
#define PWG 1
#define STG 17
#define STG0 17
#define DSM 2
#define HWM 0xc09
#define REL 1
#define NSDB 4
#define GLATE 6
#define KUP 1
#define XRAT 9
#define ORD 1

struct Scratch {
  uint2 E[2 * 13 * 10 * 8 * 16];
  uint32_t M[3 * 16 * 8 * 256];
  uint2 S[3 * SEQ];
  uint2 RS[80 * 16];
  unsigned flag[512 * 32];
  unsigned cnt[32 * 32];
  unsigned epoch[132 * 8];
  unsigned zero[128];
  unsigned prof[132 * 512];
  __align__(1024)
  __nv_bfloat16 u[SEQ * DM];
  __nv_bfloat16 h[2 * SEQ * 1280];
  __nv_bfloat16 kv[DM * SEQ];
  __nv_bfloat16 gt[DM * SEQ];
  __nv_bfloat16 bcopy[2 * DM * DM];
};
__device__ __align__(1024) Scratch g_scr;
#define PROFC(c, i) do {} while (0)
#define PSEL 1
#define PROF(i) do {} while (0)

constexpr int C_KV = 0, C_G = 10;
constexpr int F_U3 = 0, F_H = 128;

constexpr int R_OFF = 196608, R4_OFF0 = 73728, R4_OFF1 = 122880, H_OFF = 131072, KS_OFF = 131072, CV_OFF = 86272, G_OFF0 = 40960, G_OFF1 = 102400, US_OFF = 98304, OS_OFF = US_OFF + 20480, XR_OFF = 163840, MX_OFF = 32768;
constexpr int LAM_OFF = 229376, SSM_OFF = LAM_OFF + 1024, BAR_OFF = SSM_OFF + 1344;
constexpr int B_F1 = 0, B_E1 = 10, B_RF0 = 20, B_RF1 = 21, NBAR1 = 22;
constexpr int B_F2 = 22, B_KF = 32, B_GF = 37, B_CD = 38, B_XR = 40, B_ST = 41, B_HD = 42, B_LM = 43, B_E2 = 44, B_GS = 54, B_PS = 59, B_AX = 62, B_SH = 64, B_SG = 69, B_GE = 70, B_EA = 71, B_F3 = 74, NBAR = 84;
__host__ __device__ constexpr int bar_count(int i) { return i < B_E1 ? 1 : i < B_RF0 ? 9 : i < B_F2 ? 8 : i < B_E2 ? 1 : i < B_GS ? 12 : i < B_SH ? 4 : i < B_GE ? 8 : i < B_EA ? 2 : i < B_F3 ? 8 : 1; }
constexpr int MISC_OFF = BAR_OFF + NBAR * 8, SMEM_BYTES = MISC_OFF + 32;
constexpr int KV_PAD = 512, KC_OFS = KV_PAD + 4096, CH_STRIDE = 8960;
__device__ __forceinline__ uint32_t conv_buf(uint32_t sb, int slot) { return sb + CV_OFF + slot * CH_STRIDE; }
constexpr uint64_t tab6(int a, int b, int c, int d, int e, int f, int g, int h, int i, int j) {
  return (uint64_t)a | (uint64_t)b << 6 | (uint64_t)c << 12 | (uint64_t)d << 18 | (uint64_t)e << 24 | (uint64_t)f << 30 | (uint64_t)g << 36 | (uint64_t)h << 42 |
         (uint64_t)i << 48 | (uint64_t)j << 54;
}
constexpr uint64_t WTAB0 = tab6(0, 4, 8, 30, 12, 26, 0, 4, 8, 12), XTAB0 = tab6(40, 45, 50, 34, 16, 21, 40, 45, 50, 16);
constexpr uint64_t WTAB1 = tab6(16, 20, 0, 4, 8, 12, 16, 20, 24, 28), XTAB1 = tab6(40, 45, 50, 32, 40, 45, 50, 32, 40, 45);
constexpr uint32_t DEP0 = 0x4210;

struct Head {
  Scratch* s;
  const __nv_bfloat16 *x, *b0, *b1;
  uint32_t base, swap;
};
struct Params {
  const __nv_bfloat16 *lre, *lim, *ldt, *k, *v, *shk, *cre, *cim, *ssmk, *ssmd, *dskip;
  float* out;
  uint4 role[120];
  CUtensorMap mB, mA[4], mH, mC[2], mGT, mX, sH, sU, sO, sK;
};

__device__ __forceinline__ uint32_t smem_u32(const void* p) { return (uint32_t)__cvta_generic_to_shared(p); }
__device__ __forceinline__ uint32_t opaque(uint32_t x) { uint32_t y; asm volatile("mov.u32 %0, %1;" : "=r"(y) : "r"(x)); return y; }
__device__ __forceinline__ int lane_id() { int y; asm volatile("mov.u32 %0, %%laneid;" : "=r"(y)); return y; }
__device__ __forceinline__ void delay(uint32_t n) {
  asm volatile("{ .reg .pred p; .reg .u32 a, b; mov.u32 a, %%clock; L: mov.u32 b, %%clock; sub.u32 b, b, a; setp.lt.u32 p, b, %0; @p bra.uni L; }" ::"r"(n) : "memory");
}
__device__ __forceinline__ void mbar_init(uint32_t bar, uint32_t cnt) { asm volatile("mbarrier.init.shared::cta.b64 [%0], %1;" ::"r"(bar), "r"(cnt) : "memory"); }
__device__ __forceinline__ void mbar_expect_tx(uint32_t bar, uint32_t bytes) { asm volatile("mbarrier.arrive.expect_tx.shared::cta.b64 _, [%0], %1;" ::"r"(bar), "r"(bytes) : "memory"); }
__device__ __forceinline__ void mbar_arrive(uint32_t bar) { asm volatile("mbarrier.arrive.shared::cta.b64 _, [%0];" ::"r"(bar) : "memory"); }
__device__ __forceinline__ void mbar_arrive_if(uint32_t bar, bool c) {
  asm volatile("{ .reg .pred p; setp.ne.u32 p, %1, 0; @p mbarrier.arrive.shared::cta.b64 _, [%0]; }" ::"r"(bar), "r"((uint32_t)c) : "memory");
}
__device__ __forceinline__ void prefetch_if(const void* p, bool c) { asm volatile("{ .reg .pred p; setp.ne.u32 p, %1, 0; @p prefetch.global.L2 [%0]; }" ::"l"(p), "r"((uint32_t)c)); }
__device__ __forceinline__ void mbar_arrive_cl(uint32_t bar, uint32_t cta) {
  asm volatile("{ .reg .b32 ra; mapa.shared::cluster.u32 ra, %0, %1; mbarrier.arrive.shared::cluster.b64 _, [ra]; }" ::"r"(bar), "r"(cta) : "memory");
}
__device__ __forceinline__ uint32_t mapa(uint32_t a, uint32_t cta) { uint32_t r; asm("mapa.shared::cluster.u32 %0, %1, %2;" : "=r"(r) : "r"(a), "r"(cta)); return r; }
__device__ __forceinline__ void mbar_arrive_at(uint32_t ra) { asm volatile("mbarrier.arrive.shared::cluster.b64 _, [%0];" ::"r"(ra) : "memory"); }
__device__ __forceinline__ void mbar_wait(uint32_t bar, uint32_t parity = 0) {
  asm volatile("{ .reg .pred p; .reg .u32 c; mov.u32 c, 0;\n"
               "W: mbarrier.try_wait.parity.shared::cta.b64 p, [%0], %1; @p bra.uni D;\n"
               "add.u32 c, c, 1; setp.lt.u32 p, c, 0x100000; @p bra.uni W;\nD: }" ::"r"(bar), "r"(parity) : "memory");
}
__device__ __forceinline__ bool elect_one() { uint32_t p; asm volatile("{ .reg .pred P; elect.sync _|P, 0xffffffff; selp.u32 %0,1,0,P; }" : "=r"(p)); return p; }
__device__ __forceinline__ void bar_sync(int id, int n) { __syncwarp(); asm volatile("bar.sync %0, %1;" ::"r"(id), "r"(n) : "memory"); }
__device__ __forceinline__ void tma2d(uint32_t dst, const CUtensorMap* m, int c0, int c1, uint32_t bar) {
  asm volatile("cp.async.bulk.tensor.2d.shared::cluster.global.mbarrier::complete_tx::bytes [%0], [%1, {%3,%4}], [%2];"
               ::"r"(dst), "l"(m), "r"(bar), "r"(c0), "r"(c1) : "memory");
}
__device__ __forceinline__ void tma5d(uint32_t dst, const CUtensorMap* m, int c0, int c4, uint32_t bar) {
  asm volatile("cp.async.bulk.tensor.5d.shared::cluster.global.mbarrier::complete_tx::bytes [%0], [%1, {%3,%5,%5,%5,%4}], [%2];"
               ::"r"(dst), "l"(m), "r"(bar), "r"(c0), "r"(c4), "r"(0) : "memory");
}
__device__ __forceinline__ void tma4d(uint32_t dst, const CUtensorMap* m, int c0, int c3, uint32_t bar) {
  asm volatile("cp.async.bulk.tensor.4d.shared::cluster.global.mbarrier::complete_tx::bytes [%0], [%1, {%3,%5,%5,%4}], [%2];"
               ::"r"(dst), "l"(m), "r"(bar), "r"(c0), "r"(c3), "r"(0) : "memory");
}
__device__ __forceinline__ void tma4d_mc(uint32_t dst, const CUtensorMap* m, int c0, int c1, int c2, int c3, uint32_t bar, uint32_t mask) {
  asm volatile("cp.async.bulk.tensor.4d.shared::cluster.global.mbarrier::complete_tx::bytes.multicast::cluster [%0], [%1, {%3,%4,%5,%6}], [%2], %7;"
               ::"r"(dst), "l"(m), "r"(bar), "r"(c0), "r"(c1), "r"(c2), "r"(c3), "h"((uint16_t)mask) : "memory");
}
__device__ __forceinline__ void bulk_g2s(uint32_t dst, const void* src, uint32_t bytes, uint32_t bar) {
  asm volatile("cp.async.bulk.shared::cluster.global.mbarrier::complete_tx::bytes [%0], [%1], %2, [%3];" ::"r"(dst), "l"(src), "r"(bytes), "r"(bar) : "memory");
}
__device__ __forceinline__ void tma4d_store(const CUtensorMap* m, uint32_t src, int c0, int c1, int c2, int c3) {
  asm volatile("cp.async.bulk.tensor.4d.global.shared::cta.bulk_group [%0, {%2,%3,%4,%5}], [%1];" ::"l"(m), "r"(src), "r"(c0), "r"(c1), "r"(c2), "r"(c3) : "memory");
}
__device__ __forceinline__ void tma2d_store(const CUtensorMap* m, uint32_t src, int c0, int c1) {
  asm volatile("cp.async.bulk.tensor.2d.global.shared::cta.bulk_group [%0, {%2,%3}], [%1];" ::"l"(m), "r"(src), "r"(c0), "r"(c1) : "memory");
}
__device__ __forceinline__ void bulk_s2g(void* dst, uint32_t src, uint32_t bytes) {
  asm volatile("cp.async.bulk.global.shared::cta.bulk_group [%0], [%1], %2;" ::"l"(dst), "r"(src), "r"(bytes) : "memory");
}
__device__ __forceinline__ void bulk_commit() { asm volatile("cp.async.bulk.commit_group;" ::: "memory"); }
__device__ __forceinline__ void bulk_wait() { asm volatile("cp.async.bulk.wait_group 0;" ::: "memory"); }
__device__ __forceinline__ void fence_async() { asm volatile("fence.proxy.async.shared::cta;" ::: "memory"); }
__device__ __forceinline__ void prefetch_l2(const void* src, uint32_t bytes) { asm volatile("cp.async.bulk.prefetch.L2.global [%0], %1;" ::"l"(src), "r"(bytes) : "memory"); }
__device__ __forceinline__ void prefetch_map(const CUtensorMap* m) { asm volatile("prefetch.tensormap [%0];" ::"l"(m) : "memory"); }
__device__ __forceinline__ void wg_fence() { __syncwarp(); asm volatile("wgmma.fence.sync.aligned;" ::: "memory"); }
__device__ __forceinline__ void wg_commit() { asm volatile("wgmma.commit_group.sync.aligned;" ::: "memory"); }
template <int N> __device__ __forceinline__ void wg_wait() { asm volatile("wgmma.wait_group.sync.aligned %0;" ::"n"(N) : "memory"); }
template <int N> __device__ __forceinline__ void fence_regs(float (&d)[N]) {
#pragma unroll
  for (int i = 0; i < N; i++) asm volatile("" : "+f"(d[i])::"memory");
}
__device__ __forceinline__ uint64_t make_desc(uint32_t addr, uint32_t lbo, uint32_t sbo, uint32_t swz) {
  return (uint64_t)((addr & 0x3FFFF) >> 4) | ((uint64_t)(lbo >> 4) << 16) | ((uint64_t)(sbo >> 4) << 32) | ((uint64_t)swz << 62);
}
__device__ __forceinline__ uint32_t ldg1(const void* p) { uint32_t v; asm volatile("ld.global.nc.u32 %0,[%1];" : "=r"(v) : "l"(p)); return v; }
__device__ __forceinline__ uint32_t lds32(uint32_t a) { uint32_t v; asm volatile("ld.shared.u32 %0,[%1];" : "=r"(v) : "r"(a)); return v; }
__device__ __forceinline__ unsigned ld_rlx(const unsigned* p) { unsigned v; asm volatile("ld.relaxed.gpu.global.u32 %0,[%1];" : "=r"(v) : "l"(p) : "memory"); return v; }
__device__ __forceinline__ uint4 ld_rlx4(const void* p) {
  uint4 v; asm volatile("ld.relaxed.gpu.global.v4.u32 {%0,%1,%2,%3},[%4];" : "=r"(v.x), "=r"(v.y), "=r"(v.z), "=r"(v.w) : "l"(p) : "memory"); return v;
}
__device__ __forceinline__ uint2 ld_rlx2(const void* p) { uint2 v; asm volatile("ld.relaxed.gpu.global.v2.u32 {%0,%1},[%2];" : "=r"(v.x), "=r"(v.y) : "l"(p) : "memory"); return v; }
__device__ __forceinline__ void st_rlx2(void* p, uint32_t a, uint32_t b) { asm volatile("st.relaxed.gpu.global.v2.u32 [%0],{%1,%2};" ::"l"(p), "r"(a), "r"(b) : "memory"); }
__device__ __forceinline__ void st_rlx(void* p, uint32_t a) { asm volatile("st.relaxed.gpu.global.u32 [%0],%1;" ::"l"(p), "r"(a) : "memory"); }
#define PUB 15
template <int SITE> __device__ __forceinline__ void release() { if (PUB & SITE) { if (REL) asm volatile("fence.release.gpu;" ::: "memory"); else asm volatile("fence.acq_rel.gpu;" ::: "memory"); } }
__device__ __forceinline__ void signal_flag(unsigned* p, unsigned val) { asm volatile("st.relaxed.gpu.global.u32 [%0],%1;" ::"l"(p), "r"(val) : "memory"); }
__device__ __forceinline__ void signal_cnt(unsigned* p, unsigned n) { asm volatile("red.relaxed.gpu.global.add.u32 [%0],%1;" ::"l"(p), "r"(n) : "memory"); }
__device__ __forceinline__ void wait_flags(const unsigned* p, unsigned val, uint32_t need, uint32_t& ready) {
#pragma unroll 1
  for (int it = 0; (ready & need) != need && it < SPIN; it++) ready = __ballot_sync(0xffffffff, ld_rlx(p) == val);
}
__device__ __forceinline__ void wait_cnt(const unsigned* p, unsigned tgt) {
  asm volatile("{ .reg .pred p; .reg .u32 c; .reg .s32 v; mov.u32 c, 0;\n"
               "W: ld.relaxed.gpu.global.u32 v, [%0]; sub.s32 v, v, %1; setp.ge.s32 p, v, 0; @p bra.uni D;\n"
               "add.u32 c, c, 1; setp.lt.u32 p, c, 0x100000; @p bra.uni W;\nD: }" ::"l"(p), "r"(tgt) : "memory");
}
__device__ __forceinline__ uint32_t pack_bf(float lo, float hi) { uint32_t r; asm("cvt.rn.bf16x2.f32 %0, %1, %2;" : "=r"(r) : "f"(hi), "f"(lo)); return r; }
__device__ __forceinline__ float bf_lo(uint32_t v) { return __uint_as_float(v << 16); }
__device__ __forceinline__ float bf_hi(uint32_t v) { return __uint_as_float(v & 0xffff0000u); }
__device__ __forceinline__ float bf_rn(float x) { return __bfloat162float(__float2bfloat16_rn(x)); }
__device__ __forceinline__ float frcp(float x) { float r; asm("rcp.approx.ftz.f32 %0,%1;" : "=f"(r) : "f"(x)); return r; }
__device__ __forceinline__ float fsqrt(float x) { float r; asm("sqrt.approx.ftz.f32 %0,%1;" : "=f"(r) : "f"(x)); return r; }
__device__ __forceinline__ float frsqrt(float x) { float r; asm("rsqrt.approx.ftz.f32 %0,%1;" : "=f"(r) : "f"(x)); return r; }
__device__ __forceinline__ uint32_t hmul2(uint32_t a, uint32_t b) { uint32_t r; asm("mul.rn.bf16x2 %0,%1,%2;" : "=r"(r) : "r"(a), "r"(b)); return r; }
__device__ __forceinline__ uint32_t hfma2(uint32_t a, uint32_t b, uint32_t c) { uint32_t r; asm("fma.rn.bf16x2 %0,%1,%2,%3;" : "=r"(r) : "r"(a), "r"(b), "r"(c)); return r; }
__device__ __forceinline__ float2 cmul(float2 a, float2 b) { return make_float2(a.x * b.x - a.y * b.y, a.x * b.y + a.y * b.x); }
__device__ __forceinline__ float2 cfma(float2 a, float2 b, float2 c) {
  return make_float2(fmaf(a.x, b.x, fmaf(-a.y, b.y, c.x)), fmaf(a.x, b.y, fmaf(a.y, b.x, c.y)));
}
__device__ __forceinline__ uint32_t tagf(float v, uint32_t tag) { return (__float_as_uint(v) & ~1u) | tag; }
__device__ __forceinline__ float untag(uint32_t v) { return __uint_as_float(v & ~1u); }
__device__ __forceinline__ bool untagged(const uint4& v, uint32_t tag) { return (((v.x ^ tag) | (v.y ^ tag) | (v.z ^ tag) | (v.w ^ tag)) & 1) != 0; }
__device__ __forceinline__ bool untagged(const uint2& v, uint32_t tag) { return (((v.x ^ tag) | (v.y ^ tag)) & 1) != 0; }
__device__ __forceinline__ float2 lam_bar(float lr, float li, float ldt) {
  float dt = bf_rn(expf(ldt)); float e = expf(dt * lr), s, c; sincospif(dt * li * 0.31830988618379067f, &s, &c); return make_float2(e * c, e * s);
}

__device__ __forceinline__ int conv_ch(uint32_t c, int s) { return s * ((c >> 21) & 255) + (c & 255) - (s >= (int)(c >> 29) ? 8 : 0); }
struct Role {
  uint32_t v, c, p;
  __device__ __forceinline__ int tb() const { return v & 15; }
  __device__ __forceinline__ int cb() const { return (v >> 4) & 15; }
  __device__ __forceinline__ int b() const { return (v >> 8) & 255; }
  __device__ __forceinline__ int ubase() const { return (v >> 16) & 7; }
  __device__ __forceinline__ int ugs() const { return (v >> 19) & 7; }
  __device__ __forceinline__ int wpart() const { return (v >> 22) & 7; }
  __device__ __forceinline__ int rank() const { return (v >> 26) & 7; }
  __device__ __forceinline__ int cs() const { return (v >> 29) ? 8 : 2; }
  __device__ __forceinline__ int ch(int s) const { return conv_ch(c, s); }
  __device__ __forceinline__ int wlo() const { return p & 1; }
  __device__ __forceinline__ int whi() const { return (p >> 1) & 1; }
  __device__ __forceinline__ uint32_t wmask() const { return (p >> 2) & 255; }
  __device__ __forceinline__ uint32_t umask() const { return (p >> 10) & 255; }
  __device__ __forceinline__ int uj() const { return (p >> 20) & 31; }
  __device__ __forceinline__ int sm() const { return (p >> 25) & 15; }
  __device__ __forceinline__ int nch() const { return (c >> 10) & 7; }
  __device__ __forceinline__ int nprep() const { return (c >> 13) & 255; }
};

__device__ __forceinline__ void wgmma_ss80(float (&d)[40], uint64_t da, uint64_t db, int sd){
  asm volatile("{ .reg .pred p; setp.ne.b32 p, %42, 0;\n"
   "wgmma.mma_async.sync.aligned.m64n80k16.f32.bf16.bf16 {%0, %1, %2, %3, %4, %5, %6, %7, %8, %9, %10, %11, %12, %13, %14, %15, %16, %17, %18, %19, %20, %21, %22, %23, %24, %25, %26, %27, %28, %29, %30, %31, %32, %33, %34, %35, %36, %37, %38, %39}, %40, %41, p, 1, 1, 0, 0; }\n"
   : "+f"(d[0]), "+f"(d[1]), "+f"(d[2]), "+f"(d[3]), "+f"(d[4]), "+f"(d[5]), "+f"(d[6]), "+f"(d[7]), "+f"(d[8]), "+f"(d[9]), "+f"(d[10]), "+f"(d[11]), "+f"(d[12]), "+f"(d[13]), "+f"(d[14]), "+f"(d[15]), "+f"(d[16]), "+f"(d[17]), "+f"(d[18]), "+f"(d[19]), "+f"(d[20]), "+f"(d[21]), "+f"(d[22]), "+f"(d[23]), "+f"(d[24]), "+f"(d[25]), "+f"(d[26]), "+f"(d[27]), "+f"(d[28]), "+f"(d[29]), "+f"(d[30]), "+f"(d[31]), "+f"(d[32]), "+f"(d[33]), "+f"(d[34]), "+f"(d[35]), "+f"(d[36]), "+f"(d[37]), "+f"(d[38]), "+f"(d[39]) : "l"(da), "l"(db), "r"(sd));
}
__device__ __forceinline__ void wgmma_ss160(float (&d)[80], uint64_t da, uint64_t db, int sd){
  asm volatile("{ .reg .pred p; setp.ne.b32 p, %82, 0;\n"
   "wgmma.mma_async.sync.aligned.m64n160k16.f32.bf16.bf16 {%0, %1, %2, %3, %4, %5, %6, %7, %8, %9, %10, %11, %12, %13, %14, %15, %16, %17, %18, %19, %20, %21, %22, %23, %24, %25, %26, %27, %28, %29, %30, %31, %32, %33, %34, %35, %36, %37, %38, %39, %40, %41, %42, %43, %44, %45, %46, %47, %48, %49, %50, %51, %52, %53, %54, %55, %56, %57, %58, %59, %60, %61, %62, %63, %64, %65, %66, %67, %68, %69, %70, %71, %72, %73, %74, %75, %76, %77, %78, %79}, %80, %81, p, 1, 1, 0, 0; }\n"
   : "+f"(d[0]), "+f"(d[1]), "+f"(d[2]), "+f"(d[3]), "+f"(d[4]), "+f"(d[5]), "+f"(d[6]), "+f"(d[7]), "+f"(d[8]), "+f"(d[9]), "+f"(d[10]), "+f"(d[11]), "+f"(d[12]), "+f"(d[13]), "+f"(d[14]), "+f"(d[15]), "+f"(d[16]), "+f"(d[17]), "+f"(d[18]), "+f"(d[19]), "+f"(d[20]), "+f"(d[21]), "+f"(d[22]), "+f"(d[23]), "+f"(d[24]), "+f"(d[25]), "+f"(d[26]), "+f"(d[27]), "+f"(d[28]), "+f"(d[29]), "+f"(d[30]), "+f"(d[31]), "+f"(d[32]), "+f"(d[33]), "+f"(d[34]), "+f"(d[35]), "+f"(d[36]), "+f"(d[37]), "+f"(d[38]), "+f"(d[39]), "+f"(d[40]), "+f"(d[41]), "+f"(d[42]), "+f"(d[43]), "+f"(d[44]), "+f"(d[45]), "+f"(d[46]), "+f"(d[47]), "+f"(d[48]), "+f"(d[49]), "+f"(d[50]), "+f"(d[51]), "+f"(d[52]), "+f"(d[53]), "+f"(d[54]), "+f"(d[55]), "+f"(d[56]), "+f"(d[57]), "+f"(d[58]), "+f"(d[59]), "+f"(d[60]), "+f"(d[61]), "+f"(d[62]), "+f"(d[63]), "+f"(d[64]), "+f"(d[65]), "+f"(d[66]), "+f"(d[67]), "+f"(d[68]), "+f"(d[69]), "+f"(d[70]), "+f"(d[71]), "+f"(d[72]), "+f"(d[73]), "+f"(d[74]), "+f"(d[75]), "+f"(d[76]), "+f"(d[77]), "+f"(d[78]), "+f"(d[79]) : "l"(da), "l"(db), "r"(sd));
}
template<int N> __device__ __forceinline__ void wgmma_rs(float (&d)[N/2], uint32_t a0, uint32_t a1, uint32_t a2, uint32_t a3, uint64_t db, int sd);
template<> __device__ __forceinline__ void wgmma_rs<16>(float (&d)[8], uint32_t a0, uint32_t a1, uint32_t a2, uint32_t a3, uint64_t db, int sd){
  asm volatile("{ .reg .pred p; setp.ne.b32 p, %13, 0;\n"
   "wgmma.mma_async.sync.aligned.m64n16k16.f32.bf16.bf16 {%0, %1, %2, %3, %4, %5, %6, %7}, {%8,%9,%10,%11}, %12, p, 1, 1, 0; }\n"
   : "+f"(d[0]), "+f"(d[1]), "+f"(d[2]), "+f"(d[3]), "+f"(d[4]), "+f"(d[5]), "+f"(d[6]), "+f"(d[7]) : "r"(a0), "r"(a1), "r"(a2), "r"(a3), "l"(db), "r"(sd));
}
template<> __device__ __forceinline__ void wgmma_rs<32>(float (&d)[16], uint32_t a0, uint32_t a1, uint32_t a2, uint32_t a3, uint64_t db, int sd){
  asm volatile("{ .reg .pred p; setp.ne.b32 p, %21, 0;\n"
   "wgmma.mma_async.sync.aligned.m64n32k16.f32.bf16.bf16 {%0, %1, %2, %3, %4, %5, %6, %7, %8, %9, %10, %11, %12, %13, %14, %15}, {%16,%17,%18,%19}, %20, p, 1, 1, 0; }\n"
   : "+f"(d[0]), "+f"(d[1]), "+f"(d[2]), "+f"(d[3]), "+f"(d[4]), "+f"(d[5]), "+f"(d[6]), "+f"(d[7]), "+f"(d[8]), "+f"(d[9]), "+f"(d[10]), "+f"(d[11]), "+f"(d[12]), "+f"(d[13]), "+f"(d[14]), "+f"(d[15]) : "r"(a0), "r"(a1), "r"(a2), "r"(a3), "l"(db), "r"(sd));
}
template<> __device__ __forceinline__ void wgmma_rs<48>(float (&d)[24], uint32_t a0, uint32_t a1, uint32_t a2, uint32_t a3, uint64_t db, int sd){
  asm volatile("{ .reg .pred p; setp.ne.b32 p, %29, 0;\n"
   "wgmma.mma_async.sync.aligned.m64n48k16.f32.bf16.bf16 {%0, %1, %2, %3, %4, %5, %6, %7, %8, %9, %10, %11, %12, %13, %14, %15, %16, %17, %18, %19, %20, %21, %22, %23}, {%24,%25,%26,%27}, %28, p, 1, 1, 0; }\n"
   : "+f"(d[0]), "+f"(d[1]), "+f"(d[2]), "+f"(d[3]), "+f"(d[4]), "+f"(d[5]), "+f"(d[6]), "+f"(d[7]), "+f"(d[8]), "+f"(d[9]), "+f"(d[10]), "+f"(d[11]), "+f"(d[12]), "+f"(d[13]), "+f"(d[14]), "+f"(d[15]), "+f"(d[16]), "+f"(d[17]), "+f"(d[18]), "+f"(d[19]), "+f"(d[20]), "+f"(d[21]), "+f"(d[22]), "+f"(d[23]) : "r"(a0), "r"(a1), "r"(a2), "r"(a3), "l"(db), "r"(sd));
}
template<> __device__ __forceinline__ void wgmma_rs<64>(float (&d)[32], uint32_t a0, uint32_t a1, uint32_t a2, uint32_t a3, uint64_t db, int sd){
  asm volatile("{ .reg .pred p; setp.ne.b32 p, %37, 0;\n"
   "wgmma.mma_async.sync.aligned.m64n64k16.f32.bf16.bf16 {%0, %1, %2, %3, %4, %5, %6, %7, %8, %9, %10, %11, %12, %13, %14, %15, %16, %17, %18, %19, %20, %21, %22, %23, %24, %25, %26, %27, %28, %29, %30, %31}, {%32,%33,%34,%35}, %36, p, 1, 1, 0; }\n"
   : "+f"(d[0]), "+f"(d[1]), "+f"(d[2]), "+f"(d[3]), "+f"(d[4]), "+f"(d[5]), "+f"(d[6]), "+f"(d[7]), "+f"(d[8]), "+f"(d[9]), "+f"(d[10]), "+f"(d[11]), "+f"(d[12]), "+f"(d[13]), "+f"(d[14]), "+f"(d[15]), "+f"(d[16]), "+f"(d[17]), "+f"(d[18]), "+f"(d[19]), "+f"(d[20]), "+f"(d[21]), "+f"(d[22]), "+f"(d[23]), "+f"(d[24]), "+f"(d[25]), "+f"(d[26]), "+f"(d[27]), "+f"(d[28]), "+f"(d[29]), "+f"(d[30]), "+f"(d[31]) : "r"(a0), "r"(a1), "r"(a2), "r"(a3), "l"(db), "r"(sd));
}
template<> __device__ __forceinline__ void wgmma_rs<80>(float (&d)[40], uint32_t a0, uint32_t a1, uint32_t a2, uint32_t a3, uint64_t db, int sd){
  asm volatile("{ .reg .pred p; setp.ne.b32 p, %45, 0;\n"
   "wgmma.mma_async.sync.aligned.m64n80k16.f32.bf16.bf16 {%0, %1, %2, %3, %4, %5, %6, %7, %8, %9, %10, %11, %12, %13, %14, %15, %16, %17, %18, %19, %20, %21, %22, %23, %24, %25, %26, %27, %28, %29, %30, %31, %32, %33, %34, %35, %36, %37, %38, %39}, {%40,%41,%42,%43}, %44, p, 1, 1, 0; }\n"
   : "+f"(d[0]), "+f"(d[1]), "+f"(d[2]), "+f"(d[3]), "+f"(d[4]), "+f"(d[5]), "+f"(d[6]), "+f"(d[7]), "+f"(d[8]), "+f"(d[9]), "+f"(d[10]), "+f"(d[11]), "+f"(d[12]), "+f"(d[13]), "+f"(d[14]), "+f"(d[15]), "+f"(d[16]), "+f"(d[17]), "+f"(d[18]), "+f"(d[19]), "+f"(d[20]), "+f"(d[21]), "+f"(d[22]), "+f"(d[23]), "+f"(d[24]), "+f"(d[25]), "+f"(d[26]), "+f"(d[27]), "+f"(d[28]), "+f"(d[29]), "+f"(d[30]), "+f"(d[31]), "+f"(d[32]), "+f"(d[33]), "+f"(d[34]), "+f"(d[35]), "+f"(d[36]), "+f"(d[37]), "+f"(d[38]), "+f"(d[39]) : "r"(a0), "r"(a1), "r"(a2), "r"(a3), "l"(db), "r"(sd));
}
template<> __device__ __forceinline__ void wgmma_rs<96>(float (&d)[48], uint32_t a0, uint32_t a1, uint32_t a2, uint32_t a3, uint64_t db, int sd){
  asm volatile("{ .reg .pred p; setp.ne.b32 p, %53, 0;\n"
   "wgmma.mma_async.sync.aligned.m64n96k16.f32.bf16.bf16 {%0, %1, %2, %3, %4, %5, %6, %7, %8, %9, %10, %11, %12, %13, %14, %15, %16, %17, %18, %19, %20, %21, %22, %23, %24, %25, %26, %27, %28, %29, %30, %31, %32, %33, %34, %35, %36, %37, %38, %39, %40, %41, %42, %43, %44, %45, %46, %47}, {%48,%49,%50,%51}, %52, p, 1, 1, 0; }\n"
   : "+f"(d[0]), "+f"(d[1]), "+f"(d[2]), "+f"(d[3]), "+f"(d[4]), "+f"(d[5]), "+f"(d[6]), "+f"(d[7]), "+f"(d[8]), "+f"(d[9]), "+f"(d[10]), "+f"(d[11]), "+f"(d[12]), "+f"(d[13]), "+f"(d[14]), "+f"(d[15]), "+f"(d[16]), "+f"(d[17]), "+f"(d[18]), "+f"(d[19]), "+f"(d[20]), "+f"(d[21]), "+f"(d[22]), "+f"(d[23]), "+f"(d[24]), "+f"(d[25]), "+f"(d[26]), "+f"(d[27]), "+f"(d[28]), "+f"(d[29]), "+f"(d[30]), "+f"(d[31]), "+f"(d[32]), "+f"(d[33]), "+f"(d[34]), "+f"(d[35]), "+f"(d[36]), "+f"(d[37]), "+f"(d[38]), "+f"(d[39]), "+f"(d[40]), "+f"(d[41]), "+f"(d[42]), "+f"(d[43]), "+f"(d[44]), "+f"(d[45]), "+f"(d[46]), "+f"(d[47]) : "r"(a0), "r"(a1), "r"(a2), "r"(a3), "l"(db), "r"(sd));
}
template<> __device__ __forceinline__ void wgmma_rs<112>(float (&d)[56], uint32_t a0, uint32_t a1, uint32_t a2, uint32_t a3, uint64_t db, int sd){
  asm volatile("{ .reg .pred p; setp.ne.b32 p, %61, 0;\n"
   "wgmma.mma_async.sync.aligned.m64n112k16.f32.bf16.bf16 {%0, %1, %2, %3, %4, %5, %6, %7, %8, %9, %10, %11, %12, %13, %14, %15, %16, %17, %18, %19, %20, %21, %22, %23, %24, %25, %26, %27, %28, %29, %30, %31, %32, %33, %34, %35, %36, %37, %38, %39, %40, %41, %42, %43, %44, %45, %46, %47, %48, %49, %50, %51, %52, %53, %54, %55}, {%56,%57,%58,%59}, %60, p, 1, 1, 0; }\n"
   : "+f"(d[0]), "+f"(d[1]), "+f"(d[2]), "+f"(d[3]), "+f"(d[4]), "+f"(d[5]), "+f"(d[6]), "+f"(d[7]), "+f"(d[8]), "+f"(d[9]), "+f"(d[10]), "+f"(d[11]), "+f"(d[12]), "+f"(d[13]), "+f"(d[14]), "+f"(d[15]), "+f"(d[16]), "+f"(d[17]), "+f"(d[18]), "+f"(d[19]), "+f"(d[20]), "+f"(d[21]), "+f"(d[22]), "+f"(d[23]), "+f"(d[24]), "+f"(d[25]), "+f"(d[26]), "+f"(d[27]), "+f"(d[28]), "+f"(d[29]), "+f"(d[30]), "+f"(d[31]), "+f"(d[32]), "+f"(d[33]), "+f"(d[34]), "+f"(d[35]), "+f"(d[36]), "+f"(d[37]), "+f"(d[38]), "+f"(d[39]), "+f"(d[40]), "+f"(d[41]), "+f"(d[42]), "+f"(d[43]), "+f"(d[44]), "+f"(d[45]), "+f"(d[46]), "+f"(d[47]), "+f"(d[48]), "+f"(d[49]), "+f"(d[50]), "+f"(d[51]), "+f"(d[52]), "+f"(d[53]), "+f"(d[54]), "+f"(d[55]) : "r"(a0), "r"(a1), "r"(a2), "r"(a3), "l"(db), "r"(sd));
}
template<> __device__ __forceinline__ void wgmma_rs<128>(float (&d)[64], uint32_t a0, uint32_t a1, uint32_t a2, uint32_t a3, uint64_t db, int sd){
  asm volatile("{ .reg .pred p; setp.ne.b32 p, %69, 0;\n"
   "wgmma.mma_async.sync.aligned.m64n128k16.f32.bf16.bf16 {%0, %1, %2, %3, %4, %5, %6, %7, %8, %9, %10, %11, %12, %13, %14, %15, %16, %17, %18, %19, %20, %21, %22, %23, %24, %25, %26, %27, %28, %29, %30, %31, %32, %33, %34, %35, %36, %37, %38, %39, %40, %41, %42, %43, %44, %45, %46, %47, %48, %49, %50, %51, %52, %53, %54, %55, %56, %57, %58, %59, %60, %61, %62, %63}, {%64,%65,%66,%67}, %68, p, 1, 1, 0; }\n"
   : "+f"(d[0]), "+f"(d[1]), "+f"(d[2]), "+f"(d[3]), "+f"(d[4]), "+f"(d[5]), "+f"(d[6]), "+f"(d[7]), "+f"(d[8]), "+f"(d[9]), "+f"(d[10]), "+f"(d[11]), "+f"(d[12]), "+f"(d[13]), "+f"(d[14]), "+f"(d[15]), "+f"(d[16]), "+f"(d[17]), "+f"(d[18]), "+f"(d[19]), "+f"(d[20]), "+f"(d[21]), "+f"(d[22]), "+f"(d[23]), "+f"(d[24]), "+f"(d[25]), "+f"(d[26]), "+f"(d[27]), "+f"(d[28]), "+f"(d[29]), "+f"(d[30]), "+f"(d[31]), "+f"(d[32]), "+f"(d[33]), "+f"(d[34]), "+f"(d[35]), "+f"(d[36]), "+f"(d[37]), "+f"(d[38]), "+f"(d[39]), "+f"(d[40]), "+f"(d[41]), "+f"(d[42]), "+f"(d[43]), "+f"(d[44]), "+f"(d[45]), "+f"(d[46]), "+f"(d[47]), "+f"(d[48]), "+f"(d[49]), "+f"(d[50]), "+f"(d[51]), "+f"(d[52]), "+f"(d[53]), "+f"(d[54]), "+f"(d[55]), "+f"(d[56]), "+f"(d[57]), "+f"(d[58]), "+f"(d[59]), "+f"(d[60]), "+f"(d[61]), "+f"(d[62]), "+f"(d[63]) : "r"(a0), "r"(a1), "r"(a2), "r"(a3), "l"(db), "r"(sd));
}

#define BAR(i) (bars + 8u * (uint32_t)(i))

template <int G> __device__ __forceinline__ void conv_frags(uint32_t (&a)[12], uint32_t abase) {
#pragma unroll
  for (int i = 0; i < 12; i++) a[i] = lds32(abase + (G * 4 + i / 3) * 128 + (i % 3) * 4);
}
__device__ __forceinline__ void kv_prefetch(const __nv_bfloat16* pf, int task) { prefetch_if(pf + 64 * (task & 31) * DM + 64 * (task >> 5), task < 320); }
__device__ __forceinline__ void kv_load(const Params& P, Scratch* S, int task, int tid, uint32_t (&k_)[19], uint32_t (&v_)[16], uint4& sk) {
  const int row = 64 * (task & 31) + 16 * (tid >> 5), ch = 64 * (task >> 5) + 2 * (tid & 31);
  const uint32_t* kp = (const uint32_t*)(P.k + (size_t)row * DM + ch);
  const uint32_t* vp = (const uint32_t*)(P.v + (size_t)row * DM + ch);
  const uint32_t* hp = row > 0 ? kp - 3 * (DM / 2) : S->zero;
  const int hs = row > 0 ? DM / 2 : 0;
  asm volatile("ld.global.nc.v4.u32 {%0,%1,%2,%3},[%4];" : "=r"(sk.x), "=r"(sk.y), "=r"(sk.z), "=r"(sk.w) : "l"(P.shk + ch * 4));
#pragma unroll
  for (int i = 0; i < 3; i++) k_[i] = ldg1(hp + i * hs);
#pragma unroll
  for (int i = 0; i < 16; i++) { k_[i + 3] = ldg1(kp + i * (DM / 2)); v_[i] = ldg1(vp + i * (DM / 2)); }
}
template <int SH> __device__ __forceinline__ void xb_prefetch(const Head& H, int id, int tid, int c0) {
  const int ri = tid >> SH, rr = 11 * id + ri - 16;
  const __nv_bfloat16* p = ri < 16 ? H.x + (size_t)(16 * min(id, 127) + ri) * DM : (rr < DM ? H.b0 : H.b1 - DM * DM) + (size_t)rr * DM;
  prefetch_if(p + c0 + 64 * (tid & ((1 << SH) - 1)), ri < 16 || (ri < 27 && rr < 2 * DM));
}
__device__ __forceinline__ uint4 ldg4(const void* p) { uint4 v; asm volatile("ld.global.nc.v4.u32 {%0,%1,%2,%3},[%4];" : "=r"(v.x), "=r"(v.y), "=r"(v.z), "=r"(v.w) : "l"(p)); return v; }
__device__ __forceinline__ uint4 lds4(uint32_t a) { uint4 v; asm volatile("ld.shared.v4.u32 {%0,%1,%2,%3},[%4];" : "=r"(v.x), "=r"(v.y), "=r"(v.z), "=r"(v.w) : "r"(a) : "memory"); return v; }
__device__ __forceinline__ void discretise(const Head& H, const Params& P, uint32_t sb, Role R, int lane, uint32_t e1) {
  const uint32_t dn = __ldg((const unsigned short*)P.ssmd + min(conv_ch(R.c, (lane + 7) & 7), DM - 1));
  const int c = 32 * min(R.cb(), 9) + lane;
  const uint32_t lr2 = ldg1(P.lre + 2 * c), li2 = ldg1(P.lim + 2 * c), ld2 = ldg1(P.ldt + 2 * c);
  asm volatile("st.shared.u32 [%0],%1;" ::"r"(sb + MISC_OFF + 4 * (lane & 7)), "r"((lane & 7) ? dn : e1) : "memory");
#pragma unroll 1
  for (int i = 0; i < 2; i++) {
    const float lr = bf_hi(lr2 << (16 - 16 * i)), li = bf_hi(li2 << (16 - 16 * i));
    const float2 lb = lam_bar(lr, li, bf_hi(ld2 << (16 - 16 * i)));
    const float nx = lb.x - 1.f, ny = lb.y, inv = 2.f * frcp(lr * lr + li * li), cx = (nx * lr + ny * li) * inv, cy = (ny * lr - nx * li) * inv;
    const bool sw = !H.swap;
    asm volatile("st.shared.v4.f32 [%0],{%1,%2,%3,%4};" ::"r"(sb + LAM_OFF + 32 * lane + 16 * i), "f"(lb.x), "f"(sw ? -lb.y : lb.y), "f"(sw ? -cy : cx), "f"(sw ? cx : -cy) : "memory");
  }
  __syncwarp();
}
__device__ __forceinline__ void aux_prep(const Head& H, const Params& P, uint32_t sb, Role R, int tid, long long t_start) {
  Scratch* const S = H.s;
  const uint32_t bars = sb + BAR_OFF;
  tid = opaque(tid);
  const int w = tid >> 5, lane = tid & 31, tb = R.tb(), cb = R.cb();
  uint32_t k_[19], v_[16];
  uint4 sk;
  int task = R.b() < R.nprep() ? R.b() : 320;
  delay(KVDLY);
  PROFC(tid == 0, 345);
  kv_load(P, S, min(task, 319), tid, k_, v_, sk);
  const __nv_bfloat16* pf = (tid < 64 ? P.k : P.v) + (tid & 63) * DM;
  const int j = lane >> 3, sm = min(R.sm(), 9), trow = 160 * tb + 4 * sm + (tb < 12 ? 40 : 32) * w + j;
  const uint32_t so = sb + (2 * w + (j & 1) + 8 * (j >> 1)) * 128 + 16 * (lane & 7), xo = so + sm * 2048, wo = so + (tb & 1) * 8192 + (tb & 6) * 1024;
  const __nv_bfloat16* xp = H.x + (size_t)min(trow, SEQ - 1) * DM + 384 + 8 * (lane & 7);
  const __nv_bfloat16* bp = (j < 2 ? H.b0 : H.b1) + (size_t)(64 * cb + 32 * (tb & 1) + 4 * (tb & 6) + 2 * w + (j & 1)) * DM + 384 + 8 * (lane & 7);
  float s = 0.f, s2 = 0.f, sr = 0.f;
#define STAT(m, n) { const uint32_t xw[4] = {m.x, m.y, m.z, m.w}, bw[4] = {n.x, n.y, n.z, n.w}; \
  _Pragma("unroll") for (int i = 0; i < 4; i++) { const float u = bf_lo(xw[i]), v = bf_hi(xw[i]); s += u + v; s2 = fmaf(u, u, fmaf(v, v, s2)); sr += bf_lo(bw[i]) + bf_hi(bw[i]); } }
#define STATS(K0, K1) _Pragma("unroll 1") for (int kb = K0; kb < K1; kb++) { \
    mbar_wait(BAR(B_F1 + kb)); \
    const uint4 a = lds4(xo + ((uint32_t)(XTAB0 >> (6 * kb)) & 63) * 4096), c = lds4(wo + ((uint32_t)(WTAB0 >> (6 * kb)) & 63) * 4096); \
    STAT(a, c) \
    asm volatile("" : "+f"(s), "+f"(s2), "+f"(sr)); \
    if (XPFAT >= K0 && XPFAT < K1) prefetch_if(((lane & 4) ? bp : xp) + 64 * (lane & 3), kb == XPFAT); \
    kv_prefetch(pf, kb == KPFAT ? task + R.nprep() : kb == KPFAT2 ? task + 2 * R.nprep() : 320); \
  } \
  __syncwarp(); mbar_arrive_if(BAR(B_AX + K0 / 3), lane == 0);
  STATS(0, 3)
  PROFC(tid == 0, 349);
    {
      uint4 m[4], n[4];
#pragma unroll
      for (int i = 0; i < 4; i++) { m[i] = ldg4(xp + 64 * i); n[i] = ldg4(bp + 64 * i); }
      STATS(3, 6)
      PROFC(tid == 0, 346);
      mbar_wait(BAR(B_LM));
      const uint32_t tag = lds32(sb + MISC_OFF) & 1;
#pragma unroll
      for (int i = 0; i < 4; i++) { const uint4 a = m[i], c = n[i]; STAT(a, c) }
      PROFC(tid == 0 && s2 != 1.2345f, 347);
#pragma unroll
      for (int o = 1; o <= 4; o <<= 1) { s += __shfl_xor_sync(0xffffffff, s, o); s2 += __shfl_xor_sync(0xffffffff, s2, o); sr += __shfl_xor_sync(0xffffffff, sr, o); }
      const float mn = s * (1.f / DM), rs = frcp(bf_rn(fsqrt(bf_rn(bf_rn(fmaxf(s2 * (1.f / DM) - mn * mn, 0.f)) + 1e-5f))));
      asm volatile("{ .reg .pred p; setp.ne.u32 p, %2, 0; @p st.relaxed.gpu.global.u32 [%0],%1; }"
                   ::"l"((uint32_t*)(S->RS + (8 * cb + 4 * (tb & 1) + (tb >> 1)) * 16 + 4 * w + (j & 1)) + (lane & 4) + (j >> 1)), "r"(tagf(sr, tag)),
                   "r"((uint32_t)(tb < 8 && (lane & 3) == 0)) : "memory");
      asm volatile("{ .reg .pred p; setp.ne.u32 p, %3, 0; @p st.relaxed.gpu.global.v2.u32 [%0],{%1,%2}; }"
                   ::"l"(S->S + trow), "r"(tagf(rs, tag)), "r"(tagf(-bf_rn(mn) * rs, tag)), "r"((uint32_t)(R.sm() < 10 && (lane & 7) == 0)) : "memory");
      PROFC(tid == 0, 3);
    }
#pragma unroll 1
  for (int r = 0; task < 320; r++) {
    {
      const uint32_t T0 = __byte_perm(sk.x, sk.z, 0x5410), T1 = __byte_perm(sk.x, sk.z, 0x7632);
      const uint32_t T2 = __byte_perm(sk.y, sk.w, 0x5410), T3 = __byte_perm(sk.y, sk.w, 0x7632);
      PROFC(tid == 0 && v_[15] != 0x12345, 336 + r);
      uint32_t o[16];
#pragma unroll
      for (int t = 0; t < 16; t += 2) {
        const uint32_t a = hmul2(hfma2(k_[t + 3], T0, hfma2(k_[t + 2], T1, hfma2(k_[t + 1], T2, hmul2(k_[t], T3)))), v_[t]);
        const uint32_t c = hmul2(hfma2(k_[t + 4], T0, hfma2(k_[t + 3], T1, hfma2(k_[t + 2], T2, hmul2(k_[t + 1], T3)))), v_[t + 1]);
        const int wd = ((7 - t / 2) >> 1) + 4 * ((7 - t / 2) & 1);
        o[wd] = __byte_perm(c, a, 0x5410); o[8 + wd] = __byte_perm(c, a, 0x7632);
        asm volatile("" : "+r"(o[wd]), "+r"(o[8 + wd]));
        if (t == PFAT) kv_prefetch(pf, task + (1 + PFD) * R.nprep());
      }
      PROFC(tid == 0, 330 + 2 * r);
      const int ph = task & 1;
      task += R.nprep();
      if (ORD == 0 && task < 320) kv_load(P, S, task, tid, k_, v_, sk);
      mbar_wait(BAR(B_E1 + 3)); mbar_wait(BAR(B_AX + 1));
#pragma unroll
      for (int i = 0; i < 4; i++) {
        const int row = 2 * lane + (i >> 1);
        asm volatile("st.shared.v4.u32 [%0],{%1,%2,%3,%4};" ::"r"(sb + KS_OFF + r * 8192 + row * 128 + (((2 * w + ((i & 1) ^ ph)) ^ (row & 7)) << 4)),
                     "r"(o[4 * i]), "r"(o[4 * i + 1]), "r"(o[4 * i + 2]), "r"(o[4 * i + 3]) : "memory");
      }
      __syncwarp();
      mbar_arrive_if(BAR(B_PS + r), lane == 0);
      PROFC(tid == 0, 331 + 2 * r);
      if (ORD == 1 && task < 320) kv_load(P, S, task, tid, k_, v_, sk);
    }
  }
#undef STAT
#undef STATS
  PROFC(tid == 0, 40);
}
#define SPLIT(G) asm volatile("{ .reg .pred p; .reg .u32 r; L: mov.u32 r, %%clock; setp.eq.u32 p, r, %0; @p bra.uni L; }" ::"n"(G) : "memory")
template <bool AUX>
__device__ __forceinline__ void conv_loop(uint32_t sb, uint32_t rc, int wg, int tid, long long t_start) {
  sb = opaque(sb); rc = opaque(rc);
  const uint32_t bars = sb + BAR_OFF;
  int slot = AUX ? 0 : wg + 1;
  mbar_wait(BAR(B_LM));
#pragma unroll 1
  while (slot < (int)((rc >> 10) & 7)) {
    tid = opaque(tid);
    const int w = tid >> 5, lane = tid & 31, g = lane >> 2, q = lane & 3;
    const uint32_t Dn = lds32(sb + MISC_OFF + 4 + 4 * slot);
    const uint32_t d0 = (g == 1 && q == 3 - w) ? Dn : 0, d1 = (g == 0 && q == 3 - w) ? Dn : 0;
    const uint32_t cb_ = conv_buf(sb, slot), c0 = cb_ + KC_OFS;
    const uint32_t abase = c0 + 2 * (2 * (g & 1) + 4 * w + 16 * (g >> 1) + 4 * q);
    const uint64_t bd = make_desc(cb_ + KV_PAD, 16, 256, 3);
    const bool hi = lane & 16, s1 = lane & 8;
    const int qo = hi ? (q + 1) & 3 : q;
    const int srcA = hi ? (lane & 12) | ((q + 1) & 3) : (lane & 12) | 16 | ((q + 3) & 3);
    const bool h3 = hi && q == 3, wrap = s1 && qo == 3, back = wrap && hi;
    const bool chi = wrap ? !hi : hi;
    const int cq = s1 ? (qo + 1) & 3 : qo;
    const int srcB = (lane & 4) | (s1 ? 0 : 8) | (chi ? 16 | ((cq + 3) & 3) : cq);
    const uint32_t gp = c0 + 16 * (2 * (g & 1) + 4 * w) + (chi ? 256 : 0) + 2 * (2 * cq + (s1 ? 0 : 1));
    uint32_t a[12], f[16], o[8];
    float S[4], T[4], U[2], keep[2], pv[2] = {0.f, 0.f}, pr[4] = {0.f, 0.f, 0.f, 0.f};
    float e0[64], e1[56], e2[48], e3[40], e4[32], e5[24], e6[16], e7[8];
#define UNR _Pragma("unroll")
#define PERM() UNR for (int i = 0; i < 4; i++) { f[4 * i] = __byte_perm(a[3 * i], a[3 * i + 1], 0x5432); f[4 * i + 1] = a[3 * i + 1]; \
                                                 f[4 * i + 2] = __byte_perm(a[3 * i + 1], a[3 * i + 2], 0x5432); f[4 * i + 3] = a[3 * i + 2]; }
#define MMA(N, E) UNR for (int i = 0; i < 4; i++) wgmma_rs<N>(E, f[4 * i], f[4 * i + 1], f[4 * i + 2], f[4 * i + 3], bd - 8 * i, 1); wg_commit();
#define L1(c) UNR for (int i = 0; i < 4; i++) { const float ev = c[i], od = c[4 + i]; S[i] = hi ? (h3 ? ev : od) : ev; \
                                                T[i] = __shfl_sync(0xffffffff, hi ? (h3 ? pr[i] : ev) : od, srcA); pr[i] = od; }
#define L1E() UNR for (int i = 0; i < 4; i++) S[i] += T[i];
#define L2() UNR for (int h = 0; h < 2; h++) { keep[h] = back ? pv[h] : S[2 * h + 1]; pv[h] = S[2 * h + 1]; U[h] = __shfl_sync(0xffffffff, S[2 * h], srcB); }
#define L2E(j) o[j] = pack_bf(keep[0] + U[0], keep[1] + U[1]);
#define GRP(G, N, P, E) UNR for (int i = 0; i < N / 2; i++) asm volatile("mov.b32 %0,%1;" : "=f"(E[i]) : "f"(P[i + 8])); \
    wg_fence(); if (G < 7) conv_frags<(G + 1) & 7>(a, abase); if (G >= 2) { L2() } L1(P) MMA(N, E) SPLIT(G); \
    if (G < 7) { PERM() } if (G >= 2) { L2E((G + 6) & 7) } L1E() wg_wait<0>(); fence_regs(E);
    PROFC(tid == 0, 300 + 4 * slot);
    mbar_wait(BAR(B_KF + slot));
    if (tid == 0) PROF(361 + slot);
    PROFC(tid == 0, 301 + 4 * slot);
    conv_frags<0>(a, abase);
    wg_fence();
    wgmma_rs<128>(e0, d0 << 16, d0, d1 << 16, d1, bd, 0);
    PERM() conv_frags<1>(a, abase); wg_fence(); MMA(128, e0) SPLIT(0); PERM() wg_wait<0>(); fence_regs(e0);
    GRP(1, 112, e0, e1) GRP(2, 96, e1, e2) GRP(3, 80, e2, e3) GRP(4, 64, e3, e4) GRP(5, 48, e4, e5) GRP(6, 32, e5, e6) GRP(7, 16, e6, e7)
    PROFC(tid == 0, 302 + 4 * slot);
    L2() L1(e7) L2E(6) L1E() L2() L2E(7)
    bar_sync(wg + 1, 128);
#pragma unroll
    for (int jj = 0; jj < 8; jj++)
      asm volatile("st.shared.u16 [%0],%1; st.shared.u16 [%0+16],%2;" ::"r"(gp + jj * 512), "h"((uint16_t)o[jj]), "h"((uint16_t)(o[jj] >> 16)) : "memory");
#undef PERM
#undef MMA
#undef L1
#undef L1E
#undef L2
#undef L2E
#undef GRP
    PROFC(tid == 0, 303 + 4 * slot);
    __syncwarp();
    if (lane == 0) mbar_arrive(BAR(B_GS + slot));
    if (!AUX) break;
    slot = slot ? slot + 1 : 3;
  }
}

#define IDX(J, c, h) (8 * (J) + 4 * ((c) >> 1) + 2 * (h) + ((c) & 1))
__device__ __forceinline__ uint2 lds2(uint32_t a) { uint2 v; asm volatile("ld.shared.v2.u32 {%0,%1},[%2];" : "=r"(v.x), "=r"(v.y) : "r"(a) : "memory"); return v; }
__device__ __forceinline__ void resid_load(float (&r)[40], uint32_t sb, int wg, int tid, const uint4& s) {
  const uint32_t dp = sb + XR_OFF + 8 * (tid & 3), xp = dp + (64 * wg + 16 * (tid >> 5) + ((tid & 31) >> 2)) * 160;
#pragma unroll
  for (int J = 0; J < 5; J++) {
    const uint2 u = lds2(xp + 32 * J), v = lds2(xp + 32 * J + 1280), d = lds2(dp + 20480 + 32 * J);
    r[8 * J] = __uint_as_float(u.x); r[8 * J + 1] = __uint_as_float(u.y); r[8 * J + 2] = __uint_as_float(v.x); r[8 * J + 3] = __uint_as_float(v.y);
    r[8 * J + 4] = __uint_as_float(d.x); r[8 * J + 5] = __uint_as_float(d.y);
  }
  r[30] = untag(s.x); r[31] = untag(s.y); r[38] = untag(s.z); r[39] = untag(s.w);
}
__device__ __forceinline__ void resid_init(float (&r)[40]) {
  const float s[4] = {r[30], r[31], r[38], r[39]};
#pragma unroll
  for (int J = 0; J < 5; J++) {
    uint32_t w[6];
#pragma unroll
    for (int i = 0; i < 6; i++) w[i] = __float_as_uint(r[8 * J + i]);
#pragma unroll
    for (int i = 0; i < 4; i++) {
      const int h = i >> 1, c = 2 * (i & 1);
      const float rs = s[2 * h], nm = s[2 * h + 1], x0 = bf_lo(w[i]), x1 = bf_hi(w[i]);
      const uint32_t t = hmul2(pack_bf(fmaf(x0, rs, nm), fmaf(x1, rs, nm)), w[4 + (i & 1)]);
      r[IDX(J, c, h)] = x0 + bf_lo(t); r[IDX(J, c + 1, h)] = x1 + bf_hi(t);
    }
  }
}

__device__ __forceinline__ float flip(float v, uint32_t m) { return __uint_as_float(__float_as_uint(v) ^ m); }
__device__ __forceinline__ void g1_phase(const int LY, const Head& H, uint32_t sb, int wg, int tid, Role R, float (&xr)[40], long long t_start) {
  Scratch* const S = H.s;
  tid = opaque(tid); sb = opaque(sb); R.v = opaque(R.v);
  const uint32_t bars = sb + BAR_OFF;
  const int cb = R.cb(), tb = R.tb();
  const int w = tid >> 5, lane = tid & 31, g = lane >> 2, q = lane & 3;
  const bool full = tb < 12;
  uint2* Eb = S->E + ((LY * 130 + cb) * 8 + 4 * wg + w) * 16 + g;
  float a[80];
#pragma unroll
  for (int i = 0; i < 80; i++) a[i] = 0.f;
  uint32_t rel = mapa(BAR(B_E1), lane ? R.wpart() : R.ubase() + (w & (R.ugs() - 1)));
  const bool rels = lane == 0 || (tid == 1 && wg != R.wlo());
  {
    uint64_t tw = LY ? WTAB1 : WTAB0, tx = LY ? XTAB1 : XTAB0;
    uint32_t bf = BAR(B_F1);
    if (tid == 0 && wg == 0 && !LY) PROF(351);
    fence_regs(a);
    mbar_wait(bf, LY);
    if (tid == 0 && wg == 0) PROF(LY ? 20 : 4);
#pragma unroll 1
    for (int kb = 0; kb < 10; kb++) {
      const uint64_t da = make_desc(sb + ((uint32_t)tw & 63) * 4096 + wg * 8192, 16, 1024, 1);
      const uint64_t db = make_desc(sb + ((uint32_t)tx & 63) * 4096, 16, 1024, 1);
      wg_fence();
#pragma unroll
      for (int kk = 0; kk < 4; kk++) wgmma_ss160(a, da + 2 * kk, db + 2 * kk, 1);
      wg_commit();
      wg_wait<1>();
      if (kb > 0) { if (rels) mbar_arrive_at(rel); rel += 8; }
      bf += 8; tw >>= 6; tx >>= 6;
      if (kb < 9) mbar_wait(bf, LY);
    }
  }
  if (tid == 0 && wg == 0) PROF(LY ? 19 : 2);
  mbar_wait(BAR(B_LM));
  const uint32_t tag = lds32(sb + MISC_OFF) & 1;
  if (q == 3) st_rlx2(Eb + tb * 1280, tag ^ 1, tag ^ 1);
  float2 lam, mu, mu2;
  float rs0, rs1;
  const uint32_t lamp = sb + LAM_OFF + 16 * (32 * wg + 8 * w + g);
  {
    const uint2* rp = S->RS + (8 * cb + 4 * wg + w) * 16 + 2 * g - (g & 1);
    uint2 v = ld_rlx2(rp);
    asm volatile("ld.shared.v2.f32 {%0,%1},[%2];" : "=f"(lam.x), "=f"(lam.y) : "r"(lamp));
    const float2 l2 = cmul(lam, lam), l4 = cmul(l2, l2), l8 = cmul(l4, l4), l16 = cmul(l8, l8), l32 = cmul(l16, l16);
    mu = full ? cmul(l32, l8) : l32; mu2 = cmul(mu, mu);
#pragma unroll 1
    for (int it = 0; it < SPIN && __any_sync(0xffffffff, untagged(v, tag)); it++) v = ld_rlx2(rp);
    rs0 = untag(v.x); rs1 = untag(v.y);
  }
  if (tid == 0 && wg == 0 && !LY) PROF(39);
  mbar_wait(BAR(B_ST), LY);
  const uint32_t ssm = sb + SSM_OFF + q * (full ? 336 : 272);
  wg_wait<0>(); fence_regs(a);
  if (rels) mbar_arrive_at(rel);
  if (tid == 0 && wg == 0) PROF(LY ? 21 : 5);
  float2 p = make_float2(0.f, 0.f);
#pragma unroll
  for (int j = 0; j < 20; j++) {
    if (j < 16 || full) {
      float4 sv;
      asm volatile("ld.shared.v4.f32 {%0,%1,%2,%3},[%4];" : "=f"(sv.x), "=f"(sv.y), "=f"(sv.z), "=f"(sv.w) : "r"(ssm + 16 * j));
#pragma unroll
      for (int e = 0; e < 2; e++) {
        const int o = 4 * j + e;
        const float r = e ? sv.z : sv.x, nm = e ? sv.w : sv.y;
        a[o] = fmaf(a[o], r, nm * rs0); a[o + 2] = fmaf(a[o + 2], r, nm * rs1);
        p = cfma(lam, p, make_float2(a[o], a[o + 2]));
      }
    }
  }
  {
    float2 t = make_float2(__shfl_up_sync(0xffffffff, p.x, 1, 4), __shfl_up_sync(0xffffffff, p.y, 1, 4));
    if (q >= 1) p = cfma(mu, t, p);
    t = make_float2(__shfl_up_sync(0xffffffff, p.x, 2, 4), __shfl_up_sync(0xffffffff, p.y, 2, 4));
    if (q >= 2) p = cfma(mu2, t, p);
  }
  if (q == 3 && full) st_rlx2(Eb + tb * 1280, tagf(p.x, tag), tagf(p.y, tag));
  if (tid == 0 && wg == 1) PROF(96 + 64 * LY);
  uint2 ev[3];
#pragma unroll
  for (int i = 0; i < 3; i++) { const int j = tb - 1 - q - 4 * i; ev[i] = j >= 0 ? ld_rlx2(Eb + j * 1280) : make_uint2(tag, tag); }
  float2 x = make_float2(__shfl_up_sync(0xffffffff, p.x, 1, 4), __shfl_up_sync(0xffffffff, p.y, 1, 4));
  if (q == 0) x = make_float2(0.f, 0.f);
  float c0, c1;
  asm volatile("ld.shared.v2.f32 {%0,%1},[%2+8];" : "=f"(c0), "=f"(c1) : "r"(lamp));
  const float c2 = -flip(c1, H.swap), c3 = flip(c0, H.swap);
#pragma unroll
  for (int i = 0; i < 40; i++) {
    const int o = 4 * (i >> 1) + (i & 1);
    const float u = a[o], v = a[o + 2];
    a[o] = fmaf(c0, u, c1 * v); a[o + 2] = fmaf(c2, u, c3 * v);
  }
  fence_regs(a);
  if (LY == 0 && R.b() < 128) {
    const int t0 = 16 * g + 8 * wg + 2 * w;
    if (tid == 0 && wg == 1) PROF(366);
    mbar_wait(BAR(B_XR));
    if (tid == 0 && wg == 1) PROF(367);
    uint4 s = lds4(sb + XR_OFF + 20480 + 256 + 8 * t0);
    if (__any_sync(0xffffffff, untagged(s, tag))) {
#pragma unroll 1
      for (int it = 0; it < SPIN; it++) { s = ld_rlx4(S->S + 128 * (R.b() >> 3) + t0); if (!__any_sync(0xffffffff, untagged(s, tag))) break; }
    }
    resid_load(xr, sb, wg, tid, s);
  }
  float2 mq, om4, fq;
  {
    asm volatile("" : "+f"(lam.x), "+f"(lam.y));
    const float2 one = make_float2(1.f, 0.f), l2 = cmul(lam, lam), l4 = cmul(l2, l2), l8 = cmul(l4, l4), l16 = cmul(l8, l8);
    const float2 l80 = full ? mu2 : cmul(mu2, l16), om = cmul(l80, l80), om2 = cmul(om, om);
    mq = cmul((q & 1) ? mu : one, (q & 2) ? mu2 : one);
    om4 = cmul(om2, om2); fq = cmul((q & 1) ? om : one, (q & 2) ? om2 : one);
  }
  mbar_wait(BAR(B_E1 + 9), LY);
  if (tid == 0 && wg == 1) PROF(368 + LY);
#pragma unroll 1
  for (int it = 0; it < SPIN; it++) {
    const bool m0 = untagged(ev[0], tag), m1 = untagged(ev[1], tag), m2 = untagged(ev[2], tag);
    if (!__any_sync(0xffffffff, m0 || m1 || m2)) break;
    if (m0) ev[0] = ld_rlx2(Eb + (tb - 1 - q) * 1280);
    if (m1) ev[1] = ld_rlx2(Eb + (tb - 5 - q) * 1280);
    if (m2) ev[2] = ld_rlx2(Eb + (tb - 9 - q) * 1280);
  }
  if (tid == 0 && wg == 1) PROF(97 + 64 * LY);
  float2 c = make_float2(untag(ev[2].x), untag(ev[2].y));
#pragma unroll
  for (int i = 1; i >= 0; i--) c = cfma(om4, c, make_float2(untag(ev[i].x), untag(ev[i].y)));
  c = cmul(fq, c);
#pragma unroll
  for (int s = 1; s <= 2; s <<= 1) { c.x += __shfl_xor_sync(0xffffffff, c.x, s); c.y += __shfl_xor_sync(0xffffffff, c.y, s); }
  c = cfma(mq, c, x);
  float2 z = make_float2(fmaf(c0, c.x, c1 * c.y), fmaf(c2, c.x, c3 * c.y));
  if (tid == 0 && wg == 0) PROF(LY ? 22 : 6);
  const float2 lc = make_float2(lam.x, flip(lam.y, H.swap));
  const uint32_t hq = sb + (lane >> 4) * 1024 + (lane & 7) * 128 + (((4 * wg + w) ^ (lane & 7)) << 4);
  const uint32_t hp = hq + R_OFF + (lane & 8) * 2048, hp4 = hq + (LY ? R4_OFF1 : R4_OFF0) + (lane & 8) * 512;
#pragma unroll
  for (int j = 0; j < 20; j += 2) {
    if (j < 16 || full) {
      uint32_t o[4];
#pragma unroll
      for (int i = 0; i < 2; i++) {
        const float2 z0 = cfma(lc, z, make_float2(a[4 * (j + i)], a[4 * (j + i) + 2]));
        z = cfma(lc, z0, make_float2(a[4 * (j + i) + 1], a[4 * (j + i) + 3]));
        o[2 * i] = pack_bf(z0.x, z.x); o[2 * i + 1] = pack_bf(z0.y, z.y);
      }
      asm volatile("stmatrix.sync.aligned.m8n8.x4.trans.shared.b16 [%0], {%1,%2,%3,%4};" ::"r"(j < 16 ? hp + j * 1024 : hp4 + (j - 16) * 1024), "r"(o[0]), "r"(o[1]), "r"(o[2]), "r"(o[3]) : "memory");
      if (j & 2) { __syncwarp(); if (lane == 0) mbar_arrive(BAR(B_SH + j / 4)); }
    }
  }
  if (tid == 0 && wg == 0) PROF(LY ? 23 : 7);
  if (lane == 0) PROF(390 + 4 * wg + w);
}

__device__ __forceinline__ void gate_load(uint32_t (&G)[20], uint32_t sb, int LY, int wg, int tid) {
  const uint32_t bars = sb + BAR_OFF;
  const int lane = tid & 31, w = tid >> 5;
  mbar_wait(BAR(B_GF), LY);
  __syncwarp();
  {
    const uint32_t gb = sb + (LY ? G_OFF1 : G_OFF0) + wg * 10240;
    const int dr = 4 * ((lane & 7) >> 1) + (lane & 1) + 2 * ((lane >> 3) & 1), ck = 2 * w + (lane >> 4);
#pragma unroll
    for (int J = 0; J < 5; J++) {
      const int dd = 16 * J + dr;
      asm volatile("ldmatrix.sync.aligned.m8n8.x4.trans.shared.b16 {%0,%1,%2,%3},[%4];"
                   : "=r"(G[4 * J]), "=r"(G[4 * J + 1]), "=r"(G[4 * J + 2]), "=r"(G[4 * J + 3]) : "r"(gb + dd * 128 + ((ck ^ (dd & 7)) << 4)) : "memory");
    }
  }
}
__device__ __forceinline__ void g2_phase(const int LY, const Params& P, Scratch* S, uint32_t sb, int wg, int tid, Role R, float (&xr)[40], long long t_start) {
  sb = opaque(sb);
  const uint32_t bars = sb + BAR_OFF;
  if (LY) {
    const int td = opaque(tid), b = (opaque(R.v) >> 8) & 255;
    const uint32_t tag = lds32(sb + MISC_OFF) & 1;
    const uint2* sp = S->S + 2 * SEQ + 128 * (b >> 3) + 4 * (td & 28) + 8 * wg + 2 * (td >> 5);
    if (!(R.cb() & 1)) mbar_wait(BAR(B_HD), 1);
    uint2 dl[5];
#pragma unroll
    for (int J = 0; J < 5; J++) dl[J] = __ldg((const uint2*)(P.dskip + 80 * (b & 7) + 4 * (td & 3) + 16 * J));
    uint4 sv;
#pragma unroll 1
    for (int it = 0; it < SPIN; it++) { sv = ld_rlx4(sp); if (!__any_sync(0xffffffff, untagged(sv, tag))) break; }
#pragma unroll
    for (int h = 0; h < 2; h++)
#pragma unroll
      for (int J = 0; J < 5; J++)
#pragma unroll
        for (int c = 0; c < 4; c++) {
          const float x2 = xr[IDX(J, c, h)];
          const uint32_t dw = (c & 2) ? dl[J].y : dl[J].x;
          xr[IDX(J, c, h)] = fmaf(fmaf(x2, untag(h ? sv.z : sv.x), untag(h ? sv.w : sv.y)), (c & 1) ? bf_hi(dw) : bf_lo(dw), x2);
        }
    fence_regs(xr);
  }
  float acc[40];
#pragma unroll
  for (int i = 0; i < 40; i++) acc[i] = RIAT == 1 ? 0.f : xr[i];
  fence_regs(acc);
#define G2_STEP(st, cs, hf) { \
    const uint64_t da = make_desc(sb + H_OFF + (st) * 32768 + (hf) * 16384 + wg * 8192, 16, 1024, 1), db = make_desc(sb + (cs) * 20480 + (hf) * 10240, 16, 1024, 1); \
    wg_fence(); \
    _Pragma("unroll") for (int kk = 0; kk < 4; kk++) wgmma_ss80(acc, da + 2 * kk, db + 2 * kk, 1); \
    wg_commit(); }
  mbar_wait(BAR(B_F2), LY);
  if (tid == 0 && wg == 0) PROF(LY ? 25 : 10);
  G2_STEP(0, 0, 0)
  mbar_wait(BAR(B_F3), LY);
  G2_STEP(0, 0, 1)
  tid = opaque(tid); R.v = opaque(R.v);
  const uint32_t tag = lds32(sb + MISC_OFF) & 1;
  const int b = R.b(), tb2 = b >> 3, db_ = b & 7;
  const int w = tid >> 5, lane = tid & 31, g = lane >> 2, q = lane & 3;
  const int t0 = 128 * tb2 + 16 * g + 8 * wg + 2 * w;
  const int d0 = 80 * db_ + 4 * q, mrow = 64 * wg + 16 * w + g;
#define GATE(J, c, h) (((c) & 1) ? bf_hi(G[4 * (J) + 2 * (h) + ((c) >> 1)]) : bf_lo(G[4 * (J) + 2 * (h) + ((c) >> 1)]))
  uint32_t rel = mapa(BAR(B_E2), lane ? ((w & 1) ? R.wpart() : R.rank()) : R.cs() == 8 ? 4 * wg + w : wg);
  const bool rels = lane == 0 || (lane == 1 && w < 2);
  uint32_t* Mb = S->M + ((2 * LY * 16 + tb2) * 8) * 256 + (wg * 4 + w) * 32 + (2 * g + (q & 1)) * 2 + (q >> 1);
  {
    uint32_t bf = BAR(B_F2 + 1), st = 1, ra = rel + 8 * (B_EA - B_E2);
    const int lag = wg ? (LY ? STG : STG0) / 2 : 0;
#pragma unroll 1
    for (int kp = 1; kp < 10; kp++) {
      const bool more = LY == 0 || kp < 8;
      wg_wait<1>();
      if (lane == 0 && more) mbar_arrive_at(ra + 8 * (st ? st - 1 : 2));
      mbar_wait(bf, LY);
      if (STG && !(STG & 1) && kp == lag) bar_sync(5, 256);
      G2_STEP(st, kp < 5 ? kp : kp - 5, 0)
      wg_wait<1>();
      if (rels && more) mbar_arrive_at(rel);
      rel += 8;
      mbar_wait(bf + 8 * (B_F3 - B_F2), LY);
      if ((STG & 1) && kp == lag) bar_sync(5, 256);
      G2_STEP(st, kp < 5 ? kp : kp - 5, 1)
      if (kp == MIAT) {
        st_rlx(Mb + db_ * 256, tag ^ 1);
        if (LY == 0) st_rlx(Mb + (16 * 8 + db_) * 256, tag ^ 1);
      }
      bf += 8; st = st == 2 ? 0 : st + 1;
    }
  }
  if (STG && (LY || STG0) && !wg) asm volatile("bar.arrive 5, 256;" ::: "memory");
  wg_wait<0>(); fence_regs(acc);
  if (LY == 0 && rels) mbar_arrive_at(rel);
  if (tid == 0 && wg == 0) PROF(LY ? 26 : 11);
  if (lane == 0) PROF(116 + 64 * LY + wg * 4 + w);

  float mm[2] = {0.f, 0.f}, rr[2];
#pragma unroll 1
  for (int rep = 0;; rep++) {
    float m[2][2];
#pragma unroll
    for (int h = 0; h < 2; h++) {
      m[h][0] = m[h][1] = 0.f;
#pragma unroll
      for (int J = 0; J < 5; J++)
#pragma unroll
        for (int c = 0; c < 4; c++) { const float xv = acc[IDX(J, c, h)]; m[h][0] += xv; m[h][1] = fmaf(xv, xv, m[h][1]); }
    }
    float r1[2];
#pragma unroll
    for (int i = 0; i < 2; i++) { const float snd = (q & 1) ? m[0][i] : m[1][i], kp = (q & 1) ? m[1][i] : m[0][i]; r1[i] = kp + __shfl_xor_sync(0xffffffff, snd, 1); }
    const float r2 = ((q & 2) ? r1[1] : r1[0]) + __shfl_xor_sync(0xffffffff, (q & 2) ? r1[0] : r1[1], 2);
    const uint32_t mx = sb + MX_OFF + 512 * wg + 4 * tid, bx = BAR(B_KF + 1 + (PWG ? 2 * LY + wg : LY));
    if (R.cs() == 8 && !rep) {
#pragma unroll
      for (int i = 0; i < 8; i++)
        asm volatile("st.async.weak.shared::cluster.mbarrier::complete_tx::bytes.b32 [%0],%1,[%2];" ::"r"(mapa(mx + 1024 * db_, i ^ db_)), "f"(r2), "r"(mapa(bx, i ^ db_)) : "memory");
      if (tid == 0 && (PWG || wg == 0)) mbar_expect_tx(bx, PWG ? 4096 : 8192);
    }
    st_rlx(Mb + db_ * 256, tagf(r2, tag));
    if (rep) break;
    if (lane == 0) PROF(100 + 64 * LY + wg * 4 + w);
    uint32_t G[20];
    const bool late = LY == 0 && db_ >= GLATE;
#pragma unroll
    for (int i = 0; i < 20; i++) G[i] = 0;
    if (!late) gate_load(G, sb, LY, wg, tid);
    mbar_wait(BAR(B_CD + 1));
    uint32_t mv[8];
    if (R.cs() == 8) {
      mbar_wait(bx, 1);
#pragma unroll
      for (int i = 0; i < 8; i++) mv[i] = lds32(mx + 1024 * i);
    } else {
#pragma unroll
    for (int i = 0; i < 8; i++) mv[i] = ld_rlx(Mb + i * 256);
#pragma unroll 1
    for (int it = 0; it < SPIN; it++) {
      uint32_t miss = 0;
#pragma unroll
      for (int i = 0; i < 8; i++) miss |= ((mv[i] ^ tag) & 1) << i;
      if (!__any_sync(0xffffffff, miss)) break;
#pragma unroll
      for (int i = 0; i < 8; i++) if ((miss >> i) & 1) mv[i] = ld_rlx(Mb + i * 256);
    }
      bar_sync(4, 256);
    }
    if (lane == 0) PROF(108 + 64 * LY + wg * 4 + w);
    const float s = ((untag(mv[0]) + untag(mv[1])) + (untag(mv[2]) + untag(mv[3]))) + ((untag(mv[4]) + untag(mv[5])) + (untag(mv[6]) + untag(mv[7])));
    const float o = __shfl_xor_sync(0xffffffff, s, 2);
    const float S1 = (q & 2) ? o : s, S2 = (q & 2) ? s : o;
    const float mean = S1 * (1.f / DM), rs = frsqrt(fmaxf(S2 * (1.f / DM) - mean * mean, 0.f) + 1e-5f);
    const float mo = __shfl_xor_sync(0xffffffff, mean, 1), ro = __shfl_xor_sync(0xffffffff, rs, 1);
    mm[0] = (q & 1) ? mo : mean; mm[1] = (q & 1) ? mean : mo; rr[0] = (q & 1) ? ro : rs; rr[1] = (q & 1) ? rs : ro;
    if (late) gate_load(G, sb, LY, wg, tid);
    if (tid == 0 && wg == 0) PROF(LY ? 27 : 12);
    const float nm[2] = {-mm[0] * rr[0], -mm[1] * rr[1]};
    if (LY) mm[0] = mm[1] = 0.f;
#pragma unroll
    for (int h = 0; h < 2; h++)
#pragma unroll
      for (int J = 0; J < 5; J++)
#pragma unroll
        for (int c = 0; c < 4; c++) { const float xv = acc[IDX(J, c, h)]; acc[IDX(J, c, h)] = fmaf(fmaf(xv, rr[h], nm[h]), GATE(J, c, h), xv - mm[h]); }
    if (LY) break;
    if (PWG && R.cs() == 8) mbar_wait(BAR(B_KF + 2 - wg), 1);
#pragma unroll
    for (int i = 0; i < 10; i++) {
      const int J = i >> 1, h = i & 1;
      const uint32_t u0 = pack_bf(acc[IDX(J, 0, h)], acc[IDX(J, 1, h)]), u1 = pack_bf(acc[IDX(J, 2, h)], acc[IDX(J, 3, h)]);
      asm volatile("st.shared.v2.u32 [%0],{%1,%2};" ::"r"(sb + US_OFF + (mrow + 8 * h) * 160 + 32 * J + 8 * q), "r"(u0), "r"(u1) : "memory");
    }
    __syncwarp();
    if (lane == 0) mbar_arrive(BAR(B_SG));
    if (tid == 0 && wg == 0) PROF(13);
    Mb += 16 * 8 * 256;
  }
  if (LY == 0) {
#pragma unroll
    for (int i = 0; i < 40; i++) xr[i] = acc[i] + mm[(i >> 1) & 1];
    if (tid == 0 && wg == 0) PROF(15);
  }
  else {
    float* op = P.out + (size_t)t0 * DM + d0;
#pragma unroll
    for (int i = 0; i < 10; i++) {
      const int J = i >> 1, h = i & 1;
      asm volatile("st.global.v4.f32 [%0],{%1,%2,%3,%4};" ::"l"(op + h * DM + 16 * J),
                   "f"(acc[IDX(J, 0, h)]), "f"(acc[IDX(J, 1, h)]), "f"(acc[IDX(J, 2, h)]), "f"(acc[IDX(J, 3, h)]) : "memory");
    }
  }
  if (tid == 0 && wg == 0 && LY) PROF(28);
#undef IDX
#undef GATE
}

__device__ __forceinline__ void next_stats(Scratch* S, uint32_t sb, int tb2, int tid) {
  const uint32_t bars = sb + BAR_OFF, tag = lds32(sb + MISC_OFF) & 1;
  const uint32_t* Mb = S->M + tb2 * 8 * 256 + 2 * tid;
  mbar_wait(BAR(B_F1 + NSAT), 1);
  float m1, s1, s2;
#pragma unroll 1
  for (int it = 0; it < SPIN; it++) {
    uint32_t a[8], miss = 0;
    uint2 v[8];
#pragma unroll
    for (int i = 0; i < 8; i++) { a[i] = ld_rlx(Mb + i * 256); v[i] = ld_rlx2((const uint2*)(Mb + (16 * 8 + i) * 256)); }
#pragma unroll
    for (int i = 0; i < 8; i++) miss |= (a[i] ^ tag) | (v[i].x ^ tag) | (v[i].y ^ tag);
#define SUM8(F) ((untag(F(0)) + untag(F(1))) + (untag(F(2)) + untag(F(3)))) + ((untag(F(4)) + untag(F(5))) + (untag(F(6)) + untag(F(7))))
#define FA(i) a[i]
#define FX(i) v[i].x
#define FY(i) v[i].y
    m1 = SUM8(FA); s1 = SUM8(FX); s2 = SUM8(FY);
    if (!__any_sync(0xffffffff, miss & 1)) break;
  }
  const float mean = s1 * (1.f / DM), rs = frsqrt(fmaxf(s2 * (1.f / DM) - mean * mean, 0.f) + 1e-5f);
  uint2* sp = S->S + SEQ + 128 * tb2 + 8 * (tid & 14) + 2 * (tid >> 4) + (tid & 1);
  st_rlx2(sp, tagf(rs, tag), tagf(-mean * rs, tag));
  st_rlx2(sp + SEQ, tagf(rs, tag), tagf(-(mean + m1 * (1.f / DM)) * rs, tag));
}
template <int I0, int I1> __device__ __forceinline__ void init_barriers(uint32_t bars) {
#pragma unroll
  for (int i = I0; i < I1; i++) mbar_init(BAR(i), bar_count(i));
}
__device__ __forceinline__ int g2_cb(int kp) { return kp < 5 ? 2 * kp : 2 * kp - 9; }
__device__ __forceinline__ const unsigned* h_flag(Scratch* S, int ly, int tb2, int lane) {
  const int s0 = 128 * min(tb2, 15) / 160;
  const bool two = (128 * tb2 + 127) / 160 != s0;
  return &S->flag[(F_H + (ly * 13 + s0) * 10 + min(lane & 15, 9) + (two && lane >= 16 ? 10 : 0)) * 32];
}
__device__ __forceinline__ void gate_tile(const Params& P, uint32_t dst, uint32_t bar, int tb2, int db) {
  mbar_expect_tx(bar, 20480);
  tma2d(dst, &P.mGT, tb2 * 128, db * 80, bar);
  tma2d(dst + 10240, &P.mGT, tb2 * 128 + 64, db * 80, bar);
}
__global__ void __cluster_dims__() __launch_bounds__(512, 1) fused_kernel(const Head H, const __grid_constant__ Params P) {
  extern __shared__ __align__(1024) uint8_t smem[];
  const uint32_t sb = opaque(smem_u32(smem)), bars = sb + BAR_OFF;
  const int wi = __shfl_sync(0xffffffff, threadIdx.x >> 5, 0), wg = wi >> 2, tid = threadIdx.x & 127;
  const int umap = blockIdx.x >= 96;
#define CLK(v)
  CLK(c_a);
  if (wi == 14) {
    if (elect_one()) { init_barriers<0, NBAR1>(bars); asm volatile("fence.mbarrier_init.release.cluster;" ::: "memory"); }
    __syncwarp();
  } else if (wi >= 12) prefetch_map(wi == 12 ? &P.mB : &P.mA[umap]);
  else if (wg == 2) xb_prefetch<1>(H, blockIdx.x + H.base, tid, 0);
  else if (P.role[blockIdx.x].w) return;
  CLK(c_b);
  asm volatile("barrier.cluster.arrive.relaxed.aligned;" ::: "memory");
  CLK(c_c);
  Role R;
  { const uint4 r = P.role[blockIdx.x]; R.v = r.x; R.c = r.y; R.p = r.z; }
  const int id = R.c & 255;
  const int tb = R.tb(), cb = R.cb(), b = R.b(), tb2 = b >> 3, db = b & 7, rank = R.rank();
  const bool has1 = tb <= 12, has2 = b < 128, full = tb < 12;
  Scratch* const S = H.s;
  unsigned* const epoch_p = &S->epoch[id * 8];
  const long long t_start = 0;
  if (wg < 2) {
    if (threadIdx.x == 0) PROF(50);
    asm volatile("griddepcontrol.launch_dependents;");
    bar_sync(6, 448);
    asm volatile("setmaxnreg.inc.sync.aligned.u32 176;");
    float xr[40];
#pragma unroll
    for (int i = 0; i < 40; i++) xr[i] = 0.f;
#pragma unroll 1
    for (int ly = 0; ly < 2; ly++) {
      if (has1) g1_phase(ly, H, sb, wg, tid, R, xr, t_start);
      if (ly == 0) {
        resid_init(xr); fence_regs(xr);
        conv_loop<false>(sb, R.c, wg, tid, t_start);
        if (tid == 0 && wg == 0) PROF(9);
      }
      if (has2) g2_phase(ly, P, S, sb, wg, tid, R, xr, t_start);
    }
    if (tid == 0 && wg == 0) st_rlx(epoch_p, lds32(sb + MISC_OFF));
  } else if (wg == 2) {
    bar_sync(6, 448);
    if (has1) aux_prep(H, P, sb, R, tid, t_start);
    asm volatile("setmaxnreg.inc.sync.aligned.u32 136;");
    conv_loop<true>(sb, R.c, wg, tid, t_start);
    if (tid == 0) PROF(44);
    {
      const uint32_t bb = (P.role[blockIdx.x].x >> 8) & 255;
      if ((bb & 132) == NSDB && tid < 32) next_stats(H.s, sb, bb >> 3, 32 * (bb & 3) + tid);
    }
  } else {
    if (threadIdx.x == 384) PROF(354);
    asm volatile("setmaxnreg.dec.sync.aligned.u32 24;");
    const int wlo = R.wlo(), whi = R.whi();
    const uint32_t wmask = R.wmask(), umask = R.umask(), f1bytes = full ? 36864 : 32768;
    if (wi < 14) {
      if (threadIdx.x == 384) PROF(340);
      asm volatile("barrier.cluster.wait.aligned;" ::: "memory");
      if (has1 && elect_one()) {
        uint64_t tab = wi == 12 ? WTAB0 : XTAB0;
        PROF(329 + wi);
#pragma unroll 1
        for (int kb = 0; kb < 6; kb++, tab >>= 6) {
          const uint32_t dst = sb + ((uint32_t)tab & 63) * 4096;
          if (wi == 12) {
#pragma unroll 1
            for (int h = wlo; h <= whi; h++) tma4d_mc(dst + h * 8192, &P.mB, kb * 64, 0, 0, 8 * cb + 4 * h, BAR(B_F1 + kb), wmask);
          } else {
            tma4d_mc(dst + R.uj() * 1024, &P.mA[umap], kb * 64, 0, 0, 80 * tb + R.uj(), BAR(B_F1 + kb), umask);
            mbar_expect_tx(BAR(B_F1 + kb), f1bytes);
          }
        }
      }
      if (!has1 && wi == 13) bar_sync(7, 64);
    } else {
      if (wi == 15 && elect_one()) { init_barriers<NBAR1, NBAR>(bars); asm volatile("fence.mbarrier_init.release.cluster;" ::: "memory"); }
      bar_sync(6, 448);
      if (!has1 && wi == 14) bar_sync(7, 64);
    }
    const unsigned e1 = ld_rlx(epoch_p) + 1;
    if (wi == 12) {
      if (elect_one()) {
#pragma unroll 1
        for (int ly = 0; ly < 2; ly++) {
#pragma unroll 1
          for (int i = ly ? 0 : 6; i < 10 && has1; i++) {
            const int kb = (0x9876541032ull >> (4 * i)) & 15;
            if (ly == 0) { mbar_wait(BAR(B_E1 + ((DEP0 >> (4 * kb - 24)) & 15))); mbar_wait(BAR(B_AX + (kb == 9))); }
            else {
              if (has2 && i == (db >= GLATE ? 4 : 2)) {
                wait_cnt(&S->cnt[(C_G + db) * 32], e1 * 80);
                mbar_wait(BAR(B_E2 + 7));
                PROF(47);
                gate_tile(P, sb + G_OFF0, BAR(B_GF), tb2, db);
              }
              if (has2) mbar_wait(BAR(i < 4 ? B_E2 + ((0x9865u >> (4 * i)) & 15) : B_GE));
              else if (i == 0) { mbar_wait(BAR(B_E1 + 9)); mbar_wait(BAR(B_CD + 1)); }
              if (i >= 4) mbar_wait(BAR(i < 6 ? B_F1 + W4AT : B_E1 + i - 6), 1);
            }
            const uint32_t dst = sb + ((uint32_t)((ly ? WTAB1 : WTAB0) >> (6 * kb)) & 63) * 4096;
#pragma unroll 1
            for (int h = wlo; h <= whi; h++) tma4d_mc(dst + h * 8192, &P.mB, kb * 64, 0, 0, 8 * cb + 4 * h, BAR(B_F1 + kb), wmask);
          }
          if (has2) {
            if (ly == 0) {
              mbar_wait(BAR(B_E1 + XRAT));
              mbar_expect_tx(BAR(B_XR), 20480 + 160 + 1024);
              tma4d(sb + XR_OFF, &P.mX, 80 * db, tb2, BAR(B_XR));
              bulk_g2s(sb + XR_OFF + 20480, P.dskip + 80 * db, 160, BAR(B_XR));
              bulk_g2s(sb + XR_OFF + 20480 + 256, S->S + 128 * tb2, 1024, BAR(B_XR));
              if (CWAIT) mbar_wait(BAR(CWAIT == 1 ? B_KF + 2 : CWAIT == 2 ? B_KF + R.nch() - 1 : CWAIT == 3 ? B_KF + R.nch() - 2 : B_HD));
            }
#pragma unroll 1
            for (int kp = 0; kp < 10; kp++) {
              const uint32_t dst = sb + (kp < 5 ? kp : kp - 5) * 20480;
              mbar_wait(BAR(kp >= 5 ? B_E2 + kp - 5 : ly ? B_E1 + ((CTAB1 >> (4 * kp)) & 15) : kp < 3 ? B_SH : kp < 4 ? B_HD : B_CD), ly);
              mbar_expect_tx(BAR(B_F2 + kp), 10240 + 16384);
              tma5d(dst, &P.mC[0], g2_cb(kp) * 64, db * 5, BAR(B_F2 + kp));
              mbar_expect_tx(BAR(B_F3 + kp), 10240 + 16384);
              tma5d(dst + 10240, &P.mC[1], g2_cb(kp) * 64, db * 5, BAR(B_F3 + kp));
              if (ly && kp == 4) { mbar_wait(BAR(B_E1 + 9), 1); gate_tile(P, sb + G_OFF1, BAR(B_GF), tb2, db); }
            }
          }
        }
      }
    } else if (wi == 13) {
      const int h0 = R.cs() == 8 ? rank : 4 * rank;
#pragma unroll 1
      for (int ly = 0; ly < 2; ly++) {
        int lane = lane_id();
        if (has1) {
          const unsigned* fp = &S->flag[(F_U3 + 8 * ((160 * tb) >> 7) + (lane & (full ? 15 : 7))) * 32];
          uint32_t ready = ly ? __ballot_sync(0xffffffff, ld_rlx(fp) == e1) : ~0u;
          if (ly) mbar_wait(BAR(XEARLY && full ? B_KF + 1 : has2 ? B_SG : B_RF1), XEARLY && full);
          if (PWG && XEARLY && ly && full) mbar_wait(BAR(B_KF + 2), 1);
#pragma unroll 1
          for (int kb = ly ? 0 : 6; kb < 10; kb++) {
            if (ly && kb == UPAT) { mbar_wait(BAR(B_XR)); ready = ~0u; }
            wait_flags(fp, e1, 0x101u * ((1u << (64 * kb / 80)) | (1u << ((64 * kb + 63) / 80))), ready);
            if (kb >= 4) mbar_wait(BAR(B_E1 + (ly ? kb - 4 : (DEP0 >> (4 * kb - 24)) & 15)), ly);
            mbar_wait(BAR(B_AX + (kb == 9)));
            if (elect_one()) {
              if (ly && kb == 0) PROF(34);
              tma4d_mc(sb + ((uint32_t)((ly ? XTAB1 : XTAB0) >> (6 * kb)) & 63) * 4096 + R.uj() * 1024, &P.mA[2 * ly + umap], kb * 64, 0, 0, 80 * tb + R.uj(),
                       BAR(B_F1 + kb), umask);
              mbar_expect_tx(BAR(B_F1 + kb), f1bytes);
            }
            __syncwarp();
          }
        }
        if (ly == 0) {
          if (has1) mbar_wait(BAR(B_E1 + KPF));
          if (elect_one()) {
#pragma unroll 1
            for (int s = 0; s < R.nch(); s++) prefetch_l2(P.ssmk + (size_t)R.ch(s) * SEQ, 4096);
          }
          lane = lane_id();
#pragma unroll
          for (int s = 0; s < 5; s++) {
            asm volatile("st.shared.v4.u32 [%0],{%1,%1,%1,%1};" ::"r"(conv_buf(sb, s) + 16 * lane), "r"(0) : "memory");
            asm volatile("st.shared.u8 [%0],%1;" ::"r"(conv_buf(sb, s) + KC_OFS + lane), "r"(0) : "memory");
          }
          fence_async();
          __syncwarp();
          const unsigned* cp = &S->cnt[(C_KV + (R.ch(min(lane, R.nch() - 1)) >> 6)) * 32];
          uint32_t ready = 0;
#pragma unroll 1
          for (int s = 0, sk = 0; s < R.nch(); s++) {
#pragma unroll 1
            for (; sk < (s ? R.nch() : KUP); sk++)
              if (elect_one()) { mbar_expect_tx(BAR(B_KF + sk), 8192); bulk_g2s(conv_buf(sb, sk) + KC_OFS + 32, P.ssmk + (size_t)R.ch(sk) * SEQ, 4096, BAR(B_KF + sk)); }
            PROFC(s == 0, 329);
#pragma unroll 1
            for (int it = 0; !((ready >> s) & 1) && it < SPIN; it++) ready = __ballot_sync(0xffffffff, (int)(ld_rlx(cp) - e1 * 32) >= 0);
            PROFC(s == 0, 30);
            if (elect_one()) {
              bulk_g2s(conv_buf(sb, s) + KV_PAD, S->kv + (size_t)R.ch(s) * SEQ, 4096, BAR(B_KF + s));
              if (s == 0 && has2) { prefetch_l2(P.cre + (size_t)5 * b * DM, 5 * DM * 2); prefetch_l2(P.cim + (size_t)5 * b * DM, 5 * DM * 2); }
            }
            __syncwarp();
          }
          PROF(31);
          if (!has1) return;
        }
        lane = lane_id();
        const unsigned* fp = h_flag(S, ly, tb2, lane);
        uint32_t ready = __ballot_sync(0xffffffff, ld_rlx(fp) == e1), st = 0;
        if (ly == 0 && !has2) {
          mbar_wait(BAR(B_HD));
          if (lane < 8) mbar_arrive_cl(BAR(B_RF1), lane & 1);
        }
        if (has2) {
          mbar_wait(BAR(B_RF0), ly);
#pragma unroll 1
          for (int kp = 0; kp < 10; kp++) {
            if (kp == 5) { mbar_wait(BAR(B_XR), 1); ready = ~0u; }
            if (kp == 2) { mbar_wait(BAR(B_HD), ly); if (lane < 8) mbar_arrive_cl(BAR(B_RF1), lane & (R.cs() - 1)); }
            wait_flags(fp, e1, 0x10001u << g2_cb(kp), ready);
            if (kp == 2) mbar_wait(BAR(B_RF1), ly);
#pragma unroll
            for (int hf = 0; hf < 2; hf++) {
              if (kp >= 3) { if (hf) mbar_wait(BAR(B_E2 + kp - 3), ly); else mbar_wait(BAR(B_EA + st), ly ^ (kp >= 6 && kp < 9)); }
              if (elect_one()) {
                if (kp == 0 && !hf) PROF(33 + 2 * ly);
                tma4d_mc(sb + H_OFF + st * 32768 + hf * 16384 + h0 * 2048, &P.mH, g2_cb(kp) * 128 + hf * 64, 0, 2 * h0,
                         ly * 16 + tb2, BAR((hf ? B_F3 : B_F2) + kp), (1u << R.cs()) - 1);
              }
              __syncwarp();
            }
            st = st == 2 ? 0 : st + 1;
          }
        }
      }
    } else if (wi == 14) {
      if (!has1) return;
      prefetch_if(P.dskip + 64 * (tid & 31), (tid & 31) < 10);
      if (elect_one()) { prefetch_map(&P.sK); prefetch_map(&P.mX); prefetch_map(&P.sH); prefetch_map(&P.sU); prefetch_map(&P.sO); prefetch_map(&P.mC[0]); prefetch_map(&P.mC[1]); prefetch_map(&P.mH); prefetch_map(&P.mGT); prefetch_map(&P.mA[2 + umap]); }
      __syncwarp();
#pragma unroll 1
      for (int ly = 0; ly < 2; ly++) {
        if (ly) {
          mbar_wait(BAR(B_F1 + 1), 1);
          uint32_t ready = 0;
          wait_flags(&S->flag[(F_U3 + 8 * ((160 * tb) >> 7) + ((lane_id() + ly) & (full ? 15 : 7))) * 32], e1, ~0u, ready);
          if (elect_one()) mbar_arrive(BAR(B_XR));
        }
        const int lane = lane_id();
        mbar_wait(BAR(B_E1 + (ly ? STAT_AT1 : STAT_AT)), ly);
        PROFC(lane == 0 && ly == 0, 36);
        {
          const int l = lane - (full ? 0 : 16);
          const uint2* p = S->S + ly * SEQ + 160 * tb + 2 * l;
          uint4 v[3];
#pragma unroll 1
          for (int it = 0; it < SPIN; it++) {
            v[0] = ld_rlx4(p); v[1] = ld_rlx4(p + 64); v[2] = ld_rlx4(p + 96);
            const bool miss = __any_sync(0xffffffff, untagged(v[0], e1 & 1) | untagged(v[1], e1 & 1) | untagged(v[2], e1 & 1));
            PROFC(lane == 0 && ly == 0 && it == 0, 37);
            if (!miss) break;
          }
          PROFC(lane == 0 && ly == 0, 38);
#pragma unroll
          for (int i = 0; i < 3; i++) {
            const int pr = l + (i == 2 ? 48 : 32 * i);
            if (pr >= 0) asm volatile("st.shared.v4.u32 [%0],{%1,%2,%3,%4};" ::"r"(sb + SSM_OFF + 16 * (pr + ((pr * (full ? 205 : 256)) >> 12))), "r"(v[i].x & ~1u),
                                      "r"(v[i].y & ~1u), "r"(v[i].z & ~1u), "r"(v[i].w & ~1u) : "memory");
          }
          __syncwarp();
        }
        if (lane == 0) mbar_arrive(BAR(B_ST));
        if (ly && has2) {
          mbar_wait(BAR(B_E1 + 9), 1);
          if (lane < 8) mbar_arrive_cl(BAR(B_RF0), lane & (R.cs() - 1));
        }
        if (lane == 0) {
#pragma unroll 1
          for (int pc = 0; pc < (full ? 5 : 4); pc++) {
            if ((HWM >> (4 * pc)) & 8) {
              mbar_wait(BAR(B_SH + min((HWM >> (4 * pc)) & 7, full ? 4 : 3)), ly);
              PROF(380 + 5 * ly + pc);
              if (pc == 0 && (cb & 1)) delay(ly ? HDLY : HDLY0);
              fence_async();
            }
#pragma unroll
            for (int i = 0; i < 2; i++) tma4d_store(&P.sH, sb + (pc < 4 ? R_OFF + i * 16384 + pc * 4096 : (ly ? R4_OFF1 : R4_OFF0) + i * 4096), 128 * cb + 64 * i, 0, 0, ly * 1024 + 80 * tb + 4 * pc);
          }
          bulk_commit(); bulk_wait();
          PROF(ly ? 17 : 16);
          mbar_arrive(BAR(B_HD));
          release<1>();
          signal_flag(&S->flag[(F_H + (ly * 13 + tb) * 10 + cb) * 32], e1);
          PROF(ly ? 24 : 8);
        }
        __syncwarp();
        if (has2) {
          mbar_wait(BAR(B_F2 + FPAT), ly);
          uint32_t ready = 0;
          wait_flags(h_flag(S, ly, tb2, lane_id() | 1), e1, ~0u, ready);
          if (elect_one()) mbar_arrive(BAR(B_XR));
        }
        if (lane == 0 && has2 && !(ODIR && ly)) {
          mbar_wait(BAR(B_SG), ly);
          if (!(ly ? ODIR : UDIR)) {
          fence_async();
          tma4d_store(ly ? &P.sO : &P.sU, sb + (ly ? OS_OFF : US_OFF), 80 * db, 0, 0, tb2);
          bulk_commit(); bulk_wait();
          }
          if (ly == 0) { PROF(18); mbar_arrive(BAR(B_GE)); mbar_arrive_cl(BAR(B_GE), R.wpart()); release<2>(); signal_flag(&S->flag[(F_U3 + b) * 32], e1); }
          PROF(ly ? 29 : 14);
        }
        __syncwarp();
      }
    } else {
      discretise(H, P, sb, R, tid & 31, e1);
      if (elect_one()) {
        mbar_arrive(BAR(B_LM));
        PROF(348);
        if (b < R.nprep()) {
#pragma unroll 1
          for (int task = b, r = 0; task < 320; task += R.nprep(), r++) {
            mbar_wait(BAR(B_PS + r));
            PROF(320 + 3 * r);
            fence_async();
            tma2d_store(&P.sK, sb + KS_OFF + r * 8192, 64 * (task & 31), 64 * (task >> 5));
            bulk_commit(); bulk_wait();
            PROF(321 + 3 * r);
            release<4>();
            signal_cnt(&S->cnt[(C_KV + (task >> 5)) * 32], 1);
            PROF(322 + 3 * r);
          }
          PROF(41);
        }
        if (has2) {
          mbar_wait(BAR(B_SH));
#pragma unroll 1
          for (int i = 0; i < 8; i++) mbar_arrive_cl(BAR(B_RF0), i & (R.cs() - 1));
        }
#pragma unroll 1
        for (int s = 0, s0 = 0; s < R.nch(); s++) {
          mbar_wait(BAR(B_GS + s));
          fence_async();
          bulk_s2g(S->gt + (size_t)R.ch(s) * SEQ, conv_buf(sb, s) + KC_OFS, 4096); bulk_commit();
          if (s == 1 || s >= R.nch() - GSPL) bulk_wait();
          if (s == 1 || s == R.nch() - 1) mbar_arrive(BAR(B_CD + (s > 1)));
          if (s >= R.nch() - GSPL) {
            PROF(45);
            release<8>();
#pragma unroll 1
            for (; s0 <= s; s0++) signal_cnt(&S->cnt[(C_G + R.ch(s0) / 80) * 32], 1);
          }
        }
        PROF(46);
      }
    }
  }
}

typedef CUresult (*EncFn)(CUtensorMap*, CUtensorMapDataType, cuuint32_t, void*, const cuuint64_t*, const cuuint64_t*, const cuuint32_t*,
                          const cuuint32_t*, CUtensorMapInterleave, CUtensorMapSwizzle, CUtensorMapL2promotion, CUtensorMapFloatOOBfill);
bool enc(EncFn f, CUtensorMap* m, const void* base, int rank, const cuuint64_t* dims, const cuuint64_t* strides, const cuuint32_t* box, bool swz,
         bool f32 = false) {
  const cuuint32_t es[5] = {1, 1, 1, 1, 1};
  return f(m, f32 ? CU_TENSOR_MAP_DATA_TYPE_FLOAT32 : CU_TENSOR_MAP_DATA_TYPE_BFLOAT16, rank, const_cast<void*>(base), dims, strides, box, es,
           CU_TENSOR_MAP_INTERLEAVE_NONE, swz ? CU_TENSOR_MAP_SWIZZLE_128B : CU_TENSOR_MAP_SWIZZLE_NONE, CU_TENSOR_MAP_L2_PROMOTION_L2_256B,
           CU_TENSOR_MAP_FLOAT_OOB_FILL_NONE) == CUDA_SUCCESS;
}
void make_roles(Params& P, bool big) {
  for (uint32_t bx = 0; bx < (big ? 120u : 12u); bx++) {
    const uint32_t c = bx >> 3, r = bx & 7, id = big ? bx : 120 + bx;
    const uint32_t vA = c < 12 ? (2 * (c >> 1) + (r >> 2)) | (4 * (c & 1) + (r & 3)) << 4 | (r & 4) << 16 | 4 << 19 | (r ^ 4) << 22
                               : (4 * (c - 12) + (r >> 1)) | (8 + (r & 1)) << 4 | (r & 6) << 16 | 2 << 19 | (r ^ 2) << 22;
    const uint32_t vB = (bx < 10 ? 12 : 13) | bx << 4 | 2 << 19 | (bx & 1) << 22 | (bx & 1) << 26;
    P.role[bx].x = (big ? vA | r << 26 | 1u << 29 : vB) | (id < 128 ? (id & ~7u) | (r >> 1) | (r & 1) << 2 : id) << 8;
    P.role[bx].y = id | (big ? 5 : bx < 8 ? 3 : 4) << 10 | 120 << 13 | 132 << 21 | (big ? 4u : 3u) << 29;
    const uint32_t v = P.role[bx].x, cb = (v >> 4) & 15, rank = (v >> 26) & 7, ubase = (v >> 16) & 7, ugs = (v >> 19) & 7, wp = (v >> 22) & 7;
    const uint32_t wlo = rank > wp, whi = wp != rank ? wlo : 1, wmask = 1u << rank | 1u << wp;
    const uint32_t uj = (rank - ubase) * (!big ? 8 : ugs == 4 ? 5 : 10), sm = big ? (0x7296418530ull >> (4 * cb)) & 15 : bx < 8 ? 4 * (bx & 1) + (bx >> 1) : 15;
    P.role[bx].z = wlo | whi << 1 | wmask << 2 | ((1u << ugs) - 1) << (10 + ubase) | uj << 20 | sm << 25;
    P.role[bx].w = 0;
  }
}
void launch(const Head& H, const Params& P, int grid, int cs, bool dependent) {
  cudaLaunchConfig_t cfg = {};
  cfg.gridDim = grid; cfg.blockDim = 512; cfg.dynamicSmemBytes = SMEM_BYTES; cfg.stream = cudaStreamPerThread;
  cudaLaunchAttribute at[2];
  at[0].id = cudaLaunchAttributeClusterDimension; at[0].val.clusterDim.x = cs; at[0].val.clusterDim.y = 1; at[0].val.clusterDim.z = 1;
  at[1].id = cudaLaunchAttributeProgrammaticStreamSerialization; at[1].val.programmaticStreamSerializationAllowed = 1;
  cfg.attrs = at; cfg.numAttrs = dependent ? 2 : 1;
  cudaLaunchKernelEx(&cfg, fused_kernel, H, P);
}

}

extern "C" void kernel_launch(void* const* d_in, const int* in_sizes, int n_in, void* d_out, int out_size) {
  (void)in_sizes; (void)n_in; (void)out_size;
  typedef const __nv_bfloat16* cb;
  void* fp = nullptr; cudaDriverEntryPointQueryResult qr;
  cudaGetDriverEntryPoint("cuTensorMapEncodeTiled", &fp, cudaEnableDefault, &qr);
  EncFn f = (EncFn)fp;
  Scratch* sp = nullptr;
  cudaGetSymbolAddress((void**)&sp, g_scr);
  void *pu = sp->u, *ph = sp->h, *pgt = sp->gt;
  Params P;
  Head H;
  H.s = sp; H.x = (cb)d_in[0]; H.swap = (uintptr_t)d_in[4] < (uintptr_t)d_in[3] ? 0 : 0x80000000u; H.b0 = (cb)d_in[H.swap ? 3 : 4]; H.b1 = (cb)d_in[H.swap ? 4 : 3];
  for (int i = 0; i < 2; i++) {
    const cuuint64_t d[4] = {640, 8, 2, 80}, s[3] = {1280, (cuuint64_t)((uintptr_t)H.b1 - (uintptr_t)H.b0), 8 * 1280}; const cuuint32_t bx[4] = {64, 8, 2, 4};
    if (enc(f, &P.mB, H.b0, 4, d, s, bx, true)) break;
    cudaMemcpyAsync(sp->bcopy, H.b0, DM * DM * 2, cudaMemcpyDeviceToDevice, cudaStreamPerThread);
    cudaMemcpyAsync(sp->bcopy + DM * DM, H.b1, DM * DM * 2, cudaMemcpyDeviceToDevice, cudaStreamPerThread);
    H.b0 = sp->bcopy; H.b1 = sp->bcopy + DM * DM;
  }
  {
    const cuuint64_t d[5] = {640, 2, 4, 2, 40}, s[4] = {1280, 4 * 1280, 2 * 1280, 16 * 1280}; const cuuint32_t bx[5] = {64, 2, 4, 2, 5};
    enc(f, &P.mC[0], d_in[5], 5, d, s, bx, true); enc(f, &P.mC[1], d_in[6], 5, d, s, bx, true); }
  { const cuuint64_t d[2] = {2048, 640}, s[1] = {4096}; const cuuint32_t bx[2] = {64, 80}; enc(f, &P.mGT, pgt, 2, d, s, bx, true); }
  { const cuuint64_t d[4] = {640, 8, 16, 16}, s[3] = {16 * 1280, 1280, 128 * 1280}, so[3] = {16 * 2560, 2560, 128 * 2560}; const cuuint32_t bx[4] = {80, 8, 16, 1};
    enc(f, &P.sU, pu, 4, d, s, bx, false); enc(f, &P.mX, d_in[0], 4, d, s, bx, false); enc(f, &P.sO, d_out, 4, d, so, bx, false, true); }
  { const cuuint64_t d[2] = {2048, 640}, s[1] = {4096}; const cuuint32_t bx[2] = {64, 64}; enc(f, &P.sK, sp->kv, 2, d, s, bx, true); }
  P.lre = (cb)d_in[1]; P.lim = (cb)d_in[2]; P.cre = (cb)d_in[5]; P.cim = (cb)d_in[6]; P.ldt = (cb)d_in[7]; P.dskip = (cb)d_in[8];
  P.out = (float*)d_out;
  P.k = (cb)d_in[10]; P.v = (cb)d_in[11]; P.shk = (cb)d_in[12]; P.ssmk = (cb)d_in[13]; P.ssmd = (cb)d_in[14];
  cudaFuncSetAttribute(fused_kernel, cudaFuncAttributeMaxDynamicSharedMemorySize, SMEM_BYTES);
  for (int big = 1; big >= 0; big--) {
    const cuuint64_t seg = big ? 40 : 32;
    for (int i = 0; i < 4; i++) {
      const cuuint64_t d[4] = {640, 2, 4, 1024}, s[3] = {1280, seg * 1280, 2 * 1280}; const cuuint32_t bx[4] = {64, 2, 4, !big ? 8u : (i & 1) ? 10u : 5u};
      enc(f, &P.mA[i], i < 2 ? d_in[0] : pu, 4, d, s, bx, true);
    }
    {
      const cuuint64_t d[4] = {1280, 8, 16, 32}, s[3] = {16 * 2560, 2560, 128 * 2560}; const cuuint32_t bx[4] = {64, 8, big ? 2u : 8u, 1};
      enc(f, &P.mH, ph, 4, d, s, bx, true); }
    { const cuuint64_t d[4] = {1280, 2, 4, 2048}, s[3] = {2560, seg * 2560, 2 * 2560}; const cuuint32_t bx[4] = {64, 2, 4, 4};
      enc(f, &P.sH, ph, 4, d, s, bx, true); }
    make_roles(P, big);
    H.base = big ? 0 : 120;
    launch(H, P, big ? 120 : 12, big ? 8 : 2, !big);
  }
}
```

```cpp
#include <cuda_runtime.h>
#include <cuda.h>
#include <cuda_bf16.h>
#include <stdint.h>

namespace {

constexpr int SEQ = 2048, DM = 640;
constexpr int SPIN = 1 << 20;
#define PFAT 99
#define KVDLY 500
#define PFD 1
#define XPFAT 9
#define STAT_AT 6
#define KPFAT 3
#define KPFAT2 5
#define KPF 7
#define HDLY 1900
#define GSPL 2
#define CWAIT 0
#define HDLY0 1900
#define CTAB1 0x96543u
#define NSAT 0
#define SKW 1
#define RIAT 2
#define MIAT 5
#define FPAT 1
#define UPAT 7
#define STAT_AT1 4
#define W4AT 0
#define MBAR 1
#define STG 17
#define STG0 17
#define HWM 0xc09
#define NSDB 4
#define GLATE 6
#define KUP 1
#define XRAT 9
#define ORD 1

struct Scratch {
  uint2 E[2 * 13 * 10 * 8 * 16];
  uint32_t M[3 * 16 * 8 * 256];
  uint2 S[3 * SEQ];
  uint2 RS[80 * 16];
  unsigned flag[512 * 32];
  unsigned cnt[32 * 32];
  unsigned epoch[132 * 8];
  unsigned zero[128];
  unsigned prof[132 * 512];
  __align__(1024)
  __nv_bfloat16 u[SEQ * DM];
  __nv_bfloat16 h[2 * SEQ * 1280];
  __nv_bfloat16 kv[DM * SEQ];
  __nv_bfloat16 gt[DM * SEQ];
  __nv_bfloat16 bcopy[2 * DM * DM];
};
__device__ __align__(1024) Scratch g_scr;
#define PROFC(c, i) do {} while (0)
#define PSEL 1
#define PROF(i) do {} while (0)

constexpr int C_KV = 0, C_G = 10;
constexpr int F_U3 = 0, F_H = 128;

constexpr int R_OFF = 196608, R4_OFF0 = 73728, R4_OFF1 = 122880, H_OFF = 131072, KS_OFF = 131072, CV_OFF = 86272, G_OFF0 = 40960, G_OFF1 = 102400, US_OFF = 98304, XR_OFF = 163840, MX_OFF = 32768;
constexpr int LAM_OFF = 229376, SSM_OFF = LAM_OFF + 1024, BAR_OFF = SSM_OFF + 1344;
constexpr int B_F1 = 0, B_E1 = 10, B_RF0 = 20, B_RF1 = 21, NBAR1 = 22;
constexpr int B_F2 = 22, B_KF = 32, B_GF = 37, B_CD = 38, B_XR = 40, B_ST = 41, B_HD = 42, B_LM = 43, B_E2 = 44, B_GS = 54, B_PS = 59, B_AX = 62, B_SH = 64, B_SG = 69, B_GE = 70, B_EA = 71, B_F3 = 74, NBAR = 84;
__host__ __device__ constexpr int bar_count(int i) { return i < B_E1 ? 1 : i < B_RF0 ? 9 : i < B_F2 ? 8 : i < B_E2 ? 1 : i < B_GS ? 12 : i < B_SH ? 4 : i < B_GE ? 8 : i < B_EA ? 2 : i < B_F3 ? 8 : 1; }
constexpr int MISC_OFF = BAR_OFF + NBAR * 8, SMEM_BYTES = MISC_OFF + 32;
constexpr int KV_PAD = 512, KC_OFS = KV_PAD + 4096, CH_STRIDE = 8960;
__device__ __forceinline__ uint32_t conv_buf(uint32_t sb, int slot) { return sb + CV_OFF + slot * CH_STRIDE; }
constexpr uint64_t tab6(int a, int b, int c, int d, int e, int f, int g, int h, int i, int j) {
  return (uint64_t)a | (uint64_t)b << 6 | (uint64_t)c << 12 | (uint64_t)d << 18 | (uint64_t)e << 24 | (uint64_t)f << 30 | (uint64_t)g << 36 | (uint64_t)h << 42 |
         (uint64_t)i << 48 | (uint64_t)j << 54;
}
constexpr uint64_t WTAB0 = tab6(0, 4, 8, 30, 12, 26, 0, 4, 8, 12), XTAB0 = tab6(40, 45, 50, 34, 16, 21, 40, 45, 50, 16);
constexpr uint64_t WTAB1 = tab6(16, 20, 0, 4, 8, 12, 16, 20, 24, 28), XTAB1 = tab6(40, 45, 50, 32, 40, 45, 50, 32, 40, 45);
constexpr uint32_t DEP0 = 0x4210;

struct Head {
  Scratch* s;
  const __nv_bfloat16 *x, *b0, *b1;
  uint32_t base, swap;
};
struct Params {
  const __nv_bfloat16 *lre, *lim, *ldt, *k, *v, *shk, *cre, *cim, *ssmk, *ssmd, *dskip;
  float* out;
  uint4 role[120];
  CUtensorMap mB, mA[4], mH, mC[2], mGT, mX, sH, sU, sK;
};

__device__ __forceinline__ uint32_t smem_u32(const void* p) { return (uint32_t)__cvta_generic_to_shared(p); }
__device__ __forceinline__ uint32_t opaque(uint32_t x) { uint32_t y; asm volatile("mov.u32 %0, %1;" : "=r"(y) : "r"(x)); return y; }
__device__ __forceinline__ int lane_id() { int y; asm volatile("mov.u32 %0, %%laneid;" : "=r"(y)); return y; }
__device__ __forceinline__ void delay(uint32_t n) {
  asm volatile("{ .reg .pred p; .reg .u32 a, b; mov.u32 a, %%clock; L: mov.u32 b, %%clock; sub.u32 b, b, a; setp.lt.u32 p, b, %0; @p bra.uni L; }" ::"r"(n) : "memory");
}
__device__ __forceinline__ void mbar_init(uint32_t bar, uint32_t cnt) { asm volatile("mbarrier.init.shared::cta.b64 [%0], %1;" ::"r"(bar), "r"(cnt) : "memory"); }
__device__ __forceinline__ void mbar_expect_tx(uint32_t bar, uint32_t bytes) { asm volatile("mbarrier.arrive.expect_tx.shared::cta.b64 _, [%0], %1;" ::"r"(bar), "r"(bytes) : "memory"); }
__device__ __forceinline__ void mbar_arrive(uint32_t bar) { asm volatile("mbarrier.arrive.shared::cta.b64 _, [%0];" ::"r"(bar) : "memory"); }
__device__ __forceinline__ void mbar_arrive_if(uint32_t bar, bool c) {
  asm volatile("{ .reg .pred p; setp.ne.u32 p, %1, 0; @p mbarrier.arrive.shared::cta.b64 _, [%0]; }" ::"r"(bar), "r"((uint32_t)c) : "memory");
}
__device__ __forceinline__ void prefetch_if(const void* p, bool c) { asm volatile("{ .reg .pred p; setp.ne.u32 p, %1, 0; @p prefetch.global.L2 [%0]; }" ::"l"(p), "r"((uint32_t)c)); }
__device__ __forceinline__ void mbar_arrive_cl(uint32_t bar, uint32_t cta) {
  asm volatile("{ .reg .b32 ra; mapa.shared::cluster.u32 ra, %0, %1; mbarrier.arrive.shared::cluster.b64 _, [ra]; }" ::"r"(bar), "r"(cta) : "memory");
}
__device__ __forceinline__ uint32_t mapa(uint32_t a, uint32_t cta) { uint32_t r; asm("mapa.shared::cluster.u32 %0, %1, %2;" : "=r"(r) : "r"(a), "r"(cta)); return r; }
__device__ __forceinline__ void mbar_arrive_at(uint32_t ra) { asm volatile("mbarrier.arrive.shared::cluster.b64 _, [%0];" ::"r"(ra) : "memory"); }
__device__ __forceinline__ void mbar_wait(uint32_t bar, uint32_t parity = 0) {
  asm volatile("{ .reg .pred p; .reg .u32 c; mov.u32 c, 0;\n"
               "W: mbarrier.try_wait.parity.shared::cta.b64 p, [%0], %1; @p bra.uni D;\n"
               "add.u32 c, c, 1; setp.lt.u32 p, c, 0x100000; @p bra.uni W;\nD: }" ::"r"(bar), "r"(parity) : "memory");
}
__device__ __forceinline__ bool elect_one() { uint32_t p; asm volatile("{ .reg .pred P; elect.sync _|P, 0xffffffff; selp.u32 %0,1,0,P; }" : "=r"(p)); return p; }
__device__ __forceinline__ void bar_sync(int id, int n) { __syncwarp(); asm volatile("bar.sync %0, %1;" ::"r"(id), "r"(n) : "memory"); }
__device__ __forceinline__ void tma2d(uint32_t dst, const CUtensorMap* m, int c0, int c1, uint32_t bar) {
  asm volatile("cp.async.bulk.tensor.2d.shared::cluster.global.mbarrier::complete_tx::bytes [%0], [%1, {%3,%4}], [%2];"
               ::"r"(dst), "l"(m), "r"(bar), "r"(c0), "r"(c1) : "memory");
}
__device__ __forceinline__ void tma5d(uint32_t dst, const CUtensorMap* m, int c0, int c4, uint32_t bar) {
  asm volatile("cp.async.bulk.tensor.5d.shared::cluster.global.mbarrier::complete_tx::bytes [%0], [%1, {%3,%5,%5,%5,%4}], [%2];"
               ::"r"(dst), "l"(m), "r"(bar), "r"(c0), "r"(c4), "r"(0) : "memory");
}
__device__ __forceinline__ void tma4d(uint32_t dst, const CUtensorMap* m, int c0, int c3, uint32_t bar) {
  asm volatile("cp.async.bulk.tensor.4d.shared::cluster.global.mbarrier::complete_tx::bytes [%0], [%1, {%3,%5,%5,%4}], [%2];"
               ::"r"(dst), "l"(m), "r"(bar), "r"(c0), "r"(c3), "r"(0) : "memory");
}
__device__ __forceinline__ void tma4d_mc(uint32_t dst, const CUtensorMap* m, int c0, int c1, int c2, int c3, uint32_t bar, uint32_t mask) {
  asm volatile("cp.async.bulk.tensor.4d.shared::cluster.global.mbarrier::complete_tx::bytes.multicast::cluster [%0], [%1, {%3,%4,%5,%6}], [%2], %7;"
               ::"r"(dst), "l"(m), "r"(bar), "r"(c0), "r"(c1), "r"(c2), "r"(c3), "h"((uint16_t)mask) : "memory");
}
__device__ __forceinline__ void bulk_g2s(uint32_t dst, const void* src, uint32_t bytes, uint32_t bar) {
  asm volatile("cp.async.bulk.shared::cluster.global.mbarrier::complete_tx::bytes [%0], [%1], %2, [%3];" ::"r"(dst), "l"(src), "r"(bytes), "r"(bar) : "memory");
}
__device__ __forceinline__ void tma4d_store(const CUtensorMap* m, uint32_t src, int c0, int c1, int c2, int c3) {
  asm volatile("cp.async.bulk.tensor.4d.global.shared::cta.bulk_group [%0, {%2,%3,%4,%5}], [%1];" ::"l"(m), "r"(src), "r"(c0), "r"(c1), "r"(c2), "r"(c3) : "memory");
}
__device__ __forceinline__ void tma2d_store(const CUtensorMap* m, uint32_t src, int c0, int c1) {
  asm volatile("cp.async.bulk.tensor.2d.global.shared::cta.bulk_group [%0, {%2,%3}], [%1];" ::"l"(m), "r"(src), "r"(c0), "r"(c1) : "memory");
}
__device__ __forceinline__ void bulk_s2g(void* dst, uint32_t src, uint32_t bytes) {
  asm volatile("cp.async.bulk.global.shared::cta.bulk_group [%0], [%1], %2;" ::"l"(dst), "r"(src), "r"(bytes) : "memory");
}
__device__ __forceinline__ void bulk_commit() { asm volatile("cp.async.bulk.commit_group;" ::: "memory"); }
__device__ __forceinline__ void bulk_wait() { asm volatile("cp.async.bulk.wait_group 0;" ::: "memory"); }
__device__ __forceinline__ void fence_async() { asm volatile("fence.proxy.async.shared::cta;" ::: "memory"); }
__device__ __forceinline__ void prefetch_l2(const void* src, uint32_t bytes) { asm volatile("cp.async.bulk.prefetch.L2.global [%0], %1;" ::"l"(src), "r"(bytes) : "memory"); }
__device__ __forceinline__ void prefetch_map(const CUtensorMap* m) { asm volatile("prefetch.tensormap [%0];" ::"l"(m) : "memory"); }
__device__ __forceinline__ void wg_fence() { __syncwarp(); asm volatile("wgmma.fence.sync.aligned;" ::: "memory"); }
__device__ __forceinline__ void wg_commit() { asm volatile("wgmma.commit_group.sync.aligned;" ::: "memory"); }
template <int N> __device__ __forceinline__ void wg_wait() { asm volatile("wgmma.wait_group.sync.aligned %0;" ::"n"(N) : "memory"); }
template <int N> __device__ __forceinline__ void fence_regs(float (&d)[N]) {
#pragma unroll
  for (int i = 0; i < N; i++) asm volatile("" : "+f"(d[i])::"memory");
}
__device__ __forceinline__ uint64_t make_desc(uint32_t addr, uint32_t lbo, uint32_t sbo, uint32_t swz) {
  return (uint64_t)((addr & 0x3FFFF) >> 4) | ((uint64_t)(lbo >> 4) << 16) | ((uint64_t)(sbo >> 4) << 32) | ((uint64_t)swz << 62);
}
__device__ __forceinline__ uint32_t ldg1(const void* p) { uint32_t v; asm volatile("ld.global.nc.u32 %0,[%1];" : "=r"(v) : "l"(p)); return v; }
__device__ __forceinline__ uint32_t lds32(uint32_t a) { uint32_t v; asm volatile("ld.shared.u32 %0,[%1];" : "=r"(v) : "r"(a)); return v; }
__device__ __forceinline__ unsigned ld_rlx(const unsigned* p) { unsigned v; asm volatile("ld.relaxed.gpu.global.u32 %0,[%1];" : "=r"(v) : "l"(p) : "memory"); return v; }
__device__ __forceinline__ uint4 ld_rlx4(const void* p) {
  uint4 v; asm volatile("ld.relaxed.gpu.global.v4.u32 {%0,%1,%2,%3},[%4];" : "=r"(v.x), "=r"(v.y), "=r"(v.z), "=r"(v.w) : "l"(p) : "memory"); return v;
}
__device__ __forceinline__ uint2 ld_rlx2(const void* p) { uint2 v; asm volatile("ld.relaxed.gpu.global.v2.u32 {%0,%1},[%2];" : "=r"(v.x), "=r"(v.y) : "l"(p) : "memory"); return v; }
__device__ __forceinline__ void st_rlx2(void* p, uint32_t a, uint32_t b) { asm volatile("st.relaxed.gpu.global.v2.u32 [%0],{%1,%2};" ::"l"(p), "r"(a), "r"(b) : "memory"); }
__device__ __forceinline__ void st_rlx(void* p, uint32_t a) { asm volatile("st.relaxed.gpu.global.u32 [%0],%1;" ::"l"(p), "r"(a) : "memory"); }
#define PUB 15
template <int SITE> __device__ __forceinline__ void release() { if (PUB & SITE) asm volatile("fence.release.gpu;" ::: "memory"); }
__device__ __forceinline__ void signal_flag(unsigned* p, unsigned val) { asm volatile("st.relaxed.gpu.global.u32 [%0],%1;" ::"l"(p), "r"(val) : "memory"); }
__device__ __forceinline__ void signal_cnt(unsigned* p, unsigned n) { asm volatile("red.relaxed.gpu.global.add.u32 [%0],%1;" ::"l"(p), "r"(n) : "memory"); }
__device__ __forceinline__ void wait_flags(const unsigned* p, unsigned val, uint32_t need, uint32_t& ready) {
#pragma unroll 1
  for (int it = 0; (ready & need) != need && it < SPIN; it++) ready = __ballot_sync(0xffffffff, ld_rlx(p) == val);
}
__device__ __forceinline__ void wait_cnt(const unsigned* p, unsigned tgt) {
  asm volatile("{ .reg .pred p; .reg .u32 c; .reg .s32 v; mov.u32 c, 0;\n"
               "W: ld.relaxed.gpu.global.u32 v, [%0]; sub.s32 v, v, %1; setp.ge.s32 p, v, 0; @p bra.uni D;\n"
               "add.u32 c, c, 1; setp.lt.u32 p, c, 0x100000; @p bra.uni W;\nD: }" ::"l"(p), "r"(tgt) : "memory");
}
__device__ __forceinline__ uint32_t pack_bf(float lo, float hi) { uint32_t r; asm("cvt.rn.bf16x2.f32 %0, %1, %2;" : "=r"(r) : "f"(hi), "f"(lo)); return r; }
__device__ __forceinline__ float bf_lo(uint32_t v) { return __uint_as_float(v << 16); }
__device__ __forceinline__ float bf_hi(uint32_t v) { return __uint_as_float(v & 0xffff0000u); }
__device__ __forceinline__ float bf_rn(float x) { return __bfloat162float(__float2bfloat16_rn(x)); }
__device__ __forceinline__ float frcp(float x) { float r; asm("rcp.approx.ftz.f32 %0,%1;" : "=f"(r) : "f"(x)); return r; }
__device__ __forceinline__ float fsqrt(float x) { float r; asm("sqrt.approx.ftz.f32 %0,%1;" : "=f"(r) : "f"(x)); return r; }
__device__ __forceinline__ float frsqrt(float x) { float r; asm("rsqrt.approx.ftz.f32 %0,%1;" : "=f"(r) : "f"(x)); return r; }
__device__ __forceinline__ uint32_t hmul2(uint32_t a, uint32_t b) { uint32_t r; asm("mul.rn.bf16x2 %0,%1,%2;" : "=r"(r) : "r"(a), "r"(b)); return r; }
__device__ __forceinline__ uint32_t hfma2(uint32_t a, uint32_t b, uint32_t c) { uint32_t r; asm("fma.rn.bf16x2 %0,%1,%2,%3;" : "=r"(r) : "r"(a), "r"(b), "r"(c)); return r; }
__device__ __forceinline__ float2 cmul(float2 a, float2 b) { return make_float2(a.x * b.x - a.y * b.y, a.x * b.y + a.y * b.x); }
__device__ __forceinline__ float2 cfma(float2 a, float2 b, float2 c) {
  return make_float2(fmaf(a.x, b.x, fmaf(-a.y, b.y, c.x)), fmaf(a.x, b.y, fmaf(a.y, b.x, c.y)));
}
__device__ __forceinline__ uint32_t tagf(float v, uint32_t tag) { return (__float_as_uint(v) & ~1u) | tag; }
__device__ __forceinline__ float untag(uint32_t v) { return __uint_as_float(v & ~1u); }
__device__ __forceinline__ bool untagged(const uint4& v, uint32_t tag) { return (((v.x ^ tag) | (v.y ^ tag) | (v.z ^ tag) | (v.w ^ tag)) & 1) != 0; }
__device__ __forceinline__ bool untagged(const uint2& v, uint32_t tag) { return (((v.x ^ tag) | (v.y ^ tag)) & 1) != 0; }
__device__ __forceinline__ float2 lam_bar(float lr, float li, float ldt) {
  float dt = bf_rn(expf(ldt)); float e = expf(dt * lr), s, c; sincospif(dt * li * 0.31830988618379067f, &s, &c); return make_float2(e * c, e * s);
}

__device__ __forceinline__ int conv_ch(uint32_t c, int s) { return s * ((c >> 21) & 255) + (c & 255) - (s >= (int)(c >> 29) ? 8 : 0); }
struct Role {
  uint32_t v, c, p;
  __device__ __forceinline__ int tb() const { return v & 15; }
  __device__ __forceinline__ int cb() const { return (v >> 4) & 15; }
  __device__ __forceinline__ int b() const { return (v >> 8) & 255; }
  __device__ __forceinline__ int ubase() const { return (v >> 16) & 7; }
  __device__ __forceinline__ int ugs() const { return (v >> 19) & 7; }
  __device__ __forceinline__ int wpart() const { return (v >> 22) & 7; }
  __device__ __forceinline__ int rank() const { return (v >> 26) & 7; }
  __device__ __forceinline__ int cs() const { return (v >> 29) ? 8 : 2; }
  __device__ __forceinline__ int ch(int s) const { return conv_ch(c, s); }
  __device__ __forceinline__ int wlo() const { return p & 1; }
  __device__ __forceinline__ int whi() const { return (p >> 1) & 1; }
  __device__ __forceinline__ uint32_t wmask() const { return (p >> 2) & 255; }
  __device__ __forceinline__ uint32_t umask() const { return (p >> 10) & 255; }
  __device__ __forceinline__ int uj() const { return (p >> 20) & 31; }
  __device__ __forceinline__ int sm() const { return (p >> 25) & 15; }
  __device__ __forceinline__ int nch() const { return (c >> 10) & 7; }
  __device__ __forceinline__ int nprep() const { return (c >> 13) & 255; }
};

__device__ __forceinline__ void wgmma_ss80(float (&d)[40], uint64_t da, uint64_t db, int sd){
  asm volatile("{ .reg .pred p; setp.ne.b32 p, %42, 0;\n"
   "wgmma.mma_async.sync.aligned.m64n80k16.f32.bf16.bf16 {%0, %1, %2, %3, %4, %5, %6, %7, %8, %9, %10, %11, %12, %13, %14, %15, %16, %17, %18, %19, %20, %21, %22, %23, %24, %25, %26, %27, %28, %29, %30, %31, %32, %33, %34, %35, %36, %37, %38, %39}, %40, %41, p, 1, 1, 0, 0; }\n"
   : "+f"(d[0]), "+f"(d[1]), "+f"(d[2]), "+f"(d[3]), "+f"(d[4]), "+f"(d[5]), "+f"(d[6]), "+f"(d[7]), "+f"(d[8]), "+f"(d[9]), "+f"(d[10]), "+f"(d[11]), "+f"(d[12]), "+f"(d[13]), "+f"(d[14]), "+f"(d[15]), "+f"(d[16]), "+f"(d[17]), "+f"(d[18]), "+f"(d[19]), "+f"(d[20]), "+f"(d[21]), "+f"(d[22]), "+f"(d[23]), "+f"(d[24]), "+f"(d[25]), "+f"(d[26]), "+f"(d[27]), "+f"(d[28]), "+f"(d[29]), "+f"(d[30]), "+f"(d[31]), "+f"(d[32]), "+f"(d[33]), "+f"(d[34]), "+f"(d[35]), "+f"(d[36]), "+f"(d[37]), "+f"(d[38]), "+f"(d[39]) : "l"(da), "l"(db), "r"(sd));
}
__device__ __forceinline__ void wgmma_ss160(float (&d)[80], uint64_t da, uint64_t db, int sd){
  asm volatile("{ .reg .pred p; setp.ne.b32 p, %82, 0;\n"
   "wgmma.mma_async.sync.aligned.m64n160k16.f32.bf16.bf16 {%0, %1, %2, %3, %4, %5, %6, %7, %8, %9, %10, %11, %12, %13, %14, %15, %16, %17, %18, %19, %20, %21, %22, %23, %24, %25, %26, %27, %28, %29, %30, %31, %32, %33, %34, %35, %36, %37, %38, %39, %40, %41, %42, %43, %44, %45, %46, %47, %48, %49, %50, %51, %52, %53, %54, %55, %56, %57, %58, %59, %60, %61, %62, %63, %64, %65, %66, %67, %68, %69, %70, %71, %72, %73, %74, %75, %76, %77, %78, %79}, %80, %81, p, 1, 1, 0, 0; }\n"
   : "+f"(d[0]), "+f"(d[1]), "+f"(d[2]), "+f"(d[3]), "+f"(d[4]), "+f"(d[5]), "+f"(d[6]), "+f"(d[7]), "+f"(d[8]), "+f"(d[9]), "+f"(d[10]), "+f"(d[11]), "+f"(d[12]), "+f"(d[13]), "+f"(d[14]), "+f"(d[15]), "+f"(d[16]), "+f"(d[17]), "+f"(d[18]), "+f"(d[19]), "+f"(d[20]), "+f"(d[21]), "+f"(d[22]), "+f"(d[23]), "+f"(d[24]), "+f"(d[25]), "+f"(d[26]), "+f"(d[27]), "+f"(d[28]), "+f"(d[29]), "+f"(d[30]), "+f"(d[31]), "+f"(d[32]), "+f"(d[33]), "+f"(d[34]), "+f"(d[35]), "+f"(d[36]), "+f"(d[37]), "+f"(d[38]), "+f"(d[39]), "+f"(d[40]), "+f"(d[41]), "+f"(d[42]), "+f"(d[43]), "+f"(d[44]), "+f"(d[45]), "+f"(d[46]), "+f"(d[47]), "+f"(d[48]), "+f"(d[49]), "+f"(d[50]), "+f"(d[51]), "+f"(d[52]), "+f"(d[53]), "+f"(d[54]), "+f"(d[55]), "+f"(d[56]), "+f"(d[57]), "+f"(d[58]), "+f"(d[59]), "+f"(d[60]), "+f"(d[61]), "+f"(d[62]), "+f"(d[63]), "+f"(d[64]), "+f"(d[65]), "+f"(d[66]), "+f"(d[67]), "+f"(d[68]), "+f"(d[69]), "+f"(d[70]), "+f"(d[71]), "+f"(d[72]), "+f"(d[73]), "+f"(d[74]), "+f"(d[75]), "+f"(d[76]), "+f"(d[77]), "+f"(d[78]), "+f"(d[79]) : "l"(da), "l"(db), "r"(sd));
}
template<int N> __device__ __forceinline__ void wgmma_rs(float (&d)[N/2], uint32_t a0, uint32_t a1, uint32_t a2, uint32_t a3, uint64_t db, int sd);
template<> __device__ __forceinline__ void wgmma_rs<16>(float (&d)[8], uint32_t a0, uint32_t a1, uint32_t a2, uint32_t a3, uint64_t db, int sd){
  asm volatile("{ .reg .pred p; setp.ne.b32 p, %13, 0;\n"
   "wgmma.mma_async.sync.aligned.m64n16k16.f32.bf16.bf16 {%0, %1, %2, %3, %4, %5, %6, %7}, {%8,%9,%10,%11}, %12, p, 1, 1, 0; }\n"
   : "+f"(d[0]), "+f"(d[1]), "+f"(d[2]), "+f"(d[3]), "+f"(d[4]), "+f"(d[5]), "+f"(d[6]), "+f"(d[7]) : "r"(a0), "r"(a1), "r"(a2), "r"(a3), "l"(db), "r"(sd));
}
template<> __device__ __forceinline__ void wgmma_rs<32>(float (&d)[16], uint32_t a0, uint32_t a1, uint32_t a2, uint32_t a3, uint64_t db, int sd){
  asm volatile("{ .reg .pred p; setp.ne.b32 p, %21, 0;\n"
   "wgmma.mma_async.sync.aligned.m64n32k16.f32.bf16.bf16 {%0, %1, %2, %3, %4, %5, %6, %7, %8, %9, %10, %11, %12, %13, %14, %15}, {%16,%17,%18,%19}, %20, p, 1, 1, 0; }\n"
   : "+f"(d[0]), "+f"(d[1]), "+f"(d[2]), "+f"(d[3]), "+f"(d[4]), "+f"(d[5]), "+f"(d[6]), "+f"(d[7]), "+f"(d[8]), "+f"(d[9]), "+f"(d[10]), "+f"(d[11]), "+f"(d[12]), "+f"(d[13]), "+f"(d[14]), "+f"(d[15]) : "r"(a0), "r"(a1), "r"(a2), "r"(a3), "l"(db), "r"(sd));
}
template<> __device__ __forceinline__ void wgmma_rs<48>(float (&d)[24], uint32_t a0, uint32_t a1, uint32_t a2, uint32_t a3, uint64_t db, int sd){
  asm volatile("{ .reg .pred p; setp.ne.b32 p, %29, 0;\n"
   "wgmma.mma_async.sync.aligned.m64n48k16.f32.bf16.bf16 {%0, %1, %2, %3, %4, %5, %6, %7, %8, %9, %10, %11, %12, %13, %14, %15, %16, %17, %18, %19, %20, %21, %22, %23}, {%24,%25,%26,%27}, %28, p, 1, 1, 0; }\n"
   : "+f"(d[0]), "+f"(d[1]), "+f"(d[2]), "+f"(d[3]), "+f"(d[4]), "+f"(d[5]), "+f"(d[6]), "+f"(d[7]), "+f"(d[8]), "+f"(d[9]), "+f"(d[10]), "+f"(d[11]), "+f"(d[12]), "+f"(d[13]), "+f"(d[14]), "+f"(d[15]), "+f"(d[16]), "+f"(d[17]), "+f"(d[18]), "+f"(d[19]), "+f"(d[20]), "+f"(d[21]), "+f"(d[22]), "+f"(d[23]) : "r"(a0), "r"(a1), "r"(a2), "r"(a3), "l"(db), "r"(sd));
}
template<> __device__ __forceinline__ void wgmma_rs<64>(float (&d)[32], uint32_t a0, uint32_t a1, uint32_t a2, uint32_t a3, uint64_t db, int sd){
  asm volatile("{ .reg .pred p; setp.ne.b32 p, %37, 0;\n"
   "wgmma.mma_async.sync.aligned.m64n64k16.f32.bf16.bf16 {%0, %1, %2, %3, %4, %5, %6, %7, %8, %9, %10, %11, %12, %13, %14, %15, %16, %17, %18, %19, %20, %21, %22, %23, %24, %25, %26, %27, %28, %29, %30, %31}, {%32,%33,%34,%35}, %36, p, 1, 1, 0; }\n"
   : "+f"(d[0]), "+f"(d[1]), "+f"(d[2]), "+f"(d[3]), "+f"(d[4]), "+f"(d[5]), "+f"(d[6]), "+f"(d[7]), "+f"(d[8]), "+f"(d[9]), "+f"(d[10]), "+f"(d[11]), "+f"(d[12]), "+f"(d[13]), "+f"(d[14]), "+f"(d[15]), "+f"(d[16]), "+f"(d[17]), "+f"(d[18]), "+f"(d[19]), "+f"(d[20]), "+f"(d[21]), "+f"(d[22]), "+f"(d[23]), "+f"(d[24]), "+f"(d[25]), "+f"(d[26]), "+f"(d[27]), "+f"(d[28]), "+f"(d[29]), "+f"(d[30]), "+f"(d[31]) : "r"(a0), "r"(a1), "r"(a2), "r"(a3), "l"(db), "r"(sd));
}
template<> __device__ __forceinline__ void wgmma_rs<80>(float (&d)[40], uint32_t a0, uint32_t a1, uint32_t a2, uint32_t a3, uint64_t db, int sd){
  asm volatile("{ .reg .pred p; setp.ne.b32 p, %45, 0;\n"
   "wgmma.mma_async.sync.aligned.m64n80k16.f32.bf16.bf16 {%0, %1, %2, %3, %4, %5, %6, %7, %8, %9, %10, %11, %12, %13, %14, %15, %16, %17, %18, %19, %20, %21, %22, %23, %24, %25, %26, %27, %28, %29, %30, %31, %32, %33, %34, %35, %36, %37, %38, %39}, {%40,%41,%42,%43}, %44, p, 1, 1, 0; }\n"
   : "+f"(d[0]), "+f"(d[1]), "+f"(d[2]), "+f"(d[3]), "+f"(d[4]), "+f"(d[5]), "+f"(d[6]), "+f"(d[7]), "+f"(d[8]), "+f"(d[9]), "+f"(d[10]), "+f"(d[11]), "+f"(d[12]), "+f"(d[13]), "+f"(d[14]), "+f"(d[15]), "+f"(d[16]), "+f"(d[17]), "+f"(d[18]), "+f"(d[19]), "+f"(d[20]), "+f"(d[21]), "+f"(d[22]), "+f"(d[23]), "+f"(d[24]), "+f"(d[25]), "+f"(d[26]), "+f"(d[27]), "+f"(d[28]), "+f"(d[29]), "+f"(d[30]), "+f"(d[31]), "+f"(d[32]), "+f"(d[33]), "+f"(d[34]), "+f"(d[35]), "+f"(d[36]), "+f"(d[37]), "+f"(d[38]), "+f"(d[39]) : "r"(a0), "r"(a1), "r"(a2), "r"(a3), "l"(db), "r"(sd));
}
template<> __device__ __forceinline__ void wgmma_rs<96>(float (&d)[48], uint32_t a0, uint32_t a1, uint32_t a2, uint32_t a3, uint64_t db, int sd){
  asm volatile("{ .reg .pred p; setp.ne.b32 p, %53, 0;\n"
   "wgmma.mma_async.sync.aligned.m64n96k16.f32.bf16.bf16 {%0, %1, %2, %3, %4, %5, %6, %7, %8, %9, %10, %11, %12, %13, %14, %15, %16, %17, %18, %19, %20, %21, %22, %23, %24, %25, %26, %27, %28, %29, %30, %31, %32, %33, %34, %35, %36, %37, %38, %39, %40, %41, %42, %43, %44, %45, %46, %47}, {%48,%49,%50,%51}, %52, p, 1, 1, 0; }\n"
   : "+f"(d[0]), "+f"(d[1]), "+f"(d[2]), "+f"(d[3]), "+f"(d[4]), "+f"(d[5]), "+f"(d[6]), "+f"(d[7]), "+f"(d[8]), "+f"(d[9]), "+f"(d[10]), "+f"(d[11]), "+f"(d[12]), "+f"(d[13]), "+f"(d[14]), "+f"(d[15]), "+f"(d[16]), "+f"(d[17]), "+f"(d[18]), "+f"(d[19]), "+f"(d[20]), "+f"(d[21]), "+f"(d[22]), "+f"(d[23]), "+f"(d[24]), "+f"(d[25]), "+f"(d[26]), "+f"(d[27]), "+f"(d[28]), "+f"(d[29]), "+f"(d[30]), "+f"(d[31]), "+f"(d[32]), "+f"(d[33]), "+f"(d[34]), "+f"(d[35]), "+f"(d[36]), "+f"(d[37]), "+f"(d[38]), "+f"(d[39]), "+f"(d[40]), "+f"(d[41]), "+f"(d[42]), "+f"(d[43]), "+f"(d[44]), "+f"(d[45]), "+f"(d[46]), "+f"(d[47]) : "r"(a0), "r"(a1), "r"(a2), "r"(a3), "l"(db), "r"(sd));
}
template<> __device__ __forceinline__ void wgmma_rs<112>(float (&d)[56], uint32_t a0, uint32_t a1, uint32_t a2, uint32_t a3, uint64_t db, int sd){
  asm volatile("{ .reg .pred p; setp.ne.b32 p, %61, 0;\n"
   "wgmma.mma_async.sync.aligned.m64n112k16.f32.bf16.bf16 {%0, %1, %2, %3, %4, %5, %6, %7, %8, %9, %10, %11, %12, %13, %14, %15, %16, %17, %18, %19, %20, %21, %22, %23, %24, %25, %26, %27, %28, %29, %30, %31, %32, %33, %34, %35, %36, %37, %38, %39, %40, %41, %42, %43, %44, %45, %46, %47, %48, %49, %50, %51, %52, %53, %54, %55}, {%56,%57,%58,%59}, %60, p, 1, 1, 0; }\n"
   : "+f"(d[0]), "+f"(d[1]), "+f"(d[2]), "+f"(d[3]), "+f"(d[4]), "+f"(d[5]), "+f"(d[6]), "+f"(d[7]), "+f"(d[8]), "+f"(d[9]), "+f"(d[10]), "+f"(d[11]), "+f"(d[12]), "+f"(d[13]), "+f"(d[14]), "+f"(d[15]), "+f"(d[16]), "+f"(d[17]), "+f"(d[18]), "+f"(d[19]), "+f"(d[20]), "+f"(d[21]), "+f"(d[22]), "+f"(d[23]), "+f"(d[24]), "+f"(d[25]), "+f"(d[26]), "+f"(d[27]), "+f"(d[28]), "+f"(d[29]), "+f"(d[30]), "+f"(d[31]), "+f"(d[32]), "+f"(d[33]), "+f"(d[34]), "+f"(d[35]), "+f"(d[36]), "+f"(d[37]), "+f"(d[38]), "+f"(d[39]), "+f"(d[40]), "+f"(d[41]), "+f"(d[42]), "+f"(d[43]), "+f"(d[44]), "+f"(d[45]), "+f"(d[46]), "+f"(d[47]), "+f"(d[48]), "+f"(d[49]), "+f"(d[50]), "+f"(d[51]), "+f"(d[52]), "+f"(d[53]), "+f"(d[54]), "+f"(d[55]) : "r"(a0), "r"(a1), "r"(a2), "r"(a3), "l"(db), "r"(sd));
}
template<> __device__ __forceinline__ void wgmma_rs<128>(float (&d)[64], uint32_t a0, uint32_t a1, uint32_t a2, uint32_t a3, uint64_t db, int sd){
  asm volatile("{ .reg .pred p; setp.ne.b32 p, %69, 0;\n"
   "wgmma.mma_async.sync.aligned.m64n128k16.f32.bf16.bf16 {%0, %1, %2, %3, %4, %5, %6, %7, %8, %9, %10, %11, %12, %13, %14, %15, %16, %17, %18, %19, %20, %21, %22, %23, %24, %25, %26, %27, %28, %29, %30, %31, %32, %33, %34, %35, %36, %37, %38, %39, %40, %41, %42, %43, %44, %45, %46, %47, %48, %49, %50, %51, %52, %53, %54, %55, %56, %57, %58, %59, %60, %61, %62, %63}, {%64,%65,%66,%67}, %68, p, 1, 1, 0; }\n"
   : "+f"(d[0]), "+f"(d[1]), "+f"(d[2]), "+f"(d[3]), "+f"(d[4]), "+f"(d[5]), "+f"(d[6]), "+f"(d[7]), "+f"(d[8]), "+f"(d[9]), "+f"(d[10]), "+f"(d[11]), "+f"(d[12]), "+f"(d[13]), "+f"(d[14]), "+f"(d[15]), "+f"(d[16]), "+f"(d[17]), "+f"(d[18]), "+f"(d[19]), "+f"(d[20]), "+f"(d[21]), "+f"(d[22]), "+f"(d[23]), "+f"(d[24]), "+f"(d[25]), "+f"(d[26]), "+f"(d[27]), "+f"(d[28]), "+f"(d[29]), "+f"(d[30]), "+f"(d[31]), "+f"(d[32]), "+f"(d[33]), "+f"(d[34]), "+f"(d[35]), "+f"(d[36]), "+f"(d[37]), "+f"(d[38]), "+f"(d[39]), "+f"(d[40]), "+f"(d[41]), "+f"(d[42]), "+f"(d[43]), "+f"(d[44]), "+f"(d[45]), "+f"(d[46]), "+f"(d[47]), "+f"(d[48]), "+f"(d[49]), "+f"(d[50]), "+f"(d[51]), "+f"(d[52]), "+f"(d[53]), "+f"(d[54]), "+f"(d[55]), "+f"(d[56]), "+f"(d[57]), "+f"(d[58]), "+f"(d[59]), "+f"(d[60]), "+f"(d[61]), "+f"(d[62]), "+f"(d[63]) : "r"(a0), "r"(a1), "r"(a2), "r"(a3), "l"(db), "r"(sd));
}

#define BAR(i) (bars + 8u * (uint32_t)(i))

template <int G> __device__ __forceinline__ void conv_frags(uint32_t (&a)[12], uint32_t abase) {
#pragma unroll
  for (int i = 0; i < 12; i++) a[i] = lds32(abase + (G * 4 + i / 3) * 128 + (i % 3) * 4);
}
__device__ __forceinline__ void kv_prefetch(const __nv_bfloat16* pf, int task) { prefetch_if(pf + 64 * (task & 31) * DM + 64 * (task >> 5), task < 320); }
__device__ __forceinline__ void kv_load(const Params& P, Scratch* S, int task, int tid, uint32_t (&k_)[19], uint32_t (&v_)[16], uint4& sk) {
  const int row = 64 * (task & 31) + 16 * (tid >> 5), ch = 64 * (task >> 5) + 2 * (tid & 31);
  const uint32_t* kp = (const uint32_t*)(P.k + (size_t)row * DM + ch);
  const uint32_t* vp = (const uint32_t*)(P.v + (size_t)row * DM + ch);
  const uint32_t* hp = row > 0 ? kp - 3 * (DM / 2) : S->zero;
  const int hs = row > 0 ? DM / 2 : 0;
  asm volatile("ld.global.nc.v4.u32 {%0,%1,%2,%3},[%4];" : "=r"(sk.x), "=r"(sk.y), "=r"(sk.z), "=r"(sk.w) : "l"(P.shk + ch * 4));
#pragma unroll
  for (int i = 0; i < 3; i++) k_[i] = ldg1(hp + i * hs);
#pragma unroll
  for (int i = 0; i < 16; i++) { k_[i + 3] = ldg1(kp + i * (DM / 2)); v_[i] = ldg1(vp + i * (DM / 2)); }
}
template <int SH> __device__ __forceinline__ void xb_prefetch(const Head& H, int id, int tid, int c0) {
  const int ri = tid >> SH, rr = 11 * id + ri - 16;
  const __nv_bfloat16* p = ri < 16 ? H.x + (size_t)(16 * min(id, 127) + ri) * DM : (rr < DM ? H.b0 : H.b1 - DM * DM) + (size_t)rr * DM;
  prefetch_if(p + c0 + 64 * (tid & ((1 << SH) - 1)), ri < 16 || (ri < 27 && rr < 2 * DM));
}
__device__ __forceinline__ uint4 ldg4(const void* p) { uint4 v; asm volatile("ld.global.nc.v4.u32 {%0,%1,%2,%3},[%4];" : "=r"(v.x), "=r"(v.y), "=r"(v.z), "=r"(v.w) : "l"(p)); return v; }
__device__ __forceinline__ uint4 lds4(uint32_t a) { uint4 v; asm volatile("ld.shared.v4.u32 {%0,%1,%2,%3},[%4];" : "=r"(v.x), "=r"(v.y), "=r"(v.z), "=r"(v.w) : "r"(a) : "memory"); return v; }
__device__ __forceinline__ void discretise(const Head& H, const Params& P, uint32_t sb, Role R, int lane, uint32_t e1) {
  const uint32_t dn = __ldg((const unsigned short*)P.ssmd + min(conv_ch(R.c, (lane + 7) & 7), DM - 1));
  const int c = 32 * min(R.cb(), 9) + lane;
  const uint32_t lr2 = ldg1(P.lre + 2 * c), li2 = ldg1(P.lim + 2 * c), ld2 = ldg1(P.ldt + 2 * c);
  asm volatile("st.shared.u32 [%0],%1;" ::"r"(sb + MISC_OFF + 4 * (lane & 7)), "r"((lane & 7) ? dn : e1) : "memory");
#pragma unroll 1
  for (int i = 0; i < 2; i++) {
    const float lr = bf_hi(lr2 << (16 - 16 * i)), li = bf_hi(li2 << (16 - 16 * i));
    const float2 lb = lam_bar(lr, li, bf_hi(ld2 << (16 - 16 * i)));
    const float nx = lb.x - 1.f, ny = lb.y, inv = 2.f * frcp(lr * lr + li * li), cx = (nx * lr + ny * li) * inv, cy = (ny * lr - nx * li) * inv;
    const bool sw = !H.swap;
    asm volatile("st.shared.v4.f32 [%0],{%1,%2,%3,%4};" ::"r"(sb + LAM_OFF + 32 * lane + 16 * i), "f"(lb.x), "f"(sw ? -lb.y : lb.y), "f"(sw ? -cy : cx), "f"(sw ? cx : -cy) : "memory");
  }
  __syncwarp();
}
__device__ __forceinline__ void aux_prep(const Head& H, const Params& P, uint32_t sb, Role R, int tid, long long t_start) {
  Scratch* const S = H.s;
  const uint32_t bars = sb + BAR_OFF;
  tid = opaque(tid);
  const int w = tid >> 5, lane = tid & 31, tb = R.tb(), cb = R.cb();
  uint32_t k_[19], v_[16];
  uint4 sk;
  int task = R.b() < R.nprep() ? R.b() : 320;
  delay(KVDLY);
  PROFC(tid == 0, 345);
  kv_load(P, S, min(task, 319), tid, k_, v_, sk);
  const __nv_bfloat16* pf = (tid < 64 ? P.k : P.v) + (tid & 63) * DM;
  const int j = lane >> 3, sm = min(R.sm(), 9), trow = 160 * tb + 4 * sm + (tb < 12 ? 40 : 32) * w + j;
  const uint32_t so = sb + (2 * w + (j & 1) + 8 * (j >> 1)) * 128 + 16 * (lane & 7), xo = so + sm * 2048, wo = so + (tb & 1) * 8192 + (tb & 6) * 1024;
  const __nv_bfloat16* xp = H.x + (size_t)min(trow, SEQ - 1) * DM + 384 + 8 * (lane & 7);
  const __nv_bfloat16* bp = (j < 2 ? H.b0 : H.b1) + (size_t)(64 * cb + 32 * (tb & 1) + 4 * (tb & 6) + 2 * w + (j & 1)) * DM + 384 + 8 * (lane & 7);
  float s = 0.f, s2 = 0.f, sr = 0.f;
#define STAT(m, n) { const uint32_t xw[4] = {m.x, m.y, m.z, m.w}, bw[4] = {n.x, n.y, n.z, n.w}; \
  _Pragma("unroll") for (int i = 0; i < 4; i++) { const float u = bf_lo(xw[i]), v = bf_hi(xw[i]); s += u + v; s2 = fmaf(u, u, fmaf(v, v, s2)); sr += bf_lo(bw[i]) + bf_hi(bw[i]); } }
#define STATS(K0, K1) _Pragma("unroll 1") for (int kb = K0; kb < K1; kb++) { \
    mbar_wait(BAR(B_F1 + kb)); \
    const uint4 a = lds4(xo + ((uint32_t)(XTAB0 >> (6 * kb)) & 63) * 4096), c = lds4(wo + ((uint32_t)(WTAB0 >> (6 * kb)) & 63) * 4096); \
    STAT(a, c) \
    asm volatile("" : "+f"(s), "+f"(s2), "+f"(sr)); \
    if (XPFAT >= K0 && XPFAT < K1) prefetch_if(((lane & 4) ? bp : xp) + 64 * (lane & 3), kb == XPFAT); \
    kv_prefetch(pf, kb == KPFAT ? task + R.nprep() : kb == KPFAT2 ? task + 2 * R.nprep() : 320); \
  } \
  __syncwarp(); mbar_arrive_if(BAR(B_AX + K0 / 3), lane == 0);
  STATS(0, 3)
  PROFC(tid == 0, 349);
    {
      uint4 m[4], n[4];
#pragma unroll
      for (int i = 0; i < 4; i++) { m[i] = ldg4(xp + 64 * i); n[i] = ldg4(bp + 64 * i); }
      STATS(3, 6)
      PROFC(tid == 0, 346);
      mbar_wait(BAR(B_LM));
      const uint32_t tag = lds32(sb + MISC_OFF) & 1;
#pragma unroll
      for (int i = 0; i < 4; i++) { const uint4 a = m[i], c = n[i]; STAT(a, c) }
      PROFC(tid == 0 && s2 != 1.2345f, 347);
#pragma unroll
      for (int o = 1; o <= 4; o <<= 1) { s += __shfl_xor_sync(0xffffffff, s, o); s2 += __shfl_xor_sync(0xffffffff, s2, o); sr += __shfl_xor_sync(0xffffffff, sr, o); }
      const float mn = s * (1.f / DM), rs = frcp(bf_rn(fsqrt(bf_rn(bf_rn(fmaxf(s2 * (1.f / DM) - mn * mn, 0.f)) + 1e-5f))));
      asm volatile("{ .reg .pred p; setp.ne.u32 p, %2, 0; @p st.relaxed.gpu.global.u32 [%0],%1; }"
                   ::"l"((uint32_t*)(S->RS + (8 * cb + 4 * (tb & 1) + (tb >> 1)) * 16 + 4 * w + (j & 1)) + (lane & 4) + (j >> 1)), "r"(tagf(sr, tag)),
                   "r"((uint32_t)(tb < 8 && (lane & 3) == 0)) : "memory");
      asm volatile("{ .reg .pred p; setp.ne.u32 p, %3, 0; @p st.relaxed.gpu.global.v2.u32 [%0],{%1,%2}; }"
                   ::"l"(S->S + trow), "r"(tagf(rs, tag)), "r"(tagf(-bf_rn(mn) * rs, tag)), "r"((uint32_t)(R.sm() < 10 && (lane & 7) == 0)) : "memory");
      PROFC(tid == 0, 3);
    }
#pragma unroll 1
  for (int r = 0; task < 320; r++) {
    {
      const uint32_t T0 = __byte_perm(sk.x, sk.z, 0x5410), T1 = __byte_perm(sk.x, sk.z, 0x7632);
      const uint32_t T2 = __byte_perm(sk.y, sk.w, 0x5410), T3 = __byte_perm(sk.y, sk.w, 0x7632);
      PROFC(tid == 0 && v_[15] != 0x12345, 336 + r);
      uint32_t o[16];
#pragma unroll
      for (int t = 0; t < 16; t += 2) {
        const uint32_t a = hmul2(hfma2(k_[t + 3], T0, hfma2(k_[t + 2], T1, hfma2(k_[t + 1], T2, hmul2(k_[t], T3)))), v_[t]);
        const uint32_t c = hmul2(hfma2(k_[t + 4], T0, hfma2(k_[t + 3], T1, hfma2(k_[t + 2], T2, hmul2(k_[t + 1], T3)))), v_[t + 1]);
        const int wd = ((7 - t / 2) >> 1) + 4 * ((7 - t / 2) & 1);
        o[wd] = __byte_perm(c, a, 0x5410); o[8 + wd] = __byte_perm(c, a, 0x7632);
        asm volatile("" : "+r"(o[wd]), "+r"(o[8 + wd]));
        if (t == PFAT) kv_prefetch(pf, task + (1 + PFD) * R.nprep());
      }
      PROFC(tid == 0, 330 + 2 * r);
      const int ph = task & 1;
      task += R.nprep();
      if (ORD == 0 && task < 320) kv_load(P, S, task, tid, k_, v_, sk);
      mbar_wait(BAR(B_E1 + 3)); mbar_wait(BAR(B_AX + 1));
#pragma unroll
      for (int i = 0; i < 4; i++) {
        const int row = 2 * lane + (i >> 1);
        asm volatile("st.shared.v4.u32 [%0],{%1,%2,%3,%4};" ::"r"(sb + KS_OFF + r * 8192 + row * 128 + (((2 * w + ((i & 1) ^ ph)) ^ (row & 7)) << 4)),
                     "r"(o[4 * i]), "r"(o[4 * i + 1]), "r"(o[4 * i + 2]), "r"(o[4 * i + 3]) : "memory");
      }
      __syncwarp();
      mbar_arrive_if(BAR(B_PS + r), lane == 0);
      PROFC(tid == 0, 331 + 2 * r);
      if (ORD == 1 && task < 320) kv_load(P, S, task, tid, k_, v_, sk);
    }
  }
#undef STAT
#undef STATS
  PROFC(tid == 0, 40);
}
#define SPLIT(G) asm volatile("{ .reg .pred p; .reg .u32 r; L: mov.u32 r, %%clock; setp.eq.u32 p, r, %0; @p bra.uni L; }" ::"n"(G) : "memory")
template <bool AUX>
__device__ __forceinline__ void conv_loop(uint32_t sb, uint32_t rc, int wg, int tid, long long t_start) {
  sb = opaque(sb); rc = opaque(rc);
  const uint32_t bars = sb + BAR_OFF;
  int slot = AUX ? 0 : wg + 1;
  mbar_wait(BAR(B_LM));
#pragma unroll 1
  while (slot < (int)((rc >> 10) & 7)) {
    tid = opaque(tid);
    const int w = tid >> 5, lane = tid & 31, g = lane >> 2, q = lane & 3;
    const uint32_t Dn = lds32(sb + MISC_OFF + 4 + 4 * slot);
    const uint32_t d0 = (g == 1 && q == 3 - w) ? Dn : 0, d1 = (g == 0 && q == 3 - w) ? Dn : 0;
    const uint32_t cb_ = conv_buf(sb, slot), c0 = cb_ + KC_OFS;
    const uint32_t abase = c0 + 2 * (2 * (g & 1) + 4 * w + 16 * (g >> 1) + 4 * q);
    const uint64_t bd = make_desc(cb_ + KV_PAD, 16, 256, 3);
    const bool hi = lane & 16, s1 = lane & 8;
    const int qo = hi ? (q + 1) & 3 : q;
    const int srcA = hi ? (lane & 12) | ((q + 1) & 3) : (lane & 12) | 16 | ((q + 3) & 3);
    const bool h3 = hi && q == 3, wrap = s1 && qo == 3, back = wrap && hi;
    const bool chi = wrap ? !hi : hi;
    const int cq = s1 ? (qo + 1) & 3 : qo;
    const int srcB = (lane & 4) | (s1 ? 0 : 8) | (chi ? 16 | ((cq + 3) & 3) : cq);
    const uint32_t gp = c0 + 16 * (2 * (g & 1) + 4 * w) + (chi ? 256 : 0) + 2 * (2 * cq + (s1 ? 0 : 1));
    uint32_t a[12], f[16], o[8];
    float S[4], T[4], U[2], keep[2], pv[2] = {0.f, 0.f}, pr[4] = {0.f, 0.f, 0.f, 0.f};
    float e0[64], e1[56], e2[48], e3[40], e4[32], e5[24], e6[16], e7[8];
#define UNR _Pragma("unroll")
#define PERM() UNR for (int i = 0; i < 4; i++) { f[4 * i] = __byte_perm(a[3 * i], a[3 * i + 1], 0x5432); f[4 * i + 1] = a[3 * i + 1]; \
                                                 f[4 * i + 2] = __byte_perm(a[3 * i + 1], a[3 * i + 2], 0x5432); f[4 * i + 3] = a[3 * i + 2]; }
#define MMA(N, E) UNR for (int i = 0; i < 4; i++) wgmma_rs<N>(E, f[4 * i], f[4 * i + 1], f[4 * i + 2], f[4 * i + 3], bd - 8 * i, 1); wg_commit();
#define L1(c) UNR for (int i = 0; i < 4; i++) { const float ev = c[i], od = c[4 + i]; S[i] = hi ? (h3 ? ev : od) : ev; \
                                                T[i] = __shfl_sync(0xffffffff, hi ? (h3 ? pr[i] : ev) : od, srcA); pr[i] = od; }
#define L1E() UNR for (int i = 0; i < 4; i++) S[i] += T[i];
#define L2() UNR for (int h = 0; h < 2; h++) { keep[h] = back ? pv[h] : S[2 * h + 1]; pv[h] = S[2 * h + 1]; U[h] = __shfl_sync(0xffffffff, S[2 * h], srcB); }
#define L2E(j) o[j] = pack_bf(keep[0] + U[0], keep[1] + U[1]);
#define GRP(G, N, P, E) UNR for (int i = 0; i < N / 2; i++) asm volatile("mov.b32 %0,%1;" : "=f"(E[i]) : "f"(P[i + 8])); \
    wg_fence(); if (G < 7) conv_frags<(G + 1) & 7>(a, abase); if (G >= 2) { L2() } L1(P) MMA(N, E) SPLIT(G); \
    if (G < 7) { PERM() } if (G >= 2) { L2E((G + 6) & 7) } L1E() wg_wait<0>(); fence_regs(E);
    PROFC(tid == 0, 300 + 4 * slot);
    mbar_wait(BAR(B_KF + slot));
    if (tid == 0) PROF(361 + slot);
    PROFC(tid == 0, 301 + 4 * slot);
    conv_frags<0>(a, abase);
    wg_fence();
    wgmma_rs<128>(e0, d0 << 16, d0, d1 << 16, d1, bd, 0);
    PERM() conv_frags<1>(a, abase); wg_fence(); MMA(128, e0) SPLIT(0); PERM() wg_wait<0>(); fence_regs(e0);
    GRP(1, 112, e0, e1) GRP(2, 96, e1, e2) GRP(3, 80, e2, e3) GRP(4, 64, e3, e4) GRP(5, 48, e4, e5) GRP(6, 32, e5, e6) GRP(7, 16, e6, e7)
    PROFC(tid == 0, 302 + 4 * slot);
    L2() L1(e7) L2E(6) L1E() L2() L2E(7)
    bar_sync(wg + 1, 128);
#pragma unroll
    for (int jj = 0; jj < 8; jj++)
      asm volatile("st.shared.u16 [%0],%1; st.shared.u16 [%0+16],%2;" ::"r"(gp + jj * 512), "h"((uint16_t)o[jj]), "h"((uint16_t)(o[jj] >> 16)) : "memory");
#undef PERM
#undef MMA
#undef L1
#undef L1E
#undef L2
#undef L2E
#undef GRP
    PROFC(tid == 0, 303 + 4 * slot);
    __syncwarp();
    if (lane == 0) mbar_arrive(BAR(B_GS + slot));
    if (!AUX) break;
    slot = slot ? slot + 1 : 3;
  }
}

#define IDX(J, c, h) (8 * (J) + 4 * ((c) >> 1) + 2 * (h) + ((c) & 1))
__device__ __forceinline__ uint2 lds2(uint32_t a) { uint2 v; asm volatile("ld.shared.v2.u32 {%0,%1},[%2];" : "=r"(v.x), "=r"(v.y) : "r"(a) : "memory"); return v; }
__device__ __forceinline__ void resid_load(float (&r)[40], uint32_t sb, int wg, int tid, const uint4& s) {
  const uint32_t dp = sb + XR_OFF + 8 * (tid & 3), xp = dp + (64 * wg + 16 * (tid >> 5) + ((tid & 31) >> 2)) * 160;
#pragma unroll
  for (int J = 0; J < 5; J++) {
    const uint2 u = lds2(xp + 32 * J), v = lds2(xp + 32 * J + 1280), d = lds2(dp + 20480 + 32 * J);
    r[8 * J] = __uint_as_float(u.x); r[8 * J + 1] = __uint_as_float(u.y); r[8 * J + 2] = __uint_as_float(v.x); r[8 * J + 3] = __uint_as_float(v.y);
    r[8 * J + 4] = __uint_as_float(d.x); r[8 * J + 5] = __uint_as_float(d.y);
  }
  r[30] = untag(s.x); r[31] = untag(s.y); r[38] = untag(s.z); r[39] = untag(s.w);
}
__device__ __forceinline__ void resid_init(float (&r)[40]) {
  const float s[4] = {r[30], r[31], r[38], r[39]};
#pragma unroll
  for (int J = 0; J < 5; J++) {
    uint32_t w[6];
#pragma unroll
    for (int i = 0; i < 6; i++) w[i] = __float_as_uint(r[8 * J + i]);
#pragma unroll
    for (int i = 0; i < 4; i++) {
      const int h = i >> 1, c = 2 * (i & 1);
      const float rs = s[2 * h], nm = s[2 * h + 1], x0 = bf_lo(w[i]), x1 = bf_hi(w[i]);
      const uint32_t t = hmul2(pack_bf(fmaf(x0, rs, nm), fmaf(x1, rs, nm)), w[4 + (i & 1)]);
      r[IDX(J, c, h)] = x0 + bf_lo(t); r[IDX(J, c + 1, h)] = x1 + bf_hi(t);
    }
  }
}

__device__ __forceinline__ float flip(float v, uint32_t m) { return __uint_as_float(__float_as_uint(v) ^ m); }
__device__ __forceinline__ void g1_phase(const int LY, const Head& H, uint32_t sb, int wg, int tid, Role R, float (&xr)[40], long long t_start) {
  Scratch* const S = H.s;
  tid = opaque(tid); sb = opaque(sb); R.v = opaque(R.v);
  const uint32_t bars = sb + BAR_OFF;
  const int cb = R.cb(), tb = R.tb();
  const int w = tid >> 5, lane = tid & 31, g = lane >> 2, q = lane & 3;
  const bool full = tb < 12;
  uint2* Eb = S->E + ((LY * 130 + cb) * 8 + 4 * wg + w) * 16 + g;
  float a[80];
#pragma unroll
  for (int i = 0; i < 80; i++) a[i] = 0.f;
  uint32_t rel = mapa(BAR(B_E1), lane ? R.wpart() : R.ubase() + (w & (R.ugs() - 1)));
  const bool rels = lane == 0 || (tid == 1 && wg != R.wlo());
  {
    uint64_t tw = LY ? WTAB1 : WTAB0, tx = LY ? XTAB1 : XTAB0;
    uint32_t bf = BAR(B_F1);
    if (tid == 0 && wg == 0 && !LY) PROF(351);
    fence_regs(a);
    mbar_wait(bf, LY);
    if (tid == 0 && wg == 0) PROF(LY ? 20 : 4);
#pragma unroll 1
    for (int kb = 0; kb < 10; kb++) {
      const uint64_t da = make_desc(sb + ((uint32_t)tw & 63) * 4096 + wg * 8192, 16, 1024, 1);
      const uint64_t db = make_desc(sb + ((uint32_t)tx & 63) * 4096, 16, 1024, 1);
      wg_fence();
#pragma unroll
      for (int kk = 0; kk < 4; kk++) wgmma_ss160(a, da + 2 * kk, db + 2 * kk, 1);
      wg_commit();
      wg_wait<1>();
      if (kb > 0) { if (rels) mbar_arrive_at(rel); rel += 8; }
      bf += 8; tw >>= 6; tx >>= 6;
      if (kb < 9) mbar_wait(bf, LY);
    }
  }
  if (tid == 0 && wg == 0) PROF(LY ? 19 : 2);
  mbar_wait(BAR(B_LM));
  const uint32_t tag = lds32(sb + MISC_OFF) & 1;
  if (q == 3) st_rlx2(Eb + tb * 1280, tag ^ 1, tag ^ 1);
  float2 lam, mu, mu2;
  float rs0, rs1;
  const uint32_t lamp = sb + LAM_OFF + 16 * (32 * wg + 8 * w + g);
  {
    const uint2* rp = S->RS + (8 * cb + 4 * wg + w) * 16 + 2 * g - (g & 1);
    uint2 v = ld_rlx2(rp);
    asm volatile("ld.shared.v2.f32 {%0,%1},[%2];" : "=f"(lam.x), "=f"(lam.y) : "r"(lamp));
    const float2 l2 = cmul(lam, lam), l4 = cmul(l2, l2), l8 = cmul(l4, l4), l16 = cmul(l8, l8), l32 = cmul(l16, l16);
    mu = full ? cmul(l32, l8) : l32; mu2 = cmul(mu, mu);
#pragma unroll 1
    for (int it = 0; it < SPIN && __any_sync(0xffffffff, untagged(v, tag)); it++) v = ld_rlx2(rp);
    rs0 = untag(v.x); rs1 = untag(v.y);
  }
  if (tid == 0 && wg == 0 && !LY) PROF(39);
  mbar_wait(BAR(B_ST), LY);
  const uint32_t ssm = sb + SSM_OFF + q * (full ? 336 : 272);
  wg_wait<0>(); fence_regs(a);
  if (rels) mbar_arrive_at(rel);
  if (tid == 0 && wg == 0) PROF(LY ? 21 : 5);
  float2 p = make_float2(0.f, 0.f);
#pragma unroll
  for (int j = 0; j < 20; j++) {
    if (j < 16 || full) {
      float4 sv;
      asm volatile("ld.shared.v4.f32 {%0,%1,%2,%3},[%4];" : "=f"(sv.x), "=f"(sv.y), "=f"(sv.z), "=f"(sv.w) : "r"(ssm + 16 * j));
#pragma unroll
      for (int e = 0; e < 2; e++) {
        const int o = 4 * j + e;
        const float r = e ? sv.z : sv.x, nm = e ? sv.w : sv.y;
        a[o] = fmaf(a[o], r, nm * rs0); a[o + 2] = fmaf(a[o + 2], r, nm * rs1);
        p = cfma(lam, p, make_float2(a[o], a[o + 2]));
      }
    }
  }
  {
    float2 t = make_float2(__shfl_up_sync(0xffffffff, p.x, 1, 4), __shfl_up_sync(0xffffffff, p.y, 1, 4));
    if (q >= 1) p = cfma(mu, t, p);
    t = make_float2(__shfl_up_sync(0xffffffff, p.x, 2, 4), __shfl_up_sync(0xffffffff, p.y, 2, 4));
    if (q >= 2) p = cfma(mu2, t, p);
  }
  if (q == 3 && full) st_rlx2(Eb + tb * 1280, tagf(p.x, tag), tagf(p.y, tag));
  if (tid == 0 && wg == 1) PROF(96 + 64 * LY);
  uint2 ev[3];
#pragma unroll
  for (int i = 0; i < 3; i++) { const int j = tb - 1 - q - 4 * i; ev[i] = j >= 0 ? ld_rlx2(Eb + j * 1280) : make_uint2(tag, tag); }
  float2 x = make_float2(__shfl_up_sync(0xffffffff, p.x, 1, 4), __shfl_up_sync(0xffffffff, p.y, 1, 4));
  if (q == 0) x = make_float2(0.f, 0.f);
  float c0, c1;
  asm volatile("ld.shared.v2.f32 {%0,%1},[%2+8];" : "=f"(c0), "=f"(c1) : "r"(lamp));
  const float c2 = -flip(c1, H.swap), c3 = flip(c0, H.swap);
#pragma unroll
  for (int i = 0; i < 40; i++) {
    const int o = 4 * (i >> 1) + (i & 1);
    const float u = a[o], v = a[o + 2];
    a[o] = fmaf(c0, u, c1 * v); a[o + 2] = fmaf(c2, u, c3 * v);
  }
  fence_regs(a);
  if (LY == 0 && R.b() < 128) {
    const int t0 = 16 * g + 8 * wg + 2 * w;
    if (tid == 0 && wg == 1) PROF(366);
    mbar_wait(BAR(B_XR));
    if (tid == 0 && wg == 1) PROF(367);
    uint4 s = lds4(sb + XR_OFF + 20480 + 256 + 8 * t0);
    if (__any_sync(0xffffffff, untagged(s, tag))) {
#pragma unroll 1
      for (int it = 0; it < SPIN; it++) { s = ld_rlx4(S->S + 128 * (R.b() >> 3) + t0); if (!__any_sync(0xffffffff, untagged(s, tag))) break; }
    }
    resid_load(xr, sb, wg, tid, s);
  }
  float2 mq, om4, fq;
  {
    asm volatile("" : "+f"(lam.x), "+f"(lam.y));
    const float2 one = make_float2(1.f, 0.f), l2 = cmul(lam, lam), l4 = cmul(l2, l2), l8 = cmul(l4, l4), l16 = cmul(l8, l8);
    const float2 l80 = full ? mu2 : cmul(mu2, l16), om = cmul(l80, l80), om2 = cmul(om, om);
    mq = cmul((q & 1) ? mu : one, (q & 2) ? mu2 : one);
    om4 = cmul(om2, om2); fq = cmul((q & 1) ? om : one, (q & 2) ? om2 : one);
  }
  mbar_wait(BAR(B_E1 + 9), LY);
  if (tid == 0 && wg == 1) PROF(368 + LY);
#pragma unroll 1
  for (int it = 0; it < SPIN; it++) {
    const bool m0 = untagged(ev[0], tag), m1 = untagged(ev[1], tag), m2 = untagged(ev[2], tag);
    if (!__any_sync(0xffffffff, m0 || m1 || m2)) break;
    if (m0) ev[0] = ld_rlx2(Eb + (tb - 1 - q) * 1280);
    if (m1) ev[1] = ld_rlx2(Eb + (tb - 5 - q) * 1280);
    if (m2) ev[2] = ld_rlx2(Eb + (tb - 9 - q) * 1280);
  }
  if (tid == 0 && wg == 1) PROF(97 + 64 * LY);
  float2 c = make_float2(untag(ev[2].x), untag(ev[2].y));
#pragma unroll
  for (int i = 1; i >= 0; i--) c = cfma(om4, c, make_float2(untag(ev[i].x), untag(ev[i].y)));
  c = cmul(fq, c);
#pragma unroll
  for (int s = 1; s <= 2; s <<= 1) { c.x += __shfl_xor_sync(0xffffffff, c.x, s); c.y += __shfl_xor_sync(0xffffffff, c.y, s); }
  c = cfma(mq, c, x);
  float2 z = make_float2(fmaf(c0, c.x, c1 * c.y), fmaf(c2, c.x, c3 * c.y));
  if (tid == 0 && wg == 0) PROF(LY ? 22 : 6);
  const float2 lc = make_float2(lam.x, flip(lam.y, H.swap));
  const uint32_t hq = sb + (lane >> 4) * 1024 + (lane & 7) * 128 + (((4 * wg + w) ^ (lane & 7)) << 4);
  const uint32_t hp = hq + R_OFF + (lane & 8) * 2048, hp4 = hq + (LY ? R4_OFF1 : R4_OFF0) + (lane & 8) * 512;
#pragma unroll
  for (int j = 0; j < 20; j += 2) {
    if (j < 16 || full) {
      uint32_t o[4];
#pragma unroll
      for (int i = 0; i < 2; i++) {
        const float2 z0 = cfma(lc, z, make_float2(a[4 * (j + i)], a[4 * (j + i) + 2]));
        z = cfma(lc, z0, make_float2(a[4 * (j + i) + 1], a[4 * (j + i) + 3]));
        o[2 * i] = pack_bf(z0.x, z.x); o[2 * i + 1] = pack_bf(z0.y, z.y);
      }
      asm volatile("stmatrix.sync.aligned.m8n8.x4.trans.shared.b16 [%0], {%1,%2,%3,%4};" ::"r"(j < 16 ? hp + j * 1024 : hp4 + (j - 16) * 1024), "r"(o[0]), "r"(o[1]), "r"(o[2]), "r"(o[3]) : "memory");
      if (j & 2) { __syncwarp(); if (lane == 0) mbar_arrive(BAR(B_SH + j / 4)); }
    }
  }
  if (tid == 0 && wg == 0) PROF(LY ? 23 : 7);
  if (lane == 0) PROF(390 + 4 * wg + w);
}

__device__ __forceinline__ void gate_load(uint32_t (&G)[20], uint32_t sb, int LY, int wg, int tid) {
  const uint32_t bars = sb + BAR_OFF;
  const int lane = tid & 31, w = tid >> 5;
  mbar_wait(BAR(B_GF), LY);
  __syncwarp();
  {
    const uint32_t gb = sb + (LY ? G_OFF1 : G_OFF0) + wg * 10240;
    const int dr = 4 * ((lane & 7) >> 1) + (lane & 1) + 2 * ((lane >> 3) & 1), ck = 2 * w + (lane >> 4);
#pragma unroll
    for (int J = 0; J < 5; J++) {
      const int dd = 16 * J + dr;
      asm volatile("ldmatrix.sync.aligned.m8n8.x4.trans.shared.b16 {%0,%1,%2,%3},[%4];"
                   : "=r"(G[4 * J]), "=r"(G[4 * J + 1]), "=r"(G[4 * J + 2]), "=r"(G[4 * J + 3]) : "r"(gb + dd * 128 + ((ck ^ (dd & 7)) << 4)) : "memory");
    }
  }
}
__device__ __forceinline__ void g2_phase(const int LY, const Params& P, Scratch* S, uint32_t sb, int wg, int tid, Role R, float (&xr)[40], long long t_start) {
  sb = opaque(sb);
  const uint32_t bars = sb + BAR_OFF;
  if (LY) {
    const int td = opaque(tid), b = (opaque(R.v) >> 8) & 255;
    const uint32_t tag = lds32(sb + MISC_OFF) & 1;
    const uint2* sp = S->S + 2 * SEQ + 128 * (b >> 3) + 4 * (td & 28) + 8 * wg + 2 * (td >> 5);
    if (!(R.cb() & 1)) mbar_wait(BAR(B_HD), 1);
    uint2 dl[5];
#pragma unroll
    for (int J = 0; J < 5; J++) dl[J] = __ldg((const uint2*)(P.dskip + 80 * (b & 7) + 4 * (td & 3) + 16 * J));
    uint4 sv;
#pragma unroll 1
    for (int it = 0; it < SPIN; it++) { sv = ld_rlx4(sp); if (!__any_sync(0xffffffff, untagged(sv, tag))) break; }
#pragma unroll
    for (int h = 0; h < 2; h++)
#pragma unroll
      for (int J = 0; J < 5; J++)
#pragma unroll
        for (int c = 0; c < 4; c++) {
          const float x2 = xr[IDX(J, c, h)];
          const uint32_t dw = (c & 2) ? dl[J].y : dl[J].x;
          xr[IDX(J, c, h)] = fmaf(fmaf(x2, untag(h ? sv.z : sv.x), untag(h ? sv.w : sv.y)), (c & 1) ? bf_hi(dw) : bf_lo(dw), x2);
        }
    fence_regs(xr);
  }
  float acc[40];
#pragma unroll
  for (int i = 0; i < 40; i++) acc[i] = RIAT == 1 ? 0.f : xr[i];
  fence_regs(acc);
#define G2_STEP(st, cs, hf) { \
    const uint64_t da = make_desc(sb + H_OFF + (st) * 32768 + (hf) * 16384 + wg * 8192, 16, 1024, 1), db = make_desc(sb + (cs) * 20480 + (hf) * 10240, 16, 1024, 1); \
    wg_fence(); \
    _Pragma("unroll") for (int kk = 0; kk < 4; kk++) wgmma_ss80(acc, da + 2 * kk, db + 2 * kk, 1); \
    wg_commit(); }
  mbar_wait(BAR(B_F2), LY);
  if (tid == 0 && wg == 0) PROF(LY ? 25 : 10);
  G2_STEP(0, 0, 0)
  mbar_wait(BAR(B_F3), LY);
  G2_STEP(0, 0, 1)
  tid = opaque(tid); R.v = opaque(R.v);
  const uint32_t tag = lds32(sb + MISC_OFF) & 1;
  const int b = R.b(), tb2 = b >> 3, db_ = b & 7;
  const int w = tid >> 5, lane = tid & 31, g = lane >> 2, q = lane & 3;
  const int t0 = 128 * tb2 + 16 * g + 8 * wg + 2 * w;
  const int d0 = 80 * db_ + 4 * q, mrow = 64 * wg + 16 * w + g;
#define GATE(J, c, h) (((c) & 1) ? bf_hi(G[4 * (J) + 2 * (h) + ((c) >> 1)]) : bf_lo(G[4 * (J) + 2 * (h) + ((c) >> 1)]))
  uint32_t rel = mapa(BAR(B_E2), lane ? ((w & 1) ? R.wpart() : R.rank()) : R.cs() == 8 ? 4 * wg + w : wg);
  const bool rels = lane == 0 || (lane == 1 && w < 2);
  uint32_t* Mb = S->M + ((2 * LY * 16 + tb2) * 8) * 256 + (wg * 4 + w) * 32 + (2 * g + (q & 1)) * 2 + (q >> 1);
  {
    uint32_t bf = BAR(B_F2 + 1), st = 1, ra = rel + 8 * (B_EA - B_E2);
    const int lag = wg ? (LY ? STG : STG0) / 2 : 0;
#pragma unroll 1
    for (int kp = 1; kp < 10; kp++) {
      const bool more = LY == 0 || kp < 8;
      wg_wait<1>();
      if (lane == 0 && more) mbar_arrive_at(ra + 8 * (st ? st - 1 : 2));
      mbar_wait(bf, LY);
      if (STG && !(STG & 1) && kp == lag) bar_sync(5, 256);
      G2_STEP(st, kp < 5 ? kp : kp - 5, 0)
      wg_wait<1>();
      if (rels && more) mbar_arrive_at(rel);
      rel += 8;
      mbar_wait(bf + 8 * (B_F3 - B_F2), LY);
      if ((STG & 1) && kp == lag) bar_sync(5, 256);
      G2_STEP(st, kp < 5 ? kp : kp - 5, 1)
      if (kp == MIAT) {
        st_rlx(Mb + db_ * 256, tag ^ 1);
        if (LY == 0) st_rlx(Mb + (16 * 8 + db_) * 256, tag ^ 1);
      }
      bf += 8; st = st == 2 ? 0 : st + 1;
    }
  }
  if (STG && (LY || STG0) && !wg) asm volatile("bar.arrive 5, 256;" ::: "memory");
  wg_wait<0>(); fence_regs(acc);
  if (LY == 0 && rels) mbar_arrive_at(rel);
  if (tid == 0 && wg == 0) PROF(LY ? 26 : 11);
  if (lane == 0) PROF(116 + 64 * LY + wg * 4 + w);

  float mm[2] = {0.f, 0.f}, rr[2];
#pragma unroll 1
  for (int rep = 0;; rep++) {
    float m[2][2];
#pragma unroll
    for (int h = 0; h < 2; h++) {
      m[h][0] = m[h][1] = 0.f;
#pragma unroll
      for (int J = 0; J < 5; J++)
#pragma unroll
        for (int c = 0; c < 4; c++) { const float xv = acc[IDX(J, c, h)]; m[h][0] += xv; m[h][1] = fmaf(xv, xv, m[h][1]); }
    }
    float r1[2];
#pragma unroll
    for (int i = 0; i < 2; i++) { const float snd = (q & 1) ? m[0][i] : m[1][i], kp = (q & 1) ? m[1][i] : m[0][i]; r1[i] = kp + __shfl_xor_sync(0xffffffff, snd, 1); }
    const float r2 = ((q & 2) ? r1[1] : r1[0]) + __shfl_xor_sync(0xffffffff, (q & 2) ? r1[0] : r1[1], 2);
    const uint32_t mx = sb + MX_OFF + 512 * wg + 4 * tid, bx = BAR(B_KF + 1 + 2 * LY + wg);
    if (R.cs() == 8 && !rep) {
#pragma unroll
      for (int i = 0; i < 8; i++)
        asm volatile("st.async.weak.shared::cluster.mbarrier::complete_tx::bytes.b32 [%0],%1,[%2];" ::"r"(mapa(mx + 1024 * db_, i ^ db_)), "f"(r2), "r"(mapa(bx, i ^ db_)) : "memory");
      if (tid == 0) mbar_expect_tx(bx, 4096);
    }
    st_rlx(Mb + db_ * 256, tagf(r2, tag));
    if (rep) break;
    if (lane == 0) PROF(100 + 64 * LY + wg * 4 + w);
    uint32_t G[20];
    const bool late = LY == 0 && db_ >= GLATE;
#pragma unroll
    for (int i = 0; i < 20; i++) G[i] = 0;
    if (!late) gate_load(G, sb, LY, wg, tid);
    mbar_wait(BAR(B_CD + 1));
    uint32_t mv[8];
    if (R.cs() == 8) {
      mbar_wait(bx, 1);
#pragma unroll
      for (int i = 0; i < 8; i++) mv[i] = lds32(mx + 1024 * i);
    } else {
#pragma unroll
    for (int i = 0; i < 8; i++) mv[i] = ld_rlx(Mb + i * 256);
#pragma unroll 1
    for (int it = 0; it < SPIN; it++) {
      uint32_t miss = 0;
#pragma unroll
      for (int i = 0; i < 8; i++) miss |= ((mv[i] ^ tag) & 1) << i;
      if (!__any_sync(0xffffffff, miss)) break;
#pragma unroll
      for (int i = 0; i < 8; i++) if ((miss >> i) & 1) mv[i] = ld_rlx(Mb + i * 256);
    }
      if (MBAR || !LY) bar_sync(4, 256);
    }
    if (lane == 0) PROF(108 + 64 * LY + wg * 4 + w);
    const float s = ((untag(mv[0]) + untag(mv[1])) + (untag(mv[2]) + untag(mv[3]))) + ((untag(mv[4]) + untag(mv[5])) + (untag(mv[6]) + untag(mv[7])));
    const float o = __shfl_xor_sync(0xffffffff, s, 2);
    const float S1 = (q & 2) ? o : s, S2 = (q & 2) ? s : o;
    const float mean = S1 * (1.f / DM), rs = frsqrt(fmaxf(S2 * (1.f / DM) - mean * mean, 0.f) + 1e-5f);
    const float mo = __shfl_xor_sync(0xffffffff, mean, 1), ro = __shfl_xor_sync(0xffffffff, rs, 1);
    mm[0] = (q & 1) ? mo : mean; mm[1] = (q & 1) ? mean : mo; rr[0] = (q & 1) ? ro : rs; rr[1] = (q & 1) ? rs : ro;
    if (late) gate_load(G, sb, LY, wg, tid);
    if (tid == 0 && wg == 0) PROF(LY ? 27 : 12);
    const float nm[2] = {-mm[0] * rr[0], -mm[1] * rr[1]};
    if (LY) mm[0] = mm[1] = 0.f;
#pragma unroll
    for (int h = 0; h < 2; h++)
#pragma unroll
      for (int J = 0; J < 5; J++)
#pragma unroll
        for (int c = 0; c < 4; c++) { const float xv = acc[IDX(J, c, h)]; acc[IDX(J, c, h)] = fmaf(fmaf(xv, rr[h], nm[h]), GATE(J, c, h), xv - mm[h]); }
    if (LY) break;
    if (R.cs() == 8) mbar_wait(BAR(B_KF + 1), 1);
#pragma unroll
    for (int i = 0; i < 10; i++) {
      const int J = i >> 1, h = i & 1;
      const uint32_t u0 = pack_bf(acc[IDX(J, 0, h)], acc[IDX(J, 1, h)]), u1 = pack_bf(acc[IDX(J, 2, h)], acc[IDX(J, 3, h)]);
      asm volatile("st.shared.v2.u32 [%0],{%1,%2};" ::"r"(sb + US_OFF + ((mrow ^ 64) + 8 * h) * 160 + 32 * J + 8 * q), "r"(u0), "r"(u1) : "memory");
    }
    __syncwarp();
    if (lane == 0) mbar_arrive(BAR(B_GS + 1 + wg));
    if (tid == 0 && wg == 0) PROF(13);
    Mb += 16 * 8 * 256;
  }
  if (LY == 0) {
#pragma unroll
    for (int i = 0; i < 40; i++) xr[i] = acc[i] + mm[(i >> 1) & 1];
    if (tid == 0 && wg == 0) PROF(15);
  }
  else {
    float* op = P.out + (size_t)t0 * DM + d0;
#pragma unroll
    for (int i = 0; i < 10; i++) {
      const int J = i >> 1, h = i & 1;
      asm volatile("st.global.v4.f32 [%0],{%1,%2,%3,%4};" ::"l"(op + h * DM + 16 * J),
                   "f"(acc[IDX(J, 0, h)]), "f"(acc[IDX(J, 1, h)]), "f"(acc[IDX(J, 2, h)]), "f"(acc[IDX(J, 3, h)]) : "memory");
    }
  }
  if (tid == 0 && wg == 0 && LY) PROF(28);
#undef IDX
#undef GATE
}

__device__ __forceinline__ void next_stats(Scratch* S, uint32_t sb, int tb2, int tid) {
  const uint32_t bars = sb + BAR_OFF, tag = lds32(sb + MISC_OFF) & 1;
  const uint32_t* Mb = S->M + tb2 * 8 * 256 + 2 * tid;
  mbar_wait(BAR(B_F1 + NSAT), 1);
  float m1, s1, s2;
#pragma unroll 1
  for (int it = 0; it < SPIN; it++) {
    uint32_t a[8], miss = 0;
    uint2 v[8];
#pragma unroll
    for (int i = 0; i < 8; i++) { a[i] = ld_rlx(Mb + i * 256); v[i] = ld_rlx2((const uint2*)(Mb + (16 * 8 + i) * 256)); }
#pragma unroll
    for (int i = 0; i < 8; i++) miss |= (a[i] ^ tag) | (v[i].x ^ tag) | (v[i].y ^ tag);
#define SUM8(F) ((untag(F(0)) + untag(F(1))) + (untag(F(2)) + untag(F(3)))) + ((untag(F(4)) + untag(F(5))) + (untag(F(6)) + untag(F(7))))
#define FA(i) a[i]
#define FX(i) v[i].x
#define FY(i) v[i].y
    m1 = SUM8(FA); s1 = SUM8(FX); s2 = SUM8(FY);
    if (!__any_sync(0xffffffff, miss & 1)) break;
  }
  const float mean = s1 * (1.f / DM), rs = frsqrt(fmaxf(s2 * (1.f / DM) - mean * mean, 0.f) + 1e-5f);
  uint2* sp = S->S + SEQ + 128 * tb2 + 8 * (tid & 14) + 2 * (tid >> 4) + (tid & 1);
  st_rlx2(sp, tagf(rs, tag), tagf(-mean * rs, tag));
  st_rlx2(sp + SEQ, tagf(rs, tag), tagf(-(mean + m1 * (1.f / DM)) * rs, tag));
}
template <int I0, int I1> __device__ __forceinline__ void init_barriers(uint32_t bars) {
#pragma unroll
  for (int i = I0; i < I1; i++) mbar_init(BAR(i), bar_count(i));
}
__device__ __forceinline__ int g2_cb(int kp) { return kp < 5 ? 2 * kp : 2 * kp - 9; }
__device__ __forceinline__ const unsigned* h_flag(Scratch* S, int ly, int tb2, int lane) {
  const int s0 = 128 * min(tb2, 15) / 160;
  const bool two = (128 * tb2 + 127) / 160 != s0;
  return &S->flag[(F_H + (ly * 13 + s0) * 10 + min(lane & 15, 9) + (two && lane >= 16 ? 10 : 0)) * 32];
}
__device__ __forceinline__ void gate_tile(const Params& P, uint32_t dst, uint32_t bar, int tb2, int db) {
  mbar_expect_tx(bar, 20480);
  tma2d(dst, &P.mGT, tb2 * 128, db * 80, bar);
  tma2d(dst + 10240, &P.mGT, tb2 * 128 + 64, db * 80, bar);
}
__global__ void __cluster_dims__() __launch_bounds__(512, 1) fused_kernel(const Head H, const __grid_constant__ Params P) {
  extern __shared__ __align__(1024) uint8_t smem[];
  const uint32_t sb = opaque(smem_u32(smem)), bars = sb + BAR_OFF;
  const int wi = __shfl_sync(0xffffffff, threadIdx.x >> 5, 0), wg = wi >> 2, tid = threadIdx.x & 127;
  const int umap = blockIdx.x >= 96;
#define CLK(v)
  CLK(c_a);
  if (wi == 14) {
    if (elect_one()) { init_barriers<0, NBAR1>(bars); asm volatile("fence.mbarrier_init.release.cluster;" ::: "memory"); }
    __syncwarp();
  } else if (wi >= 12) prefetch_map(wi == 12 ? &P.mB : &P.mA[umap]);
  else if (wg == 2) xb_prefetch<1>(H, blockIdx.x + H.base, tid, 0);
  else if (P.role[blockIdx.x].w) return;
  CLK(c_b);
  asm volatile("barrier.cluster.arrive.relaxed.aligned;" ::: "memory");
  CLK(c_c);
  Role R;
  { const uint4 r = P.role[blockIdx.x]; R.v = r.x; R.c = r.y; R.p = r.z; }
  const int id = R.c & 255;
  const int tb = R.tb(), cb = R.cb(), b = R.b(), tb2 = b >> 3, db = b & 7, rank = R.rank();
  const bool has1 = tb <= 12, has2 = b < 128, full = tb < 12;
  Scratch* const S = H.s;
  unsigned* const epoch_p = &S->epoch[id * 8];
  const long long t_start = 0;
  if (wg < 2) {
    if (threadIdx.x == 0) PROF(50);
    asm volatile("griddepcontrol.launch_dependents;");
    bar_sync(6, 448);
    asm volatile("setmaxnreg.inc.sync.aligned.u32 176;");
    float xr[40];
#pragma unroll
    for (int i = 0; i < 40; i++) xr[i] = 0.f;
#pragma unroll 1
    for (int ly = 0; ly < 2; ly++) {
      if (has1) g1_phase(ly, H, sb, wg, tid, R, xr, t_start);
      if (ly == 0) {
        resid_init(xr); fence_regs(xr);
        conv_loop<false>(sb, R.c, wg, tid, t_start);
        if (tid == 0 && wg == 0) PROF(9);
      }
      if (has2) g2_phase(ly, P, S, sb, wg, tid, R, xr, t_start);
    }
    if (tid == 0 && wg == 0) st_rlx(epoch_p, lds32(sb + MISC_OFF));
  } else if (wg == 2) {
    bar_sync(6, 448);
    if (has1) aux_prep(H, P, sb, R, tid, t_start);
    asm volatile("setmaxnreg.inc.sync.aligned.u32 136;");
    conv_loop<true>(sb, R.c, wg, tid, t_start);
    if (tid == 0) PROF(44);
    {
      const uint32_t bb = (P.role[blockIdx.x].x >> 8) & 255;
      if ((bb & 132) == NSDB && tid < 32) next_stats(H.s, sb, bb >> 3, 32 * (bb & 3) + tid);
    }
  } else {
    if (threadIdx.x == 384) PROF(354);
    asm volatile("setmaxnreg.dec.sync.aligned.u32 24;");
    const int wlo = R.wlo(), whi = R.whi();
    const uint32_t wmask = R.wmask(), umask = R.umask(), f1bytes = full ? 36864 : 32768;
    if (wi < 14) {
      if (threadIdx.x == 384) PROF(340);
      asm volatile("barrier.cluster.wait.aligned;" ::: "memory");
      if (has1 && elect_one()) {
        uint64_t tab = wi == 12 ? WTAB0 : XTAB0;
        PROF(329 + wi);
#pragma unroll 1
        for (int kb = 0; kb < 6; kb++, tab >>= 6) {
          const uint32_t dst = sb + ((uint32_t)tab & 63) * 4096;
          if (wi == 12) {
#pragma unroll 1
            for (int h = wlo; h <= whi; h++) tma4d_mc(dst + h * 8192, &P.mB, kb * 64, 0, 0, 8 * cb + 4 * h, BAR(B_F1 + kb), wmask);
          } else {
            tma4d_mc(dst + R.uj() * 1024, &P.mA[umap], kb * 64, 0, 0, 80 * tb + R.uj(), BAR(B_F1 + kb), umask);
            mbar_expect_tx(BAR(B_F1 + kb), f1bytes);
          }
        }
      }
      if (!has1 && wi == 13) bar_sync(7, 64);
    } else {
      if (wi == 15 && elect_one()) { init_barriers<NBAR1, NBAR>(bars); asm volatile("fence.mbarrier_init.release.cluster;" ::: "memory"); }
      bar_sync(6, 448);
      if (!has1 && wi == 14) bar_sync(7, 64);
    }
    const unsigned e1 = ld_rlx(epoch_p) + 1;
    if (wi == 12) {
      if (elect_one()) {
#pragma unroll 1
        for (int ly = 0; ly < 2; ly++) {
#pragma unroll 1
          for (int i = ly ? 0 : 6; i < 10 && has1; i++) {
            const int kb = (0x9876541032ull >> (4 * i)) & 15;
            if (ly == 0) { mbar_wait(BAR(B_E1 + ((DEP0 >> (4 * kb - 24)) & 15))); mbar_wait(BAR(B_AX + (kb == 9))); }
            else {
              if (has2 && i == (db >= GLATE ? 4 : 2)) {
                wait_cnt(&S->cnt[(C_G + db) * 32], e1 * 80);
                mbar_wait(BAR(B_E2 + 7));
                PROF(47);
                gate_tile(P, sb + G_OFF0, BAR(B_GF), tb2, db);
              }
              if (has2) mbar_wait(BAR(i < 4 ? B_E2 + ((0x9865u >> (4 * i)) & 15) : B_GE));
              else if (i == 0) { mbar_wait(BAR(B_E1 + 9)); mbar_wait(BAR(B_CD + 1)); }
              if (i >= 4) mbar_wait(BAR(i < 6 ? B_F1 + W4AT : B_E1 + i - 6), 1);
            }
            const uint32_t dst = sb + ((uint32_t)((ly ? WTAB1 : WTAB0) >> (6 * kb)) & 63) * 4096;
#pragma unroll 1
            for (int h = wlo; h <= whi; h++) tma4d_mc(dst + h * 8192, &P.mB, kb * 64, 0, 0, 8 * cb + 4 * h, BAR(B_F1 + kb), wmask);
          }
          if (has2) {
            if (ly == 0) {
              mbar_wait(BAR(B_E1 + XRAT));
              mbar_expect_tx(BAR(B_XR), 20480 + 160 + 1024);
              tma4d(sb + XR_OFF, &P.mX, 80 * db, tb2, BAR(B_XR));
              bulk_g2s(sb + XR_OFF + 20480, P.dskip + 80 * db, 160, BAR(B_XR));
              bulk_g2s(sb + XR_OFF + 20480 + 256, S->S + 128 * tb2, 1024, BAR(B_XR));
              if (CWAIT) mbar_wait(BAR(CWAIT == 1 ? B_KF + 2 : CWAIT == 2 ? B_KF + R.nch() - 1 : CWAIT == 3 ? B_KF + R.nch() - 2 : B_HD));
            }
#pragma unroll 1
            for (int kp = 0; kp < 10; kp++) {
              const uint32_t dst = sb + (kp < 5 ? kp : kp - 5) * 20480;
              mbar_wait(BAR(kp >= 5 ? B_E2 + kp - 5 : ly ? B_E1 + ((CTAB1 >> (4 * kp)) & 15) : kp < 3 ? B_SH : kp < 4 ? B_HD : B_CD), ly);
              mbar_expect_tx(BAR(B_F2 + kp), 10240 + 16384);
              tma5d(dst, &P.mC[0], g2_cb(kp) * 64, db * 5, BAR(B_F2 + kp));
              mbar_expect_tx(BAR(B_F3 + kp), 10240 + 16384);
              tma5d(dst + 10240, &P.mC[1], g2_cb(kp) * 64, db * 5, BAR(B_F3 + kp));
              if (ly && kp == 4) { mbar_wait(BAR(B_E1 + 9), 1); gate_tile(P, sb + G_OFF1, BAR(B_GF), tb2, db); }
            }
          }
        }
      }
    } else if (wi == 13) {
      const int h0 = R.cs() == 8 ? rank : 4 * rank;
#pragma unroll 1
      for (int ly = 0; ly < 2; ly++) {
        int lane = lane_id();
        if (has1) {
          const unsigned* fp = &S->flag[(F_U3 + 8 * ((160 * tb) >> 7) + (lane & (full ? 15 : 7))) * 32];
          uint32_t ready = ly ? __ballot_sync(0xffffffff, ld_rlx(fp) == e1) : ~0u;
          if (ly) mbar_wait(BAR(full ? B_KF + 1 : has2 ? B_GS + 1 : B_RF1), has2);
          if (ly && full) mbar_wait(BAR(B_KF + 2), 1);
#pragma unroll 1
          for (int kb = ly ? 0 : 6; kb < 10; kb++) {
            if (ly && kb == UPAT) { mbar_wait(BAR(B_XR)); ready = ~0u; }
            wait_flags(fp, e1, 0x101u * ((1u << (64 * kb / 80)) | (1u << ((64 * kb + 63) / 80))), ready);
            if (kb >= 4) mbar_wait(BAR(B_E1 + (ly ? kb - 4 : (DEP0 >> (4 * kb - 24)) & 15)), ly);
            mbar_wait(BAR(B_AX + (kb == 9)));
            if (elect_one()) {
              if (ly && kb == 0) PROF(34);
              tma4d_mc(sb + ((uint32_t)((ly ? XTAB1 : XTAB0) >> (6 * kb)) & 63) * 4096 + R.uj() * 1024, &P.mA[2 * ly + umap], kb * 64, 0, 0, 80 * tb + R.uj(),
                       BAR(B_F1 + kb), umask);
              mbar_expect_tx(BAR(B_F1 + kb), f1bytes);
            }
            __syncwarp();
          }
        }
        if (ly == 0) {
          if (has1) mbar_wait(BAR(B_E1 + KPF));
          if (elect_one()) {
#pragma unroll 1
            for (int s = 0; s < R.nch(); s++) prefetch_l2(P.ssmk + (size_t)R.ch(s) * SEQ, 4096);
          }
          lane = lane_id();
#pragma unroll
          for (int s = 0; s < 5; s++) {
            asm volatile("st.shared.v4.u32 [%0],{%1,%1,%1,%1};" ::"r"(conv_buf(sb, s) + 16 * lane), "r"(0) : "memory");
            asm volatile("st.shared.u8 [%0],%1;" ::"r"(conv_buf(sb, s) + KC_OFS + lane), "r"(0) : "memory");
          }
          fence_async();
          __syncwarp();
          const unsigned* cp = &S->cnt[(C_KV + (R.ch(min(lane, R.nch() - 1)) >> 6)) * 32];
          uint32_t ready = 0;
#pragma unroll 1
          for (int s = 0, sk = 0; s < R.nch(); s++) {
#pragma unroll 1
            for (; sk < (s ? R.nch() : KUP); sk++)
              if (elect_one()) { mbar_expect_tx(BAR(B_KF + sk), 8192); bulk_g2s(conv_buf(sb, sk) + KC_OFS + 32, P.ssmk + (size_t)R.ch(sk) * SEQ, 4096, BAR(B_KF + sk)); }
            PROFC(s == 0, 329);
#pragma unroll 1
            for (int it = 0; !((ready >> s) & 1) && it < SPIN; it++) ready = __ballot_sync(0xffffffff, (int)(ld_rlx(cp) - e1 * 32) >= 0);
            PROFC(s == 0, 30);
            if (elect_one()) {
              bulk_g2s(conv_buf(sb, s) + KV_PAD, S->kv + (size_t)R.ch(s) * SEQ, 4096, BAR(B_KF + s));
              if (s == 0 && has2) { prefetch_l2(P.cre + (size_t)5 * b * DM, 5 * DM * 2); prefetch_l2(P.cim + (size_t)5 * b * DM, 5 * DM * 2); }
            }
            __syncwarp();
          }
          PROF(31);
          if (!has1) return;
        }
        lane = lane_id();
        const unsigned* fp = h_flag(S, ly, tb2, lane);
        uint32_t ready = __ballot_sync(0xffffffff, ld_rlx(fp) == e1), st = 0;
        if (ly == 0 && !has2) {
          mbar_wait(BAR(B_HD));
          if (lane < 8) mbar_arrive_cl(BAR(B_RF1), lane & 1);
        }
        if (has2) {
          mbar_wait(BAR(B_RF0), ly);
#pragma unroll 1
          for (int kp = 0; kp < 10; kp++) {
            if (kp == 5) { mbar_wait(BAR(B_XR), 1); ready = ~0u; }
            if (kp == 2) { mbar_wait(BAR(B_HD), ly); if (lane < 8) mbar_arrive_cl(BAR(B_RF1), lane & (R.cs() - 1)); }
            wait_flags(fp, e1, 0x10001u << g2_cb(kp), ready);
            if (kp == 2) mbar_wait(BAR(B_RF1), ly);
#pragma unroll
            for (int hf = 0; hf < 2; hf++) {
              if (kp >= 3) { if (hf) mbar_wait(BAR(B_E2 + kp - 3), ly); else mbar_wait(BAR(B_EA + st), ly ^ (kp >= 6 && kp < 9)); }
              if (elect_one()) {
                if (kp == 0 && !hf) PROF(33 + 2 * ly);
                tma4d_mc(sb + H_OFF + st * 32768 + hf * 16384 + h0 * 2048, &P.mH, g2_cb(kp) * 128 + hf * 64, 0, 2 * h0,
                         ly * 16 + tb2, BAR((hf ? B_F3 : B_F2) + kp), (1u << R.cs()) - 1);
              }
              __syncwarp();
            }
            st = st == 2 ? 0 : st + 1;
          }
        }
      }
    } else if (wi == 14) {
      if (!has1) return;
      prefetch_if(P.dskip + 64 * (tid & 31), (tid & 31) < 10);
      if (elect_one()) { prefetch_map(&P.sK); prefetch_map(&P.mX); prefetch_map(&P.sH); prefetch_map(&P.sU); prefetch_map(&P.mC[0]); prefetch_map(&P.mC[1]); prefetch_map(&P.mH); prefetch_map(&P.mGT); prefetch_map(&P.mA[2 + umap]); }
      __syncwarp();
#pragma unroll 1
      for (int ly = 0; ly < 2; ly++) {
        if (ly) {
          mbar_wait(BAR(B_F1 + 1), 1);
          uint32_t ready = 0;
          wait_flags(&S->flag[(F_U3 + 8 * ((160 * tb) >> 7) + ((lane_id() + ly) & (full ? 15 : 7))) * 32], e1, ~0u, ready);
          if (elect_one()) mbar_arrive(BAR(B_XR));
        }
        const int lane = lane_id();
        mbar_wait(BAR(B_E1 + (ly ? STAT_AT1 : STAT_AT)), ly);
        PROFC(lane == 0 && ly == 0, 36);
        {
          const int l = lane - (full ? 0 : 16);
          const uint2* p = S->S + ly * SEQ + 160 * tb + 2 * l;
          uint4 v[3];
#pragma unroll 1
          for (int it = 0; it < SPIN; it++) {
            v[0] = ld_rlx4(p); v[1] = ld_rlx4(p + 64); v[2] = ld_rlx4(p + 96);
            const bool miss = __any_sync(0xffffffff, untagged(v[0], e1 & 1) | untagged(v[1], e1 & 1) | untagged(v[2], e1 & 1));
            PROFC(lane == 0 && ly == 0 && it == 0, 37);
            if (!miss) break;
          }
          PROFC(lane == 0 && ly == 0, 38);
#pragma unroll
          for (int i = 0; i < 3; i++) {
            const int pr = l + (i == 2 ? 48 : 32 * i);
            if (pr >= 0) asm volatile("st.shared.v4.u32 [%0],{%1,%2,%3,%4};" ::"r"(sb + SSM_OFF + 16 * (pr + ((pr * (full ? 205 : 256)) >> 12))), "r"(v[i].x & ~1u),
                                      "r"(v[i].y & ~1u), "r"(v[i].z & ~1u), "r"(v[i].w & ~1u) : "memory");
          }
          __syncwarp();
        }
        if (lane == 0) mbar_arrive(BAR(B_ST));
        if (ly && has2) {
          mbar_wait(BAR(B_E1 + 9), 1);
          if (lane < 8) mbar_arrive_cl(BAR(B_RF0), lane & (R.cs() - 1));
        }
        if (lane == 0) {
#pragma unroll 1
          for (int pc = 0; pc < (full ? 5 : 4); pc++) {
            if ((HWM >> (4 * pc)) & 8) {
              mbar_wait(BAR(B_SH + min((HWM >> (4 * pc)) & 7, full ? 4 : 3)), ly);
              PROF(380 + 5 * ly + pc);
              if (pc == 0 && (cb & 1)) delay(ly ? HDLY : HDLY0);
              fence_async();
            }
#pragma unroll
            for (int i = 0; i < 2; i++) tma4d_store(&P.sH, sb + (pc < 4 ? R_OFF + i * 16384 + pc * 4096 : (ly ? R4_OFF1 : R4_OFF0) + i * 4096), 128 * cb + 64 * i, 0, 0, ly * 1024 + 80 * tb + 4 * pc);
          }
          bulk_commit(); bulk_wait();
          PROF(ly ? 17 : 16);
          mbar_arrive(BAR(B_HD));
          release<1>();
          signal_flag(&S->flag[(F_H + (ly * 13 + tb) * 10 + cb) * 32], e1);
          PROF(ly ? 24 : 8);
        }
        __syncwarp();
        if (has2) {
          mbar_wait(BAR(B_F2 + FPAT), ly);
          uint32_t ready = 0;
          wait_flags(h_flag(S, ly, tb2, lane_id() | 1), e1, ~0u, ready);
          if (elect_one()) mbar_arrive(BAR(B_XR));
        }
        if (lane == 0 && has2 && !ly) {
          mbar_wait(BAR(B_CD + 1));
#pragma unroll
          for (int i = 0; i < 2; i++) {
            mbar_wait(BAR(B_GS + 1 + i), 1);
            fence_async();
            tma4d_store(&P.sU, sb + US_OFF + 10240 - 10240 * i, 80 * db, 0, 8 * i, tb2);
          }
          bulk_commit(); bulk_wait();
          PROF(18); mbar_arrive(BAR(B_GE)); mbar_arrive_cl(BAR(B_GE), R.wpart()); release<2>(); signal_flag(&S->flag[(F_U3 + b) * 32], e1);
          PROF(14);
        }
        __syncwarp();
      }
    } else {
      discretise(H, P, sb, R, tid & 31, e1);
      if (elect_one()) {
        mbar_arrive(BAR(B_LM));
        PROF(348);
        if (b < R.nprep()) {
#pragma unroll 1
          for (int task = b, r = 0; task < 320; task += R.nprep(), r++) {
            mbar_wait(BAR(B_PS + r));
            PROF(320 + 3 * r);
            fence_async();
            tma2d_store(&P.sK, sb + KS_OFF + r * 8192, 64 * (task & 31), 64 * (task >> 5));
            bulk_commit(); bulk_wait();
            PROF(321 + 3 * r);
            release<4>();
            signal_cnt(&S->cnt[(C_KV + (task >> 5)) * 32], 1);
            PROF(322 + 3 * r);
          }
          PROF(41);
        }
        if (has2) {
          mbar_wait(BAR(B_SH));
#pragma unroll 1
          for (int i = 0; i < 8; i++) mbar_arrive_cl(BAR(B_RF0), i & (R.cs() - 1));
        }
#pragma unroll 1
        for (int s = 0, s0 = 0; s < R.nch(); s++) {
          mbar_wait(BAR(B_GS + s));
          fence_async();
          bulk_s2g(S->gt + (size_t)R.ch(s) * SEQ, conv_buf(sb, s) + KC_OFS, 4096); bulk_commit();
          if (s == 1 || s >= R.nch() - GSPL) bulk_wait();
          if (s == 1 || s == R.nch() - 1) mbar_arrive(BAR(B_CD + (s > 1)));
          if (s >= R.nch() - GSPL) {
            PROF(45);
            release<8>();
#pragma unroll 1
            for (; s0 <= s; s0++) signal_cnt(&S->cnt[(C_G + R.ch(s0) / 80) * 32], 1);
          }
        }
        PROF(46);
      }
    }
  }
}

typedef CUresult (*EncFn)(CUtensorMap*, CUtensorMapDataType, cuuint32_t, void*, const cuuint64_t*, const cuuint64_t*, const cuuint32_t*,
                          const cuuint32_t*, CUtensorMapInterleave, CUtensorMapSwizzle, CUtensorMapL2promotion, CUtensorMapFloatOOBfill);
bool enc(EncFn f, CUtensorMap* m, const void* base, int rank, const cuuint64_t* dims, const cuuint64_t* strides, const cuuint32_t* box, bool swz,
         bool f32 = false) {
  const cuuint32_t es[5] = {1, 1, 1, 1, 1};
  return f(m, f32 ? CU_TENSOR_MAP_DATA_TYPE_FLOAT32 : CU_TENSOR_MAP_DATA_TYPE_BFLOAT16, rank, const_cast<void*>(base), dims, strides, box, es,
           CU_TENSOR_MAP_INTERLEAVE_NONE, swz ? CU_TENSOR_MAP_SWIZZLE_128B : CU_TENSOR_MAP_SWIZZLE_NONE, CU_TENSOR_MAP_L2_PROMOTION_L2_256B,
           CU_TENSOR_MAP_FLOAT_OOB_FILL_NONE) == CUDA_SUCCESS;
}
void make_roles(Params& P, bool big) {
  for (uint32_t bx = 0; bx < (big ? 120u : 12u); bx++) {
    const uint32_t c = bx >> 3, r = bx & 7, id = big ? bx : 120 + bx;
    const uint32_t vA = c < 12 ? (2 * (c >> 1) + (r >> 2)) | (4 * (c & 1) + (r & 3)) << 4 | (r & 4) << 16 | 4 << 19 | (r ^ 4) << 22
                               : (4 * (c - 12) + (r >> 1)) | (8 + (r & 1)) << 4 | (r & 6) << 16 | 2 << 19 | (r ^ 2) << 22;
    const uint32_t vB = (bx < 10 ? 12 : 13) | bx << 4 | 2 << 19 | (bx & 1) << 22 | (bx & 1) << 26;
    P.role[bx].x = (big ? vA | r << 26 | 1u << 29 : vB) | (id < 128 ? (id & ~7u) | (r >> 1) | (r & 1) << 2 : id) << 8;
    P.role[bx].y = id | (big ? 5 : bx < 8 ? 3 : 4) << 10 | 120 << 13 | 132 << 21 | (big ? 4u : 3u) << 29;
    const uint32_t v = P.role[bx].x, cb = (v >> 4) & 15, rank = (v >> 26) & 7, ubase = (v >> 16) & 7, ugs = (v >> 19) & 7, wp = (v >> 22) & 7;
    const uint32_t wlo = rank > wp, whi = wp != rank ? wlo : 1, wmask = 1u << rank | 1u << wp;
    const uint32_t uj = (rank - ubase) * (!big ? 8 : ugs == 4 ? 5 : 10), sm = big ? (0x7296418530ull >> (4 * cb)) & 15 : bx < 8 ? 4 * (bx & 1) + (bx >> 1) : 15;
    P.role[bx].z = wlo | whi << 1 | wmask << 2 | ((1u << ugs) - 1) << (10 + ubase) | uj << 20 | sm << 25;
    P.role[bx].w = 0;
  }
}
void launch(const Head& H, const Params& P, int grid, int cs, bool dependent) {
  cudaLaunchConfig_t cfg = {};
  cfg.gridDim = grid; cfg.blockDim = 512; cfg.dynamicSmemBytes = SMEM_BYTES; cfg.stream = cudaStreamPerThread;
  cudaLaunchAttribute at[2];
  at[0].id = cudaLaunchAttributeClusterDimension; at[0].val.clusterDim.x = cs; at[0].val.clusterDim.y = 1; at[0].val.clusterDim.z = 1;
  at[1].id = cudaLaunchAttributeProgrammaticStreamSerialization; at[1].val.programmaticStreamSerializationAllowed = 1;
  cfg.attrs = at; cfg.numAttrs = dependent ? 2 : 1;
  cudaLaunchKernelEx(&cfg, fused_kernel, H, P);
}

}

extern "C" void kernel_launch(void* const* d_in, const int* in_sizes, int n_in, void* d_out, int out_size) {
  (void)in_sizes; (void)n_in; (void)out_size;
  typedef const __nv_bfloat16* cb;
  void* fp = nullptr; cudaDriverEntryPointQueryResult qr;
  cudaGetDriverEntryPoint("cuTensorMapEncodeTiled", &fp, cudaEnableDefault, &qr);
  EncFn f = (EncFn)fp;
  Scratch* sp = nullptr;
  cudaGetSymbolAddress((void**)&sp, g_scr);
  void *pu = sp->u, *ph = sp->h, *pgt = sp->gt;
  Params P;
  Head H;
  H.s = sp; H.x = (cb)d_in[0]; H.swap = (uintptr_t)d_in[4] < (uintptr_t)d_in[3] ? 0 : 0x80000000u; H.b0 = (cb)d_in[H.swap ? 3 : 4]; H.b1 = (cb)d_in[H.swap ? 4 : 3];
  for (int i = 0; i < 2; i++) {
    const cuuint64_t d[4] = {640, 8, 2, 80}, s[3] = {1280, (cuuint64_t)((uintptr_t)H.b1 - (uintptr_t)H.b0), 8 * 1280}; const cuuint32_t bx[4] = {64, 8, 2, 4};
    if (enc(f, &P.mB, H.b0, 4, d, s, bx, true)) break;
    cudaMemcpyAsync(sp->bcopy, H.b0, DM * DM * 2, cudaMemcpyDeviceToDevice, cudaStreamPerThread);
    cudaMemcpyAsync(sp->bcopy + DM * DM, H.b1, DM * DM * 2, cudaMemcpyDeviceToDevice, cudaStreamPerThread);
    H.b0 = sp->bcopy; H.b1 = sp->bcopy + DM * DM;
  }
  {
    const cuuint64_t d[5] = {640, 2, 4, 2, 40}, s[4] = {1280, 4 * 1280, 2 * 1280, 16 * 1280}; const cuuint32_t bx[5] = {64, 2, 4, 2, 5};
    enc(f, &P.mC[0], d_in[5], 5, d, s, bx, true); enc(f, &P.mC[1], d_in[6], 5, d, s, bx, true); }
  { const cuuint64_t d[2] = {2048, 640}, s[1] = {4096}; const cuuint32_t bx[2] = {64, 80}; enc(f, &P.mGT, pgt, 2, d, s, bx, true); }
  { const cuuint64_t d[4] = {640, 8, 16, 16}, s[3] = {16 * 1280, 1280, 128 * 1280}; const cuuint32_t bx[4] = {80, 8, 16, 1}, bh[4] = {80, 8, 8, 1};
    enc(f, &P.sU, pu, 4, d, s, bh, false); enc(f, &P.mX, d_in[0], 4, d, s, bx, false); }
  { const cuuint64_t d[2] = {2048, 640}, s[1] = {4096}; const cuuint32_t bx[2] = {64, 64}; enc(f, &P.sK, sp->kv, 2, d, s, bx, true); }
  P.lre = (cb)d_in[1]; P.lim = (cb)d_in[2]; P.cre = (cb)d_in[5]; P.cim = (cb)d_in[6]; P.ldt = (cb)d_in[7]; P.dskip = (cb)d_in[8];
  P.out = (float*)d_out;
  P.k = (cb)d_in[10]; P.v = (cb)d_in[11]; P.shk = (cb)d_in[12]; P.ssmk = (cb)d_in[13]; P.ssmd = (cb)d_in[14];
  cudaFuncSetAttribute(fused_kernel, cudaFuncAttributeMaxDynamicSharedMemorySize, SMEM_BYTES);
  for (int big = 1; big >= 0; big--) {
    const cuuint64_t seg = big ? 40 : 32;
    for (int i = 0; i < 4; i++) {
      const cuuint64_t d[4] = {640, 2, 4, 1024}, s[3] = {1280, seg * 1280, 2 * 1280}; const cuuint32_t bx[4] = {64, 2, 4, !big ? 8u : (i & 1) ? 10u : 5u};
      enc(f, &P.mA[i], i < 2 ? d_in[0] : pu, 4, d, s, bx, true);
    }
    {
      const cuuint64_t d[4] = {1280, 8, 16, 32}, s[3] = {16 * 2560, 2560, 128 * 2560}; const cuuint32_t bx[4] = {64, 8, big ? 2u : 8u, 1};
      enc(f, &P.mH, ph, 4, d, s, bx, true); }
    { const cuuint64_t d[4] = {1280, 2, 4, 2048}, s[3] = {2560, seg * 2560, 2 * 2560}; const cuuint32_t bx[4] = {64, 2, 4, 4};
      enc(f, &P.sH, ph, 4, d, s, bx, true); }
    make_roles(P, big);
    H.base = big ? 0 : 120;
    launch(H, P, big ? 120 : 12, big ? 8 : 2, !big);
  }
}
```

```cpp
#include <cuda_runtime.h>
#include <cuda.h>
#include <cuda_bf16.h>
#include <stdint.h>

namespace {

constexpr int SEQ = 2048, DM = 640;
constexpr int SPIN = 1 << 20;
#define PFAT 99
#define KVDLY 500
#define PFD 1
#define XPFAT 9
#define STAT_AT 6
#define KPFAT 3
#define KPFAT2 5
#define KPF 7
#define HDLY 1900
#define GSPL 2
#define CWAIT 0
#define HDLY0 1900
#define CTAB1 0x96543u
#define NSAT 0
#define SKW 1
#define RIAT 2
#define MIAT 5
#define FPAT 1
#define UPAT 7
#define STAT_AT1 4
#define W4AT 0
#define MBAR 1
#define STG 17
#define STG0 17
#define HWM 0xc09
#define NSDB 4
#define GLATE 6
#define KUP 1
#define XRAT 9
#define ORD 1

struct Scratch {
  uint2 E[2 * 13 * 10 * 8 * 16];
  uint32_t M[3 * 16 * 8 * 256];
  uint2 S[3 * SEQ];
  uint2 RS[80 * 16];
  unsigned flag[512 * 32];
  unsigned cnt[32 * 32];
  unsigned epoch[132 * 8];
  unsigned zero[128];
  unsigned prof[132 * 512];
  __align__(1024)
  __nv_bfloat16 u[SEQ * DM];
  __nv_bfloat16 h[2 * SEQ * 1280];
  __nv_bfloat16 kv[DM * SEQ];
  __nv_bfloat16 gt[DM * SEQ];
  __nv_bfloat16 bcopy[2 * DM * DM];
};
__device__ __align__(1024) Scratch g_scr;
#define PROFC(c, i) do {} while (0)
#define PSEL 1
#define PROF(i) do {} while (0)

constexpr int C_KV = 0, C_G = 10;
constexpr int F_U3 = 0, F_H = 128;

constexpr int R_OFF = 196608, R4_OFF0 = 73728, R4_OFF1 = 122880, H_OFF = 131072, KS_OFF = 131072, CV_OFF = 86272, G_OFF0 = 40960, G_OFF1 = 102400, US_OFF = 98304, XR_OFF = 163840, MX_OFF = 32768;
constexpr int LAM_OFF = 229376, SSM_OFF = LAM_OFF + 1024, BAR_OFF = SSM_OFF + 1344;
constexpr int B_F1 = 0, B_E1 = 10, B_RF0 = 20, B_RF1 = 21, NBAR1 = 22;
constexpr int B_F2 = 22, B_KF = 32, B_GF = 37, B_CD = 38, B_XR = 40, B_ST = 41, B_HD = 42, B_LM = 43, B_E2 = 44, B_GS = 54, B_PS = 59, B_AX = 62, B_SH = 64, B_SG = 69, B_GE = 70, B_EA = 71, B_F3 = 74, NBAR = 84;
__host__ __device__ constexpr int bar_count(int i) { return i < B_E1 ? 1 : i < B_RF0 ? 9 : i < B_F2 ? 8 : i < B_E2 ? 1 : i < B_GS ? 12 : i < B_SH ? 4 : i < B_SG ? 8 : i < B_GE ? 1 : i < B_EA ? 2 : i < B_F3 ? 8 : 1; }
constexpr int MISC_OFF = BAR_OFF + NBAR * 8, SMEM_BYTES = MISC_OFF + 32;
constexpr int KV_PAD = 512, KC_OFS = KV_PAD + 4096, CH_STRIDE = 8960;
__device__ __forceinline__ uint32_t conv_buf(uint32_t sb, int slot) { return sb + CV_OFF + slot * CH_STRIDE; }
constexpr uint64_t tab6(int a, int b, int c, int d, int e, int f, int g, int h, int i, int j) {
  return (uint64_t)a | (uint64_t)b << 6 | (uint64_t)c << 12 | (uint64_t)d << 18 | (uint64_t)e << 24 | (uint64_t)f << 30 | (uint64_t)g << 36 | (uint64_t)h << 42 |
         (uint64_t)i << 48 | (uint64_t)j << 54;
}
constexpr uint64_t WTAB0 = tab6(0, 4, 8, 30, 12, 26, 0, 4, 8, 12), XTAB0 = tab6(40, 45, 50, 34, 16, 21, 40, 45, 50, 16);
constexpr uint64_t WTAB1 = tab6(16, 20, 0, 4, 8, 12, 16, 20, 24, 28), XTAB1 = tab6(40, 45, 50, 32, 40, 45, 50, 32, 40, 45);
constexpr uint32_t DEP0 = 0x4210;

struct Head {
  Scratch* s;
  const __nv_bfloat16 *x, *b0, *b1;
  uint32_t base, swap;
};
struct Params {
  const __nv_bfloat16 *lre, *lim, *ldt, *k, *v, *shk, *cre, *cim, *ssmk, *ssmd, *dskip;
  float* out;
  uint4 role[120];
  CUtensorMap mB, mA[4], mH, mC[2], mGT, mX, sH, sU, sK;
};

__device__ __forceinline__ uint32_t smem_u32(const void* p) { return (uint32_t)__cvta_generic_to_shared(p); }
__device__ __forceinline__ uint32_t opaque(uint32_t x) { uint32_t y; asm volatile("mov.u32 %0, %1;" : "=r"(y) : "r"(x)); return y; }
__device__ __forceinline__ int lane_id() { int y; asm volatile("mov.u32 %0, %%laneid;" : "=r"(y)); return y; }
__device__ __forceinline__ void delay(uint32_t n) {
  asm volatile("{ .reg .pred p; .reg .u32 a, b; mov.u32 a, %%clock; L: mov.u32 b, %%clock; sub.u32 b, b, a; setp.lt.u32 p, b, %0; @p bra.uni L; }" ::"r"(n) : "memory");
}
__device__ __forceinline__ void mbar_init(uint32_t bar, uint32_t cnt) { asm volatile("mbarrier.init.shared::cta.b64 [%0], %1;" ::"r"(bar), "r"(cnt) : "memory"); }
__device__ __forceinline__ void mbar_expect_tx(uint32_t bar, uint32_t bytes) { asm volatile("mbarrier.arrive.expect_tx.shared::cta.b64 _, [%0], %1;" ::"r"(bar), "r"(bytes) : "memory"); }
__device__ __forceinline__ void mbar_arrive(uint32_t bar) { asm volatile("mbarrier.arrive.shared::cta.b64 _, [%0];" ::"r"(bar) : "memory"); }
__device__ __forceinline__ void mbar_arrive_if(uint32_t bar, bool c) {
  asm volatile("{ .reg .pred p; setp.ne.u32 p, %1, 0; @p mbarrier.arrive.shared::cta.b64 _, [%0]; }" ::"r"(bar), "r"((uint32_t)c) : "memory");
}
__device__ __forceinline__ void prefetch_if(const void* p, bool c) { asm volatile("{ .reg .pred p; setp.ne.u32 p, %1, 0; @p prefetch.global.L2 [%0]; }" ::"l"(p), "r"((uint32_t)c)); }
__device__ __forceinline__ void mbar_arrive_cl(uint32_t bar, uint32_t cta) {
  asm volatile("{ .reg .b32 ra; mapa.shared::cluster.u32 ra, %0, %1; mbarrier.arrive.shared::cluster.b64 _, [ra]; }" ::"r"(bar), "r"(cta) : "memory");
}
__device__ __forceinline__ uint32_t mapa(uint32_t a, uint32_t cta) { uint32_t r; asm("mapa.shared::cluster.u32 %0, %1, %2;" : "=r"(r) : "r"(a), "r"(cta)); return r; }
__device__ __forceinline__ void mbar_arrive_at(uint32_t ra) { asm volatile("mbarrier.arrive.shared::cluster.b64 _, [%0];" ::"r"(ra) : "memory"); }
__device__ __forceinline__ void mbar_wait(uint32_t bar, uint32_t parity = 0) {
  asm volatile("{ .reg .pred p; .reg .u32 c; mov.u32 c, 0;\n"
               "W: mbarrier.try_wait.parity.shared::cta.b64 p, [%0], %1; @p bra.uni D;\n"
               "add.u32 c, c, 1; setp.lt.u32 p, c, 0x100000; @p bra.uni W;\nD: }" ::"r"(bar), "r"(parity) : "memory");
}
__device__ __forceinline__ bool elect_one() { uint32_t p; asm volatile("{ .reg .pred P; elect.sync _|P, 0xffffffff; selp.u32 %0,1,0,P; }" : "=r"(p)); return p; }
__device__ __forceinline__ void bar_sync(int id, int n) { __syncwarp(); asm volatile("bar.sync %0, %1;" ::"r"(id), "r"(n) : "memory"); }
__device__ __forceinline__ void tma2d(uint32_t dst, const CUtensorMap* m, int c0, int c1, uint32_t bar) {
  asm volatile("cp.async.bulk.tensor.2d.shared::cluster.global.mbarrier::complete_tx::bytes [%0], [%1, {%3,%4}], [%2];"
               ::"r"(dst), "l"(m), "r"(bar), "r"(c0), "r"(c1) : "memory");
}
__device__ __forceinline__ void tma5d(uint32_t dst, const CUtensorMap* m, int c0, int c4, uint32_t bar) {
  asm volatile("cp.async.bulk.tensor.5d.shared::cluster.global.mbarrier::complete_tx::bytes [%0], [%1, {%3,%5,%5,%5,%4}], [%2];"
               ::"r"(dst), "l"(m), "r"(bar), "r"(c0), "r"(c4), "r"(0) : "memory");
}
__device__ __forceinline__ void tma4d(uint32_t dst, const CUtensorMap* m, int c0, int c3, uint32_t bar) {
  asm volatile("cp.async.bulk.tensor.4d.shared::cluster.global.mbarrier::complete_tx::bytes [%0], [%1, {%3,%5,%5,%4}], [%2];"
               ::"r"(dst), "l"(m), "r"(bar), "r"(c0), "r"(c3), "r"(0) : "memory");
}
__device__ __forceinline__ void tma4d_mc(uint32_t dst, const CUtensorMap* m, int c0, int c1, int c2, int c3, uint32_t bar, uint32_t mask) {
  asm volatile("cp.async.bulk.tensor.4d.shared::cluster.global.mbarrier::complete_tx::bytes.multicast::cluster [%0], [%1, {%3,%4,%5,%6}], [%2], %7;"
               ::"r"(dst), "l"(m), "r"(bar), "r"(c0), "r"(c1), "r"(c2), "r"(c3), "h"((uint16_t)mask) : "memory");
}
__device__ __forceinline__ void bulk_g2s(uint32_t dst, const void* src, uint32_t bytes, uint32_t bar) {
  asm volatile("cp.async.bulk.shared::cluster.global.mbarrier::complete_tx::bytes [%0], [%1], %2, [%3];" ::"r"(dst), "l"(src), "r"(bytes), "r"(bar) : "memory");
}
__device__ __forceinline__ void tma4d_store(const CUtensorMap* m, uint32_t src, int c0, int c1, int c2, int c3) {
  asm volatile("cp.async.bulk.tensor.4d.global.shared::cta.bulk_group [%0, {%2,%3,%4,%5}], [%1];" ::"l"(m), "r"(src), "r"(c0), "r"(c1), "r"(c2), "r"(c3) : "memory");
}
__device__ __forceinline__ void tma2d_store(const CUtensorMap* m, uint32_t src, int c0, int c1) {
  asm volatile("cp.async.bulk.tensor.2d.global.shared::cta.bulk_group [%0, {%2,%3}], [%1];" ::"l"(m), "r"(src), "r"(c0), "r"(c1) : "memory");
}
__device__ __forceinline__ void bulk_s2g(void* dst, uint32_t src, uint32_t bytes) {
  asm volatile("cp.async.bulk.global.shared::cta.bulk_group [%0], [%1], %2;" ::"l"(dst), "r"(src), "r"(bytes) : "memory");
}
__device__ __forceinline__ void bulk_commit() { asm volatile("cp.async.bulk.commit_group;" ::: "memory"); }
__device__ __forceinline__ void bulk_wait() { asm volatile("cp.async.bulk.wait_group 0;" ::: "memory"); }
__device__ __forceinline__ void fence_async() { asm volatile("fence.proxy.async.shared::cta;" ::: "memory"); }
__device__ __forceinline__ void prefetch_l2(const void* src, uint32_t bytes) { asm volatile("cp.async.bulk.prefetch.L2.global [%0], %1;" ::"l"(src), "r"(bytes) : "memory"); }
__device__ __forceinline__ void prefetch_map(const CUtensorMap* m) { asm volatile("prefetch.tensormap [%0];" ::"l"(m) : "memory"); }
__device__ __forceinline__ void wg_fence() { __syncwarp(); asm volatile("wgmma.fence.sync.aligned;" ::: "memory"); }
__device__ __forceinline__ void wg_commit() { asm volatile("wgmma.commit_group.sync.aligned;" ::: "memory"); }
template <int N> __device__ __forceinline__ void wg_wait() { asm volatile("wgmma.wait_group.sync.aligned %0;" ::"n"(N) : "memory"); }
template <int N> __device__ __forceinline__ void fence_regs(float (&d)[N]) {
#pragma unroll
  for (int i = 0; i < N; i++) asm volatile("" : "+f"(d[i])::"memory");
}
__device__ __forceinline__ uint64_t make_desc(uint32_t addr, uint32_t lbo, uint32_t sbo, uint32_t swz) {
  return (uint64_t)((addr & 0x3FFFF) >> 4) | ((uint64_t)(lbo >> 4) << 16) | ((uint64_t)(sbo >> 4) << 32) | ((uint64_t)swz << 62);
}
__device__ __forceinline__ uint32_t ldg1(const void* p) { uint32_t v; asm volatile("ld.global.nc.u32 %0,[%1];" : "=r"(v) : "l"(p)); return v; }
__device__ __forceinline__ uint32_t lds32(uint32_t a) { uint32_t v; asm volatile("ld.shared.u32 %0,[%1];" : "=r"(v) : "r"(a)); return v; }
__device__ __forceinline__ unsigned ld_rlx(const unsigned* p) { unsigned v; asm volatile("ld.relaxed.gpu.global.u32 %0,[%1];" : "=r"(v) : "l"(p) : "memory"); return v; }
__device__ __forceinline__ uint4 ld_rlx4(const void* p) {
  uint4 v; asm volatile("ld.relaxed.gpu.global.v4.u32 {%0,%1,%2,%3},[%4];" : "=r"(v.x), "=r"(v.y), "=r"(v.z), "=r"(v.w) : "l"(p) : "memory"); return v;
}
__device__ __forceinline__ uint2 ld_rlx2(const void* p) { uint2 v; asm volatile("ld.relaxed.gpu.global.v2.u32 {%0,%1},[%2];" : "=r"(v.x), "=r"(v.y) : "l"(p) : "memory"); return v; }
__device__ __forceinline__ void st_rlx2(void* p, uint32_t a, uint32_t b) { asm volatile("st.relaxed.gpu.global.v2.u32 [%0],{%1,%2};" ::"l"(p), "r"(a), "r"(b) : "memory"); }
__device__ __forceinline__ void st_rlx(void* p, uint32_t a) { asm volatile("st.relaxed.gpu.global.u32 [%0],%1;" ::"l"(p), "r"(a) : "memory"); }
#define PUB 15
template <int SITE> __device__ __forceinline__ void release() { if (PUB & SITE) asm volatile("fence.release.gpu;" ::: "memory"); }
__device__ __forceinline__ void signal_flag(unsigned* p, unsigned val) { asm volatile("st.relaxed.gpu.global.u32 [%0],%1;" ::"l"(p), "r"(val) : "memory"); }
__device__ __forceinline__ void signal_cnt(unsigned* p, unsigned n) { asm volatile("red.relaxed.gpu.global.add.u32 [%0],%1;" ::"l"(p), "r"(n) : "memory"); }
__device__ __forceinline__ void wait_flags(const unsigned* p, unsigned val, uint32_t need, uint32_t& ready) {
#pragma unroll 1
  for (int it = 0; (ready & need) != need && it < SPIN; it++) ready = __ballot_sync(0xffffffff, ld_rlx(p) == val);
}
__device__ __forceinline__ void wait_cnt(const unsigned* p, unsigned tgt) {
  asm volatile("{ .reg .pred p; .reg .u32 c; .reg .s32 v; mov.u32 c, 0;\n"
               "W: ld.relaxed.gpu.global.u32 v, [%0]; sub.s32 v, v, %1; setp.ge.s32 p, v, 0; @p bra.uni D;\n"
               "add.u32 c, c, 1; setp.lt.u32 p, c, 0x100000; @p bra.uni W;\nD: }" ::"l"(p), "r"(tgt) : "memory");
}
__device__ __forceinline__ uint32_t pack_bf(float lo, float hi) { uint32_t r; asm("cvt.rn.bf16x2.f32 %0, %1, %2;" : "=r"(r) : "f"(hi), "f"(lo)); return r; }
__device__ __forceinline__ float bf_lo(uint32_t v) { return __uint_as_float(v << 16); }
__device__ __forceinline__ float bf_hi(uint32_t v) { return __uint_as_float(v & 0xffff0000u); }
__device__ __forceinline__ float bf_rn(float x) { return __bfloat162float(__float2bfloat16_rn(x)); }
__device__ __forceinline__ float frcp(float x) { float r; asm("rcp.approx.ftz.f32 %0,%1;" : "=f"(r) : "f"(x)); return r; }
__device__ __forceinline__ float fsqrt(float x) { float r; asm("sqrt.approx.ftz.f32 %0,%1;" : "=f"(r) : "f"(x)); return r; }
__device__ __forceinline__ float frsqrt(float x) { float r; asm("rsqrt.approx.ftz.f32 %0,%1;" : "=f"(r) : "f"(x)); return r; }
__device__ __forceinline__ uint32_t hmul2(uint32_t a, uint32_t b) { uint32_t r; asm("mul.rn.bf16x2 %0,%1,%2;" : "=r"(r) : "r"(a), "r"(b)); return r; }
__device__ __forceinline__ uint32_t hfma2(uint32_t a, uint32_t b, uint32_t c) { uint32_t r; asm("fma.rn.bf16x2 %0,%1,%2,%3;" : "=r"(r) : "r"(a), "r"(b), "r"(c)); return r; }
__device__ __forceinline__ float2 cmul(float2 a, float2 b) { return make_float2(a.x * b.x - a.y * b.y, a.x * b.y + a.y * b.x); }
__device__ __forceinline__ float2 cfma(float2 a, float2 b, float2 c) {
  return make_float2(fmaf(a.x, b.x, fmaf(-a.y, b.y, c.x)), fmaf(a.x, b.y, fmaf(a.y, b.x, c.y)));
}
__device__ __forceinline__ uint32_t tagf(float v, uint32_t tag) { return (__float_as_uint(v) & ~1u) | tag; }
__device__ __forceinline__ float untag(uint32_t v) { return __uint_as_float(v & ~1u); }
__device__ __forceinline__ bool untagged(const uint4& v, uint32_t tag) { return (((v.x ^ tag) | (v.y ^ tag) | (v.z ^ tag) | (v.w ^ tag)) & 1) != 0; }
__device__ __forceinline__ bool untagged(const uint2& v, uint32_t tag) { return (((v.x ^ tag) | (v.y ^ tag)) & 1) != 0; }
__device__ __forceinline__ float2 lam_bar(float lr, float li, float ldt) {
  float dt = bf_rn(expf(ldt)); float e = expf(dt * lr), s, c; sincospif(dt * li * 0.31830988618379067f, &s, &c); return make_float2(e * c, e * s);
}

__device__ __forceinline__ int conv_ch(uint32_t c, int s) { return s * ((c >> 21) & 255) + (c & 255) - (s >= (int)(c >> 29) ? 8 : 0); }
struct Role {
  uint32_t v, c, p;
  __device__ __forceinline__ int tb() const { return v & 15; }
  __device__ __forceinline__ int cb() const { return (v >> 4) & 15; }
  __device__ __forceinline__ int b() const { return (v >> 8) & 255; }
  __device__ __forceinline__ int ubase() const { return (v >> 16) & 7; }
  __device__ __forceinline__ int ugs() const { return (v >> 19) & 7; }
  __device__ __forceinline__ int wpart() const { return (v >> 22) & 7; }
  __device__ __forceinline__ int rank() const { return (v >> 26) & 7; }
  __device__ __forceinline__ int cs() const { return (v >> 29) ? 8 : 2; }
  __device__ __forceinline__ int ch(int s) const { return conv_ch(c, s); }
  __device__ __forceinline__ int wlo() const { return p & 1; }
  __device__ __forceinline__ int whi() const { return (p >> 1) & 1; }
  __device__ __forceinline__ uint32_t wmask() const { return (p >> 2) & 255; }
  __device__ __forceinline__ uint32_t umask() const { return (p >> 10) & 255; }
  __device__ __forceinline__ int uj() const { return (p >> 20) & 31; }
  __device__ __forceinline__ int sm() const { return (p >> 25) & 15; }
  __device__ __forceinline__ int nch() const { return (c >> 10) & 7; }
  __device__ __forceinline__ int nprep() const { return (c >> 13) & 255; }
};

__device__ __forceinline__ void wgmma_ss80(float (&d)[40], uint64_t da, uint64_t db, int sd){
  asm volatile("{ .reg .pred p; setp.ne.b32 p, %42, 0;\n"
   "wgmma.mma_async.sync.aligned.m64n80k16.f32.bf16.bf16 {%0, %1, %2, %3, %4, %5, %6, %7, %8, %9, %10, %11, %12, %13, %14, %15, %16, %17, %18, %19, %20, %21, %22, %23, %24, %25, %26, %27, %28, %29, %30, %31, %32, %33, %34, %35, %36, %37, %38, %39}, %40, %41, p, 1, 1, 0, 0; }\n"
   : "+f"(d[0]), "+f"(d[1]), "+f"(d[2]), "+f"(d[3]), "+f"(d[4]), "+f"(d[5]), "+f"(d[6]), "+f"(d[7]), "+f"(d[8]), "+f"(d[9]), "+f"(d[10]), "+f"(d[11]), "+f"(d[12]), "+f"(d[13]), "+f"(d[14]), "+f"(d[15]), "+f"(d[16]), "+f"(d[17]), "+f"(d[18]), "+f"(d[19]), "+f"(d[20]), "+f"(d[21]), "+f"(d[22]), "+f"(d[23]), "+f"(d[24]), "+f"(d[25]), "+f"(d[26]), "+f"(d[27]), "+f"(d[28]), "+f"(d[29]), "+f"(d[30]), "+f"(d[31]), "+f"(d[32]), "+f"(d[33]), "+f"(d[34]), "+f"(d[35]), "+f"(d[36]), "+f"(d[37]), "+f"(d[38]), "+f"(d[39]) : "l"(da), "l"(db), "r"(sd));
}
__device__ __forceinline__ void wgmma_ss160(float (&d)[80], uint64_t da, uint64_t db, int sd){
  asm volatile("{ .reg .pred p; setp.ne.b32 p, %82, 0;\n"
   "wgmma.mma_async.sync.aligned.m64n160k16.f32.bf16.bf16 {%0, %1, %2, %3, %4, %5, %6, %7, %8, %9, %10, %11, %12, %13, %14, %15, %16, %17, %18, %19, %20, %21, %22, %23, %24, %25, %26, %27, %28, %29, %30, %31, %32, %33, %34, %35, %36, %37, %38, %39, %40, %41, %42, %43, %44, %45, %46, %47, %48, %49, %50, %51, %52, %53, %54, %55, %56, %57, %58, %59, %60, %61, %62, %63, %64, %65, %66, %67, %68, %69, %70, %71, %72, %73, %74, %75, %76, %77, %78, %79}, %80, %81, p, 1, 1, 0, 0; }\n"
   : "+f"(d[0]), "+f"(d[1]), "+f"(d[2]), "+f"(d[3]), "+f"(d[4]), "+f"(d[5]), "+f"(d[6]), "+f"(d[7]), "+f"(d[8]), "+f"(d[9]), "+f"(d[10]), "+f"(d[11]), "+f"(d[12]), "+f"(d[13]), "+f"(d[14]), "+f"(d[15]), "+f"(d[16]), "+f"(d[17]), "+f"(d[18]), "+f"(d[19]), "+f"(d[20]), "+f"(d[21]), "+f"(d[22]), "+f"(d[23]), "+f"(d[24]), "+f"(d[25]), "+f"(d[26]), "+f"(d[27]), "+f"(d[28]), "+f"(d[29]), "+f"(d[30]), "+f"(d[31]), "+f"(d[32]), "+f"(d[33]), "+f"(d[34]), "+f"(d[35]), "+f"(d[36]), "+f"(d[37]), "+f"(d[38]), "+f"(d[39]), "+f"(d[40]), "+f"(d[41]), "+f"(d[42]), "+f"(d[43]), "+f"(d[44]), "+f"(d[45]), "+f"(d[46]), "+f"(d[47]), "+f"(d[48]), "+f"(d[49]), "+f"(d[50]), "+f"(d[51]), "+f"(d[52]), "+f"(d[53]), "+f"(d[54]), "+f"(d[55]), "+f"(d[56]), "+f"(d[57]), "+f"(d[58]), "+f"(d[59]), "+f"(d[60]), "+f"(d[61]), "+f"(d[62]), "+f"(d[63]), "+f"(d[64]), "+f"(d[65]), "+f"(d[66]), "+f"(d[67]), "+f"(d[68]), "+f"(d[69]), "+f"(d[70]), "+f"(d[71]), "+f"(d[72]), "+f"(d[73]), "+f"(d[74]), "+f"(d[75]), "+f"(d[76]), "+f"(d[77]), "+f"(d[78]), "+f"(d[79]) : "l"(da), "l"(db), "r"(sd));
}
template<int N> __device__ __forceinline__ void wgmma_rs(float (&d)[N/2], uint32_t a0, uint32_t a1, uint32_t a2, uint32_t a3, uint64_t db, int sd);
template<> __device__ __forceinline__ void wgmma_rs<16>(float (&d)[8], uint32_t a0, uint32_t a1, uint32_t a2, uint32_t a3, uint64_t db, int sd){
  asm volatile("{ .reg .pred p; setp.ne.b32 p, %13, 0;\n"
   "wgmma.mma_async.sync.aligned.m64n16k16.f32.bf16.bf16 {%0, %1, %2, %3, %4, %5, %6, %7}, {%8,%9,%10,%11}, %12, p, 1, 1, 0; }\n"
   : "+f"(d[0]), "+f"(d[1]), "+f"(d[2]), "+f"(d[3]), "+f"(d[4]), "+f"(d[5]), "+f"(d[6]), "+f"(d[7]) : "r"(a0), "r"(a1), "r"(a2), "r"(a3), "l"(db), "r"(sd));
}
template<> __device__ __forceinline__ void wgmma_rs<32>(float (&d)[16], uint32_t a0, uint32_t a1, uint32_t a2, uint32_t a3, uint64_t db, int sd){
  asm volatile("{ .reg .pred p; setp.ne.b32 p, %21, 0;\n"
   "wgmma.mma_async.sync.aligned.m64n32k16.f32.bf16.bf16 {%0, %1, %2, %3, %4, %5, %6, %7, %8, %9, %10, %11, %12, %13, %14, %15}, {%16,%17,%18,%19}, %20, p, 1, 1, 0; }\n"
   : "+f"(d[0]), "+f"(d[1]), "+f"(d[2]), "+f"(d[3]), "+f"(d[4]), "+f"(d[5]), "+f"(d[6]), "+f"(d[7]), "+f"(d[8]), "+f"(d[9]), "+f"(d[10]), "+f"(d[11]), "+f"(d[12]), "+f"(d[13]), "+f"(d[14]), "+f"(d[15]) : "r"(a0), "r"(a1), "r"(a2), "r"(a3), "l"(db), "r"(sd));
}
template<> __device__ __forceinline__ void wgmma_rs<48>(float (&d)[24], uint32_t a0, uint32_t a1, uint32_t a2, uint32_t a3, uint64_t db, int sd){
  asm volatile("{ .reg .pred p; setp.ne.b32 p, %29, 0;\n"
   "wgmma.mma_async.sync.aligned.m64n48k16.f32.bf16.bf16 {%0, %1, %2, %3, %4, %5, %6, %7, %8, %9, %10, %11, %12, %13, %14, %15, %16, %17, %18, %19, %20, %21, %22, %23}, {%24,%25,%26,%27}, %28, p, 1, 1, 0; }\n"
   : "+f"(d[0]), "+f"(d[1]), "+f"(d[2]), "+f"(d[3]), "+f"(d[4]), "+f"(d[5]), "+f"(d[6]), "+f"(d[7]), "+f"(d[8]), "+f"(d[9]), "+f"(d[10]), "+f"(d[11]), "+f"(d[12]), "+f"(d[13]), "+f"(d[14]), "+f"(d[15]), "+f"(d[16]), "+f"(d[17]), "+f"(d[18]), "+f"(d[19]), "+f"(d[20]), "+f"(d[21]), "+f"(d[22]), "+f"(d[23]) : "r"(a0), "r"(a1), "r"(a2), "r"(a3), "l"(db), "r"(sd));
}
template<> __device__ __forceinline__ void wgmma_rs<64>(float (&d)[32], uint32_t a0, uint32_t a1, uint32_t a2, uint32_t a3, uint64_t db, int sd){
  asm volatile("{ .reg .pred p; setp.ne.b32 p, %37, 0;\n"
   "wgmma.mma_async.sync.aligned.m64n64k16.f32.bf16.bf16 {%0, %1, %2, %3, %4, %5, %6, %7, %8, %9, %10, %11, %12, %13, %14, %15, %16, %17, %18, %19, %20, %21, %22, %23, %24, %25, %26, %27, %28, %29, %30, %31}, {%32,%33,%34,%35}, %36, p, 1, 1, 0; }\n"
   : "+f"(d[0]), "+f"(d[1]), "+f"(d[2]), "+f"(d[3]), "+f"(d[4]), "+f"(d[5]), "+f"(d[6]), "+f"(d[7]), "+f"(d[8]), "+f"(d[9]), "+f"(d[10]), "+f"(d[11]), "+f"(d[12]), "+f"(d[13]), "+f"(d[14]), "+f"(d[15]), "+f"(d[16]), "+f"(d[17]), "+f"(d[18]), "+f"(d[19]), "+f"(d[20]), "+f"(d[21]), "+f"(d[22]), "+f"(d[23]), "+f"(d[24]), "+f"(d[25]), "+f"(d[26]), "+f"(d[27]), "+f"(d[28]), "+f"(d[29]), "+f"(d[30]), "+f"(d[31]) : "r"(a0), "r"(a1), "r"(a2), "r"(a3), "l"(db), "r"(sd));
}
template<> __device__ __forceinline__ void wgmma_rs<80>(float (&d)[40], uint32_t a0, uint32_t a1, uint32_t a2, uint32_t a3, uint64_t db, int sd){
  asm volatile("{ .reg .pred p; setp.ne.b32 p, %45, 0;\n"
   "wgmma.mma_async.sync.aligned.m64n80k16.f32.bf16.bf16 {%0, %1, %2, %3, %4, %5, %6, %7, %8, %9, %10, %11, %12, %13, %14, %15, %16, %17, %18, %19, %20, %21, %22, %23, %24, %25, %26, %27, %28, %29, %30, %31, %32, %33, %34, %35, %36, %37, %38, %39}, {%40,%41,%42,%43}, %44, p, 1, 1, 0; }\n"
   : "+f"(d[0]), "+f"(d[1]), "+f"(d[2]), "+f"(d[3]), "+f"(d[4]), "+f"(d[5]), "+f"(d[6]), "+f"(d[7]), "+f"(d[8]), "+f"(d[9]), "+f"(d[10]), "+f"(d[11]), "+f"(d[12]), "+f"(d[13]), "+f"(d[14]), "+f"(d[15]), "+f"(d[16]), "+f"(d[17]), "+f"(d[18]), "+f"(d[19]), "+f"(d[20]), "+f"(d[21]), "+f"(d[22]), "+f"(d[23]), "+f"(d[24]), "+f"(d[25]), "+f"(d[26]), "+f"(d[27]), "+f"(d[28]), "+f"(d[29]), "+f"(d[30]), "+f"(d[31]), "+f"(d[32]), "+f"(d[33]), "+f"(d[34]), "+f"(d[35]), "+f"(d[36]), "+f"(d[37]), "+f"(d[38]), "+f"(d[39]) : "r"(a0), "r"(a1), "r"(a2), "r"(a3), "l"(db), "r"(sd));
}
template<> __device__ __forceinline__ void wgmma_rs<96>(float (&d)[48], uint32_t a0, uint32_t a1, uint32_t a2, uint32_t a3, uint64_t db, int sd){
  asm volatile("{ .reg .pred p; setp.ne.b32 p, %53, 0;\n"
   "wgmma.mma_async.sync.aligned.m64n96k16.f32.bf16.bf16 {%0, %1, %2, %3, %4, %5, %6, %7, %8, %9, %10, %11, %12, %13, %14, %15, %16, %17, %18, %19, %20, %21, %22, %23, %24, %25, %26, %27, %28, %29, %30, %31, %32, %33, %34, %35, %36, %37, %38, %39, %40, %41, %42, %43, %44, %45, %46, %47}, {%48,%49,%50,%51}, %52, p, 1, 1, 0; }\n"
   : "+f"(d[0]), "+f"(d[1]), "+f"(d[2]), "+f"(d[3]), "+f"(d[4]), "+f"(d[5]), "+f"(d[6]), "+f"(d[7]), "+f"(d[8]), "+f"(d[9]), "+f"(d[10]), "+f"(d[11]), "+f"(d[12]), "+f"(d[13]), "+f"(d[14]), "+f"(d[15]), "+f"(d[16]), "+f"(d[17]), "+f"(d[18]), "+f"(d[19]), "+f"(d[20]), "+f"(d[21]), "+f"(d[22]), "+f"(d[23]), "+f"(d[24]), "+f"(d[25]), "+f"(d[26]), "+f"(d[27]), "+f"(d[28]), "+f"(d[29]), "+f"(d[30]), "+f"(d[31]), "+f"(d[32]), "+f"(d[33]), "+f"(d[34]), "+f"(d[35]), "+f"(d[36]), "+f"(d[37]), "+f"(d[38]), "+f"(d[39]), "+f"(d[40]), "+f"(d[41]), "+f"(d[42]), "+f"(d[43]), "+f"(d[44]), "+f"(d[45]), "+f"(d[46]), "+f"(d[47]) : "r"(a0), "r"(a1), "r"(a2), "r"(a3), "l"(db), "r"(sd));
}
template<> __device__ __forceinline__ void wgmma_rs<112>(float (&d)[56], uint32_t a0, uint32_t a1, uint32_t a2, uint32_t a3, uint64_t db, int sd){
  asm volatile("{ .reg .pred p; setp.ne.b32 p, %61, 0;\n"
   "wgmma.mma_async.sync.aligned.m64n112k16.f32.bf16.bf16 {%0, %1, %2, %3, %4, %5, %6, %7, %8, %9, %10, %11, %12, %13, %14, %15, %16, %17, %18, %19, %20, %21, %22, %23, %24, %25, %26, %27, %28, %29, %30, %31, %32, %33, %34, %35, %36, %37, %38, %39, %40, %41, %42, %43, %44, %45, %46, %47, %48, %49, %50, %51, %52, %53, %54, %55}, {%56,%57,%58,%59}, %60, p, 1, 1, 0; }\n"
   : "+f"(d[0]), "+f"(d[1]), "+f"(d[2]), "+f"(d[3]), "+f"(d[4]), "+f"(d[5]), "+f"(d[6]), "+f"(d[7]), "+f"(d[8]), "+f"(d[9]), "+f"(d[10]), "+f"(d[11]), "+f"(d[12]), "+f"(d[13]), "+f"(d[14]), "+f"(d[15]), "+f"(d[16]), "+f"(d[17]), "+f"(d[18]), "+f"(d[19]), "+f"(d[20]), "+f"(d[21]), "+f"(d[22]), "+f"(d[23]), "+f"(d[24]), "+f"(d[25]), "+f"(d[26]), "+f"(d[27]), "+f"(d[28]), "+f"(d[29]), "+f"(d[30]), "+f"(d[31]), "+f"(d[32]), "+f"(d[33]), "+f"(d[34]), "+f"(d[35]), "+f"(d[36]), "+f"(d[37]), "+f"(d[38]), "+f"(d[39]), "+f"(d[40]), "+f"(d[41]), "+f"(d[42]), "+f"(d[43]), "+f"(d[44]), "+f"(d[45]), "+f"(d[46]), "+f"(d[47]), "+f"(d[48]), "+f"(d[49]), "+f"(d[50]), "+f"(d[51]), "+f"(d[52]), "+f"(d[53]), "+f"(d[54]), "+f"(d[55]) : "r"(a0), "r"(a1), "r"(a2), "r"(a3), "l"(db), "r"(sd));
}
template<> __device__ __forceinline__ void wgmma_rs<128>(float (&d)[64], uint32_t a0, uint32_t a1, uint32_t a2, uint32_t a3, uint64_t db, int sd){
  asm volatile("{ .reg .pred p; setp.ne.b32 p, %69, 0;\n"
   "wgmma.mma_async.sync.aligned.m64n128k16.f32.bf16.bf16 {%0, %1, %2, %3, %4, %5, %6, %7, %8, %9, %10, %11, %12, %13, %14, %15, %16, %17, %18, %19, %20, %21, %22, %23, %24, %25, %26, %27, %28, %29, %30, %31, %32, %33, %34, %35, %36, %37, %38, %39, %40, %41, %42, %43, %44, %45, %46, %47, %48, %49, %50, %51, %52, %53, %54, %55, %56, %57, %58, %59, %60, %61, %62, %63}, {%64,%65,%66,%67}, %68, p, 1, 1, 0; }\n"
   : "+f"(d[0]), "+f"(d[1]), "+f"(d[2]), "+f"(d[3]), "+f"(d[4]), "+f"(d[5]), "+f"(d[6]), "+f"(d[7]), "+f"(d[8]), "+f"(d[9]), "+f"(d[10]), "+f"(d[11]), "+f"(d[12]), "+f"(d[13]), "+f"(d[14]), "+f"(d[15]), "+f"(d[16]), "+f"(d[17]), "+f"(d[18]), "+f"(d[19]), "+f"(d[20]), "+f"(d[21]), "+f"(d[22]), "+f"(d[23]), "+f"(d[24]), "+f"(d[25]), "+f"(d[26]), "+f"(d[27]), "+f"(d[28]), "+f"(d[29]), "+f"(d[30]), "+f"(d[31]), "+f"(d[32]), "+f"(d[33]), "+f"(d[34]), "+f"(d[35]), "+f"(d[36]), "+f"(d[37]), "+f"(d[38]), "+f"(d[39]), "+f"(d[40]), "+f"(d[41]), "+f"(d[42]), "+f"(d[43]), "+f"(d[44]), "+f"(d[45]), "+f"(d[46]), "+f"(d[47]), "+f"(d[48]), "+f"(d[49]), "+f"(d[50]), "+f"(d[51]), "+f"(d[52]), "+f"(d[53]), "+f"(d[54]), "+f"(d[55]), "+f"(d[56]), "+f"(d[57]), "+f"(d[58]), "+f"(d[59]), "+f"(d[60]), "+f"(d[61]), "+f"(d[62]), "+f"(d[63]) : "r"(a0), "r"(a1), "r"(a2), "r"(a3), "l"(db), "r"(sd));
}

#define BAR(i) (bars + 8u * (uint32_t)(i))

template <int G> __device__ __forceinline__ void conv_frags(uint32_t (&a)[12], uint32_t abase) {
#pragma unroll
  for (int i = 0; i < 12; i++) a[i] = lds32(abase + (G * 4 + i / 3) * 128 + (i % 3) * 4);
}
__device__ __forceinline__ void kv_prefetch(const __nv_bfloat16* pf, int task) { prefetch_if(pf + 64 * (task & 31) * DM + 64 * (task >> 5), task < 320); }
__device__ __forceinline__ void kv_load(const Params& P, Scratch* S, int task, int tid, uint32_t (&k_)[19], uint32_t (&v_)[16], uint4& sk) {
  const int row = 64 * (task & 31) + 16 * (tid >> 5), ch = 64 * (task >> 5) + 2 * (tid & 31);
  const uint32_t* kp = (const uint32_t*)(P.k + (size_t)row * DM + ch);
  const uint32_t* vp = (const uint32_t*)(P.v + (size_t)row * DM + ch);
  const uint32_t* hp = row > 0 ? kp - 3 * (DM / 2) : S->zero;
  const int hs = row > 0 ? DM / 2 : 0;
  asm volatile("ld.global.nc.v4.u32 {%0,%1,%2,%3},[%4];" : "=r"(sk.x), "=r"(sk.y), "=r"(sk.z), "=r"(sk.w) : "l"(P.shk + ch * 4));
#pragma unroll
  for (int i = 0; i < 3; i++) k_[i] = ldg1(hp + i * hs);
#pragma unroll
  for (int i = 0; i < 16; i++) { k_[i + 3] = ldg1(kp + i * (DM / 2)); v_[i] = ldg1(vp + i * (DM / 2)); }
}
template <int SH> __device__ __forceinline__ void xb_prefetch(const Head& H, int id, int tid, int c0) {
  const int ri = tid >> SH, rr = 11 * id + ri - 16;
  const __nv_bfloat16* p = ri < 16 ? H.x + (size_t)(16 * min(id, 127) + ri) * DM : (rr < DM ? H.b0 : H.b1 - DM * DM) + (size_t)rr * DM;
  prefetch_if(p + c0 + 64 * (tid & ((1 << SH) - 1)), ri < 16 || (ri < 27 && rr < 2 * DM));
}
__device__ __forceinline__ uint4 ldg4(const void* p) { uint4 v; asm volatile("ld.global.nc.v4.u32 {%0,%1,%2,%3},[%4];" : "=r"(v.x), "=r"(v.y), "=r"(v.z), "=r"(v.w) : "l"(p)); return v; }
__device__ __forceinline__ uint4 lds4(uint32_t a) { uint4 v; asm volatile("ld.shared.v4.u32 {%0,%1,%2,%3},[%4];" : "=r"(v.x), "=r"(v.y), "=r"(v.z), "=r"(v.w) : "r"(a) : "memory"); return v; }
__device__ __forceinline__ void discretise(const Head& H, const Params& P, uint32_t sb, Role R, int lane, uint32_t e1) {
  const uint32_t dn = __ldg((const unsigned short*)P.ssmd + min(conv_ch(R.c, (lane + 7) & 7), DM - 1));
  const int c = 32 * min(R.cb(), 9) + lane;
  const uint32_t lr2 = ldg1(P.lre + 2 * c), li2 = ldg1(P.lim + 2 * c), ld2 = ldg1(P.ldt + 2 * c);
  asm volatile("st.shared.u32 [%0],%1;" ::"r"(sb + MISC_OFF + 4 * (lane & 7)), "r"((lane & 7) ? dn : e1) : "memory");
#pragma unroll 1
  for (int i = 0; i < 2; i++) {
    const float lr = bf_hi(lr2 << (16 - 16 * i)), li = bf_hi(li2 << (16 - 16 * i));
    const float2 lb = lam_bar(lr, li, bf_hi(ld2 << (16 - 16 * i)));
    const float nx = lb.x - 1.f, ny = lb.y, inv = 2.f * frcp(lr * lr + li * li), cx = (nx * lr + ny * li) * inv, cy = (ny * lr - nx * li) * inv;
    const bool sw = !H.swap;
    asm volatile("st.shared.v4.f32 [%0],{%1,%2,%3,%4};" ::"r"(sb + LAM_OFF + 32 * lane + 16 * i), "f"(lb.x), "f"(sw ? -lb.y : lb.y), "f"(sw ? -cy : cx), "f"(sw ? cx : -cy) : "memory");
  }
  __syncwarp();
}
__device__ __forceinline__ void aux_prep(const Head& H, const Params& P, uint32_t sb, Role R, int tid, long long t_start) {
  Scratch* const S = H.s;
  const uint32_t bars = sb + BAR_OFF;
  tid = opaque(tid);
  const int w = tid >> 5, lane = tid & 31, tb = R.tb(), cb = R.cb();
  uint32_t k_[19], v_[16];
  uint4 sk;
  int task = R.b() < R.nprep() ? R.b() : 320;
  delay(KVDLY);
  PROFC(tid == 0, 345);
  kv_load(P, S, min(task, 319), tid, k_, v_, sk);
  const __nv_bfloat16* pf = (tid < 64 ? P.k : P.v) + (tid & 63) * DM;
  const int j = lane >> 3, sm = min(R.sm(), 9), trow = 160 * tb + 4 * sm + (tb < 12 ? 40 : 32) * w + j;
  const uint32_t so = sb + (2 * w + (j & 1) + 8 * (j >> 1)) * 128 + 16 * (lane & 7), xo = so + sm * 2048, wo = so + (tb & 1) * 8192 + (tb & 6) * 1024;
  const __nv_bfloat16* xp = H.x + (size_t)min(trow, SEQ - 1) * DM + 384 + 8 * (lane & 7);
  const __nv_bfloat16* bp = (j < 2 ? H.b0 : H.b1) + (size_t)(64 * cb + 32 * (tb & 1) + 4 * (tb & 6) + 2 * w + (j & 1)) * DM + 384 + 8 * (lane & 7);
  float s = 0.f, s2 = 0.f, sr = 0.f;
#define STAT(m, n) { const uint32_t xw[4] = {m.x, m.y, m.z, m.w}, bw[4] = {n.x, n.y, n.z, n.w}; \
  _Pragma("unroll") for (int i = 0; i < 4; i++) { const float u = bf_lo(xw[i]), v = bf_hi(xw[i]); s += u + v; s2 = fmaf(u, u, fmaf(v, v, s2)); sr += bf_lo(bw[i]) + bf_hi(bw[i]); } }
#define STATS(K0, K1) _Pragma("unroll 1") for (int kb = K0; kb < K1; kb++) { \
    mbar_wait(BAR(B_F1 + kb)); \
    const uint4 a = lds4(xo + ((uint32_t)(XTAB0 >> (6 * kb)) & 63) * 4096), c = lds4(wo + ((uint32_t)(WTAB0 >> (6 * kb)) & 63) * 4096); \
    STAT(a, c) \
    asm volatile("" : "+f"(s), "+f"(s2), "+f"(sr)); \
    if (XPFAT >= K0 && XPFAT < K1) prefetch_if(((lane & 4) ? bp : xp) + 64 * (lane & 3), kb == XPFAT); \
    kv_prefetch(pf, kb == KPFAT ? task + R.nprep() : kb == KPFAT2 ? task + 2 * R.nprep() : 320); \
  } \
  __syncwarp(); mbar_arrive_if(BAR(B_AX + K0 / 3), lane == 0);
  STATS(0, 3)
  PROFC(tid == 0, 349);
    {
      uint4 m[4], n[4];
#pragma unroll
      for (int i = 0; i < 4; i++) { m[i] = ldg4(xp + 64 * i); n[i] = ldg4(bp + 64 * i); }
      STATS(3, 6)
      PROFC(tid == 0, 346);
      mbar_wait(BAR(B_LM));
      const uint32_t tag = lds32(sb + MISC_OFF) & 1;
#pragma unroll
      for (int i = 0; i < 4; i++) { const uint4 a = m[i], c = n[i]; STAT(a, c) }
      PROFC(tid == 0 && s2 != 1.2345f, 347);
#pragma unroll
      for (int o = 1; o <= 4; o <<= 1) { s += __shfl_xor_sync(0xffffffff, s, o); s2 += __shfl_xor_sync(0xffffffff, s2, o); sr += __shfl_xor_sync(0xffffffff, sr, o); }
      const float mn = s * (1.f / DM), rs = frcp(bf_rn(fsqrt(bf_rn(bf_rn(fmaxf(s2 * (1.f / DM) - mn * mn, 0.f)) + 1e-5f))));
      asm volatile("{ .reg .pred p; setp.ne.u32 p, %2, 0; @p st.relaxed.gpu.global.u32 [%0],%1; }"
                   ::"l"((uint32_t*)(S->RS + (8 * cb + 4 * (tb & 1) + (tb >> 1)) * 16 + 4 * w + (j & 1)) + (lane & 4) + (j >> 1)), "r"(tagf(sr, tag)),
                   "r"((uint32_t)(tb < 8 && (lane & 3) == 0)) : "memory");
      asm volatile("{ .reg .pred p; setp.ne.u32 p, %3, 0; @p st.relaxed.gpu.global.v2.u32 [%0],{%1,%2}; }"
                   ::"l"(S->S + trow), "r"(tagf(rs, tag)), "r"(tagf(-bf_rn(mn) * rs, tag)), "r"((uint32_t)(R.sm() < 10 && (lane & 7) == 0)) : "memory");
      PROFC(tid == 0, 3);
    }
#pragma unroll 1
  for (int r = 0; task < 320; r++) {
    {
      const uint32_t T0 = __byte_perm(sk.x, sk.z, 0x5410), T1 = __byte_perm(sk.x, sk.z, 0x7632);
      const uint32_t T2 = __byte_perm(sk.y, sk.w, 0x5410), T3 = __byte_perm(sk.y, sk.w, 0x7632);
      PROFC(tid == 0 && v_[15] != 0x12345, 336 + r);
      uint32_t o[16];
#pragma unroll
      for (int t = 0; t < 16; t += 2) {
        const uint32_t a = hmul2(hfma2(k_[t + 3], T0, hfma2(k_[t + 2], T1, hfma2(k_[t + 1], T2, hmul2(k_[t], T3)))), v_[t]);
        const uint32_t c = hmul2(hfma2(k_[t + 4], T0, hfma2(k_[t + 3], T1, hfma2(k_[t + 2], T2, hmul2(k_[t + 1], T3)))), v_[t + 1]);
        const int wd = ((7 - t / 2) >> 1) + 4 * ((7 - t / 2) & 1);
        o[wd] = __byte_perm(c, a, 0x5410); o[8 + wd] = __byte_perm(c, a, 0x7632);
        asm volatile("" : "+r"(o[wd]), "+r"(o[8 + wd]));
        if (t == PFAT) kv_prefetch(pf, task + (1 + PFD) * R.nprep());
      }
      PROFC(tid == 0, 330 + 2 * r);
      const int ph = task & 1;
      task += R.nprep();
      if (ORD == 0 && task < 320) kv_load(P, S, task, tid, k_, v_, sk);
      mbar_wait(BAR(B_E1 + 3)); mbar_wait(BAR(B_AX + 1));
#pragma unroll
      for (int i = 0; i < 4; i++) {
        const int row = 2 * lane + (i >> 1);
        asm volatile("st.shared.v4.u32 [%0],{%1,%2,%3,%4};" ::"r"(sb + KS_OFF + r * 8192 + row * 128 + (((2 * w + ((i & 1) ^ ph)) ^ (row & 7)) << 4)),
                     "r"(o[4 * i]), "r"(o[4 * i + 1]), "r"(o[4 * i + 2]), "r"(o[4 * i + 3]) : "memory");
      }
      __syncwarp();
      mbar_arrive_if(BAR(B_PS + r), lane == 0);
      PROFC(tid == 0, 331 + 2 * r);
      if (ORD == 1 && task < 320) kv_load(P, S, task, tid, k_, v_, sk);
    }
  }
#undef STAT
#undef STATS
  PROFC(tid == 0, 40);
}
#define SPLIT(G) asm volatile("{ .reg .pred p; .reg .u32 r; L: mov.u32 r, %%clock; setp.eq.u32 p, r, %0; @p bra.uni L; }" ::"n"(G) : "memory")
template <bool AUX>
__device__ __forceinline__ void conv_loop(uint32_t sb, uint32_t rc, int wg, int tid, long long t_start) {
  sb = opaque(sb); rc = opaque(rc);
  const uint32_t bars = sb + BAR_OFF;
  int slot = AUX ? 0 : wg + 1;
  mbar_wait(BAR(B_LM));
#pragma unroll 1
  while (slot < (int)((rc >> 10) & 7)) {
    tid = opaque(tid);
    const int w = tid >> 5, lane = tid & 31, g = lane >> 2, q = lane & 3;
    const uint32_t Dn = lds32(sb + MISC_OFF + 4 + 4 * slot);
    const uint32_t d0 = (g == 1 && q == 3 - w) ? Dn : 0, d1 = (g == 0 && q == 3 - w) ? Dn : 0;
    const uint32_t cb_ = conv_buf(sb, slot), c0 = cb_ + KC_OFS;
    const uint32_t abase = c0 + 2 * (2 * (g & 1) + 4 * w + 16 * (g >> 1) + 4 * q);
    const uint64_t bd = make_desc(cb_ + KV_PAD, 16, 256, 3);
    const bool hi = lane & 16, s1 = lane & 8;
    const int qo = hi ? (q + 1) & 3 : q;
    const int srcA = hi ? (lane & 12) | ((q + 1) & 3) : (lane & 12) | 16 | ((q + 3) & 3);
    const bool h3 = hi && q == 3, wrap = s1 && qo == 3, back = wrap && hi;
    const bool chi = wrap ? !hi : hi;
    const int cq = s1 ? (qo + 1) & 3 : qo;
    const int srcB = (lane & 4) | (s1 ? 0 : 8) | (chi ? 16 | ((cq + 3) & 3) : cq);
    const uint32_t gp = c0 + ((32 * (2 * w + (g & 1)) + (chi ? 256 : 0)) ^ (chi ? 64 : 0) ^ ((conv_ch(rc, slot) & 8) << 2)) + 4 * (2 * cq + (s1 ? 0 : 1));
    uint32_t a[12], f[16], o[8];
    float S[4], T[4], U[2], keep[2], pv[2] = {0.f, 0.f}, pr[4] = {0.f, 0.f, 0.f, 0.f};
    float e0[64], e1[56], e2[48], e3[40], e4[32], e5[24], e6[16], e7[8];
#define UNR _Pragma("unroll")
#define PERM() UNR for (int i = 0; i < 4; i++) { f[4 * i] = __byte_perm(a[3 * i], a[3 * i + 1], 0x5432); f[4 * i + 1] = a[3 * i + 1]; \
                                                 f[4 * i + 2] = __byte_perm(a[3 * i + 1], a[3 * i + 2], 0x5432); f[4 * i + 3] = a[3 * i + 2]; }
#define MMA(N, E) UNR for (int i = 0; i < 4; i++) wgmma_rs<N>(E, f[4 * i], f[4 * i + 1], f[4 * i + 2], f[4 * i + 3], bd - 8 * i, 1); wg_commit();
#define L1(c) UNR for (int i = 0; i < 4; i++) { const float ev = c[i], od = c[4 + i]; S[i] = hi ? (h3 ? ev : od) : ev; \
                                                T[i] = __shfl_sync(0xffffffff, hi ? (h3 ? pr[i] : ev) : od, srcA); pr[i] = od; }
#define L1E() UNR for (int i = 0; i < 4; i++) S[i] += T[i];
#define L2() UNR for (int h = 0; h < 2; h++) { keep[h] = back ? pv[h] : S[2 * h + 1]; pv[h] = S[2 * h + 1]; U[h] = __shfl_sync(0xffffffff, S[2 * h], srcB); }
#define L2E(j) o[j] = pack_bf(keep[0] + U[0], keep[1] + U[1]);
#define GRP(G, N, P, E) UNR for (int i = 0; i < N / 2; i++) asm volatile("mov.b32 %0,%1;" : "=f"(E[i]) : "f"(P[i + 8])); \
    wg_fence(); if (G < 7) conv_frags<(G + 1) & 7>(a, abase); if (G >= 2) { L2() } L1(P) MMA(N, E) SPLIT(G); \
    if (G < 7) { PERM() } if (G >= 2) { L2E((G + 6) & 7) } L1E() wg_wait<0>(); fence_regs(E);
    PROFC(tid == 0, 300 + 4 * slot);
    mbar_wait(BAR(B_KF + slot));
    if (tid == 0) PROF(361 + slot);
    PROFC(tid == 0, 301 + 4 * slot);
    conv_frags<0>(a, abase);
    wg_fence();
    wgmma_rs<128>(e0, d0 << 16, d0, d1 << 16, d1, bd, 0);
    PERM() conv_frags<1>(a, abase); wg_fence(); MMA(128, e0) SPLIT(0); PERM() wg_wait<0>(); fence_regs(e0);
    GRP(1, 112, e0, e1) GRP(2, 96, e1, e2) GRP(3, 80, e2, e3) GRP(4, 64, e3, e4) GRP(5, 48, e4, e5) GRP(6, 32, e5, e6) GRP(7, 16, e6, e7)
    PROFC(tid == 0, 302 + 4 * slot);
    L2() L1(e7) L2E(6) L1E() L2() L2E(7)
    bar_sync(wg + 1, 128);
#pragma unroll
    for (int jj = 0; jj < 8; jj++) asm volatile("st.shared.u32 [%0],%1;" ::"r"(gp + jj * 512), "r"(o[jj]) : "memory");
#undef PERM
#undef MMA
#undef L1
#undef L1E
#undef L2
#undef L2E
#undef GRP
    PROFC(tid == 0, 303 + 4 * slot);
    __syncwarp();
    if (lane == 0) mbar_arrive(BAR(B_GS + slot));
    if (!AUX) break;
    slot = slot ? slot + 1 : 3;
  }
}

#define IDX(J, c, h) (8 * (J) + 4 * ((c) >> 1) + 2 * (h) + ((c) & 1))
__device__ __forceinline__ uint2 lds2(uint32_t a) { uint2 v; asm volatile("ld.shared.v2.u32 {%0,%1},[%2];" : "=r"(v.x), "=r"(v.y) : "r"(a) : "memory"); return v; }
__device__ __forceinline__ void resid_load(float (&r)[40], uint32_t sb, int wg, int tid, const uint4& s) {
  const uint32_t dp = sb + XR_OFF + 8 * (tid & 3), xp = dp + (64 * wg + 16 * (tid >> 5) + ((tid & 31) >> 2)) * 160;
#pragma unroll
  for (int J = 0; J < 5; J++) {
    const uint2 u = lds2(xp + 32 * J), v = lds2(xp + 32 * J + 1280), d = lds2(dp + 20480 + 32 * J);
    r[8 * J] = __uint_as_float(u.x); r[8 * J + 1] = __uint_as_float(u.y); r[8 * J + 2] = __uint_as_float(v.x); r[8 * J + 3] = __uint_as_float(v.y);
    r[8 * J + 4] = __uint_as_float(d.x); r[8 * J + 5] = __uint_as_float(d.y);
  }
  r[30] = untag(s.x); r[31] = untag(s.y); r[38] = untag(s.z); r[39] = untag(s.w);
}
__device__ __forceinline__ void resid_init(float (&r)[40]) {
  const float s[4] = {r[30], r[31], r[38], r[39]};
#pragma unroll
  for (int J = 0; J < 5; J++) {
    uint32_t w[6];
#pragma unroll
    for (int i = 0; i < 6; i++) w[i] = __float_as_uint(r[8 * J + i]);
#pragma unroll
    for (int i = 0; i < 4; i++) {
      const int h = i >> 1, c = 2 * (i & 1);
      const float rs = s[2 * h], nm = s[2 * h + 1], x0 = bf_lo(w[i]), x1 = bf_hi(w[i]);
      const uint32_t t = hmul2(pack_bf(fmaf(x0, rs, nm), fmaf(x1, rs, nm)), w[4 + (i & 1)]);
      r[IDX(J, c, h)] = x0 + bf_lo(t); r[IDX(J, c + 1, h)] = x1 + bf_hi(t);
    }
  }
}

__device__ __forceinline__ float flip(float v, uint32_t m) { return __uint_as_float(__float_as_uint(v) ^ m); }
__device__ __forceinline__ void g1_phase(const int LY, const Head& H, uint32_t sb, int wg, int tid, Role R, float (&xr)[40], long long t_start) {
  Scratch* const S = H.s;
  tid = opaque(tid); sb = opaque(sb); R.v = opaque(R.v);
  const uint32_t bars = sb + BAR_OFF;
  const int cb = R.cb(), tb = R.tb();
  const int w = tid >> 5, lane = tid & 31, g = lane >> 2, q = lane & 3;
  const bool full = tb < 12;
  uint2* Eb = S->E + ((LY * 130 + cb) * 8 + 4 * wg + w) * 16 + g;
  float a[80];
#pragma unroll
  for (int i = 0; i < 80; i++) a[i] = 0.f;
  uint32_t rel = mapa(BAR(B_E1), lane ? R.wpart() : R.ubase() + (w & (R.ugs() - 1)));
  const bool rels = lane == 0 || (tid == 1 && wg != R.wlo());
  {
    uint64_t tw = LY ? WTAB1 : WTAB0, tx = LY ? XTAB1 : XTAB0;
    uint32_t bf = BAR(B_F1);
    if (tid == 0 && wg == 0 && !LY) PROF(351);
    fence_regs(a);
    mbar_wait(bf, LY);
    if (tid == 0 && wg == 0) PROF(LY ? 20 : 4);
#pragma unroll 1
    for (int kb = 0; kb < 10; kb++) {
      const uint64_t da = make_desc(sb + ((uint32_t)tw & 63) * 4096 + wg * 8192, 16, 1024, 1);
      const uint64_t db = make_desc(sb + ((uint32_t)tx & 63) * 4096, 16, 1024, 1);
      wg_fence();
#pragma unroll
      for (int kk = 0; kk < 4; kk++) wgmma_ss160(a, da + 2 * kk, db + 2 * kk, 1);
      wg_commit();
      wg_wait<1>();
      if (kb > 0) { if (rels) mbar_arrive_at(rel); rel += 8; }
      bf += 8; tw >>= 6; tx >>= 6;
      if (kb < 9) mbar_wait(bf, LY);
    }
  }
  if (tid == 0 && wg == 0) PROF(LY ? 19 : 2);
  mbar_wait(BAR(B_LM));
  const uint32_t tag = lds32(sb + MISC_OFF) & 1;
  if (q == 3) st_rlx2(Eb + tb * 1280, tag ^ 1, tag ^ 1);
  float2 lam, mu, mu2;
  float rs0, rs1;
  const uint32_t lamp = sb + LAM_OFF + 16 * (32 * wg + 8 * w + g);
  {
    const uint2* rp = S->RS + (8 * cb + 4 * wg + w) * 16 + 2 * g - (g & 1);
    uint2 v = ld_rlx2(rp);
    asm volatile("ld.shared.v2.f32 {%0,%1},[%2];" : "=f"(lam.x), "=f"(lam.y) : "r"(lamp));
    const float2 l2 = cmul(lam, lam), l4 = cmul(l2, l2), l8 = cmul(l4, l4), l16 = cmul(l8, l8), l32 = cmul(l16, l16);
    mu = full ? cmul(l32, l8) : l32; mu2 = cmul(mu, mu);
#pragma unroll 1
    for (int it = 0; it < SPIN && __any_sync(0xffffffff, untagged(v, tag)); it++) v = ld_rlx2(rp);
    rs0 = untag(v.x); rs1 = untag(v.y);
  }
  if (tid == 0 && wg == 0 && !LY) PROF(39);
  mbar_wait(BAR(B_ST), LY);
  const uint32_t ssm = sb + SSM_OFF + q * (full ? 336 : 272);
  wg_wait<0>(); fence_regs(a);
  if (rels) mbar_arrive_at(rel);
  if (tid == 0 && wg == 0) PROF(LY ? 21 : 5);
  float2 p = make_float2(0.f, 0.f);
#pragma unroll
  for (int j = 0; j < 20; j++) {
    if (j < 16 || full) {
      float4 sv;
      asm volatile("ld.shared.v4.f32 {%0,%1,%2,%3},[%4];" : "=f"(sv.x), "=f"(sv.y), "=f"(sv.z), "=f"(sv.w) : "r"(ssm + 16 * j));
#pragma unroll
      for (int e = 0; e < 2; e++) {
        const int o = 4 * j + e;
        const float r = e ? sv.z : sv.x, nm = e ? sv.w : sv.y;
        a[o] = fmaf(a[o], r, nm * rs0); a[o + 2] = fmaf(a[o + 2], r, nm * rs1);
        p = cfma(lam, p, make_float2(a[o], a[o + 2]));
      }
    }
  }
  {
    float2 t = make_float2(__shfl_up_sync(0xffffffff, p.x, 1, 4), __shfl_up_sync(0xffffffff, p.y, 1, 4));
    if (q >= 1) p = cfma(mu, t, p);
    t = make_float2(__shfl_up_sync(0xffffffff, p.x, 2, 4), __shfl_up_sync(0xffffffff, p.y, 2, 4));
    if (q >= 2) p = cfma(mu2, t, p);
  }
  if (q == 3 && full) st_rlx2(Eb + tb * 1280, tagf(p.x, tag), tagf(p.y, tag));
  if (tid == 0 && wg == 1) PROF(96 + 64 * LY);
  uint2 ev[3];
#pragma unroll
  for (int i = 0; i < 3; i++) { const int j = tb - 1 - q - 4 * i; ev[i] = j >= 0 ? ld_rlx2(Eb + j * 1280) : make_uint2(tag, tag); }
  float2 x = make_float2(__shfl_up_sync(0xffffffff, p.x, 1, 4), __shfl_up_sync(0xffffffff, p.y, 1, 4));
  if (q == 0) x = make_float2(0.f, 0.f);
  float c0, c1;
  asm volatile("ld.shared.v2.f32 {%0,%1},[%2+8];" : "=f"(c0), "=f"(c1) : "r"(lamp));
  const float c2 = -flip(c1, H.swap), c3 = flip(c0, H.swap);
#pragma unroll
  for (int i = 0; i < 40; i++) {
    const int o = 4 * (i >> 1) + (i & 1);
    const float u = a[o], v = a[o + 2];
    a[o] = fmaf(c0, u, c1 * v); a[o + 2] = fmaf(c2, u, c3 * v);
  }
  fence_regs(a);
  if (LY == 0 && R.b() < 128) {
    const int t0 = 16 * g + 8 * wg + 2 * w;
    if (tid == 0 && wg == 1) PROF(366);
    mbar_wait(BAR(B_XR));
    if (tid == 0 && wg == 1) PROF(367);
    uint4 s = lds4(sb + XR_OFF + 20480 + 256 + 8 * t0);
    if (__any_sync(0xffffffff, untagged(s, tag))) {
#pragma unroll 1
      for (int it = 0; it < SPIN; it++) { s = ld_rlx4(S->S + 128 * (R.b() >> 3) + t0); if (!__any_sync(0xffffffff, untagged(s, tag))) break; }
    }
    resid_load(xr, sb, wg, tid, s);
  }
  float2 mq, om4, fq;
  {
    asm volatile("" : "+f"(lam.x), "+f"(lam.y));
    const float2 one = make_float2(1.f, 0.f), l2 = cmul(lam, lam), l4 = cmul(l2, l2), l8 = cmul(l4, l4), l16 = cmul(l8, l8);
    const float2 l80 = full ? mu2 : cmul(mu2, l16), om = cmul(l80, l80), om2 = cmul(om, om);
    mq = cmul((q & 1) ? mu : one, (q & 2) ? mu2 : one);
    om4 = cmul(om2, om2); fq = cmul((q & 1) ? om : one, (q & 2) ? om2 : one);
  }
  mbar_wait(BAR(B_E1 + 9), LY);
  if (tid == 0 && wg == 1) PROF(368 + LY);
#pragma unroll 1
  for (int it = 0; it < SPIN; it++) {
    const bool m0 = untagged(ev[0], tag), m1 = untagged(ev[1], tag), m2 = untagged(ev[2], tag);
    if (!__any_sync(0xffffffff, m0 || m1 || m2)) break;
    if (m0) ev[0] = ld_rlx2(Eb + (tb - 1 - q) * 1280);
    if (m1) ev[1] = ld_rlx2(Eb + (tb - 5 - q) * 1280);
    if (m2) ev[2] = ld_rlx2(Eb + (tb - 9 - q) * 1280);
  }
  if (tid == 0 && wg == 1) PROF(97 + 64 * LY);
  float2 c = make_float2(untag(ev[2].x), untag(ev[2].y));
#pragma unroll
  for (int i = 1; i >= 0; i--) c = cfma(om4, c, make_float2(untag(ev[i].x), untag(ev[i].y)));
  c = cmul(fq, c);
#pragma unroll
  for (int s = 1; s <= 2; s <<= 1) { c.x += __shfl_xor_sync(0xffffffff, c.x, s); c.y += __shfl_xor_sync(0xffffffff, c.y, s); }
  c = cfma(mq, c, x);
  float2 z = make_float2(fmaf(c0, c.x, c1 * c.y), fmaf(c2, c.x, c3 * c.y));
  if (tid == 0 && wg == 0) PROF(LY ? 22 : 6);
  const float2 lc = make_float2(lam.x, flip(lam.y, H.swap));
  const uint32_t hq = sb + (lane >> 4) * 1024 + (lane & 7) * 128 + (((4 * wg + w) ^ (lane & 7)) << 4);
  const uint32_t hp = hq + R_OFF + (lane & 8) * 2048, hp4 = hq + (LY ? R4_OFF1 : R4_OFF0) + (lane & 8) * 512;
#pragma unroll
  for (int j = 0; j < 20; j += 2) {
    if (j < 16 || full) {
      uint32_t o[4];
#pragma unroll
      for (int i = 0; i < 2; i++) {
        const float2 z0 = cfma(lc, z, make_float2(a[4 * (j + i)], a[4 * (j + i) + 2]));
        z = cfma(lc, z0, make_float2(a[4 * (j + i) + 1], a[4 * (j + i) + 3]));
        o[2 * i] = pack_bf(z0.x, z.x); o[2 * i + 1] = pack_bf(z0.y, z.y);
      }
      asm volatile("stmatrix.sync.aligned.m8n8.x4.trans.shared.b16 [%0], {%1,%2,%3,%4};" ::"r"(j < 16 ? hp + j * 1024 : hp4 + (j - 16) * 1024), "r"(o[0]), "r"(o[1]), "r"(o[2]), "r"(o[3]) : "memory");
      if (j & 2) { __syncwarp(); if (lane == 0) mbar_arrive(BAR(B_SH + j / 4)); }
    }
  }
  if (tid == 0 && wg == 0) PROF(LY ? 23 : 7);
  if (lane == 0) PROF(390 + 4 * wg + w);
}

__device__ __forceinline__ void gate_load(uint32_t (&G)[20], uint32_t sb, int LY, int wg, int tid, int tb2) {
  const uint32_t bars = sb + BAR_OFF;
  const int lane = tid & 31, w = tid >> 5;
  mbar_wait(BAR(B_GF), LY);
  const int g = lane >> 2, q = lane & 3;
  const uint32_t gb = sb + (LY ? G_OFF1 : G_OFF0) + wg * 10240 + 512 * q + ((32 * w + 4 * g) ^ (64 * ((tb2 ^ q) & 1)) ^ (16 * (q & 2)));
#pragma unroll
  for (int i = 0; i < 20; i++) G[i] = lds32((gb ^ (16 * (i & 3))) + 128 * (i & 3) + 2048 * (i >> 2));
}
__device__ __forceinline__ void g2_phase(const int LY, const Params& P, Scratch* S, uint32_t sb, int wg, int tid, Role R, float (&xr)[40], long long t_start) {
  sb = opaque(sb);
  const uint32_t bars = sb + BAR_OFF;
  if (LY) {
    const int td = opaque(tid), b = (opaque(R.v) >> 8) & 255;
    const uint32_t tag = lds32(sb + MISC_OFF) & 1;
    const uint2* sp = S->S + 2 * SEQ + 128 * (b >> 3) + 4 * (td & 28) + 8 * wg + 2 * (td >> 5);
    if (!(R.cb() & 1)) mbar_wait(BAR(B_HD), 1);
    uint2 dl[5];
#pragma unroll
    for (int J = 0; J < 5; J++) dl[J] = __ldg((const uint2*)(P.dskip + 80 * (b & 7) + 4 * (td & 3) + 16 * J));
    uint4 sv;
#pragma unroll 1
    for (int it = 0; it < SPIN; it++) { sv = ld_rlx4(sp); if (!__any_sync(0xffffffff, untagged(sv, tag))) break; }
#pragma unroll
    for (int h = 0; h < 2; h++)
#pragma unroll
      for (int J = 0; J < 5; J++)
#pragma unroll
        for (int c = 0; c < 4; c++) {
          const float x2 = xr[IDX(J, c, h)];
          const uint32_t dw = (c & 2) ? dl[J].y : dl[J].x;
          xr[IDX(J, c, h)] = fmaf(fmaf(x2, untag(h ? sv.z : sv.x), untag(h ? sv.w : sv.y)), (c & 1) ? bf_hi(dw) : bf_lo(dw), x2);
        }
    fence_regs(xr);
  }
  float acc[40];
#pragma unroll
  for (int i = 0; i < 40; i++) acc[i] = RIAT == 1 ? 0.f : xr[i];
  fence_regs(acc);
#define G2_STEP(st, cs, hf) { \
    const uint64_t da = make_desc(sb + H_OFF + (st) * 32768 + (hf) * 16384 + wg * 8192, 16, 1024, 1), db = make_desc(sb + (cs) * 20480 + (hf) * 10240, 16, 1024, 1); \
    wg_fence(); \
    _Pragma("unroll") for (int kk = 0; kk < 4; kk++) wgmma_ss80(acc, da + 2 * kk, db + 2 * kk, 1); \
    wg_commit(); }
  mbar_wait(BAR(B_F2), LY);
  if (tid == 0 && wg == 0) PROF(LY ? 25 : 10);
  G2_STEP(0, 0, 0)
  mbar_wait(BAR(B_F3), LY);
  G2_STEP(0, 0, 1)
  tid = opaque(tid); R.v = opaque(R.v);
  const uint32_t tag = lds32(sb + MISC_OFF) & 1;
  const int b = R.b(), tb2 = b >> 3, db_ = b & 7;
  const int w = tid >> 5, lane = tid & 31, g = lane >> 2, q = lane & 3;
  const int t0 = 128 * tb2 + 16 * g + 8 * wg + 2 * w;
  const int d0 = 80 * db_ + 4 * q, mrow = 64 * wg + 16 * w + g;
#define GATE(J, c, h) ((h) ? bf_hi(G[4 * (J) + (c)]) : bf_lo(G[4 * (J) + (c)]))
  uint32_t rel = mapa(BAR(B_E2), lane ? ((w & 1) ? R.wpart() : R.rank()) : R.cs() == 8 ? 4 * wg + w : wg);
  const bool rels = lane == 0 || (lane == 1 && w < 2);
  uint32_t* Mb = S->M + ((2 * LY * 16 + tb2) * 8) * 256 + (wg * 4 + w) * 32 + (2 * g + (q & 1)) * 2 + (q >> 1);
  {
    uint32_t bf = BAR(B_F2 + 1), st = 1, ra = rel + 8 * (B_EA - B_E2);
    const int lag = wg ? (LY ? STG : STG0) / 2 : 0;
#pragma unroll 1
    for (int kp = 1; kp < 10; kp++) {
      const bool more = LY == 0 || kp < 8;
      wg_wait<1>();
      if (lane == 0 && more) mbar_arrive_at(ra + 8 * (st ? st - 1 : 2));
      mbar_wait(bf, LY);
      if (STG && !(STG & 1) && kp == lag) bar_sync(5, 256);
      G2_STEP(st, kp < 5 ? kp : kp - 5, 0)
      wg_wait<1>();
      if (rels && more) mbar_arrive_at(rel);
      rel += 8;
      mbar_wait(bf + 8 * (B_F3 - B_F2), LY);
      if ((STG & 1) && kp == lag) bar_sync(5, 256);
      G2_STEP(st, kp < 5 ? kp : kp - 5, 1)
      if (kp == MIAT) {
        st_rlx(Mb + db_ * 256, tag ^ 1);
        if (LY == 0) st_rlx(Mb + (16 * 8 + db_) * 256, tag ^ 1);
      }
      bf += 8; st = st == 2 ? 0 : st + 1;
    }
  }
  if (STG && (LY || STG0) && !wg) asm volatile("bar.arrive 5, 256;" ::: "memory");
  wg_wait<0>(); fence_regs(acc);
  if (LY == 0 && rels) mbar_arrive_at(rel);
  if (tid == 0 && wg == 0) PROF(LY ? 26 : 11);
  if (lane == 0) PROF(116 + 64 * LY + wg * 4 + w);

  float mm[2] = {0.f, 0.f}, rr[2];
#pragma unroll 1
  for (int rep = 0;; rep++) {
    float m[2][2];
#pragma unroll
    for (int h = 0; h < 2; h++) {
      m[h][0] = m[h][1] = 0.f;
#pragma unroll
      for (int J = 0; J < 5; J++)
#pragma unroll
        for (int c = 0; c < 4; c++) { const float xv = acc[IDX(J, c, h)]; m[h][0] += xv; m[h][1] = fmaf(xv, xv, m[h][1]); }
    }
    float r1[2];
#pragma unroll
    for (int i = 0; i < 2; i++) { const float snd = (q & 1) ? m[0][i] : m[1][i], kp = (q & 1) ? m[1][i] : m[0][i]; r1[i] = kp + __shfl_xor_sync(0xffffffff, snd, 1); }
    const float r2 = ((q & 2) ? r1[1] : r1[0]) + __shfl_xor_sync(0xffffffff, (q & 2) ? r1[0] : r1[1], 2);
    const uint32_t mx = sb + MX_OFF + 512 * wg + 4 * tid, bx = BAR(B_KF + 1 + 2 * LY + wg);
    if (R.cs() == 8 && !rep) {
#pragma unroll
      for (int i = 0; i < 8; i++)
        asm volatile("st.async.weak.shared::cluster.mbarrier::complete_tx::bytes.b32 [%0],%1,[%2];" ::"r"(mapa(mx + 1024 * db_, i ^ db_)), "f"(r2), "r"(mapa(bx, i ^ db_)) : "memory");
      if (tid == 0) mbar_expect_tx(bx, 4096);
    }
    st_rlx(Mb + db_ * 256, tagf(r2, tag));
    if (rep) break;
    if (lane == 0) PROF(100 + 64 * LY + wg * 4 + w);
    uint32_t G[20];
    const bool late = LY == 0 && db_ >= GLATE;
#pragma unroll
    for (int i = 0; i < 20; i++) G[i] = 0;
    if (!late) gate_load(G, sb, LY, wg, tid, tb2);
    mbar_wait(BAR(B_CD + 1));
    uint32_t mv[8];
    if (R.cs() == 8) {
      mbar_wait(bx, 1);
#pragma unroll
      for (int i = 0; i < 8; i++) mv[i] = lds32(mx + 1024 * i);
    } else {
#pragma unroll
    for (int i = 0; i < 8; i++) mv[i] = ld_rlx(Mb + i * 256);
#pragma unroll 1
    for (int it = 0; it < SPIN; it++) {
      uint32_t miss = 0;
#pragma unroll
      for (int i = 0; i < 8; i++) miss |= ((mv[i] ^ tag) & 1) << i;
      if (!__any_sync(0xffffffff, miss)) break;
#pragma unroll
      for (int i = 0; i < 8; i++) if ((miss >> i) & 1) mv[i] = ld_rlx(Mb + i * 256);
    }
      if (MBAR || !LY) bar_sync(4, 256);
    }
    if (lane == 0) PROF(108 + 64 * LY + wg * 4 + w);
    const float s = ((untag(mv[0]) + untag(mv[1])) + (untag(mv[2]) + untag(mv[3]))) + ((untag(mv[4]) + untag(mv[5])) + (untag(mv[6]) + untag(mv[7])));
    const float o = __shfl_xor_sync(0xffffffff, s, 2);
    const float S1 = (q & 2) ? o : s, S2 = (q & 2) ? s : o;
    const float mean = S1 * (1.f / DM), rs = frsqrt(fmaxf(S2 * (1.f / DM) - mean * mean, 0.f) + 1e-5f);
    const float mo = __shfl_xor_sync(0xffffffff, mean, 1), ro = __shfl_xor_sync(0xffffffff, rs, 1);
    mm[0] = (q & 1) ? mo : mean; mm[1] = (q & 1) ? mean : mo; rr[0] = (q & 1) ? ro : rs; rr[1] = (q & 1) ? rs : ro;
    if (late) gate_load(G, sb, LY, wg, tid, tb2);
    if (tid == 0 && wg == 0) PROF(LY ? 27 : 12);
    const float nm[2] = {-mm[0] * rr[0], -mm[1] * rr[1]};
    if (LY) mm[0] = mm[1] = 0.f;
#pragma unroll
    for (int h = 0; h < 2; h++)
#pragma unroll
      for (int J = 0; J < 5; J++)
#pragma unroll
        for (int c = 0; c < 4; c++) { const float xv = acc[IDX(J, c, h)]; acc[IDX(J, c, h)] = fmaf(fmaf(xv, rr[h], nm[h]), GATE(J, c, h), xv - mm[h]); }
    if (LY) break;
    if (R.cs() == 8) mbar_wait(BAR(B_KF + 1), 1);
#pragma unroll
    for (int i = 0; i < 10; i++) {
      const int J = i >> 1, h = i & 1;
      const uint32_t u0 = pack_bf(acc[IDX(J, 0, h)], acc[IDX(J, 1, h)]), u1 = pack_bf(acc[IDX(J, 2, h)], acc[IDX(J, 3, h)]);
      asm volatile("st.shared.v2.u32 [%0],{%1,%2};" ::"r"(sb + US_OFF + ((mrow ^ 64) + 8 * h) * 160 + 32 * J + 8 * q), "r"(u0), "r"(u1) : "memory");
    }
    __syncwarp();
    if (lane == 0) mbar_arrive(BAR(B_GS + 1 + wg));
    if (tid == 0 && wg == 0) PROF(13);
    Mb += 16 * 8 * 256;
  }
  if (LY == 0) {
#pragma unroll
    for (int i = 0; i < 40; i++) xr[i] = acc[i] + mm[(i >> 1) & 1];
    if (tid == 0 && wg == 0) PROF(15);
  }
  else {
    float* op = P.out + (size_t)t0 * DM + d0;
#pragma unroll
    for (int i = 0; i < 10; i++) {
      const int J = i >> 1, h = i & 1;
      asm volatile("st.global.v4.f32 [%0],{%1,%2,%3,%4};" ::"l"(op + h * DM + 16 * J),
                   "f"(acc[IDX(J, 0, h)]), "f"(acc[IDX(J, 1, h)]), "f"(acc[IDX(J, 2, h)]), "f"(acc[IDX(J, 3, h)]) : "memory");
    }
  }
  if (tid == 0 && wg == 0 && LY) PROF(28);
#undef IDX
#undef GATE
}

__device__ __forceinline__ void next_stats(Scratch* S, uint32_t sb, int tb2, int tid) {
  const uint32_t bars = sb + BAR_OFF, tag = lds32(sb + MISC_OFF) & 1;
  const uint32_t* Mb = S->M + tb2 * 8 * 256 + 2 * tid;
  mbar_wait(BAR(B_F1 + NSAT), 1);
  float m1, s1, s2;
#pragma unroll 1
  for (int it = 0; it < SPIN; it++) {
    uint32_t a[8], miss = 0;
    uint2 v[8];
#pragma unroll
    for (int i = 0; i < 8; i++) { a[i] = ld_rlx(Mb + i * 256); v[i] = ld_rlx2((const uint2*)(Mb + (16 * 8 + i) * 256)); }
#pragma unroll
    for (int i = 0; i < 8; i++) miss |= (a[i] ^ tag) | (v[i].x ^ tag) | (v[i].y ^ tag);
#define SUM8(F) ((untag(F(0)) + untag(F(1))) + (untag(F(2)) + untag(F(3)))) + ((untag(F(4)) + untag(F(5))) + (untag(F(6)) + untag(F(7))))
#define FA(i) a[i]
#define FX(i) v[i].x
#define FY(i) v[i].y
    m1 = SUM8(FA); s1 = SUM8(FX); s2 = SUM8(FY);
    if (!__any_sync(0xffffffff, miss & 1)) break;
  }
  const float mean = s1 * (1.f / DM), rs = frsqrt(fmaxf(s2 * (1.f / DM) - mean * mean, 0.f) + 1e-5f);
  uint2* sp = S->S + SEQ + 128 * tb2 + 8 * (tid & 14) + 2 * (tid >> 4) + (tid & 1);
  st_rlx2(sp, tagf(rs, tag), tagf(-mean * rs, tag));
  st_rlx2(sp + SEQ, tagf(rs, tag), tagf(-(mean + m1 * (1.f / DM)) * rs, tag));
}
template <int I0, int I1> __device__ __forceinline__ void init_barriers(uint32_t bars) {
#pragma unroll
  for (int i = I0; i < I1; i++) mbar_init(BAR(i), bar_count(i));
}
__device__ __forceinline__ int g2_cb(int kp) { return kp < 5 ? 2 * kp : 2 * kp - 9; }
__device__ __forceinline__ const unsigned* h_flag(Scratch* S, int ly, int tb2, int lane) {
  const int s0 = 128 * min(tb2, 15) / 160;
  const bool two = (128 * tb2 + 127) / 160 != s0;
  return &S->flag[(F_H + (ly * 13 + s0) * 10 + min(lane & 15, 9) + (two && lane >= 16 ? 10 : 0)) * 32];
}
__device__ __forceinline__ void gate_tile(const Params& P, uint32_t dst, uint32_t bar, int tb2, int db) {
  mbar_expect_tx(bar, 20480);
  tma2d(dst, &P.mGT, tb2 * 128, db * 80, bar);
  tma2d(dst + 10240, &P.mGT, tb2 * 128 + 64, db * 80, bar);
}
__global__ void __cluster_dims__() __launch_bounds__(512, 1) fused_kernel(const Head H, const __grid_constant__ Params P) {
  extern __shared__ __align__(1024) uint8_t smem[];
  const uint32_t sb = opaque(smem_u32(smem)), bars = sb + BAR_OFF;
  const int wi = __shfl_sync(0xffffffff, threadIdx.x >> 5, 0), wg = wi >> 2, tid = threadIdx.x & 127;
  const int umap = blockIdx.x >= 96;
#define CLK(v)
  CLK(c_a);
  if (wi == 14) {
    if (elect_one()) { init_barriers<0, NBAR1>(bars); asm volatile("fence.mbarrier_init.release.cluster;" ::: "memory"); }
    __syncwarp();
  } else if (wi >= 12) prefetch_map(wi == 12 ? &P.mB : &P.mA[umap]);
  else if (wg == 2) xb_prefetch<1>(H, blockIdx.x + H.base, tid, 0);
  else if (P.role[blockIdx.x].w) return;
  CLK(c_b);
  asm volatile("barrier.cluster.arrive.relaxed.aligned;" ::: "memory");
  CLK(c_c);
  Role R;
  { const uint4 r = P.role[blockIdx.x]; R.v = r.x; R.c = r.y; R.p = r.z; }
  const int id = R.c & 255;
  const int tb = R.tb(), cb = R.cb(), b = R.b(), tb2 = b >> 3, db = b & 7, rank = R.rank();
  const bool has1 = tb <= 12, has2 = b < 128, full = tb < 12;
  Scratch* const S = H.s;
  unsigned* const epoch_p = &S->epoch[id * 8];
  const long long t_start = 0;
  if (wg < 2) {
    if (threadIdx.x == 0) PROF(50);
    asm volatile("griddepcontrol.launch_dependents;");
    bar_sync(6, 448);
    asm volatile("setmaxnreg.inc.sync.aligned.u32 176;");
    float xr[40];
#pragma unroll
    for (int i = 0; i < 40; i++) xr[i] = 0.f;
#pragma unroll 1
    for (int ly = 0; ly < 2; ly++) {
      if (has1) g1_phase(ly, H, sb, wg, tid, R, xr, t_start);
      if (ly == 0) {
        resid_init(xr); fence_regs(xr);
        conv_loop<false>(sb, R.c, wg, tid, t_start);
        if (tid == 0 && wg == 0) PROF(9);
      }
      if (has2) g2_phase(ly, P, S, sb, wg, tid, R, xr, t_start);
    }
    if (tid == 0 && wg == 0) st_rlx(epoch_p, lds32(sb + MISC_OFF));
  } else if (wg == 2) {
    bar_sync(6, 448);
    if (has1) aux_prep(H, P, sb, R, tid, t_start);
    asm volatile("setmaxnreg.inc.sync.aligned.u32 136;");
    conv_loop<true>(sb, R.c, wg, tid, t_start);
    if (tid == 0) PROF(44);
    {
      const uint32_t bb = (P.role[blockIdx.x].x >> 8) & 255;
      if ((bb & 132) == NSDB && tid < 32) next_stats(H.s, sb, bb >> 3, 32 * (bb & 3) + tid);
    }
  } else {
    if (threadIdx.x == 384) PROF(354);
    asm volatile("setmaxnreg.dec.sync.aligned.u32 24;");
    const int wlo = R.wlo(), whi = R.whi();
    const uint32_t wmask = R.wmask(), umask = R.umask(), f1bytes = full ? 36864 : 32768;
    if (wi < 14) {
      if (threadIdx.x == 384) PROF(340);
      asm volatile("barrier.cluster.wait.aligned;" ::: "memory");
      if (has1 && elect_one()) {
        uint64_t tab = wi == 12 ? WTAB0 : XTAB0;
        PROF(329 + wi);
#pragma unroll 1
        for (int kb = 0; kb < 6; kb++, tab >>= 6) {
          const uint32_t dst = sb + ((uint32_t)tab & 63) * 4096;
          if (wi == 12) {
#pragma unroll 1
            for (int h = wlo; h <= whi; h++) tma4d_mc(dst + h * 8192, &P.mB, kb * 64, 0, 0, 8 * cb + 4 * h, BAR(B_F1 + kb), wmask);
          } else {
            tma4d_mc(dst + R.uj() * 1024, &P.mA[umap], kb * 64, 0, 0, 80 * tb + R.uj(), BAR(B_F1 + kb), umask);
            mbar_expect_tx(BAR(B_F1 + kb), f1bytes);
          }
        }
      }
      if (!has1 && wi == 13) bar_sync(7, 64);
    } else {
      if (wi == 15 && elect_one()) { init_barriers<NBAR1, NBAR>(bars); asm volatile("fence.mbarrier_init.release.cluster;" ::: "memory"); }
      bar_sync(6, 448);
      if (!has1 && wi == 14) bar_sync(7, 64);
    }
    const unsigned e1 = ld_rlx(epoch_p) + 1;
    if (wi == 12) {
      if (elect_one()) {
#pragma unroll 1
        for (int ly = 0; ly < 2; ly++) {
#pragma unroll 1
          for (int i = ly ? 0 : 6; i < 10 && has1; i++) {
            const int kb = (0x9876541032ull >> (4 * i)) & 15;
            if (ly == 0) { mbar_wait(BAR(B_E1 + ((DEP0 >> (4 * kb - 24)) & 15))); mbar_wait(BAR(B_AX + (kb == 9))); }
            else {
              if (has2 && i == (db >= GLATE ? 4 : 2)) {
                wait_cnt(&S->cnt[(C_G + db) * 32], e1 * 80);
                mbar_wait(BAR(B_E2 + 7));
                PROF(47);
                gate_tile(P, sb + G_OFF0, BAR(B_GF), tb2, db);
              }
              if (has2) mbar_wait(BAR(i < 4 ? B_E2 + ((0x9865u >> (4 * i)) & 15) : B_GE));
              else if (i == 0) { mbar_wait(BAR(B_E1 + 9)); mbar_wait(BAR(B_CD + 1)); }
              if (i >= 4) mbar_wait(BAR(i < 6 ? B_F1 + W4AT : B_E1 + i - 6), 1);
            }
            const uint32_t dst = sb + ((uint32_t)((ly ? WTAB1 : WTAB0) >> (6 * kb)) & 63) * 4096;
#pragma unroll 1
            for (int h = wlo; h <= whi; h++) tma4d_mc(dst + h * 8192, &P.mB, kb * 64, 0, 0, 8 * cb + 4 * h, BAR(B_F1 + kb), wmask);
          }
          if (has2) {
            if (ly == 0) {
              mbar_wait(BAR(B_E1 + XRAT));
              mbar_expect_tx(BAR(B_XR), 20480 + 160 + 1024);
              tma4d(sb + XR_OFF, &P.mX, 80 * db, tb2, BAR(B_XR));
              bulk_g2s(sb + XR_OFF + 20480, P.dskip + 80 * db, 160, BAR(B_XR));
              bulk_g2s(sb + XR_OFF + 20480 + 256, S->S + 128 * tb2, 1024, BAR(B_XR));
              if (CWAIT) mbar_wait(BAR(CWAIT == 1 ? B_KF + 2 : CWAIT == 2 ? B_KF + R.nch() - 1 : CWAIT == 3 ? B_KF + R.nch() - 2 : B_HD));
            }
#pragma unroll 1
            for (int kp = 0; kp < 10; kp++) {
              const uint32_t dst = sb + (kp < 5 ? kp : kp - 5) * 20480;
              mbar_wait(BAR(kp >= 5 ? B_E2 + kp - 5 : ly ? B_E1 + ((CTAB1 >> (4 * kp)) & 15) : kp < 3 ? B_SH : kp < 4 ? B_HD : B_CD), ly);
              mbar_expect_tx(BAR(B_F2 + kp), 10240 + 16384);
              tma5d(dst, &P.mC[0], g2_cb(kp) * 64, db * 5, BAR(B_F2 + kp));
              mbar_expect_tx(BAR(B_F3 + kp), 10240 + 16384);
              tma5d(dst + 10240, &P.mC[1], g2_cb(kp) * 64, db * 5, BAR(B_F3 + kp));
              if (ly && kp == 4) { mbar_wait(BAR(B_E1 + 9), 1); gate_tile(P, sb + G_OFF1, BAR(B_GF), tb2, db); }
            }
          }
        }
      }
    } else if (wi == 13) {
      const int h0 = R.cs() == 8 ? rank : 4 * rank;
#pragma unroll 1
      for (int ly = 0; ly < 2; ly++) {
        int lane = lane_id();
        if (has1) {
          const unsigned* fp = &S->flag[(F_U3 + 8 * ((160 * tb) >> 7) + (lane & (full ? 15 : 7))) * 32];
          uint32_t ready = ly ? __ballot_sync(0xffffffff, ld_rlx(fp) == e1) : ~0u;
          if (ly) mbar_wait(BAR(full ? B_KF + 1 : has2 ? B_GS + 1 : B_RF1), has2);
          if (ly && full) mbar_wait(BAR(B_KF + 2), 1);
#pragma unroll 1
          for (int kb = ly ? 0 : 6; kb < 10; kb++) {
            if (ly && kb == UPAT) { mbar_wait(BAR(B_XR)); ready = ~0u; }
            wait_flags(fp, e1, 0x101u * ((1u << (64 * kb / 80)) | (1u << ((64 * kb + 63) / 80))), ready);
            if (kb >= 4) mbar_wait(BAR(B_E1 + (ly ? kb - 4 : (DEP0 >> (4 * kb - 24)) & 15)), ly);
            mbar_wait(BAR(B_AX + (kb == 9)));
            if (elect_one()) {
              if (ly && kb == 0) PROF(34);
              tma4d_mc(sb + ((uint32_t)((ly ? XTAB1 : XTAB0) >> (6 * kb)) & 63) * 4096 + R.uj() * 1024, &P.mA[2 * ly + umap], kb * 64, 0, 0, 80 * tb + R.uj(),
                       BAR(B_F1 + kb), umask);
              mbar_expect_tx(BAR(B_F1 + kb), f1bytes);
            }
            __syncwarp();
          }
        }
        if (ly == 0) {
          if (has1) mbar_wait(BAR(B_E1 + KPF));
          if (elect_one()) {
#pragma unroll 1
            for (int s = 0; s < R.nch(); s++) prefetch_l2(P.ssmk + (size_t)R.ch(s) * SEQ, 4096);
          }
          lane = lane_id();
#pragma unroll
          for (int s = 0; s < 5; s++) {
            asm volatile("st.shared.v4.u32 [%0],{%1,%1,%1,%1};" ::"r"(conv_buf(sb, s) + 16 * lane), "r"(0) : "memory");
            asm volatile("st.shared.u8 [%0],%1;" ::"r"(conv_buf(sb, s) + KC_OFS + lane), "r"(0) : "memory");
          }
          fence_async();
          __syncwarp();
          const unsigned* cp = &S->cnt[(C_KV + (R.ch(min(lane, R.nch() - 1)) >> 6)) * 32];
          uint32_t ready = 0;
#pragma unroll 1
          for (int s = 0, sk = 0; s < R.nch(); s++) {
#pragma unroll 1
            for (; sk < (s ? R.nch() : KUP); sk++)
              if (elect_one()) { mbar_expect_tx(BAR(B_KF + sk), 8192); bulk_g2s(conv_buf(sb, sk) + KC_OFS + 32, P.ssmk + (size_t)R.ch(sk) * SEQ, 4096, BAR(B_KF + sk)); }
            PROFC(s == 0, 329);
#pragma unroll 1
            for (int it = 0; !((ready >> s) & 1) && it < SPIN; it++) ready = __ballot_sync(0xffffffff, (int)(ld_rlx(cp) - e1 * 32) >= 0);
            PROFC(s == 0, 30);
            if (elect_one()) {
              bulk_g2s(conv_buf(sb, s) + KV_PAD, S->kv + (size_t)R.ch(s) * SEQ, 4096, BAR(B_KF + s));
              if (s == 0 && has2) { prefetch_l2(P.cre + (size_t)5 * b * DM, 5 * DM * 2); prefetch_l2(P.cim + (size_t)5 * b * DM, 5 * DM * 2); }
            }
            __syncwarp();
          }
          PROF(31);
          if (!has1) return;
        }
        lane = lane_id();
        const unsigned* fp = h_flag(S, ly, tb2, lane);
        uint32_t ready = __ballot_sync(0xffffffff, ld_rlx(fp) == e1), st = 0;
        if (ly == 0 && !has2) {
          mbar_wait(BAR(B_HD));
          if (lane < 8) mbar_arrive_cl(BAR(B_RF1), lane & 1);
        }
        if (has2) {
          mbar_wait(BAR(B_RF0), ly);
#pragma unroll 1
          for (int kp = 0; kp < 10; kp++) {
            if (kp == 5) { mbar_wait(BAR(B_XR), 1); ready = ~0u; }
            if (kp == 2) { mbar_wait(BAR(B_HD), ly); if (lane < 8) mbar_arrive_cl(BAR(B_RF1), lane & (R.cs() - 1)); }
            wait_flags(fp, e1, 0x10001u << g2_cb(kp), ready);
            if (kp == 2) mbar_wait(BAR(B_RF1), ly);
#pragma unroll
            for (int hf = 0; hf < 2; hf++) {
              if (kp >= 3) { if (hf) mbar_wait(BAR(B_E2 + kp - 3), ly); else mbar_wait(BAR(B_EA + st), ly ^ (kp >= 6 && kp < 9)); }
              if (elect_one()) {
                if (kp == 0 && !hf) PROF(33 + 2 * ly);
                tma4d_mc(sb + H_OFF + st * 32768 + hf * 16384 + h0 * 2048, &P.mH, g2_cb(kp) * 128 + hf * 64, 0, 2 * h0,
                         ly * 16 + tb2, BAR((hf ? B_F3 : B_F2) + kp), (1u << R.cs()) - 1);
              }
              __syncwarp();
            }
            st = st == 2 ? 0 : st + 1;
          }
        }
      }
    } else if (wi == 14) {
      if (!has1) return;
      prefetch_if(P.dskip + 64 * (tid & 31), (tid & 31) < 10);
      if (elect_one()) { prefetch_map(&P.sK); prefetch_map(&P.mX); prefetch_map(&P.sH); prefetch_map(&P.sU); prefetch_map(&P.mC[0]); prefetch_map(&P.mC[1]); prefetch_map(&P.mH); prefetch_map(&P.mGT); prefetch_map(&P.mA[2 + umap]); }
      __syncwarp();
#pragma unroll 1
      for (int ly = 0; ly < 2; ly++) {
        if (ly) {
          mbar_wait(BAR(B_F1 + 1), 1);
          uint32_t ready = 0;
          wait_flags(&S->flag[(F_U3 + 8 * ((160 * tb) >> 7) + ((lane_id() + ly) & (full ? 15 : 7))) * 32], e1, ~0u, ready);
          if (elect_one()) mbar_arrive(BAR(B_XR));
        }
        const int lane = lane_id();
        mbar_wait(BAR(B_E1 + (ly ? STAT_AT1 : STAT_AT)), ly);
        PROFC(lane == 0 && ly == 0, 36);
        {
          const int l = lane - (full ? 0 : 16);
          const uint2* p = S->S + ly * SEQ + 160 * tb + 2 * l;
          uint4 v[3];
#pragma unroll 1
          for (int it = 0; it < SPIN; it++) {
            v[0] = ld_rlx4(p); v[1] = ld_rlx4(p + 64); v[2] = ld_rlx4(p + 96);
            const bool miss = __any_sync(0xffffffff, untagged(v[0], e1 & 1) | untagged(v[1], e1 & 1) | untagged(v[2], e1 & 1));
            PROFC(lane == 0 && ly == 0 && it == 0, 37);
            if (!miss) break;
          }
          PROFC(lane == 0 && ly == 0, 38);
#pragma unroll
          for (int i = 0; i < 3; i++) {
            const int pr = l + (i == 2 ? 48 : 32 * i);
            if (pr >= 0) asm volatile("st.shared.v4.u32 [%0],{%1,%2,%3,%4};" ::"r"(sb + SSM_OFF + 16 * (pr + ((pr * (full ? 205 : 256)) >> 12))), "r"(v[i].x & ~1u),
                                      "r"(v[i].y & ~1u), "r"(v[i].z & ~1u), "r"(v[i].w & ~1u) : "memory");
          }
          __syncwarp();
        }
        if (lane == 0) mbar_arrive(BAR(B_ST));
        if (ly && has2) {
          mbar_wait(BAR(B_E1 + 9), 1);
          if (lane < 8) mbar_arrive_cl(BAR(B_RF0), lane & (R.cs() - 1));
        }
        if (lane == 0) {
#pragma unroll 1
          for (int pc = 0; pc < (full ? 5 : 4); pc++) {
            if ((HWM >> (4 * pc)) & 8) {
              mbar_wait(BAR(B_SH + min((HWM >> (4 * pc)) & 7, full ? 4 : 3)), ly);
              PROF(380 + 5 * ly + pc);
              if (pc == 0 && (cb & 1)) delay(ly ? HDLY : HDLY0);
              fence_async();
            }
#pragma unroll
            for (int i = 0; i < 2; i++) tma4d_store(&P.sH, sb + (pc < 4 ? R_OFF + i * 16384 + pc * 4096 : (ly ? R4_OFF1 : R4_OFF0) + i * 4096), 128 * cb + 64 * i, 0, 0, ly * 1024 + 80 * tb + 4 * pc);
          }
          bulk_commit(); bulk_wait();
          PROF(ly ? 17 : 16);
          mbar_arrive(BAR(B_HD));
          release<1>();
          signal_flag(&S->flag[(F_H + (ly * 13 + tb) * 10 + cb) * 32], e1);
          PROF(ly ? 24 : 8);
        }
        __syncwarp();
        if (has2) {
          mbar_wait(BAR(B_F2 + FPAT), ly);
          uint32_t ready = 0;
          wait_flags(h_flag(S, ly, tb2, lane_id() | 1), e1, ~0u, ready);
          if (elect_one()) mbar_arrive(BAR(B_XR));
        }
        if (lane == 0 && has2 && !ly) {
          mbar_wait(BAR(B_CD + 1));
#pragma unroll
          for (int i = 0; i < 2; i++) {
            mbar_wait(BAR(B_GS + 1 + i), 1);
            fence_async();
            tma4d_store(&P.sU, sb + US_OFF + 10240 - 10240 * i, 80 * db, 0, 8 * i, tb2);
          }
          bulk_commit(); bulk_wait();
          PROF(18);
          release<2>(); signal_flag(&S->flag[(F_U3 + b) * 32], e1);
          PROF(14);
          mbar_wait(BAR(B_SG));
          mbar_arrive(BAR(B_GE)); mbar_arrive_cl(BAR(B_GE), R.wpart());
        }
        __syncwarp();
      }
    } else {
      discretise(H, P, sb, R, tid & 31, e1);
      if (elect_one()) {
        mbar_arrive(BAR(B_LM));
        PROF(348);
        if (b < R.nprep()) {
#pragma unroll 1
          for (int task = b, r = 0; task < 320; task += R.nprep(), r++) {
            mbar_wait(BAR(B_PS + r));
            PROF(320 + 3 * r);
            fence_async();
            tma2d_store(&P.sK, sb + KS_OFF + r * 8192, 64 * (task & 31), 64 * (task >> 5));
            bulk_commit(); bulk_wait();
            PROF(321 + 3 * r);
            release<4>();
            signal_cnt(&S->cnt[(C_KV + (task >> 5)) * 32], 1);
            PROF(322 + 3 * r);
          }
          PROF(41);
        }
        if (has2) {
          mbar_wait(BAR(B_SH));
#pragma unroll 1
          for (int i = 0; i < 8; i++) mbar_arrive_cl(BAR(B_RF0), i & (R.cs() - 1));
        }
#pragma unroll 1
        for (int s = 0, s0 = 0; s < R.nch(); s++) {
          mbar_wait(BAR(B_GS + s));
          fence_async();
          bulk_s2g(S->gt + (size_t)R.ch(s) * SEQ, conv_buf(sb, s) + KC_OFS, 4096); bulk_commit();
          if (s == 1 || s >= R.nch() - GSPL) bulk_wait();
          if (s == 1 || s == min(R.nch() - 1, 3)) mbar_arrive(BAR(B_CD + (s > 1)));
          mbar_arrive_if(BAR(B_SG), s == R.nch() - 1);
          if (s >= R.nch() - GSPL) {
            PROF(45);
            release<8>();
#pragma unroll 1
            for (; s0 <= s; s0++) signal_cnt(&S->cnt[(C_G + R.ch(s0) / 80) * 32], 1);
          }
        }
        PROF(46);
      }
    }
  }
}

typedef CUresult (*EncFn)(CUtensorMap*, CUtensorMapDataType, cuuint32_t, void*, const cuuint64_t*, const cuuint64_t*, const cuuint32_t*,
                          const cuuint32_t*, CUtensorMapInterleave, CUtensorMapSwizzle, CUtensorMapL2promotion, CUtensorMapFloatOOBfill);
bool enc(EncFn f, CUtensorMap* m, const void* base, int rank, const cuuint64_t* dims, const cuuint64_t* strides, const cuuint32_t* box, bool swz,
         bool f32 = false) {
  const cuuint32_t es[5] = {1, 1, 1, 1, 1};
  return f(m, f32 ? CU_TENSOR_MAP_DATA_TYPE_FLOAT32 : CU_TENSOR_MAP_DATA_TYPE_BFLOAT16, rank, const_cast<void*>(base), dims, strides, box, es,
           CU_TENSOR_MAP_INTERLEAVE_NONE, swz ? CU_TENSOR_MAP_SWIZZLE_128B : CU_TENSOR_MAP_SWIZZLE_NONE, CU_TENSOR_MAP_L2_PROMOTION_L2_256B,
           CU_TENSOR_MAP_FLOAT_OOB_FILL_NONE) == CUDA_SUCCESS;
}
void make_roles(Params& P, bool big) {
  for (uint32_t bx = 0; bx < (big ? 120u : 12u); bx++) {
    const uint32_t c = bx >> 3, r = bx & 7, id = big ? bx : 120 + bx;
    const uint32_t vA = c < 12 ? (2 * (c >> 1) + (r >> 2)) | (4 * (c & 1) + (r & 3)) << 4 | (r & 4) << 16 | 4 << 19 | (r ^ 4) << 22
                               : (4 * (c - 12) + (r >> 1)) | (8 + (r & 1)) << 4 | (r & 6) << 16 | 2 << 19 | (r ^ 2) << 22;
    const uint32_t vB = (bx < 10 ? 12 : 13) | bx << 4 | 2 << 19 | (bx & 1) << 22 | (bx & 1) << 26;
    P.role[bx].x = (big ? vA | r << 26 | 1u << 29 : vB) | (id < 128 ? (id & ~7u) | (r >> 1) | (r & 1) << 2 : id) << 8;
    P.role[bx].y = id | (big ? 5 : bx < 8 ? 3 : 4) << 10 | 120 << 13 | 132 << 21 | (big ? 4u : 3u) << 29;
    const uint32_t v = P.role[bx].x, cb = (v >> 4) & 15, rank = (v >> 26) & 7, ubase = (v >> 16) & 7, ugs = (v >> 19) & 7, wp = (v >> 22) & 7;
    const uint32_t wlo = rank > wp, whi = wp != rank ? wlo : 1, wmask = 1u << rank | 1u << wp;
    const uint32_t uj = (rank - ubase) * (!big ? 8 : ugs == 4 ? 5 : 10), sm = big ? (0x7296418530ull >> (4 * cb)) & 15 : bx < 8 ? 4 * (bx & 1) + (bx >> 1) : 15;
    P.role[bx].z = wlo | whi << 1 | wmask << 2 | ((1u << ugs) - 1) << (10 + ubase) | uj << 20 | sm << 25;
    P.role[bx].w = 0;
  }
}
void launch(const Head& H, const Params& P, int grid, int cs, bool dependent) {
  cudaLaunchConfig_t cfg = {};
  cfg.gridDim = grid; cfg.blockDim = 512; cfg.dynamicSmemBytes = SMEM_BYTES; cfg.stream = cudaStreamPerThread;
  cudaLaunchAttribute at[2];
  at[0].id = cudaLaunchAttributeClusterDimension; at[0].val.clusterDim.x = cs; at[0].val.clusterDim.y = 1; at[0].val.clusterDim.z = 1;
  at[1].id = cudaLaunchAttributeProgrammaticStreamSerialization; at[1].val.programmaticStreamSerializationAllowed = 1;
  cfg.attrs = at; cfg.numAttrs = dependent ? 2 : 1;
  cudaLaunchKernelEx(&cfg, fused_kernel, H, P);
}

}

extern "C" void kernel_launch(void* const* d_in, const int* in_sizes, int n_in, void* d_out, int out_size) {
  (void)in_sizes; (void)n_in; (void)out_size;
  typedef const __nv_bfloat16* cb;
  void* fp = nullptr; cudaDriverEntryPointQueryResult qr;
  cudaGetDriverEntryPoint("cuTensorMapEncodeTiled", &fp, cudaEnableDefault, &qr);
  EncFn f = (EncFn)fp;
  Scratch* sp = nullptr;
  cudaGetSymbolAddress((void**)&sp, g_scr);
  void *pu = sp->u, *ph = sp->h, *pgt = sp->gt;
  Params P;
  Head H;
  H.s = sp; H.x = (cb)d_in[0]; H.swap = (uintptr_t)d_in[4] < (uintptr_t)d_in[3] ? 0 : 0x80000000u; H.b0 = (cb)d_in[H.swap ? 3 : 4]; H.b1 = (cb)d_in[H.swap ? 4 : 3];
  for (int i = 0; i < 2; i++) {
    const cuuint64_t d[4] = {640, 8, 2, 80}, s[3] = {1280, (cuuint64_t)((uintptr_t)H.b1 - (uintptr_t)H.b0), 8 * 1280}; const cuuint32_t bx[4] = {64, 8, 2, 4};
    if (enc(f, &P.mB, H.b0, 4, d, s, bx, true)) break;
    cudaMemcpyAsync(sp->bcopy, H.b0, DM * DM * 2, cudaMemcpyDeviceToDevice, cudaStreamPerThread);
    cudaMemcpyAsync(sp->bcopy + DM * DM, H.b1, DM * DM * 2, cudaMemcpyDeviceToDevice, cudaStreamPerThread);
    H.b0 = sp->bcopy; H.b1 = sp->bcopy + DM * DM;
  }
  {
    const cuuint64_t d[5] = {640, 2, 4, 2, 40}, s[4] = {1280, 4 * 1280, 2 * 1280, 16 * 1280}; const cuuint32_t bx[5] = {64, 2, 4, 2, 5};
    enc(f, &P.mC[0], d_in[5], 5, d, s, bx, true); enc(f, &P.mC[1], d_in[6], 5, d, s, bx, true); }
  { const cuuint64_t d[2] = {2048, 640}, s[1] = {4096}; const cuuint32_t bx[2] = {64, 80}; enc(f, &P.mGT, pgt, 2, d, s, bx, true); }
  { const cuuint64_t d[4] = {640, 8, 16, 16}, s[3] = {16 * 1280, 1280, 128 * 1280}; const cuuint32_t bx[4] = {80, 8, 16, 1}, bh[4] = {80, 8, 8, 1};
    enc(f, &P.sU, pu, 4, d, s, bh, false); enc(f, &P.mX, d_in[0], 4, d, s, bx, false); }
  { const cuuint64_t d[2] = {2048, 640}, s[1] = {4096}; const cuuint32_t bx[2] = {64, 64}; enc(f, &P.sK, sp->kv, 2, d, s, bx, true); }
  P.lre = (cb)d_in[1]; P.lim = (cb)d_in[2]; P.cre = (cb)d_in[5]; P.cim = (cb)d_in[6]; P.ldt = (cb)d_in[7]; P.dskip = (cb)d_in[8];
  P.out = (float*)d_out;
  P.k = (cb)d_in[10]; P.v = (cb)d_in[11]; P.shk = (cb)d_in[12]; P.ssmk = (cb)d_in[13]; P.ssmd = (cb)d_in[14];
  cudaFuncSetAttribute(fused_kernel, cudaFuncAttributeMaxDynamicSharedMemorySize, SMEM_BYTES);
  for (int big = 1; big >= 0; big--) {
    const cuuint64_t seg = big ? 40 : 32;
    for (int i = 0; i < 4; i++) {
      const cuuint64_t d[4] = {640, 2, 4, 1024}, s[3] = {1280, seg * 1280, 2 * 1280}; const cuuint32_t bx[4] = {64, 2, 4, !big ? 8u : (i & 1) ? 10u : 5u};
      enc(f, &P.mA[i], i < 2 ? d_in[0] : pu, 4, d, s, bx, true);
    }
    {
      const cuuint64_t d[4] = {1280, 8, 16, 32}, s[3] = {16 * 2560, 2560, 128 * 2560}; const cuuint32_t bx[4] = {64, 8, big ? 2u : 8u, 1};
      enc(f, &P.mH, ph, 4, d, s, bx, true); }
    { const cuuint64_t d[4] = {1280, 2, 4, 2048}, s[3] = {2560, seg * 2560, 2 * 2560}; const cuuint32_t bx[4] = {64, 2, 4, 4};
      enc(f, &P.sH, ph, 4, d, s, bx, true); }
    make_roles(P, big);
    H.base = big ? 0 : 120;
    launch(H, P, big ? 120 : 12, big ? 8 : 2, !big);
  }
}
```

```cpp
#include <cuda_runtime.h>
#include <cuda.h>
#include <cuda_bf16.h>
#include <stdint.h>

namespace {

constexpr int SEQ = 2048, DM = 640;
constexpr int SPIN = 1 << 20;
#define PFAT 99
#define KVDLY 500
#define PFD 1
#define XPFAT 9
#define STAT_AT 6
#define KPFAT 3
#define KPFAT2 5
#define KPF 7
#define HDLY 1900
#define GSPL 2
#define CWAIT 0
#define HDLY0 1900
#define CTAB1 0x96543u
#define NSAT 0
#define SKW 1
#define RIAT 2
#define MIAT 5
#define FPAT 1
#define UPAT 7
#define STAT_AT1 4
#define W4AT 0
#define MBAR 1
#define STG 17
#define STG0 17
#define HWM 0xc09
#define NSDB 4
#define GLATE 6
#define KUP 1
#define XRAT 9
#define ORD 1

struct Scratch {
  uint2 E[2 * 13 * 10 * 8 * 16];
  uint32_t M[3 * 16 * 8 * 256];
  uint2 S[3 * SEQ];
  uint2 RS[80 * 16];
  unsigned flag[512 * 32];
  unsigned cnt[32 * 32];
  unsigned epoch[132 * 8];
  unsigned zero[128];
  unsigned prof[132 * 512];
  __align__(1024)
  __nv_bfloat16 u[SEQ * DM];
  __nv_bfloat16 h[2 * SEQ * 1280];
  __nv_bfloat16 kv[DM * SEQ];
  __nv_bfloat16 gt[DM * SEQ];
  __nv_bfloat16 bcopy[2 * DM * DM];
};
__device__ __align__(1024) Scratch g_scr;
#define PROFC(c, i) do {} while (0)
#define PSEL 1
#define PROF(i) do {} while (0)

constexpr int C_KV = 0, C_G = 10;
constexpr int F_U3 = 0, F_H = 128;

constexpr int R_OFF = 196608, R4_OFF0 = 73728, R4_OFF1 = 122880, H_OFF = 131072, KS_OFF = 131072, CV_OFF = 86272, G_OFF0 = 40960, G_OFF1 = 102400, US_OFF = 98304, XR_OFF = 163840, MX_OFF = 32768;
constexpr int LAM_OFF = 229376, SSM_OFF = LAM_OFF + 1024, BAR_OFF = SSM_OFF + 1344;
constexpr int B_F1 = 0, B_E1 = 10, B_RF0 = 20, B_RF1 = 21, NBAR1 = 22;
constexpr int B_F2 = 22, B_KF = 32, B_GF = 37, B_CD = 38, B_XR = 40, B_ST = 41, B_HD = 42, B_LM = 43, B_E2 = 44, B_GS = 54, B_PS = 59, B_AX = 62, B_SH = 64, B_SG = 69, B_GE = 70, B_EA = 71, B_F3 = 74, NBAR = 84;
__host__ __device__ constexpr int bar_count(int i) { return i < B_E1 ? 1 : i < B_RF0 ? 9 : i < B_F2 ? 8 : i < B_E2 ? 1 : i < B_GS ? 12 : i < B_SH ? 4 : i < B_SG ? 8 : i < B_GE ? 1 : i < B_EA ? 2 : i < B_F3 ? 8 : 1; }
constexpr int MISC_OFF = BAR_OFF + NBAR * 8, SMEM_BYTES = MISC_OFF + 32;
constexpr int KV_PAD = 512, KC_OFS = KV_PAD + 4096, CH_STRIDE = 8960;
__device__ __forceinline__ uint32_t conv_buf(uint32_t sb, int slot) { return sb + CV_OFF + slot * CH_STRIDE; }
constexpr uint64_t tab6(int a, int b, int c, int d, int e, int f, int g, int h, int i, int j) {
  return (uint64_t)a | (uint64_t)b << 6 | (uint64_t)c << 12 | (uint64_t)d << 18 | (uint64_t)e << 24 | (uint64_t)f << 30 | (uint64_t)g << 36 | (uint64_t)h << 42 |
         (uint64_t)i << 48 | (uint64_t)j << 54;
}
constexpr uint64_t WTAB0 = tab6(0, 4, 8, 30, 12, 26, 0, 4, 8, 12), XTAB0 = tab6(40, 45, 50, 34, 16, 21, 40, 45, 50, 16);
constexpr uint64_t WTAB1 = tab6(16, 20, 0, 4, 8, 12, 16, 20, 24, 28), XTAB1 = tab6(40, 45, 50, 32, 40, 45, 50, 32, 40, 45);
constexpr uint32_t DEP0 = 0x4210;

struct Head {
  Scratch* s;
  const __nv_bfloat16 *x, *b0, *b1;
  uint32_t base, swap;
};
struct Params {
  const __nv_bfloat16 *lre, *lim, *ldt, *k, *v, *shk, *cre, *cim, *ssmk, *ssmd, *dskip;
  float* out;
  uint4 role[120];
  CUtensorMap mB, mA[4], mH, mC[2], mGT, mX, sH, sU, sK;
};

__device__ __forceinline__ uint32_t smem_u32(const void* p) { return (uint32_t)__cvta_generic_to_shared(p); }
__device__ __forceinline__ uint32_t opaque(uint32_t x) { uint32_t y; asm volatile("mov.u32 %0, %1;" : "=r"(y) : "r"(x)); return y; }
__device__ __forceinline__ int lane_id() { int y; asm volatile("mov.u32 %0, %%laneid;" : "=r"(y)); return y; }
__device__ __forceinline__ void delay(uint32_t n) {
  asm volatile("{ .reg .pred p; .reg .u32 a, b; mov.u32 a, %%clock; L: mov.u32 b, %%clock; sub.u32 b, b, a; setp.lt.u32 p, b, %0; @p bra.uni L; }" ::"r"(n) : "memory");
}
__device__ __forceinline__ void mbar_init(uint32_t bar, uint32_t cnt) { asm volatile("mbarrier.init.shared::cta.b64 [%0], %1;" ::"r"(bar), "r"(cnt) : "memory"); }
__device__ __forceinline__ void mbar_expect_tx(uint32_t bar, uint32_t bytes) { asm volatile("mbarrier.arrive.expect_tx.shared::cta.b64 _, [%0], %1;" ::"r"(bar), "r"(bytes) : "memory"); }
__device__ __forceinline__ void mbar_arrive(uint32_t bar) { asm volatile("mbarrier.arrive.shared::cta.b64 _, [%0];" ::"r"(bar) : "memory"); }
__device__ __forceinline__ void mbar_arrive_if(uint32_t bar, bool c) {
  asm volatile("{ .reg .pred p; setp.ne.u32 p, %1, 0; @p mbarrier.arrive.shared::cta.b64 _, [%0]; }" ::"r"(bar), "r"((uint32_t)c) : "memory");
}
__device__ __forceinline__ void prefetch_if(const void* p, bool c) { asm volatile("{ .reg .pred p; setp.ne.u32 p, %1, 0; @p prefetch.global.L2 [%0]; }" ::"l"(p), "r"((uint32_t)c)); }
__device__ __forceinline__ void mbar_arrive_cl(uint32_t bar, uint32_t cta) {
  asm volatile("{ .reg .b32 ra; mapa.shared::cluster.u32 ra, %0, %1; mbarrier.arrive.shared::cluster.b64 _, [ra]; }" ::"r"(bar), "r"(cta) : "memory");
}
__device__ __forceinline__ uint32_t mapa(uint32_t a, uint32_t cta) { uint32_t r; asm("mapa.shared::cluster.u32 %0, %1, %2;" : "=r"(r) : "r"(a), "r"(cta)); return r; }
__device__ __forceinline__ void mbar_arrive_at(uint32_t ra) { asm volatile("mbarrier.arrive.shared::cluster.b64 _, [%0];" ::"r"(ra) : "memory"); }
__device__ __forceinline__ void mbar_wait(uint32_t bar, uint32_t parity = 0) {
  asm volatile("{ .reg .pred p; .reg .u32 c; mov.u32 c, 0;\n"
               "W: mbarrier.try_wait.parity.shared::cta.b64 p, [%0], %1; @p bra.uni D;\n"
               "add.u32 c, c, 1; setp.lt.u32 p, c, 0x100000; @p bra.uni W;\nD: }" ::"r"(bar), "r"(parity) : "memory");
}
__device__ __forceinline__ bool elect_one() { uint32_t p; asm volatile("{ .reg .pred P; elect.sync _|P, 0xffffffff; selp.u32 %0,1,0,P; }" : "=r"(p)); return p; }
__device__ __forceinline__ void bar_sync(int id, int n) { __syncwarp(); asm volatile("bar.sync %0, %1;" ::"r"(id), "r"(n) : "memory"); }
__device__ __forceinline__ void tma2d(uint32_t dst, const CUtensorMap* m, int c0, int c1, uint32_t bar) {
  asm volatile("cp.async.bulk.tensor.2d.shared::cluster.global.mbarrier::complete_tx::bytes [%0], [%1, {%3,%4}], [%2];"
               ::"r"(dst), "l"(m), "r"(bar), "r"(c0), "r"(c1) : "memory");
}
__device__ __forceinline__ void tma5d(uint32_t dst, const CUtensorMap* m, int c0, int c4, uint32_t bar) {
  asm volatile("cp.async.bulk.tensor.5d.shared::cluster.global.mbarrier::complete_tx::bytes [%0], [%1, {%3,%5,%5,%5,%4}], [%2];"
               ::"r"(dst), "l"(m), "r"(bar), "r"(c0), "r"(c4), "r"(0) : "memory");
}
__device__ __forceinline__ void tma4d(uint32_t dst, const CUtensorMap* m, int c0, int c3, uint32_t bar) {
  asm volatile("cp.async.bulk.tensor.4d.shared::cluster.global.mbarrier::complete_tx::bytes [%0], [%1, {%3,%5,%5,%4}], [%2];"
               ::"r"(dst), "l"(m), "r"(bar), "r"(c0), "r"(c3), "r"(0) : "memory");
}
__device__ __forceinline__ void tma4d_mc(uint32_t dst, const CUtensorMap* m, int c0, int c1, int c2, int c3, uint32_t bar, uint32_t mask) {
  asm volatile("cp.async.bulk.tensor.4d.shared::cluster.global.mbarrier::complete_tx::bytes.multicast::cluster [%0], [%1, {%3,%4,%5,%6}], [%2], %7;"
               ::"r"(dst), "l"(m), "r"(bar), "r"(c0), "r"(c1), "r"(c2), "r"(c3), "h"((uint16_t)mask) : "memory");
}
__device__ __forceinline__ void bulk_g2s(uint32_t dst, const void* src, uint32_t bytes, uint32_t bar) {
  asm volatile("cp.async.bulk.shared::cluster.global.mbarrier::complete_tx::bytes [%0], [%1], %2, [%3];" ::"r"(dst), "l"(src), "r"(bytes), "r"(bar) : "memory");
}
__device__ __forceinline__ void tma4d_store(const CUtensorMap* m, uint32_t src, int c0, int c1, int c2, int c3) {
  asm volatile("cp.async.bulk.tensor.4d.global.shared::cta.bulk_group [%0, {%2,%3,%4,%5}], [%1];" ::"l"(m), "r"(src), "r"(c0), "r"(c1), "r"(c2), "r"(c3) : "memory");
}
__device__ __forceinline__ void tma2d_store(const CUtensorMap* m, uint32_t src, int c0, int c1) {
  asm volatile("cp.async.bulk.tensor.2d.global.shared::cta.bulk_group [%0, {%2,%3}], [%1];" ::"l"(m), "r"(src), "r"(c0), "r"(c1) : "memory");
}
__device__ __forceinline__ void bulk_s2g(void* dst, uint32_t src, uint32_t bytes) {
  asm volatile("cp.async.bulk.global.shared::cta.bulk_group [%0], [%1], %2;" ::"l"(dst), "r"(src), "r"(bytes) : "memory");
}
__device__ __forceinline__ void bulk_commit() { asm volatile("cp.async.bulk.commit_group;" ::: "memory"); }
__device__ __forceinline__ void bulk_wait() { asm volatile("cp.async.bulk.wait_group 0;" ::: "memory"); }
__device__ __forceinline__ void fence_async() { asm volatile("fence.proxy.async.shared::cta;" ::: "memory"); }
__device__ __forceinline__ void prefetch_l2(const void* src, uint32_t bytes) { asm volatile("cp.async.bulk.prefetch.L2.global [%0], %1;" ::"l"(src), "r"(bytes) : "memory"); }
__device__ __forceinline__ void prefetch_map(const CUtensorMap* m) { asm volatile("prefetch.tensormap [%0];" ::"l"(m) : "memory"); }
__device__ __forceinline__ void wg_fence() { __syncwarp(); asm volatile("wgmma.fence.sync.aligned;" ::: "memory"); }
__device__ __forceinline__ void wg_commit() { asm volatile("wgmma.commit_group.sync.aligned;" ::: "memory"); }
template <int N> __device__ __forceinline__ void wg_wait() { asm volatile("wgmma.wait_group.sync.aligned %0;" ::"n"(N) : "memory"); }
template <int N> __device__ __forceinline__ void fence_regs(float (&d)[N]) {
#pragma unroll
  for (int i = 0; i < N; i++) asm volatile("" : "+f"(d[i])::"memory");
}
__device__ __forceinline__ uint64_t make_desc(uint32_t addr, uint32_t lbo, uint32_t sbo, uint32_t swz) {
  return (uint64_t)((addr & 0x3FFFF) >> 4) | ((uint64_t)(lbo >> 4) << 16) | ((uint64_t)(sbo >> 4) << 32) | ((uint64_t)swz << 62);
}
__device__ __forceinline__ uint32_t ldg1(const void* p) { uint32_t v; asm volatile("ld.global.nc.u32 %0,[%1];" : "=r"(v) : "l"(p)); return v; }
__device__ __forceinline__ uint32_t lds32(uint32_t a) { uint32_t v; asm volatile("ld.shared.u32 %0,[%1];" : "=r"(v) : "r"(a)); return v; }
__device__ __forceinline__ unsigned ld_rlx(const unsigned* p) { unsigned v; asm volatile("ld.relaxed.gpu.global.u32 %0,[%1];" : "=r"(v) : "l"(p) : "memory"); return v; }
__device__ __forceinline__ uint4 ld_rlx4(const void* p) {
  uint4 v; asm volatile("ld.relaxed.gpu.global.v4.u32 {%0,%1,%2,%3},[%4];" : "=r"(v.x), "=r"(v.y), "=r"(v.z), "=r"(v.w) : "l"(p) : "memory"); return v;
}
__device__ __forceinline__ uint2 ld_rlx2(const void* p) { uint2 v; asm volatile("ld.relaxed.gpu.global.v2.u32 {%0,%1},[%2];" : "=r"(v.x), "=r"(v.y) : "l"(p) : "memory"); return v; }
__device__ __forceinline__ void st_rlx2(void* p, uint32_t a, uint32_t b) { asm volatile("st.relaxed.gpu.global.v2.u32 [%0],{%1,%2};" ::"l"(p), "r"(a), "r"(b) : "memory"); }
__device__ __forceinline__ void st_rlx(void* p, uint32_t a) { asm volatile("st.relaxed.gpu.global.u32 [%0],%1;" ::"l"(p), "r"(a) : "memory"); }
#define PUB 15
template <int SITE> __device__ __forceinline__ void release() { if (PUB & SITE) asm volatile("fence.release.gpu;" ::: "memory"); }
__device__ __forceinline__ void signal_flag(unsigned* p, unsigned val) { asm volatile("st.relaxed.gpu.global.u32 [%0],%1;" ::"l"(p), "r"(val) : "memory"); }
__device__ __forceinline__ void signal_cnt(unsigned* p, unsigned n) { asm volatile("red.relaxed.gpu.global.add.u32 [%0],%1;" ::"l"(p), "r"(n) : "memory"); }
__device__ __forceinline__ void wait_flags(const unsigned* p, unsigned val, uint32_t need, uint32_t& ready) {
#pragma unroll 1
  for (int it = 0; (ready & need) != need && it < SPIN; it++) ready = __ballot_sync(0xffffffff, ld_rlx(p) == val);
}
__device__ __forceinline__ void wait_cnt(const unsigned* p, unsigned tgt) {
  asm volatile("{ .reg .pred p; .reg .u32 c; .reg .s32 v; mov.u32 c, 0;\n"
               "W: ld.relaxed.gpu.global.u32 v, [%0]; sub.s32 v, v, %1; setp.ge.s32 p, v, 0; @p bra.uni D;\n"
               "add.u32 c, c, 1; setp.lt.u32 p, c, 0x100000; @p bra.uni W;\nD: }" ::"l"(p), "r"(tgt) : "memory");
}
__device__ __forceinline__ uint32_t pack_bf(float lo, float hi) { uint32_t r; asm("cvt.rn.bf16x2.f32 %0, %1, %2;" : "=r"(r) : "f"(hi), "f"(lo)); return r; }
__device__ __forceinline__ float bf_lo(uint32_t v) { return __uint_as_float(v << 16); }
__device__ __forceinline__ float bf_hi(uint32_t v) { return __uint_as_float(v & 0xffff0000u); }
__device__ __forceinline__ float bf_rn(float x) { return __bfloat162float(__float2bfloat16_rn(x)); }
__device__ __forceinline__ float frcp(float x) { float r; asm("rcp.approx.ftz.f32 %0,%1;" : "=f"(r) : "f"(x)); return r; }
__device__ __forceinline__ float fsqrt(float x) { float r; asm("sqrt.approx.ftz.f32 %0,%1;" : "=f"(r) : "f"(x)); return r; }
__device__ __forceinline__ float frsqrt(float x) { float r; asm("rsqrt.approx.ftz.f32 %0,%1;" : "=f"(r) : "f"(x)); return r; }
__device__ __forceinline__ uint32_t hmul2(uint32_t a, uint32_t b) { uint32_t r; asm("mul.rn.bf16x2 %0,%1,%2;" : "=r"(r) : "r"(a), "r"(b)); return r; }
__device__ __forceinline__ uint32_t hfma2(uint32_t a, uint32_t b, uint32_t c) { uint32_t r; asm("fma.rn.bf16x2 %0,%1,%2,%3;" : "=r"(r) : "r"(a), "r"(b), "r"(c)); return r; }
__device__ __forceinline__ float2 cmul(float2 a, float2 b) { return make_float2(a.x * b.x - a.y * b.y, a.x * b.y + a.y * b.x); }
__device__ __forceinline__ float2 cfma(float2 a, float2 b, float2 c) {
  return make_float2(fmaf(a.x, b.x, fmaf(-a.y, b.y, c.x)), fmaf(a.x, b.y, fmaf(a.y, b.x, c.y)));
}
__device__ __forceinline__ uint32_t tagf(float v, uint32_t tag) { return (__float_as_uint(v) & ~1u) | tag; }
__device__ __forceinline__ float untag(uint32_t v) { return __uint_as_float(v & ~1u); }
__device__ __forceinline__ bool untagged(const uint4& v, uint32_t tag) { return (((v.x ^ tag) | (v.y ^ tag) | (v.z ^ tag) | (v.w ^ tag)) & 1) != 0; }
__device__ __forceinline__ bool untagged(const uint2& v, uint32_t tag) { return (((v.x ^ tag) | (v.y ^ tag)) & 1) != 0; }
__device__ __forceinline__ float2 lam_bar(float lr, float li, float ldt) {
  float dt = bf_rn(expf(ldt)); float e = expf(dt * lr), s, c; sincospif(dt * li * 0.31830988618379067f, &s, &c); return make_float2(e * c, e * s);
}

__device__ __forceinline__ int conv_ch(uint32_t c, int s) { return s * ((c >> 21) & 255) + (c & 255) - (s >= (int)(c >> 29) ? 8 : 0); }
struct Role {
  uint32_t v, c, p;
  __device__ __forceinline__ int tb() const { return v & 15; }
  __device__ __forceinline__ int cb() const { return (v >> 4) & 15; }
  __device__ __forceinline__ int b() const { return (v >> 8) & 255; }
  __device__ __forceinline__ int ubase() const { return (v >> 16) & 7; }
  __device__ __forceinline__ int ugs() const { return (v >> 19) & 7; }
  __device__ __forceinline__ int wpart() const { return (v >> 22) & 7; }
  __device__ __forceinline__ int rank() const { return (v >> 26) & 7; }
  __device__ __forceinline__ int cs() const { return (v >> 29) ? 8 : 2; }
  __device__ __forceinline__ int ch(int s) const { return conv_ch(c, s); }
  __device__ __forceinline__ int wlo() const { return p & 1; }
  __device__ __forceinline__ int whi() const { return (p >> 1) & 1; }
  __device__ __forceinline__ uint32_t wmask() const { return (p >> 2) & 255; }
  __device__ __forceinline__ uint32_t umask() const { return (p >> 10) & 255; }
  __device__ __forceinline__ int uj() const { return (p >> 20) & 31; }
  __device__ __forceinline__ int sm() const { return (p >> 25) & 15; }
  __device__ __forceinline__ int nch() const { return (c >> 10) & 7; }
  __device__ __forceinline__ int nprep() const { return (c >> 13) & 255; }
};

__device__ __forceinline__ void wgmma_ss80(float (&d)[40], uint64_t da, uint64_t db, int sd){
  asm volatile("{ .reg .pred p; setp.ne.b32 p, %42, 0;\n"
   "wgmma.mma_async.sync.aligned.m64n80k16.f32.bf16.bf16 {%0, %1, %2, %3, %4, %5, %6, %7, %8, %9, %10, %11, %12, %13, %14, %15, %16, %17, %18, %19, %20, %21, %22, %23, %24, %25, %26, %27, %28, %29, %30, %31, %32, %33, %34, %35, %36, %37, %38, %39}, %40, %41, p, 1, 1, 0, 0; }\n"
   : "+f"(d[0]), "+f"(d[1]), "+f"(d[2]), "+f"(d[3]), "+f"(d[4]), "+f"(d[5]), "+f"(d[6]), "+f"(d[7]), "+f"(d[8]), "+f"(d[9]), "+f"(d[10]), "+f"(d[11]), "+f"(d[12]), "+f"(d[13]), "+f"(d[14]), "+f"(d[15]), "+f"(d[16]), "+f"(d[17]), "+f"(d[18]), "+f"(d[19]), "+f"(d[20]), "+f"(d[21]), "+f"(d[22]), "+f"(d[23]), "+f"(d[24]), "+f"(d[25]), "+f"(d[26]), "+f"(d[27]), "+f"(d[28]), "+f"(d[29]), "+f"(d[30]), "+f"(d[31]), "+f"(d[32]), "+f"(d[33]), "+f"(d[34]), "+f"(d[35]), "+f"(d[36]), "+f"(d[37]), "+f"(d[38]), "+f"(d[39]) : "l"(da), "l"(db), "r"(sd));
}
__device__ __forceinline__ void wgmma_ss160(float (&d)[80], uint64_t da, uint64_t db, int sd){
  asm volatile("{ .reg .pred p; setp.ne.b32 p, %82, 0;\n"
   "wgmma.mma_async.sync.aligned.m64n160k16.f32.bf16.bf16 {%0, %1, %2, %3, %4, %5, %6, %7, %8, %9, %10, %11, %12, %13, %14, %15, %16, %17, %18, %19, %20, %21, %22, %23, %24, %25, %26, %27, %28, %29, %30, %31, %32, %33, %34, %35, %36, %37, %38, %39, %40, %41, %42, %43, %44, %45, %46, %47, %48, %49, %50, %51, %52, %53, %54, %55, %56, %57, %58, %59, %60, %61, %62, %63, %64, %65, %66, %67, %68, %69, %70, %71, %72, %73, %74, %75, %76, %77, %78, %79}, %80, %81, p, 1, 1, 0, 0; }\n"
   : "+f"(d[0]), "+f"(d[1]), "+f"(d[2]), "+f"(d[3]), "+f"(d[4]), "+f"(d[5]), "+f"(d[6]), "+f"(d[7]), "+f"(d[8]), "+f"(d[9]), "+f"(d[10]), "+f"(d[11]), "+f"(d[12]), "+f"(d[13]), "+f"(d[14]), "+f"(d[15]), "+f"(d[16]), "+f"(d[17]), "+f"(d[18]), "+f"(d[19]), "+f"(d[20]), "+f"(d[21]), "+f"(d[22]), "+f"(d[23]), "+f"(d[24]), "+f"(d[25]), "+f"(d[26]), "+f"(d[27]), "+f"(d[28]), "+f"(d[29]), "+f"(d[30]), "+f"(d[31]), "+f"(d[32]), "+f"(d[33]), "+f"(d[34]), "+f"(d[35]), "+f"(d[36]), "+f"(d[37]), "+f"(d[38]), "+f"(d[39]), "+f"(d[40]), "+f"(d[41]), "+f"(d[42]), "+f"(d[43]), "+f"(d[44]), "+f"(d[45]), "+f"(d[46]), "+f"(d[47]), "+f"(d[48]), "+f"(d[49]), "+f"(d[50]), "+f"(d[51]), "+f"(d[52]), "+f"(d[53]), "+f"(d[54]), "+f"(d[55]), "+f"(d[56]), "+f"(d[57]), "+f"(d[58]), "+f"(d[59]), "+f"(d[60]), "+f"(d[61]), "+f"(d[62]), "+f"(d[63]), "+f"(d[64]), "+f"(d[65]), "+f"(d[66]), "+f"(d[67]), "+f"(d[68]), "+f"(d[69]), "+f"(d[70]), "+f"(d[71]), "+f"(d[72]), "+f"(d[73]), "+f"(d[74]), "+f"(d[75]), "+f"(d[76]), "+f"(d[77]), "+f"(d[78]), "+f"(d[79]) : "l"(da), "l"(db), "r"(sd));
}
template<int N> __device__ __forceinline__ void wgmma_rs(float (&d)[N/2], uint32_t a0, uint32_t a1, uint32_t a2, uint32_t a3, uint64_t db, int sd);
template<> __device__ __forceinline__ void wgmma_rs<16>(float (&d)[8], uint32_t a0, uint32_t a1, uint32_t a2, uint32_t a3, uint64_t db, int sd){
  asm volatile("{ .reg .pred p; setp.ne.b32 p, %13, 0;\n"
   "wgmma.mma_async.sync.aligned.m64n16k16.f32.bf16.bf16 {%0, %1, %2, %3, %4, %5, %6, %7}, {%8,%9,%10,%11}, %12, p, 1, 1, 0; }\n"
   : "+f"(d[0]), "+f"(d[1]), "+f"(d[2]), "+f"(d[3]), "+f"(d[4]), "+f"(d[5]), "+f"(d[6]), "+f"(d[7]) : "r"(a0), "r"(a1), "r"(a2), "r"(a3), "l"(db), "r"(sd));
}
template<> __device__ __forceinline__ void wgmma_rs<32>(float (&d)[16], uint32_t a0, uint32_t a1, uint32_t a2, uint32_t a3, uint64_t db, int sd){
  asm volatile("{ .reg .pred p; setp.ne.b32 p, %21, 0;\n"
   "wgmma.mma_async.sync.aligned.m64n32k16.f32.bf16.bf16 {%0, %1, %2, %3, %4, %5, %6, %7, %8, %9, %10, %11, %12, %13, %14, %15}, {%16,%17,%18,%19}, %20, p, 1, 1, 0; }\n"
   : "+f"(d[0]), "+f"(d[1]), "+f"(d[2]), "+f"(d[3]), "+f"(d[4]), "+f"(d[5]), "+f"(d[6]), "+f"(d[7]), "+f"(d[8]), "+f"(d[9]), "+f"(d[10]), "+f"(d[11]), "+f"(d[12]), "+f"(d[13]), "+f"(d[14]), "+f"(d[15]) : "r"(a0), "r"(a1), "r"(a2), "r"(a3), "l"(db), "r"(sd));
}
template<> __device__ __forceinline__ void wgmma_rs<48>(float (&d)[24], uint32_t a0, uint32_t a1, uint32_t a2, uint32_t a3, uint64_t db, int sd){
  asm volatile("{ .reg .pred p; setp.ne.b32 p, %29, 0;\n"
   "wgmma.mma_async.sync.aligned.m64n48k16.f32.bf16.bf16 {%0, %1, %2, %3, %4, %5, %6, %7, %8, %9, %10, %11, %12, %13, %14, %15, %16, %17, %18, %19, %20, %21, %22, %23}, {%24,%25,%26,%27}, %28, p, 1, 1, 0; }\n"
   : "+f"(d[0]), "+f"(d[1]), "+f"(d[2]), "+f"(d[3]), "+f"(d[4]), "+f"(d[5]), "+f"(d[6]), "+f"(d[7]), "+f"(d[8]), "+f"(d[9]), "+f"(d[10]), "+f"(d[11]), "+f"(d[12]), "+f"(d[13]), "+f"(d[14]), "+f"(d[15]), "+f"(d[16]), "+f"(d[17]), "+f"(d[18]), "+f"(d[19]), "+f"(d[20]), "+f"(d[21]), "+f"(d[22]), "+f"(d[23]) : "r"(a0), "r"(a1), "r"(a2), "r"(a3), "l"(db), "r"(sd));
}
template<> __device__ __forceinline__ void wgmma_rs<64>(float (&d)[32], uint32_t a0, uint32_t a1, uint32_t a2, uint32_t a3, uint64_t db, int sd){
  asm volatile("{ .reg .pred p; setp.ne.b32 p, %37, 0;\n"
   "wgmma.mma_async.sync.aligned.m64n64k16.f32.bf16.bf16 {%0, %1, %2, %3, %4, %5, %6, %7, %8, %9, %10, %11, %12, %13, %14, %15, %16, %17, %18, %19, %20, %21, %22, %23, %24, %25, %26, %27, %28, %29, %30, %31}, {%32,%33,%34,%35}, %36, p, 1, 1, 0; }\n"
   : "+f"(d[0]), "+f"(d[1]), "+f"(d[2]), "+f"(d[3]), "+f"(d[4]), "+f"(d[5]), "+f"(d[6]), "+f"(d[7]), "+f"(d[8]), "+f"(d[9]), "+f"(d[10]), "+f"(d[11]), "+f"(d[12]), "+f"(d[13]), "+f"(d[14]), "+f"(d[15]), "+f"(d[16]), "+f"(d[17]), "+f"(d[18]), "+f"(d[19]), "+f"(d[20]), "+f"(d[21]), "+f"(d[22]), "+f"(d[23]), "+f"(d[24]), "+f"(d[25]), "+f"(d[26]), "+f"(d[27]), "+f"(d[28]), "+f"(d[29]), "+f"(d[30]), "+f"(d[31]) : "r"(a0), "r"(a1), "r"(a2), "r"(a3), "l"(db), "r"(sd));
}
template<> __device__ __forceinline__ void wgmma_rs<80>(float (&d)[40], uint32_t a0, uint32_t a1, uint32_t a2, uint32_t a3, uint64_t db, int sd){
  asm volatile("{ .reg .pred p; setp.ne.b32 p, %45, 0;\n"
   "wgmma.mma_async.sync.aligned.m64n80k16.f32.bf16.bf16 {%0, %1, %2, %3, %4, %5, %6, %7, %8, %9, %10, %11, %12, %13, %14, %15, %16, %17, %18, %19, %20, %21, %22, %23, %24, %25, %26, %27, %28, %29, %30, %31, %32, %33, %34, %35, %36, %37, %38, %39}, {%40,%41,%42,%43}, %44, p, 1, 1, 0; }\n"
   : "+f"(d[0]), "+f"(d[1]), "+f"(d[2]), "+f"(d[3]), "+f"(d[4]), "+f"(d[5]), "+f"(d[6]), "+f"(d[7]), "+f"(d[8]), "+f"(d[9]), "+f"(d[10]), "+f"(d[11]), "+f"(d[12]), "+f"(d[13]), "+f"(d[14]), "+f"(d[15]), "+f"(d[16]), "+f"(d[17]), "+f"(d[18]), "+f"(d[19]), "+f"(d[20]), "+f"(d[21]), "+f"(d[22]), "+f"(d[23]), "+f"(d[24]), "+f"(d[25]), "+f"(d[26]), "+f"(d[27]), "+f"(d[28]), "+f"(d[29]), "+f"(d[30]), "+f"(d[31]), "+f"(d[32]), "+f"(d[33]), "+f"(d[34]), "+f"(d[35]), "+f"(d[36]), "+f"(d[37]), "+f"(d[38]), "+f"(d[39]) : "r"(a0), "r"(a1), "r"(a2), "r"(a3), "l"(db), "r"(sd));
}
template<> __device__ __forceinline__ void wgmma_rs<96>(float (&d)[48], uint32_t a0, uint32_t a1, uint32_t a2, uint32_t a3, uint64_t db, int sd){
  asm volatile("{ .reg .pred p; setp.ne.b32 p, %53, 0;\n"
   "wgmma.mma_async.sync.aligned.m64n96k16.f32.bf16.bf16 {%0, %1, %2, %3, %4, %5, %6, %7, %8, %9, %10, %11, %12, %13, %14, %15, %16, %17, %18, %19, %20, %21, %22, %23, %24, %25, %26, %27, %28, %29, %30, %31, %32, %33, %34, %35, %36, %37, %38, %39, %40, %41, %42, %43, %44, %45, %46, %47}, {%48,%49,%50,%51}, %52, p, 1, 1, 0; }\n"
   : "+f"(d[0]), "+f"(d[1]), "+f"(d[2]), "+f"(d[3]), "+f"(d[4]), "+f"(d[5]), "+f"(d[6]), "+f"(d[7]), "+f"(d[8]), "+f"(d[9]), "+f"(d[10]), "+f"(d[11]), "+f"(d[12]), "+f"(d[13]), "+f"(d[14]), "+f"(d[15]), "+f"(d[16]), "+f"(d[17]), "+f"(d[18]), "+f"(d[19]), "+f"(d[20]), "+f"(d[21]), "+f"(d[22]), "+f"(d[23]), "+f"(d[24]), "+f"(d[25]), "+f"(d[26]), "+f"(d[27]), "+f"(d[28]), "+f"(d[29]), "+f"(d[30]), "+f"(d[31]), "+f"(d[32]), "+f"(d[33]), "+f"(d[34]), "+f"(d[35]), "+f"(d[36]), "+f"(d[37]), "+f"(d[38]), "+f"(d[39]), "+f"(d[40]), "+f"(d[41]), "+f"(d[42]), "+f"(d[43]), "+f"(d[44]), "+f"(d[45]), "+f"(d[46]), "+f"(d[47]) : "r"(a0), "r"(a1), "r"(a2), "r"(a3), "l"(db), "r"(sd));
}
template<> __device__ __forceinline__ void wgmma_rs<112>(float (&d)[56], uint32_t a0, uint32_t a1, uint32_t a2, uint32_t a3, uint64_t db, int sd){
  asm volatile("{ .reg .pred p; setp.ne.b32 p, %61, 0;\n"
   "wgmma.mma_async.sync.aligned.m64n112k16.f32.bf16.bf16 {%0, %1, %2, %3, %4, %5, %6, %7, %8, %9, %10, %11, %12, %13, %14, %15, %16, %17, %18, %19, %20, %21, %22, %23, %24, %25, %26, %27, %28, %29, %30, %31, %32, %33, %34, %35, %36, %37, %38, %39, %40, %41, %42, %43, %44, %45, %46, %47, %48, %49, %50, %51, %52, %53, %54, %55}, {%56,%57,%58,%59}, %60, p, 1, 1, 0; }\n"
   : "+f"(d[0]), "+f"(d[1]), "+f"(d[2]), "+f"(d[3]), "+f"(d[4]), "+f"(d[5]), "+f"(d[6]), "+f"(d[7]), "+f"(d[8]), "+f"(d[9]), "+f"(d[10]), "+f"(d[11]), "+f"(d[12]), "+f"(d[13]), "+f"(d[14]), "+f"(d[15]), "+f"(d[16]), "+f"(d[17]), "+f"(d[18]), "+f"(d[19]), "+f"(d[20]), "+f"(d[21]), "+f"(d[22]), "+f"(d[23]), "+f"(d[24]), "+f"(d[25]), "+f"(d[26]), "+f"(d[27]), "+f"(d[28]), "+f"(d[29]), "+f"(d[30]), "+f"(d[31]), "+f"(d[32]), "+f"(d[33]), "+f"(d[34]), "+f"(d[35]), "+f"(d[36]), "+f"(d[37]), "+f"(d[38]), "+f"(d[39]), "+f"(d[40]), "+f"(d[41]), "+f"(d[42]), "+f"(d[43]), "+f"(d[44]), "+f"(d[45]), "+f"(d[46]), "+f"(d[47]), "+f"(d[48]), "+f"(d[49]), "+f"(d[50]), "+f"(d[51]), "+f"(d[52]), "+f"(d[53]), "+f"(d[54]), "+f"(d[55]) : "r"(a0), "r"(a1), "r"(a2), "r"(a3), "l"(db), "r"(sd));
}
template<> __device__ __forceinline__ void wgmma_rs<128>(float (&d)[64], uint32_t a0, uint32_t a1, uint32_t a2, uint32_t a3, uint64_t db, int sd){
  asm volatile("{ .reg .pred p; setp.ne.b32 p, %69, 0;\n"
   "wgmma.mma_async.sync.aligned.m64n128k16.f32.bf16.bf16 {%0, %1, %2, %3, %4, %5, %6, %7, %8, %9, %10, %11, %12, %13, %14, %15, %16, %17, %18, %19, %20, %21, %22, %23, %24, %25, %26, %27, %28, %29, %30, %31, %32, %33, %34, %35, %36, %37, %38, %39, %40, %41, %42, %43, %44, %45, %46, %47, %48, %49, %50, %51, %52, %53, %54, %55, %56, %57, %58, %59, %60, %61, %62, %63}, {%64,%65,%66,%67}, %68, p, 1, 1, 0; }\n"
   : "+f"(d[0]), "+f"(d[1]), "+f"(d[2]), "+f"(d[3]), "+f"(d[4]), "+f"(d[5]), "+f"(d[6]), "+f"(d[7]), "+f"(d[8]), "+f"(d[9]), "+f"(d[10]), "+f"(d[11]), "+f"(d[12]), "+f"(d[13]), "+f"(d[14]), "+f"(d[15]), "+f"(d[16]), "+f"(d[17]), "+f"(d[18]), "+f"(d[19]), "+f"(d[20]), "+f"(d[21]), "+f"(d[22]), "+f"(d[23]), "+f"(d[24]), "+f"(d[25]), "+f"(d[26]), "+f"(d[27]), "+f"(d[28]), "+f"(d[29]), "+f"(d[30]), "+f"(d[31]), "+f"(d[32]), "+f"(d[33]), "+f"(d[34]), "+f"(d[35]), "+f"(d[36]), "+f"(d[37]), "+f"(d[38]), "+f"(d[39]), "+f"(d[40]), "+f"(d[41]), "+f"(d[42]), "+f"(d[43]), "+f"(d[44]), "+f"(d[45]), "+f"(d[46]), "+f"(d[47]), "+f"(d[48]), "+f"(d[49]), "+f"(d[50]), "+f"(d[51]), "+f"(d[52]), "+f"(d[53]), "+f"(d[54]), "+f"(d[55]), "+f"(d[56]), "+f"(d[57]), "+f"(d[58]), "+f"(d[59]), "+f"(d[60]), "+f"(d[61]), "+f"(d[62]), "+f"(d[63]) : "r"(a0), "r"(a1), "r"(a2), "r"(a3), "l"(db), "r"(sd));
}

#define BAR(i) (bars + 8u * (uint32_t)(i))

template <int G> __device__ __forceinline__ void conv_frags(uint32_t (&a)[12], uint32_t abase) {
#pragma unroll
  for (int i = 0; i < 12; i++) a[i] = lds32(abase + (G * 4 + i / 3) * 128 + (i % 3) * 4);
}
__device__ __forceinline__ void kv_prefetch(const __nv_bfloat16* pf, int task) { prefetch_if(pf + 64 * (task & 31) * DM + 64 * (task >> 5), task < 320); }
__device__ __forceinline__ void kv_load(const Params& P, Scratch* S, int task, int tid, uint32_t (&k_)[19], uint32_t (&v_)[16], uint4& sk) {
  const int row = 64 * (task & 31) + 16 * (tid >> 5), ch = 64 * (task >> 5) + 2 * (tid & 31);
  const uint32_t* kp = (const uint32_t*)(P.k + (size_t)row * DM + ch);
  const uint32_t* vp = (const uint32_t*)(P.v + (size_t)row * DM + ch);
  const uint32_t* hp = row > 0 ? kp - 3 * (DM / 2) : S->zero;
  const int hs = row > 0 ? DM / 2 : 0;
  asm volatile("ld.global.nc.v4.u32 {%0,%1,%2,%3},[%4];" : "=r"(sk.x), "=r"(sk.y), "=r"(sk.z), "=r"(sk.w) : "l"(P.shk + ch * 4));
#pragma unroll
  for (int i = 0; i < 3; i++) k_[i] = ldg1(hp + i * hs);
#pragma unroll
  for (int i = 0; i < 16; i++) { k_[i + 3] = ldg1(kp + i * (DM / 2)); v_[i] = ldg1(vp + i * (DM / 2)); }
}
template <int SH> __device__ __forceinline__ void xb_prefetch(const Head& H, int id, int tid, int c0) {
  const int ri = tid >> SH, rr = 11 * id + ri - 16;
  const __nv_bfloat16* p = ri < 16 ? H.x + (size_t)(16 * min(id, 127) + ri) * DM : (rr < DM ? H.b0 : H.b1 - DM * DM) + (size_t)rr * DM;
  prefetch_if(p + c0 + 64 * (tid & ((1 << SH) - 1)), ri < 16 || (ri < 27 && rr < 2 * DM));
}
__device__ __forceinline__ uint4 ldg4(const void* p) { uint4 v; asm volatile("ld.global.nc.v4.u32 {%0,%1,%2,%3},[%4];" : "=r"(v.x), "=r"(v.y), "=r"(v.z), "=r"(v.w) : "l"(p)); return v; }
__device__ __forceinline__ uint4 lds4(uint32_t a) { uint4 v; asm volatile("ld.shared.v4.u32 {%0,%1,%2,%3},[%4];" : "=r"(v.x), "=r"(v.y), "=r"(v.z), "=r"(v.w) : "r"(a) : "memory"); return v; }
__device__ __forceinline__ void discretise(const Head& H, const Params& P, uint32_t sb, Role R, int lane, uint32_t e1) {
  const uint32_t dn = __ldg((const unsigned short*)P.ssmd + min(conv_ch(R.c, (lane + 7) & 7), DM - 1));
  const int c = 32 * min(R.cb(), 9) + lane;
  const uint32_t lr2 = ldg1(P.lre + 2 * c), li2 = ldg1(P.lim + 2 * c), ld2 = ldg1(P.ldt + 2 * c);
  asm volatile("st.shared.u32 [%0],%1;" ::"r"(sb + MISC_OFF + 4 * (lane & 7)), "r"((lane & 7) ? dn : e1) : "memory");
#pragma unroll 1
  for (int i = 0; i < 2; i++) {
    const float lr = bf_hi(lr2 << (16 - 16 * i)), li = bf_hi(li2 << (16 - 16 * i));
    const float2 lb = lam_bar(lr, li, bf_hi(ld2 << (16 - 16 * i)));
    const float nx = lb.x - 1.f, ny = lb.y, inv = 2.f * frcp(lr * lr + li * li), cx = (nx * lr + ny * li) * inv, cy = (ny * lr - nx * li) * inv;
    const bool sw = !H.swap;
    asm volatile("st.shared.v4.f32 [%0],{%1,%2,%3,%4};" ::"r"(sb + LAM_OFF + 32 * lane + 16 * i), "f"(lb.x), "f"(sw ? -lb.y : lb.y), "f"(sw ? -cy : cx), "f"(sw ? cx : -cy) : "memory");
  }
  __syncwarp();
}
__device__ __forceinline__ void aux_prep(const Head& H, const Params& P, uint32_t sb, Role R, int tid, long long t_start) {
  Scratch* const S = H.s;
  const uint32_t bars = sb + BAR_OFF;
  tid = opaque(tid);
  const int w = tid >> 5, lane = tid & 31, tb = R.tb(), cb = R.cb();
  uint32_t k_[19], v_[16];
  uint4 sk;
  int task = R.b() < R.nprep() ? R.b() : 320;
  delay(KVDLY);
  PROFC(tid == 0, 345);
  kv_load(P, S, min(task, 319), tid, k_, v_, sk);
  const __nv_bfloat16* pf = (tid < 64 ? P.k : P.v) + (tid & 63) * DM;
  const int j = lane >> 3, sm = min(R.sm(), 9), trow = 160 * tb + 4 * sm + (tb < 12 ? 40 : 32) * w + j;
  const uint32_t so = sb + (2 * w + (j & 1) + 8 * (j >> 1)) * 128 + 16 * (lane & 7), xo = so + sm * 2048, wo = so + (tb & 1) * 8192 + (tb & 6) * 1024;
  const __nv_bfloat16* xp = H.x + (size_t)min(trow, SEQ - 1) * DM + 384 + 8 * (lane & 7);
  const __nv_bfloat16* bp = (j < 2 ? H.b0 : H.b1) + (size_t)(64 * cb + 32 * (tb & 1) + 4 * (tb & 6) + 2 * w + (j & 1)) * DM + 384 + 8 * (lane & 7);
  float s = 0.f, s2 = 0.f, sr = 0.f;
#define STAT(m, n) { const uint32_t xw[4] = {m.x, m.y, m.z, m.w}, bw[4] = {n.x, n.y, n.z, n.w}; \
  _Pragma("unroll") for (int i = 0; i < 4; i++) { const float u = bf_lo(xw[i]), v = bf_hi(xw[i]); s += u + v; s2 = fmaf(u, u, fmaf(v, v, s2)); sr += bf_lo(bw[i]) + bf_hi(bw[i]); } }
#define STATS(K0, K1) _Pragma("unroll 1") for (int kb = K0; kb < K1; kb++) { \
    mbar_wait(BAR(B_F1 + kb)); \
    const uint4 a = lds4(xo + ((uint32_t)(XTAB0 >> (6 * kb)) & 63) * 4096), c = lds4(wo + ((uint32_t)(WTAB0 >> (6 * kb)) & 63) * 4096); \
    STAT(a, c) \
    asm volatile("" : "+f"(s), "+f"(s2), "+f"(sr)); \
    if (XPFAT >= K0 && XPFAT < K1) prefetch_if(((lane & 4) ? bp : xp) + 64 * (lane & 3), kb == XPFAT); \
    kv_prefetch(pf, kb == KPFAT ? task + R.nprep() : kb == KPFAT2 ? task + 2 * R.nprep() : 320); \
  } \
  __syncwarp(); mbar_arrive_if(BAR(B_AX + K0 / 3), lane == 0);
  STATS(0, 3)
  PROFC(tid == 0, 349);
    {
      uint4 m[4], n[4];
#pragma unroll
      for (int i = 0; i < 4; i++) { m[i] = ldg4(xp + 64 * i); n[i] = ldg4(bp + 64 * i); }
      STATS(3, 6)
      PROFC(tid == 0, 346);
      mbar_wait(BAR(B_LM));
      const uint32_t tag = lds32(sb + MISC_OFF) & 1;
#pragma unroll
      for (int i = 0; i < 4; i++) { const uint4 a = m[i], c = n[i]; STAT(a, c) }
      PROFC(tid == 0 && s2 != 1.2345f, 347);
#pragma unroll
      for (int o = 1; o <= 4; o <<= 1) { s += __shfl_xor_sync(0xffffffff, s, o); s2 += __shfl_xor_sync(0xffffffff, s2, o); sr += __shfl_xor_sync(0xffffffff, sr, o); }
      const float mn = s * (1.f / DM), rs = frcp(bf_rn(fsqrt(bf_rn(bf_rn(fmaxf(s2 * (1.f / DM) - mn * mn, 0.f)) + 1e-5f))));
      asm volatile("{ .reg .pred p; setp.ne.u32 p, %2, 0; @p st.relaxed.gpu.global.u32 [%0],%1; }"
                   ::"l"((uint32_t*)(S->RS + (8 * cb + 4 * (tb & 1) + (tb >> 1)) * 16 + 4 * w + (j & 1)) + (lane & 4) + (j >> 1)), "r"(tagf(sr, tag)),
                   "r"((uint32_t)(tb < 8 && (lane & 3) == 0)) : "memory");
      asm volatile("{ .reg .pred p; setp.ne.u32 p, %3, 0; @p st.relaxed.gpu.global.v2.u32 [%0],{%1,%2}; }"
                   ::"l"(S->S + trow), "r"(tagf(rs, tag)), "r"(tagf(-bf_rn(mn) * rs, tag)), "r"((uint32_t)(R.sm() < 10 && (lane & 7) == 0)) : "memory");
      PROFC(tid == 0, 3);
    }
#pragma unroll 1
  for (int r = 0; task < 320; r++) {
    {
      const uint32_t T0 = __byte_perm(sk.x, sk.z, 0x5410), T1 = __byte_perm(sk.x, sk.z, 0x7632);
      const uint32_t T2 = __byte_perm(sk.y, sk.w, 0x5410), T3 = __byte_perm(sk.y, sk.w, 0x7632);
      PROFC(tid == 0 && v_[15] != 0x12345, 336 + r);
      uint32_t o[16];
#pragma unroll
      for (int t = 0; t < 16; t += 2) {
        const uint32_t a = hmul2(hfma2(k_[t + 3], T0, hfma2(k_[t + 2], T1, hfma2(k_[t + 1], T2, hmul2(k_[t], T3)))), v_[t]);
        const uint32_t c = hmul2(hfma2(k_[t + 4], T0, hfma2(k_[t + 3], T1, hfma2(k_[t + 2], T2, hmul2(k_[t + 1], T3)))), v_[t + 1]);
        const int wd = ((7 - t / 2) >> 1) + 4 * ((7 - t / 2) & 1);
        o[wd] = __byte_perm(c, a, 0x5410); o[8 + wd] = __byte_perm(c, a, 0x7632);
        asm volatile("" : "+r"(o[wd]), "+r"(o[8 + wd]));
        if (t == PFAT) kv_prefetch(pf, task + (1 + PFD) * R.nprep());
      }
      PROFC(tid == 0, 330 + 2 * r);
      const int ph = task & 1;
      task += R.nprep();
      if (ORD == 0 && task < 320) kv_load(P, S, task, tid, k_, v_, sk);
      mbar_wait(BAR(B_E1 + 3)); mbar_wait(BAR(B_AX + 1));
#pragma unroll
      for (int i = 0; i < 4; i++) {
        const int row = 2 * lane + (i >> 1);
        asm volatile("st.shared.v4.u32 [%0],{%1,%2,%3,%4};" ::"r"(sb + KS_OFF + r * 8192 + row * 128 + (((2 * w + ((i & 1) ^ ph)) ^ (row & 7)) << 4)),
                     "r"(o[4 * i]), "r"(o[4 * i + 1]), "r"(o[4 * i + 2]), "r"(o[4 * i + 3]) : "memory");
      }
      __syncwarp();
      mbar_arrive_if(BAR(B_PS + r), lane == 0);
      PROFC(tid == 0, 331 + 2 * r);
      if (ORD == 1 && task < 320) kv_load(P, S, task, tid, k_, v_, sk);
    }
  }
#undef STAT
#undef STATS
  PROFC(tid == 0, 40);
}
#define SPLIT(G) asm volatile("{ .reg .pred p; .reg .u32 r; L: mov.u32 r, %%clock; setp.eq.u32 p, r, %0; @p bra.uni L; }" ::"n"(G) : "memory")
template <bool AUX>
__device__ __forceinline__ void conv_loop(uint32_t sb, uint32_t rc, int wg, int tid, long long t_start) {
  sb = opaque(sb); rc = opaque(rc);
  const uint32_t bars = sb + BAR_OFF;
  int slot = AUX ? 0 : wg + 1;
  mbar_wait(BAR(B_LM));
#pragma unroll 1
  while (slot < (int)((rc >> 10) & 7)) {
    tid = opaque(tid);
    const int w = tid >> 5, lane = tid & 31, g = lane >> 2, q = lane & 3;
    const uint32_t Dn = lds32(sb + MISC_OFF + 4 + 4 * slot);
    const uint32_t d0 = (g == 1 && q == 3 - w) ? Dn : 0, d1 = (g == 0 && q == 3 - w) ? Dn : 0;
    const uint32_t cb_ = conv_buf(sb, slot), c0 = cb_ + KC_OFS;
    const uint32_t abase = c0 + 2 * (2 * (g & 1) + 4 * w + 16 * (g >> 1) + 4 * q);
    const uint64_t bd = make_desc(cb_ + KV_PAD, 16, 256, 3);
    const bool hi = lane & 16, s1 = lane & 8;
    const int qo = hi ? (q + 1) & 3 : q;
    const int srcA = hi ? (lane & 12) | ((q + 1) & 3) : (lane & 12) | 16 | ((q + 3) & 3);
    const bool h3 = hi && q == 3, wrap = s1 && qo == 3, back = wrap && hi;
    const bool chi = wrap ? !hi : hi;
    const int cq = s1 ? (qo + 1) & 3 : qo;
    const int srcB = (lane & 4) | (s1 ? 0 : 8) | (chi ? 16 | ((cq + 3) & 3) : cq);
    const uint32_t gp = c0 + ((32 * (2 * w + (g & 1)) + (chi ? 256 : 0)) ^ (chi ? 64 : 0) ^ ((conv_ch(rc, slot) & 8) << 2)) + 4 * (2 * cq + (s1 ? 0 : 1));
    uint32_t a[12], f[16], o[8];
    float S[4], T[4], U[2], keep[2], pv[2] = {0.f, 0.f}, pr[4] = {0.f, 0.f, 0.f, 0.f};
    float e0[64], e1[56], e2[48], e3[40], e4[32], e5[24], e6[16], e7[8];
#define UNR _Pragma("unroll")
#define PERM() UNR for (int i = 0; i < 4; i++) { f[4 * i] = __byte_perm(a[3 * i], a[3 * i + 1], 0x5432); f[4 * i + 1] = a[3 * i + 1]; \
                                                 f[4 * i + 2] = __byte_perm(a[3 * i + 1], a[3 * i + 2], 0x5432); f[4 * i + 3] = a[3 * i + 2]; }
#define MMA(N, E) UNR for (int i = 0; i < 4; i++) wgmma_rs<N>(E, f[4 * i], f[4 * i + 1], f[4 * i + 2], f[4 * i + 3], bd - 8 * i, 1); wg_commit();
#define L1(c) UNR for (int i = 0; i < 4; i++) { const float ev = c[i], od = c[4 + i]; S[i] = hi ? (h3 ? ev : od) : ev; \
                                                T[i] = __shfl_sync(0xffffffff, hi ? (h3 ? pr[i] : ev) : od, srcA); pr[i] = od; }
#define L1E() UNR for (int i = 0; i < 4; i++) S[i] += T[i];
#define L2() UNR for (int h = 0; h < 2; h++) { keep[h] = back ? pv[h] : S[2 * h + 1]; pv[h] = S[2 * h + 1]; U[h] = __shfl_sync(0xffffffff, S[2 * h], srcB); }
#define L2E(j) o[j] = pack_bf(keep[0] + U[0], keep[1] + U[1]);
#define GRP(G, N, P, E) UNR for (int i = 0; i < N / 2; i++) asm volatile("mov.b32 %0,%1;" : "=f"(E[i]) : "f"(P[i + 8])); \
    wg_fence(); if (G < 7) conv_frags<(G + 1) & 7>(a, abase); if (G >= 2) { L2() } L1(P) MMA(N, E) SPLIT(G); \
    if (G < 7) { PERM() } if (G >= 2) { L2E((G + 6) & 7) } L1E() wg_wait<0>(); fence_regs(E);
    PROFC(tid == 0, 300 + 4 * slot);
    mbar_wait(BAR(B_KF + slot));
    if (tid == 0) PROF(361 + slot);
    PROFC(tid == 0, 301 + 4 * slot);
    conv_frags<0>(a, abase);
    wg_fence();
    wgmma_rs<128>(e0, d0 << 16, d0, d1 << 16, d1, bd, 0);
    PERM() conv_frags<1>(a, abase); wg_fence(); MMA(128, e0) SPLIT(0); PERM() wg_wait<0>(); fence_regs(e0);
    GRP(1, 112, e0, e1) GRP(2, 96, e1, e2) GRP(3, 80, e2, e3) GRP(4, 64, e3, e4) GRP(5, 48, e4, e5) GRP(6, 32, e5, e6) GRP(7, 16, e6, e7)
    PROFC(tid == 0, 302 + 4 * slot);
    L2() L1(e7) L2E(6) L1E() L2() L2E(7)
    bar_sync(wg + 1, 128);
#pragma unroll
    for (int jj = 0; jj < 8; jj++) asm volatile("st.shared.u32 [%0],%1;" ::"r"(gp + jj * 512), "r"(o[jj]) : "memory");
#undef PERM
#undef MMA
#undef L1
#undef L1E
#undef L2
#undef L2E
#undef GRP
    PROFC(tid == 0, 303 + 4 * slot);
    __syncwarp();
    if (lane == 0) mbar_arrive(BAR(B_GS + slot));
    if (!AUX) break;
    slot = slot ? slot + 1 : 3;
  }
}

#define IDX(J, c, h) (8 * (J) + 4 * ((c) >> 1) + 2 * (h) + ((c) & 1))
__device__ __forceinline__ uint2 lds2(uint32_t a) { uint2 v; asm volatile("ld.shared.v2.u32 {%0,%1},[%2];" : "=r"(v.x), "=r"(v.y) : "r"(a) : "memory"); return v; }
__device__ __forceinline__ void resid_load(float (&r)[40], uint32_t sb, int wg, int tid, const uint4& s) {
  const uint32_t dp = sb + XR_OFF + 8 * (tid & 3), xp = dp + (64 * wg + 16 * (tid >> 5) + ((tid & 31) >> 2)) * 160;
#pragma unroll
  for (int J = 0; J < 5; J++) {
    const uint2 u = lds2(xp + 32 * J), v = lds2(xp + 32 * J + 1280), d = lds2(dp + 20480 + 32 * J);
    r[8 * J] = __uint_as_float(u.x); r[8 * J + 1] = __uint_as_float(u.y); r[8 * J + 2] = __uint_as_float(v.x); r[8 * J + 3] = __uint_as_float(v.y);
    r[8 * J + 4] = __uint_as_float(d.x); r[8 * J + 5] = __uint_as_float(d.y);
  }
  r[30] = untag(s.x); r[31] = untag(s.y); r[38] = untag(s.z); r[39] = untag(s.w);
}
__device__ __forceinline__ void resid_init(float (&r)[40]) {
  const float s[4] = {r[30], r[31], r[38], r[39]};
#pragma unroll
  for (int J = 0; J < 5; J++) {
    uint32_t w[6];
#pragma unroll
    for (int i = 0; i < 6; i++) w[i] = __float_as_uint(r[8 * J + i]);
#pragma unroll
    for (int i = 0; i < 4; i++) {
      const int h = i >> 1, c = 2 * (i & 1);
      const float rs = s[2 * h], nm = s[2 * h + 1], x0 = bf_lo(w[i]), x1 = bf_hi(w[i]);
      const uint32_t t = hmul2(pack_bf(fmaf(x0, rs, nm), fmaf(x1, rs, nm)), w[4 + (i & 1)]);
      r[IDX(J, c, h)] = x0 + bf_lo(t); r[IDX(J, c + 1, h)] = x1 + bf_hi(t);
    }
  }
}

__device__ __forceinline__ float flip(float v, uint32_t m) { return __uint_as_float(__float_as_uint(v) ^ m); }
__device__ __forceinline__ void g1_phase(const int LY, const Head& H, uint32_t sb, int wg, int tid, Role R, float (&xr)[40], long long t_start) {
  Scratch* const S = H.s;
  tid = opaque(tid); sb = opaque(sb); R.v = opaque(R.v);
  const uint32_t bars = sb + BAR_OFF;
  const int cb = R.cb(), tb = R.tb();
  const int w = tid >> 5, lane = tid & 31, g = lane >> 2, q = lane & 3;
  const bool full = tb < 12;
  uint2* Eb = S->E + ((LY * 130 + cb) * 8 + 4 * wg + w) * 16 + g;
  float a[80];
#pragma unroll
  for (int i = 0; i < 80; i++) a[i] = 0.f;
  uint32_t rel = mapa(BAR(B_E1), lane ? R.wpart() : R.ubase() + (w & (R.ugs() - 1)));
  const bool rels = lane == 0 || (tid == 1 && wg != R.wlo());
  {
    uint64_t tw = LY ? WTAB1 : WTAB0, tx = LY ? XTAB1 : XTAB0;
    uint32_t bf = BAR(B_F1);
    if (tid == 0 && wg == 0 && !LY) PROF(351);
    fence_regs(a);
    mbar_wait(bf, LY);
    if (tid == 0 && wg == 0) PROF(LY ? 20 : 4);
#pragma unroll 1
    for (int kb = 0; kb < 10; kb++) {
      const uint64_t da = make_desc(sb + ((uint32_t)tw & 63) * 4096 + wg * 8192, 16, 1024, 1);
      const uint64_t db = make_desc(sb + ((uint32_t)tx & 63) * 4096, 16, 1024, 1);
      wg_fence();
#pragma unroll
      for (int kk = 0; kk < 4; kk++) wgmma_ss160(a, da + 2 * kk, db + 2 * kk, 1);
      wg_commit();
      wg_wait<1>();
      if (kb > 0) { if (rels) mbar_arrive_at(rel); rel += 8; }
      bf += 8; tw >>= 6; tx >>= 6;
      if (kb < 9) mbar_wait(bf, LY);
    }
  }
  if (tid == 0 && wg == 0) PROF(LY ? 19 : 2);
  mbar_wait(BAR(B_LM));
  const uint32_t tag = lds32(sb + MISC_OFF) & 1;
  if (q == 3) st_rlx2(Eb + tb * 1280, tag ^ 1, tag ^ 1);
  float2 lam, mu, mu2;
  float rs0, rs1;
  const uint32_t lamp = sb + LAM_OFF + 16 * (32 * wg + 8 * w + g);
  {
    const uint2* rp = S->RS + (8 * cb + 4 * wg + w) * 16 + 2 * g - (g & 1);
    uint2 v = ld_rlx2(rp);
    asm volatile("ld.shared.v2.f32 {%0,%1},[%2];" : "=f"(lam.x), "=f"(lam.y) : "r"(lamp));
    const float2 l2 = cmul(lam, lam), l4 = cmul(l2, l2), l8 = cmul(l4, l4), l16 = cmul(l8, l8), l32 = cmul(l16, l16);
    mu = full ? cmul(l32, l8) : l32; mu2 = cmul(mu, mu);
#pragma unroll 1
    for (int it = 0; it < SPIN && __any_sync(0xffffffff, untagged(v, tag)); it++) v = ld_rlx2(rp);
    rs0 = untag(v.x); rs1 = untag(v.y);
  }
  if (tid == 0 && wg == 0 && !LY) PROF(39);
  mbar_wait(BAR(B_ST), LY);
  const uint32_t ssm = sb + SSM_OFF + q * (full ? 336 : 272);
  wg_wait<0>(); fence_regs(a);
  if (rels) mbar_arrive_at(rel);
  if (tid == 0 && wg == 0) PROF(LY ? 21 : 5);
  float2 p = make_float2(0.f, 0.f);
#pragma unroll
  for (int j = 0; j < 20; j++) {
    if (j < 16 || full) {
      float4 sv;
      asm volatile("ld.shared.v4.f32 {%0,%1,%2,%3},[%4];" : "=f"(sv.x), "=f"(sv.y), "=f"(sv.z), "=f"(sv.w) : "r"(ssm + 16 * j));
#pragma unroll
      for (int e = 0; e < 2; e++) {
        const int o = 4 * j + e;
        const float r = e ? sv.z : sv.x, nm = e ? sv.w : sv.y;
        a[o] = fmaf(a[o], r, nm * rs0); a[o + 2] = fmaf(a[o + 2], r, nm * rs1);
        p = cfma(lam, p, make_float2(a[o], a[o + 2]));
      }
    }
  }
  {
    float2 t = make_float2(__shfl_up_sync(0xffffffff, p.x, 1, 4), __shfl_up_sync(0xffffffff, p.y, 1, 4));
    if (q >= 1) p = cfma(mu, t, p);
    t = make_float2(__shfl_up_sync(0xffffffff, p.x, 2, 4), __shfl_up_sync(0xffffffff, p.y, 2, 4));
    if (q >= 2) p = cfma(mu2, t, p);
  }
  if (q == 3 && full) st_rlx2(Eb + tb * 1280, tagf(p.x, tag), tagf(p.y, tag));
  if (tid == 0 && wg == 1) PROF(96 + 64 * LY);
  uint2 ev[3];
#pragma unroll
  for (int i = 0; i < 3; i++) { const int j = tb - 1 - q - 4 * i; ev[i] = j >= 0 ? ld_rlx2(Eb + j * 1280) : make_uint2(tag, tag); }
  float2 x = make_float2(__shfl_up_sync(0xffffffff, p.x, 1, 4), __shfl_up_sync(0xffffffff, p.y, 1, 4));
  if (q == 0) x = make_float2(0.f, 0.f);
  float c0, c1;
  asm volatile("ld.shared.v2.f32 {%0,%1},[%2+8];" : "=f"(c0), "=f"(c1) : "r"(lamp));
  const float c2 = -flip(c1, H.swap), c3 = flip(c0, H.swap);
#pragma unroll
  for (int i = 0; i < 40; i++) {
    const int o = 4 * (i >> 1) + (i & 1);
    const float u = a[o], v = a[o + 2];
    a[o] = fmaf(c0, u, c1 * v); a[o + 2] = fmaf(c2, u, c3 * v);
  }
  fence_regs(a);
  if (LY == 0 && R.b() < 128) {
    const int t0 = 16 * g + 8 * wg + 2 * w;
    if (tid == 0 && wg == 1) PROF(366);
    mbar_wait(BAR(B_XR));
    if (tid == 0 && wg == 1) PROF(367);
    uint4 s = lds4(sb + XR_OFF + 20480 + 256 + 8 * t0);
    if (__any_sync(0xffffffff, untagged(s, tag))) {
#pragma unroll 1
      for (int it = 0; it < SPIN; it++) { s = ld_rlx4(S->S + 128 * (R.b() >> 3) + t0); if (!__any_sync(0xffffffff, untagged(s, tag))) break; }
    }
    resid_load(xr, sb, wg, tid, s);
  }
  float2 mq, om4, fq;
  {
    asm volatile("" : "+f"(lam.x), "+f"(lam.y));
    const float2 one = make_float2(1.f, 0.f), l2 = cmul(lam, lam), l4 = cmul(l2, l2), l8 = cmul(l4, l4), l16 = cmul(l8, l8);
    const float2 l80 = full ? mu2 : cmul(mu2, l16), om = cmul(l80, l80), om2 = cmul(om, om);
    mq = cmul((q & 1) ? mu : one, (q & 2) ? mu2 : one);
    om4 = cmul(om2, om2); fq = cmul((q & 1) ? om : one, (q & 2) ? om2 : one);
  }
  mbar_wait(BAR(B_E1 + 9), LY);
  if (tid == 0 && wg == 1) PROF(368 + LY);
#pragma unroll 1
  for (int it = 0; it < SPIN; it++) {
    const bool m0 = untagged(ev[0], tag), m1 = untagged(ev[1], tag), m2 = untagged(ev[2], tag);
    if (!__any_sync(0xffffffff, m0 || m1 || m2)) break;
    if (m0) ev[0] = ld_rlx2(Eb + (tb - 1 - q) * 1280);
    if (m1) ev[1] = ld_rlx2(Eb + (tb - 5 - q) * 1280);
    if (m2) ev[2] = ld_rlx2(Eb + (tb - 9 - q) * 1280);
  }
  if (tid == 0 && wg == 1) PROF(97 + 64 * LY);
  float2 c = make_float2(untag(ev[2].x), untag(ev[2].y));
#pragma unroll
  for (int i = 1; i >= 0; i--) c = cfma(om4, c, make_float2(untag(ev[i].x), untag(ev[i].y)));
  c = cmul(fq, c);
#pragma unroll
  for (int s = 1; s <= 2; s <<= 1) { c.x += __shfl_xor_sync(0xffffffff, c.x, s); c.y += __shfl_xor_sync(0xffffffff, c.y, s); }
  c = cfma(mq, c, x);
  float2 z = make_float2(fmaf(c0, c.x, c1 * c.y), fmaf(c2, c.x, c3 * c.y));
  if (tid == 0 && wg == 0) PROF(LY ? 22 : 6);
  const float2 lc = make_float2(lam.x, flip(lam.y, H.swap));
  const uint32_t hq = sb + (lane >> 4) * 1024 + (lane & 7) * 128 + (((4 * wg + w) ^ (lane & 7)) << 4);
  const uint32_t hp = hq + R_OFF + (lane & 8) * 2048, hp4 = hq + (LY ? R4_OFF1 : R4_OFF0) + (lane & 8) * 512;
#pragma unroll
  for (int j = 0; j < 20; j += 2) {
    if (j < 16 || full) {
      uint32_t o[4];
#pragma unroll
      for (int i = 0; i < 2; i++) {
        const float2 z0 = cfma(lc, z, make_float2(a[4 * (j + i)], a[4 * (j + i) + 2]));
        z = cfma(lc, z0, make_float2(a[4 * (j + i) + 1], a[4 * (j + i) + 3]));
        o[2 * i] = pack_bf(z0.x, z.x); o[2 * i + 1] = pack_bf(z0.y, z.y);
      }
      asm volatile("stmatrix.sync.aligned.m8n8.x4.trans.shared.b16 [%0], {%1,%2,%3,%4};" ::"r"(j < 16 ? hp + j * 1024 : hp4 + (j - 16) * 1024), "r"(o[0]), "r"(o[1]), "r"(o[2]), "r"(o[3]) : "memory");
      if (j & 2) { __syncwarp(); if (lane == 0) mbar_arrive(BAR(B_SH + j / 4)); }
    }
  }
  if (tid == 0 && wg == 0) PROF(LY ? 23 : 7);
  if (lane == 0) PROF(390 + 4 * wg + w);
}

__device__ __forceinline__ void gate_load(float (&G)[40], uint32_t sb, int LY, int wg, int tid, int tb2) {
  const uint32_t bars = sb + BAR_OFF;
  const int lane = tid & 31, w = tid >> 5;
  mbar_wait(BAR(B_GF), LY);
  const int g = lane >> 2, q = lane & 3;
  const uint32_t gb = sb + (LY ? G_OFF1 : G_OFF0) + wg * 10240 + 512 * q + ((32 * w + 4 * g) ^ (64 * ((tb2 ^ q) & 1)) ^ (16 * (q & 2)));
#pragma unroll
  for (int i = 0; i < 20; i++) { const uint32_t v = lds32((gb ^ (16 * (i & 3))) + 128 * (i & 3) + 2048 * (i >> 2)); G[2 * i] = bf_lo(v); G[2 * i + 1] = bf_hi(v); }
  fence_regs(G);
}
__device__ __forceinline__ void g2_phase(const int LY, const Params& P, Scratch* S, uint32_t sb, int wg, int tid, Role R, float (&xr)[40], long long t_start) {
  sb = opaque(sb);
  const uint32_t bars = sb + BAR_OFF;
  if (LY) {
    const int td = opaque(tid), b = (opaque(R.v) >> 8) & 255;
    const uint32_t tag = lds32(sb + MISC_OFF) & 1;
    const uint2* sp = S->S + 2 * SEQ + 128 * (b >> 3) + 4 * (td & 28) + 8 * wg + 2 * (td >> 5);
    if (!(R.cb() & 1)) mbar_wait(BAR(B_HD), 1);
    uint2 dl[5];
#pragma unroll
    for (int J = 0; J < 5; J++) dl[J] = __ldg((const uint2*)(P.dskip + 80 * (b & 7) + 4 * (td & 3) + 16 * J));
    uint4 sv;
#pragma unroll 1
    for (int it = 0; it < SPIN; it++) { sv = ld_rlx4(sp); if (!__any_sync(0xffffffff, untagged(sv, tag))) break; }
#pragma unroll
    for (int h = 0; h < 2; h++)
#pragma unroll
      for (int J = 0; J < 5; J++)
#pragma unroll
        for (int c = 0; c < 4; c++) {
          const float x2 = xr[IDX(J, c, h)];
          const uint32_t dw = (c & 2) ? dl[J].y : dl[J].x;
          xr[IDX(J, c, h)] = fmaf(fmaf(x2, untag(h ? sv.z : sv.x), untag(h ? sv.w : sv.y)), (c & 1) ? bf_hi(dw) : bf_lo(dw), x2);
        }
    fence_regs(xr);
  }
  float acc[40];
#pragma unroll
  for (int i = 0; i < 40; i++) acc[i] = RIAT == 1 ? 0.f : xr[i];
  fence_regs(acc);
#define G2_STEP(st, cs, hf) { \
    const uint64_t da = make_desc(sb + H_OFF + (st) * 32768 + (hf) * 16384 + wg * 8192, 16, 1024, 1), db = make_desc(sb + (cs) * 20480 + (hf) * 10240, 16, 1024, 1); \
    wg_fence(); \
    _Pragma("unroll") for (int kk = 0; kk < 4; kk++) wgmma_ss80(acc, da + 2 * kk, db + 2 * kk, 1); \
    wg_commit(); }
  mbar_wait(BAR(B_F2), LY);
  if (tid == 0 && wg == 0) PROF(LY ? 25 : 10);
  G2_STEP(0, 0, 0)
  mbar_wait(BAR(B_F3), LY);
  G2_STEP(0, 0, 1)
  tid = opaque(tid); R.v = opaque(R.v);
  const uint32_t tag = lds32(sb + MISC_OFF) & 1;
  const int b = R.b(), tb2 = b >> 3, db_ = b & 7;
  const int w = tid >> 5, lane = tid & 31, g = lane >> 2, q = lane & 3;
  const int t0 = 128 * tb2 + 16 * g + 8 * wg + 2 * w;
  const int d0 = 80 * db_ + 4 * q, mrow = 64 * wg + 16 * w + g;
#define GATE(J, c, h) G[8 * (J) + 2 * (c) + (h)]
  uint32_t rel = mapa(BAR(B_E2), lane ? ((w & 1) ? R.wpart() : R.rank()) : R.cs() == 8 ? 4 * wg + w : wg);
  const bool rels = lane == 0 || (lane == 1 && w < 2);
  uint32_t* Mb = S->M + ((2 * LY * 16 + tb2) * 8) * 256 + (wg * 4 + w) * 32 + (2 * g + (q & 1)) * 2 + (q >> 1);
  {
    uint32_t bf = BAR(B_F2 + 1), st = 1, ra = rel + 8 * (B_EA - B_E2);
    const int lag = wg ? (LY ? STG : STG0) / 2 : 0;
#pragma unroll 1
    for (int kp = 1; kp < 10; kp++) {
      const bool more = LY == 0 || kp < 8;
      wg_wait<1>();
      if (lane == 0 && more) mbar_arrive_at(ra + 8 * (st ? st - 1 : 2));
      mbar_wait(bf, LY);
      if (STG && !(STG & 1) && kp == lag) bar_sync(5, 256);
      G2_STEP(st, kp < 5 ? kp : kp - 5, 0)
      wg_wait<1>();
      if (rels && more) mbar_arrive_at(rel);
      rel += 8;
      mbar_wait(bf + 8 * (B_F3 - B_F2), LY);
      if ((STG & 1) && kp == lag) bar_sync(5, 256);
      G2_STEP(st, kp < 5 ? kp : kp - 5, 1)
      if (kp == MIAT) {
        st_rlx(Mb + db_ * 256, tag ^ 1);
        if (LY == 0) st_rlx(Mb + (16 * 8 + db_) * 256, tag ^ 1);
      }
      bf += 8; st = st == 2 ? 0 : st + 1;
    }
  }
  if (STG && (LY || STG0) && !wg) asm volatile("bar.arrive 5, 256;" ::: "memory");
  wg_wait<0>(); fence_regs(acc);
  if (LY == 0 && rels) mbar_arrive_at(rel);
  if (tid == 0 && wg == 0) PROF(LY ? 26 : 11);
  if (lane == 0) PROF(116 + 64 * LY + wg * 4 + w);

  float mm[2] = {0.f, 0.f}, rr[2];
#pragma unroll 1
  for (int rep = 0;; rep++) {
    float m[2][2];
#pragma unroll
    for (int h = 0; h < 2; h++) {
      m[h][0] = m[h][1] = 0.f;
#pragma unroll
      for (int J = 0; J < 5; J++)
#pragma unroll
        for (int c = 0; c < 4; c++) { const float xv = acc[IDX(J, c, h)]; m[h][0] += xv; m[h][1] = fmaf(xv, xv, m[h][1]); }
    }
    float r1[2];
#pragma unroll
    for (int i = 0; i < 2; i++) { const float snd = (q & 1) ? m[0][i] : m[1][i], kp = (q & 1) ? m[1][i] : m[0][i]; r1[i] = kp + __shfl_xor_sync(0xffffffff, snd, 1); }
    const float r2 = ((q & 2) ? r1[1] : r1[0]) + __shfl_xor_sync(0xffffffff, (q & 2) ? r1[0] : r1[1], 2);
    const uint32_t mx = sb + MX_OFF + 512 * wg + 4 * tid, bx = BAR(B_KF + 1 + 2 * LY + wg);
    if (R.cs() == 8 && !rep) {
#pragma unroll
      for (int i = 0; i < 8; i++)
        asm volatile("st.async.weak.shared::cluster.mbarrier::complete_tx::bytes.b32 [%0],%1,[%2];" ::"r"(mapa(mx + 1024 * db_, i ^ db_)), "f"(r2), "r"(mapa(bx, i ^ db_)) : "memory");
      if (tid == 0) mbar_expect_tx(bx, 4096);
    }
    st_rlx(Mb + db_ * 256, tagf(r2, tag));
    if (rep) break;
    if (lane == 0) PROF(100 + 64 * LY + wg * 4 + w);
    float G[40];
    const bool late = LY == 0 && db_ >= GLATE;
#pragma unroll
    for (int i = 0; i < 40; i++) G[i] = 0.f;
#pragma unroll 1
    for (int ps = late;; ps += 2) {
    if (ps != 1) gate_load(G, sb, LY, wg, tid, tb2);
    if (ps == 3) break;
    mbar_wait(BAR(B_CD + 1));
    uint32_t mv[8];
    if (R.cs() == 8) {
      mbar_wait(bx, 1);
#pragma unroll
      for (int i = 0; i < 8; i++) mv[i] = lds32(mx + 1024 * i);
    } else {
#pragma unroll
    for (int i = 0; i < 8; i++) mv[i] = ld_rlx(Mb + i * 256);
#pragma unroll 1
    for (int it = 0; it < SPIN; it++) {
      uint32_t miss = 0;
#pragma unroll
      for (int i = 0; i < 8; i++) miss |= ((mv[i] ^ tag) & 1) << i;
      if (!__any_sync(0xffffffff, miss)) break;
#pragma unroll
      for (int i = 0; i < 8; i++) if ((miss >> i) & 1) mv[i] = ld_rlx(Mb + i * 256);
    }
      if (MBAR || !LY) bar_sync(4, 256);
    }
    if (lane == 0) PROF(108 + 64 * LY + wg * 4 + w);
    const float s = ((untag(mv[0]) + untag(mv[1])) + (untag(mv[2]) + untag(mv[3]))) + ((untag(mv[4]) + untag(mv[5])) + (untag(mv[6]) + untag(mv[7])));
    const float o = __shfl_xor_sync(0xffffffff, s, 2);
    const float S1 = (q & 2) ? o : s, S2 = (q & 2) ? s : o;
    const float mean = S1 * (1.f / DM), rs = frsqrt(fmaxf(S2 * (1.f / DM) - mean * mean, 0.f) + 1e-5f);
    const float mo = __shfl_xor_sync(0xffffffff, mean, 1), ro = __shfl_xor_sync(0xffffffff, rs, 1);
    mm[0] = (q & 1) ? mo : mean; mm[1] = (q & 1) ? mean : mo; rr[0] = (q & 1) ? ro : rs; rr[1] = (q & 1) ? rs : ro;
    if (ps == 0) break;
    }
    if (tid == 0 && wg == 0) PROF(LY ? 27 : 12);
    const float nm[2] = {-mm[0] * rr[0], -mm[1] * rr[1]};
    if (LY) mm[0] = mm[1] = 0.f;
#pragma unroll
    for (int h = 0; h < 2; h++)
#pragma unroll
      for (int J = 0; J < 5; J++)
#pragma unroll
        for (int c = 0; c < 4; c++) { const float xv = acc[IDX(J, c, h)]; acc[IDX(J, c, h)] = fmaf(fmaf(xv, rr[h], nm[h]), GATE(J, c, h), xv - mm[h]); }
    if (LY) break;
    if (R.cs() == 8) mbar_wait(BAR(B_KF + 1), 1);
#pragma unroll
    for (int i = 0; i < 10; i++) {
      const int J = i >> 1, h = i & 1;
      const uint32_t u0 = pack_bf(acc[IDX(J, 0, h)], acc[IDX(J, 1, h)]), u1 = pack_bf(acc[IDX(J, 2, h)], acc[IDX(J, 3, h)]);
      asm volatile("st.shared.v2.u32 [%0],{%1,%2};" ::"r"(sb + US_OFF + ((mrow ^ 64) + 8 * h) * 160 + 32 * J + 8 * q), "r"(u0), "r"(u1) : "memory");
    }
    __syncwarp();
    if (lane == 0) mbar_arrive(BAR(B_GS + 1 + wg));
    if (tid == 0 && wg == 0) PROF(13);
    Mb += 16 * 8 * 256;
  }
  if (LY == 0) {
#pragma unroll
    for (int i = 0; i < 40; i++) xr[i] = acc[i] + mm[(i >> 1) & 1];
    if (tid == 0 && wg == 0) PROF(15);
  }
  else {
    float* op = P.out + (size_t)t0 * DM + d0;
#pragma unroll
    for (int i = 0; i < 10; i++) {
      const int J = i >> 1, h = i & 1;
      asm volatile("st.global.v4.f32 [%0],{%1,%2,%3,%4};" ::"l"(op + h * DM + 16 * J),
                   "f"(acc[IDX(J, 0, h)]), "f"(acc[IDX(J, 1, h)]), "f"(acc[IDX(J, 2, h)]), "f"(acc[IDX(J, 3, h)]) : "memory");
    }
  }
  if (tid == 0 && wg == 0 && LY) PROF(28);
#undef IDX
#undef GATE
}

__device__ __forceinline__ void next_stats(Scratch* S, uint32_t sb, int tb2, int tid) {
  const uint32_t bars = sb + BAR_OFF, tag = lds32(sb + MISC_OFF) & 1;
  const uint32_t* Mb = S->M + tb2 * 8 * 256 + 2 * tid;
  mbar_wait(BAR(B_F1 + NSAT), 1);
  float m1, s1, s2;
#pragma unroll 1
  for (int it = 0; it < SPIN; it++) {
    uint32_t a[8], miss = 0;
    uint2 v[8];
#pragma unroll
    for (int i = 0; i < 8; i++) { a[i] = ld_rlx(Mb + i * 256); v[i] = ld_rlx2((const uint2*)(Mb + (16 * 8 + i) * 256)); }
#pragma unroll
    for (int i = 0; i < 8; i++) miss |= (a[i] ^ tag) | (v[i].x ^ tag) | (v[i].y ^ tag);
#define SUM8(F) ((untag(F(0)) + untag(F(1))) + (untag(F(2)) + untag(F(3)))) + ((untag(F(4)) + untag(F(5))) + (untag(F(6)) + untag(F(7))))
#define FA(i) a[i]
#define FX(i) v[i].x
#define FY(i) v[i].y
    m1 = SUM8(FA); s1 = SUM8(FX); s2 = SUM8(FY);
    if (!__any_sync(0xffffffff, miss & 1)) break;
  }
  const float mean = s1 * (1.f / DM), rs = frsqrt(fmaxf(s2 * (1.f / DM) - mean * mean, 0.f) + 1e-5f);
  uint2* sp = S->S + SEQ + 128 * tb2 + 8 * (tid & 14) + 2 * (tid >> 4) + (tid & 1);
  st_rlx2(sp, tagf(rs, tag), tagf(-mean * rs, tag));
  st_rlx2(sp + SEQ, tagf(rs, tag), tagf(-(mean + m1 * (1.f / DM)) * rs, tag));
}
template <int I0, int I1> __device__ __forceinline__ void init_barriers(uint32_t bars) {
#pragma unroll
  for (int i = I0; i < I1; i++) mbar_init(BAR(i), bar_count(i));
}
__device__ __forceinline__ int g2_cb(int kp) { return kp < 5 ? 2 * kp : 2 * kp - 9; }
__device__ __forceinline__ const unsigned* h_flag(Scratch* S, int ly, int tb2, int lane) {
  const int s0 = 128 * min(tb2, 15) / 160;
  const bool two = (128 * tb2 + 127) / 160 != s0;
  return &S->flag[(F_H + (ly * 13 + s0) * 10 + min(lane & 15, 9) + (two && lane >= 16 ? 10 : 0)) * 32];
}
__device__ __forceinline__ void gate_tile(const Params& P, uint32_t dst, uint32_t bar, int tb2, int db) {
  mbar_expect_tx(bar, 20480);
  tma2d(dst, &P.mGT, tb2 * 128, db * 80, bar);
  tma2d(dst + 10240, &P.mGT, tb2 * 128 + 64, db * 80, bar);
}
__global__ void __cluster_dims__() __launch_bounds__(512, 1) fused_kernel(const Head H, const __grid_constant__ Params P) {
  extern __shared__ __align__(1024) uint8_t smem[];
  const uint32_t sb = opaque(smem_u32(smem)), bars = sb + BAR_OFF;
  const int wi = __shfl_sync(0xffffffff, threadIdx.x >> 5, 0), wg = wi >> 2, tid = threadIdx.x & 127;
  const int umap = blockIdx.x >= 96;
#define CLK(v)
  CLK(c_a);
  if (wi == 14) {
    if (elect_one()) { init_barriers<0, NBAR1>(bars); asm volatile("fence.mbarrier_init.release.cluster;" ::: "memory"); }
    __syncwarp();
  } else if (wi >= 12) prefetch_map(wi == 12 ? &P.mB : &P.mA[umap]);
  else if (wg == 2) xb_prefetch<1>(H, blockIdx.x + H.base, tid, 0);
  else if (P.role[blockIdx.x].w) return;
  CLK(c_b);
  asm volatile("barrier.cluster.arrive.relaxed.aligned;" ::: "memory");
  CLK(c_c);
  Role R;
  { const uint4 r = P.role[blockIdx.x]; R.v = r.x; R.c = r.y; R.p = r.z; }
  const int id = R.c & 255;
  const int tb = R.tb(), cb = R.cb(), b = R.b(), tb2 = b >> 3, db = b & 7, rank = R.rank();
  const bool has1 = tb <= 12, has2 = b < 128, full = tb < 12;
  Scratch* const S = H.s;
  unsigned* const epoch_p = &S->epoch[id * 8];
  const long long t_start = 0;
  if (wg < 2) {
    if (threadIdx.x == 0) PROF(50);
    asm volatile("griddepcontrol.launch_dependents;");
    bar_sync(6, 448);
    asm volatile("setmaxnreg.inc.sync.aligned.u32 176;");
    float xr[40];
#pragma unroll
    for (int i = 0; i < 40; i++) xr[i] = 0.f;
#pragma unroll 1
    for (int ly = 0; ly < 2; ly++) {
      if (has1) g1_phase(ly, H, sb, wg, tid, R, xr, t_start);
      if (ly == 0) {
        resid_init(xr); fence_regs(xr);
        conv_loop<false>(sb, R.c, wg, tid, t_start);
        if (tid == 0 && wg == 0) PROF(9);
      }
      if (has2) g2_phase(ly, P, S, sb, wg, tid, R, xr, t_start);
    }
    if (tid == 0 && wg == 0) st_rlx(epoch_p, lds32(sb + MISC_OFF));
  } else if (wg == 2) {
    bar_sync(6, 448);
    if (has1) aux_prep(H, P, sb, R, tid, t_start);
    asm volatile("setmaxnreg.inc.sync.aligned.u32 136;");
    conv_loop<true>(sb, R.c, wg, tid, t_start);
    if (tid == 0) PROF(44);
    {
      const uint32_t bb = (P.role[blockIdx.x].x >> 8) & 255;
      if ((bb & 132) == NSDB && tid < 32) next_stats(H.s, sb, bb >> 3, 32 * (bb & 3) + tid);
    }
  } else {
    if (threadIdx.x == 384) PROF(354);
    asm volatile("setmaxnreg.dec.sync.aligned.u32 24;");
    const int wlo = R.wlo(), whi = R.whi();
    const uint32_t wmask = R.wmask(), umask = R.umask(), f1bytes = full ? 36864 : 32768;
    if (wi < 14) {
      if (threadIdx.x == 384) PROF(340);
      asm volatile("barrier.cluster.wait.aligned;" ::: "memory");
      if (has1 && elect_one()) {
        uint64_t tab = wi == 12 ? WTAB0 : XTAB0;
        PROF(329 + wi);
#pragma unroll 1
        for (int kb = 0; kb < 6; kb++, tab >>= 6) {
          const uint32_t dst = sb + ((uint32_t)tab & 63) * 4096;
          if (wi == 12) {
#pragma unroll 1
            for (int h = wlo; h <= whi; h++) tma4d_mc(dst + h * 8192, &P.mB, kb * 64, 0, 0, 8 * cb + 4 * h, BAR(B_F1 + kb), wmask);
          } else {
            tma4d_mc(dst + R.uj() * 1024, &P.mA[umap], kb * 64, 0, 0, 80 * tb + R.uj(), BAR(B_F1 + kb), umask);
            mbar_expect_tx(BAR(B_F1 + kb), f1bytes);
          }
        }
      }
      if (!has1 && wi == 13) bar_sync(7, 64);
    } else {
      if (wi == 15 && elect_one()) { init_barriers<NBAR1, NBAR>(bars); asm volatile("fence.mbarrier_init.release.cluster;" ::: "memory"); }
      bar_sync(6, 448);
      if (!has1 && wi == 14) bar_sync(7, 64);
    }
    const unsigned e1 = ld_rlx(epoch_p) + 1;
    if (wi == 12) {
      if (elect_one()) {
#pragma unroll 1
        for (int ly = 0; ly < 2; ly++) {
#pragma unroll 1
          for (int i = ly ? 0 : 6; i < 10 && has1; i++) {
            const int kb = (0x9876541032ull >> (4 * i)) & 15;
            if (ly == 0) { mbar_wait(BAR(B_E1 + ((DEP0 >> (4 * kb - 24)) & 15))); mbar_wait(BAR(B_AX + (kb == 9))); }
            else {
              if (has2 && i == (db >= GLATE ? 4 : 2)) {
                wait_cnt(&S->cnt[(C_G + db) * 32], e1 * 80);
                mbar_wait(BAR(B_E2 + 7));
                PROF(47);
                gate_tile(P, sb + G_OFF0, BAR(B_GF), tb2, db);
              }
              if (has2) mbar_wait(BAR(i < 4 ? B_E2 + ((0x9865u >> (4 * i)) & 15) : B_GE));
              else if (i == 0) { mbar_wait(BAR(B_E1 + 9)); mbar_wait(BAR(B_CD + 1)); }
              if (i >= 4) mbar_wait(BAR(i < 6 ? B_F1 + W4AT : B_E1 + i - 6), 1);
            }
            const uint32_t dst = sb + ((uint32_t)((ly ? WTAB1 : WTAB0) >> (6 * kb)) & 63) * 4096;
#pragma unroll 1
            for (int h = wlo; h <= whi; h++) tma4d_mc(dst + h * 8192, &P.mB, kb * 64, 0, 0, 8 * cb + 4 * h, BAR(B_F1 + kb), wmask);
          }
          if (has2) {
            if (ly == 0) {
              mbar_wait(BAR(B_E1 + XRAT));
              mbar_expect_tx(BAR(B_XR), 20480 + 160 + 1024);
              tma4d(sb + XR_OFF, &P.mX, 80 * db, tb2, BAR(B_XR));
              bulk_g2s(sb + XR_OFF + 20480, P.dskip + 80 * db, 160, BAR(B_XR));
              bulk_g2s(sb + XR_OFF + 20480 + 256, S->S + 128 * tb2, 1024, BAR(B_XR));
              if (CWAIT) mbar_wait(BAR(CWAIT == 1 ? B_KF + 2 : CWAIT == 2 ? B_KF + R.nch() - 1 : CWAIT == 3 ? B_KF + R.nch() - 2 : B_HD));
            }
#pragma unroll 1
            for (int kp = 0; kp < 10; kp++) {
              const uint32_t dst = sb + (kp < 5 ? kp : kp - 5) * 20480;
              mbar_wait(BAR(kp >= 5 ? B_E2 + kp - 5 : ly ? B_E1 + ((CTAB1 >> (4 * kp)) & 15) : kp < 3 ? B_SH : kp < 4 ? B_HD : B_CD), ly);
              mbar_expect_tx(BAR(B_F2 + kp), 10240 + 16384);
              tma5d(dst, &P.mC[0], g2_cb(kp) * 64, db * 5, BAR(B_F2 + kp));
              mbar_expect_tx(BAR(B_F3 + kp), 10240 + 16384);
              tma5d(dst + 10240, &P.mC[1], g2_cb(kp) * 64, db * 5, BAR(B_F3 + kp));
              if (ly && kp == 4) { mbar_wait(BAR(B_E1 + 9), 1); gate_tile(P, sb + G_OFF1, BAR(B_GF), tb2, db); }
            }
          }
        }
      }
    } else if (wi == 13) {
      const int h0 = R.cs() == 8 ? rank : 4 * rank;
#pragma unroll 1
      for (int ly = 0; ly < 2; ly++) {
        int lane = lane_id();
        if (has1) {
          const unsigned* fp = &S->flag[(F_U3 + 8 * ((160 * tb) >> 7) + (lane & (full ? 15 : 7))) * 32];
          uint32_t ready = ly ? __ballot_sync(0xffffffff, ld_rlx(fp) == e1) : ~0u;
          if (ly) mbar_wait(BAR(full ? B_KF + 1 : has2 ? B_GS + 1 : B_RF1), has2);
          if (ly && full) mbar_wait(BAR(B_KF + 2), 1);
#pragma unroll 1
          for (int kb = ly ? 0 : 6; kb < 10; kb++) {
            if (ly && kb == UPAT) { mbar_wait(BAR(B_XR)); ready = ~0u; }
            wait_flags(fp, e1, 0x101u * ((1u << (64 * kb / 80)) | (1u << ((64 * kb + 63) / 80))), ready);
            if (kb >= 4) mbar_wait(BAR(B_E1 + (ly ? kb - 4 : (DEP0 >> (4 * kb - 24)) & 15)), ly);
            mbar_wait(BAR(B_AX + (kb == 9)));
            if (elect_one()) {
              if (ly && kb == 0) PROF(34);
              tma4d_mc(sb + ((uint32_t)((ly ? XTAB1 : XTAB0) >> (6 * kb)) & 63) * 4096 + R.uj() * 1024, &P.mA[2 * ly + umap], kb * 64, 0, 0, 80 * tb + R.uj(),
                       BAR(B_F1 + kb), umask);
              mbar_expect_tx(BAR(B_F1 + kb), f1bytes);
            }
            __syncwarp();
          }
        }
        if (ly == 0) {
          if (has1) mbar_wait(BAR(B_E1 + KPF));
          if (elect_one()) {
#pragma unroll 1
            for (int s = 0; s < R.nch(); s++) prefetch_l2(P.ssmk + (size_t)R.ch(s) * SEQ, 4096);
          }
          lane = lane_id();
#pragma unroll
          for (int s = 0; s < 5; s++) {
            asm volatile("st.shared.v4.u32 [%0],{%1,%1,%1,%1};" ::"r"(conv_buf(sb, s) + 16 * lane), "r"(0) : "memory");
            asm volatile("st.shared.u8 [%0],%1;" ::"r"(conv_buf(sb, s) + KC_OFS + lane), "r"(0) : "memory");
          }
          fence_async();
          __syncwarp();
          const unsigned* cp = &S->cnt[(C_KV + (R.ch(min(lane, R.nch() - 1)) >> 6)) * 32];
          uint32_t ready = 0;
#pragma unroll 1
          for (int s = 0, sk = 0; s < R.nch(); s++) {
#pragma unroll 1
            for (; sk < (s ? R.nch() : KUP); sk++)
              if (elect_one()) { mbar_expect_tx(BAR(B_KF + sk), 8192); bulk_g2s(conv_buf(sb, sk) + KC_OFS + 32, P.ssmk + (size_t)R.ch(sk) * SEQ, 4096, BAR(B_KF + sk)); }
            PROFC(s == 0, 329);
#pragma unroll 1
            for (int it = 0; !((ready >> s) & 1) && it < SPIN; it++) ready = __ballot_sync(0xffffffff, (int)(ld_rlx(cp) - e1 * 32) >= 0);
            PROFC(s == 0, 30);
            if (elect_one()) {
              bulk_g2s(conv_buf(sb, s) + KV_PAD, S->kv + (size_t)R.ch(s) * SEQ, 4096, BAR(B_KF + s));
              if (s == 0 && has2) { prefetch_l2(P.cre + (size_t)5 * b * DM, 5 * DM * 2); prefetch_l2(P.cim + (size_t)5 * b * DM, 5 * DM * 2); }
            }
            __syncwarp();
          }
          PROF(31);
          if (!has1) return;
        }
        lane = lane_id();
        const unsigned* fp = h_flag(S, ly, tb2, lane);
        uint32_t ready = __ballot_sync(0xffffffff, ld_rlx(fp) == e1), st = 0;
        if (ly == 0 && !has2) {
          mbar_wait(BAR(B_HD));
          if (lane < 8) mbar_arrive_cl(BAR(B_RF1), lane & 1);
        }
        if (has2) {
          mbar_wait(BAR(B_RF0), ly);
#pragma unroll 1
          for (int kp = 0; kp < 10; kp++) {
            if (kp == 5) { mbar_wait(BAR(B_XR), 1); ready = ~0u; }
            if (kp == 2) { mbar_wait(BAR(B_HD), ly); if (lane < 8) mbar_arrive_cl(BAR(B_RF1), lane & (R.cs() - 1)); }
            wait_flags(fp, e1, 0x10001u << g2_cb(kp), ready);
            if (kp == 2) mbar_wait(BAR(B_RF1), ly);
#pragma unroll
            for (int hf = 0; hf < 2; hf++) {
              if (kp >= 3) { if (hf) mbar_wait(BAR(B_E2 + kp - 3), ly); else mbar_wait(BAR(B_EA + st), ly ^ (kp >= 6 && kp < 9)); }
              if (elect_one()) {
                if (kp == 0 && !hf) PROF(33 + 2 * ly);
                tma4d_mc(sb + H_OFF + st * 32768 + hf * 16384 + h0 * 2048, &P.mH, g2_cb(kp) * 128 + hf * 64, 0, 2 * h0,
                         ly * 16 + tb2, BAR((hf ? B_F3 : B_F2) + kp), (1u << R.cs()) - 1);
              }
              __syncwarp();
            }
            st = st == 2 ? 0 : st + 1;
          }
        }
      }
    } else if (wi == 14) {
      if (!has1) return;
      prefetch_if(P.dskip + 64 * (tid & 31), (tid & 31) < 10);
      if (elect_one()) { prefetch_map(&P.sK); prefetch_map(&P.mX); prefetch_map(&P.sH); prefetch_map(&P.sU); prefetch_map(&P.mC[0]); prefetch_map(&P.mC[1]); prefetch_map(&P.mH); prefetch_map(&P.mGT); prefetch_map(&P.mA[2 + umap]); }
      __syncwarp();
#pragma unroll 1
      for (int ly = 0; ly < 2; ly++) {
        if (ly) {
          mbar_wait(BAR(B_F1 + 1), 1);
          uint32_t ready = 0;
          wait_flags(&S->flag[(F_U3 + 8 * ((160 * tb) >> 7) + ((lane_id() + ly) & (full ? 15 : 7))) * 32], e1, ~0u, ready);
          if (elect_one()) mbar_arrive(BAR(B_XR));
        }
        const int lane = lane_id();
        mbar_wait(BAR(B_E1 + (ly ? STAT_AT1 : STAT_AT)), ly);
        PROFC(lane == 0 && ly == 0, 36);
        {
          const int l = lane - (full ? 0 : 16);
          const uint2* p = S->S + ly * SEQ + 160 * tb + 2 * l;
          uint4 v[3];
#pragma unroll 1
          for (int it = 0; it < SPIN; it++) {
            v[0] = ld_rlx4(p); v[1] = ld_rlx4(p + 64); v[2] = ld_rlx4(p + 96);
            const bool miss = __any_sync(0xffffffff, untagged(v[0], e1 & 1) | untagged(v[1], e1 & 1) | untagged(v[2], e1 & 1));
            PROFC(lane == 0 && ly == 0 && it == 0, 37);
            if (!miss) break;
          }
          PROFC(lane == 0 && ly == 0, 38);
#pragma unroll
          for (int i = 0; i < 3; i++) {
            const int pr = l + (i == 2 ? 48 : 32 * i);
            if (pr >= 0) asm volatile("st.shared.v4.u32 [%0],{%1,%2,%3,%4};" ::"r"(sb + SSM_OFF + 16 * (pr + ((pr * (full ? 205 : 256)) >> 12))), "r"(v[i].x & ~1u),
                                      "r"(v[i].y & ~1u), "r"(v[i].z & ~1u), "r"(v[i].w & ~1u) : "memory");
          }
          __syncwarp();
        }
        if (lane == 0) mbar_arrive(BAR(B_ST));
        if (ly && has2) {
          mbar_wait(BAR(B_E1 + 9), 1);
          if (lane < 8) mbar_arrive_cl(BAR(B_RF0), lane & (R.cs() - 1));
        }
        if (lane == 0) {
#pragma unroll 1
          for (int pc = 0; pc < (full ? 5 : 4); pc++) {
            if ((HWM >> (4 * pc)) & 8) {
              mbar_wait(BAR(B_SH + min((HWM >> (4 * pc)) & 7, full ? 4 : 3)), ly);
              PROF(380 + 5 * ly + pc);
              if (pc == 0 && (cb & 1)) delay(ly ? HDLY : HDLY0);
              fence_async();
            }
#pragma unroll
            for (int i = 0; i < 2; i++) tma4d_store(&P.sH, sb + (pc < 4 ? R_OFF + i * 16384 + pc * 4096 : (ly ? R4_OFF1 : R4_OFF0) + i * 4096), 128 * cb + 64 * i, 0, 0, ly * 1024 + 80 * tb + 4 * pc);
          }
          bulk_commit(); bulk_wait();
          PROF(ly ? 17 : 16);
          mbar_arrive(BAR(B_HD));
          release<1>();
          signal_flag(&S->flag[(F_H + (ly * 13 + tb) * 10 + cb) * 32], e1);
          PROF(ly ? 24 : 8);
        }
        __syncwarp();
        if (has2) {
          mbar_wait(BAR(B_F2 + FPAT), ly);
          uint32_t ready = 0;
          wait_flags(h_flag(S, ly, tb2, lane_id() | 1), e1, ~0u, ready);
          if (elect_one()) mbar_arrive(BAR(B_XR));
        }
        if (lane == 0 && has2 && !ly) {
          mbar_wait(BAR(B_CD + 1));
#pragma unroll
          for (int i = 0; i < 2; i++) {
            mbar_wait(BAR(B_GS + 1 + i), 1);
            fence_async();
            tma4d_store(&P.sU, sb + US_OFF + 10240 - 10240 * i, 80 * db, 0, 8 * i, tb2);
          }
          bulk_commit(); bulk_wait();
          PROF(18);
          release<2>(); signal_flag(&S->flag[(F_U3 + b) * 32], e1);
          PROF(14);
          mbar_wait(BAR(B_SG));
          mbar_arrive(BAR(B_GE)); mbar_arrive_cl(BAR(B_GE), R.wpart());
        }
        __syncwarp();
      }
    } else {
      discretise(H, P, sb, R, tid & 31, e1);
      if (elect_one()) {
        mbar_arrive(BAR(B_LM));
        PROF(348);
        if (b < R.nprep()) {
#pragma unroll 1
          for (int task = b, r = 0; task < 320; task += R.nprep(), r++) {
            mbar_wait(BAR(B_PS + r));
            PROF(320 + 3 * r);
            fence_async();
            tma2d_store(&P.sK, sb + KS_OFF + r * 8192, 64 * (task & 31), 64 * (task >> 5));
            bulk_commit(); bulk_wait();
            PROF(321 + 3 * r);
            release<4>();
            signal_cnt(&S->cnt[(C_KV + (task >> 5)) * 32], 1);
            PROF(322 + 3 * r);
          }
          PROF(41);
        }
        if (has2) {
          mbar_wait(BAR(B_SH));
#pragma unroll 1
          for (int i = 0; i < 8; i++) mbar_arrive_cl(BAR(B_RF0), i & (R.cs() - 1));
        }
#pragma unroll 1
        for (int s = 0, s0 = 0; s < R.nch(); s++) {
          mbar_wait(BAR(B_GS + s));
          fence_async();
          bulk_s2g(S->gt + (size_t)R.ch(s) * SEQ, conv_buf(sb, s) + KC_OFS, 4096); bulk_commit();
          if (s == 1 || s >= R.nch() - GSPL) bulk_wait();
          if (s == 1 || s == min(R.nch() - 1, 3)) mbar_arrive(BAR(B_CD + (s > 1)));
          mbar_arrive_if(BAR(B_SG), s == R.nch() - 1);
          if (s >= R.nch() - GSPL) {
            PROF(45);
            release<8>();
#pragma unroll 1
            for (; s0 <= s; s0++) signal_cnt(&S->cnt[(C_G + R.ch(s0) / 80) * 32], 1);
          }
        }
        PROF(46);
      }
    }
  }
}

typedef CUresult (*EncFn)(CUtensorMap*, CUtensorMapDataType, cuuint32_t, void*, const cuuint64_t*, const cuuint64_t*, const cuuint32_t*,
                          const cuuint32_t*, CUtensorMapInterleave, CUtensorMapSwizzle, CUtensorMapL2promotion, CUtensorMapFloatOOBfill);
bool enc(EncFn f, CUtensorMap* m, const void* base, int rank, const cuuint64_t* dims, const cuuint64_t* strides, const cuuint32_t* box, bool swz,
         bool f32 = false) {
  const cuuint32_t es[5] = {1, 1, 1, 1, 1};
  return f(m, f32 ? CU_TENSOR_MAP_DATA_TYPE_FLOAT32 : CU_TENSOR_MAP_DATA_TYPE_BFLOAT16, rank, const_cast<void*>(base), dims, strides, box, es,
           CU_TENSOR_MAP_INTERLEAVE_NONE, swz ? CU_TENSOR_MAP_SWIZZLE_128B : CU_TENSOR_MAP_SWIZZLE_NONE, CU_TENSOR_MAP_L2_PROMOTION_L2_256B,
           CU_TENSOR_MAP_FLOAT_OOB_FILL_NONE) == CUDA_SUCCESS;
}
void make_roles(Params& P, bool big) {
  for (uint32_t bx = 0; bx < (big ? 120u : 12u); bx++) {
    const uint32_t c = bx >> 3, r = bx & 7, id = big ? bx : 120 + bx;
    const uint32_t vA = c < 12 ? (2 * (c >> 1) + (r >> 2)) | (4 * (c & 1) + (r & 3)) << 4 | (r & 4) << 16 | 4 << 19 | (r ^ 4) << 22
                               : (4 * (c - 12) + (r >> 1)) | (8 + (r & 1)) << 4 | (r & 6) << 16 | 2 << 19 | (r ^ 2) << 22;
    const uint32_t vB = (bx < 10 ? 12 : 13) | bx << 4 | 2 << 19 | (bx & 1) << 22 | (bx & 1) << 26;
    P.role[bx].x = (big ? vA | r << 26 | 1u << 29 : vB) | (id < 128 ? (id & ~7u) | (r >> 1) | (r & 1) << 2 : id) << 8;
    P.role[bx].y = id | (big ? 5 : bx < 8 ? 3 : 4) << 10 | 120 << 13 | 132 << 21 | (big ? 4u : 3u) << 29;
    const uint32_t v = P.role[bx].x, cb = (v >> 4) & 15, rank = (v >> 26) & 7, ubase = (v >> 16) & 7, ugs = (v >> 19) & 7, wp = (v >> 22) & 7;
    const uint32_t wlo = rank > wp, whi = wp != rank ? wlo : 1, wmask = 1u << rank | 1u << wp;
    const uint32_t uj = (rank - ubase) * (!big ? 8 : ugs == 4 ? 5 : 10), sm = big ? (0x7296418530ull >> (4 * cb)) & 15 : bx < 8 ? 4 * (bx & 1) + (bx >> 1) : 15;
    P.role[bx].z = wlo | whi << 1 | wmask << 2 | ((1u << ugs) - 1) << (10 + ubase) | uj << 20 | sm << 25;
    P.role[bx].w = 0;
  }
}
void launch(const Head& H, const Params& P, int grid, int cs, bool dependent) {
  cudaLaunchConfig_t cfg = {};
  cfg.gridDim = grid; cfg.blockDim = 512; cfg.dynamicSmemBytes = SMEM_BYTES; cfg.stream = cudaStreamPerThread;
  cudaLaunchAttribute at[2];
  at[0].id = cudaLaunchAttributeClusterDimension; at[0].val.clusterDim.x = cs; at[0].val.clusterDim.y = 1; at[0].val.clusterDim.z = 1;
  at[1].id = cudaLaunchAttributeProgrammaticStreamSerialization; at[1].val.programmaticStreamSerializationAllowed = 1;
  cfg.attrs = at; cfg.numAttrs = dependent ? 2 : 1;
  cudaLaunchKernelEx(&cfg, fused_kernel, H, P);
}

}

extern "C" void kernel_launch(void* const* d_in, const int* in_sizes, int n_in, void* d_out, int out_size) {
  (void)in_sizes; (void)n_in; (void)out_size;
  typedef const __nv_bfloat16* cb;
  void* fp = nullptr; cudaDriverEntryPointQueryResult qr;
  cudaGetDriverEntryPoint("cuTensorMapEncodeTiled", &fp, cudaEnableDefault, &qr);
  EncFn f = (EncFn)fp;
  Scratch* sp = nullptr;
  cudaGetSymbolAddress((void**)&sp, g_scr);
  void *pu = sp->u, *ph = sp->h, *pgt = sp->gt;
  Params P;
  Head H;
  H.s = sp; H.x = (cb)d_in[0]; H.swap = (uintptr_t)d_in[4] < (uintptr_t)d_in[3] ? 0 : 0x80000000u; H.b0 = (cb)d_in[H.swap ? 3 : 4]; H.b1 = (cb)d_in[H.swap ? 4 : 3];
  for (int i = 0; i < 2; i++) {
    const cuuint64_t d[4] = {640, 8, 2, 80}, s[3] = {1280, (cuuint64_t)((uintptr_t)H.b1 - (uintptr_t)H.b0), 8 * 1280}; const cuuint32_t bx[4] = {64, 8, 2, 4};
    if (enc(f, &P.mB, H.b0, 4, d, s, bx, true)) break;
    cudaMemcpyAsync(sp->bcopy, H.b0, DM * DM * 2, cudaMemcpyDeviceToDevice, cudaStreamPerThread);
    cudaMemcpyAsync(sp->bcopy + DM * DM, H.b1, DM * DM * 2, cudaMemcpyDeviceToDevice, cudaStreamPerThread);
    H.b0 = sp->bcopy; H.b1 = sp->bcopy + DM * DM;
  }
  {
    const cuuint64_t d[5] = {640, 2, 4, 2, 40}, s[4] = {1280, 4 * 1280, 2 * 1280, 16 * 1280}; const cuuint32_t bx[5] = {64, 2, 4, 2, 5};
    enc(f, &P.mC[0], d_in[5], 5, d, s, bx, true); enc(f, &P.mC[1], d_in[6], 5, d, s, bx, true); }
  { const cuuint64_t d[2] = {2048, 640}, s[1] = {4096}; const cuuint32_t bx[2] = {64, 80}; enc(f, &P.mGT, pgt, 2, d, s, bx, true); }
  { const cuuint64_t d[4] = {640, 8, 16, 16}, s[3] = {16 * 1280, 1280, 128 * 1280}; const cuuint32_t bx[4] = {80, 8, 16, 1}, bh[4] = {80, 8, 8, 1};
    enc(f, &P.sU, pu, 4, d, s, bh, false); enc(f, &P.mX, d_in[0], 4, d, s, bx, false); }
  { const cuuint64_t d[2] = {2048, 640}, s[1] = {4096}; const cuuint32_t bx[2] = {64, 64}; enc(f, &P.sK, sp->kv, 2, d, s, bx, true); }
  P.lre = (cb)d_in[1]; P.lim = (cb)d_in[2]; P.cre = (cb)d_in[5]; P.cim = (cb)d_in[6]; P.ldt = (cb)d_in[7]; P.dskip = (cb)d_in[8];
  P.out = (float*)d_out;
  P.k = (cb)d_in[10]; P.v = (cb)d_in[11]; P.shk = (cb)d_in[12]; P.ssmk = (cb)d_in[13]; P.ssmd = (cb)d_in[14];
  cudaFuncSetAttribute(fused_kernel, cudaFuncAttributeMaxDynamicSharedMemorySize, SMEM_BYTES);
  for (int big = 1; big >= 0; big--) {
    const cuuint64_t seg = big ? 40 : 32;
    for (int i = 0; i < 4; i++) {
      const cuuint64_t d[4] = {640, 2, 4, 1024}, s[3] = {1280, seg * 1280, 2 * 1280}; const cuuint32_t bx[4] = {64, 2, 4, !big ? 8u : (i & 1) ? 10u : 5u};
      enc(f, &P.mA[i], i < 2 ? d_in[0] : pu, 4, d, s, bx, true);
    }
    {
      const cuuint64_t d[4] = {1280, 8, 16, 32}, s[3] = {16 * 2560, 2560, 128 * 2560}; const cuuint32_t bx[4] = {64, 8, big ? 2u : 8u, 1};
      enc(f, &P.mH, ph, 4, d, s, bx, true); }
    { const cuuint64_t d[4] = {1280, 2, 4, 2048}, s[3] = {2560, seg * 2560, 2 * 2560}; const cuuint32_t bx[4] = {64, 2, 4, 4};
      enc(f, &P.sH, ph, 4, d, s, bx, true); }
    make_roles(P, big);
    H.base = big ? 0 : 120;
    launch(H, P, big ? 120 : 12, big ? 8 : 2, !big);
  }
}
```

```cpp
#include <cuda_runtime.h>
#include <cuda.h>
#include <cuda_bf16.h>
#include <stdint.h>

namespace {

constexpr int SEQ = 2048, DM = 640;
constexpr int SPIN = 1 << 20;
#define PFAT 99
#define KVDLY 500
#define PFD 1
#define XPFAT 9
#define STAT_AT 6
#define KPFAT 3
#define KPFAT2 5
#define KPF 7
#define HDLY 1900
#define GSPL 2
#define CWAIT 0
#define HDLY0 1900
#define CTAB1 0x96543u
#define NSAT 0
#define SKW 1
#define RIAT 2
#define MIAT 5
#define FPAT 1
#define UPAT 7
#define STAT_AT1 4
#define W4AT 0
#define MBAR 1
#define STG 17
#define STG0 17
#define HWM 0xc09
#define NSDB 4
#define GLATE 6
#define KUP 1
#define XRAT 9
#define ORD 1

struct Scratch {
  uint2 E[2 * 13 * 10 * 8 * 16];
  uint32_t M[3 * 16 * 8 * 256];
  uint2 S[3 * SEQ];
  uint2 RS[80 * 16];
  unsigned flag[512 * 32];
  unsigned cnt[32 * 32];
  unsigned epoch[132 * 8];
  unsigned zero[128];
  unsigned prof[132 * 512];
  __align__(1024)
  __nv_bfloat16 u[SEQ * DM];
  __nv_bfloat16 h[2 * SEQ * 1280];
  __nv_bfloat16 kv[DM * SEQ];
  __nv_bfloat16 gt[DM * SEQ];
  __nv_bfloat16 bcopy[2 * DM * DM];
};
__device__ __align__(1024) Scratch g_scr;
#define PROFC(c, i) do {} while (0)
#define PSEL 1
#define PROF(i) do {} while (0)

constexpr int C_KV = 0, C_G = 10;
constexpr int F_U3 = 0, F_H = 128;

constexpr int R_OFF = 196608, R4_OFF0 = 73728, R4_OFF1 = 122880, H_OFF = 131072, KS_OFF = 131072, CV_OFF = 86272, G_OFF0 = 40960, G_OFF1 = 102400, US_OFF = 98304, XR_OFF = 163840, MX_OFF = 32768;
constexpr int LAM_OFF = 229376, SSM_OFF = LAM_OFF + 1024, BAR_OFF = SSM_OFF + 1344;
constexpr int B_F1 = 0, B_E1 = 10, B_RF0 = 20, B_RF1 = 21, NBAR1 = 22;
constexpr int B_F2 = 22, B_KF = 32, B_GF = 37, B_CD = 38, B_XR = 40, B_ST = 41, B_HD = 42, B_LM = 43, B_E2 = 44, B_GS = 54, B_PS = 59, B_AX = 62, B_SH = 64, B_SG = 69, B_GE = 70, B_EA = 71, B_F3 = 74, NBAR = 84;
__host__ __device__ constexpr int bar_count(int i) { return i < B_E1 ? 1 : i < B_RF0 ? 9 : i < B_F2 ? 8 : i < B_E2 ? 1 : i < B_GS ? 12 : i < B_SH ? 4 : i < B_SG ? 8 : i < B_GE ? 1 : i < B_EA ? 2 : i < B_F3 ? 8 : 1; }
constexpr int MISC_OFF = BAR_OFF + NBAR * 8, SMEM_BYTES = MISC_OFF + 32;
constexpr int KV_PAD = 512, KC_OFS = KV_PAD + 4096, CH_STRIDE = 8960;
__device__ __forceinline__ uint32_t conv_buf(uint32_t sb, int slot) { return sb + CV_OFF + slot * CH_STRIDE; }
constexpr uint64_t tab6(int a, int b, int c, int d, int e, int f, int g, int h, int i, int j) {
  return (uint64_t)a | (uint64_t)b << 6 | (uint64_t)c << 12 | (uint64_t)d << 18 | (uint64_t)e << 24 | (uint64_t)f << 30 | (uint64_t)g << 36 | (uint64_t)h << 42 |
         (uint64_t)i << 48 | (uint64_t)j << 54;
}
constexpr uint64_t WTAB0 = tab6(0, 4, 8, 30, 12, 26, 0, 4, 8, 12), XTAB0 = tab6(40, 45, 50, 34, 16, 21, 40, 45, 50, 16);
constexpr uint64_t WTAB1 = tab6(16, 20, 0, 4, 8, 12, 16, 20, 24, 28), XTAB1 = tab6(40, 45, 50, 32, 40, 45, 50, 32, 40, 45);
constexpr uint32_t DEP0 = 0x4210;

struct Head {
  Scratch* s;
  const __nv_bfloat16 *x, *b0, *b1;
  uint32_t base, swap;
};
struct Params {
  const __nv_bfloat16 *lre, *lim, *ldt, *k, *v, *shk, *cre, *cim, *ssmk, *ssmd, *dskip;
  float* out;
  uint4 role[120];
  CUtensorMap mB, mA[4], mH, mC[2], mGT, mX, sH, sU, sK;
};

__device__ __forceinline__ uint32_t smem_u32(const void* p) { return (uint32_t)__cvta_generic_to_shared(p); }
__device__ __forceinline__ uint32_t opaque(uint32_t x) { uint32_t y; asm volatile("mov.u32 %0, %1;" : "=r"(y) : "r"(x)); return y; }
__device__ __forceinline__ int lane_id() { int y; asm volatile("mov.u32 %0, %%laneid;" : "=r"(y)); return y; }
__device__ __forceinline__ void delay(uint32_t n) {
  asm volatile("{ .reg .pred p; .reg .u32 a, b; mov.u32 a, %%clock; L: mov.u32 b, %%clock; sub.u32 b, b, a; setp.lt.u32 p, b, %0; @p bra.uni L; }" ::"r"(n) : "memory");
}
__device__ __forceinline__ void mbar_init(uint32_t bar, uint32_t cnt) { asm volatile("mbarrier.init.shared::cta.b64 [%0], %1;" ::"r"(bar), "r"(cnt) : "memory"); }
__device__ __forceinline__ void mbar_expect_tx(uint32_t bar, uint32_t bytes) { asm volatile("mbarrier.arrive.expect_tx.shared::cta.b64 _, [%0], %1;" ::"r"(bar), "r"(bytes) : "memory"); }
__device__ __forceinline__ void mbar_arrive(uint32_t bar) { asm volatile("mbarrier.arrive.shared::cta.b64 _, [%0];" ::"r"(bar) : "memory"); }
__device__ __forceinline__ void mbar_arrive_if(uint32_t bar, bool c) {
  asm volatile("{ .reg .pred p; setp.ne.u32 p, %1, 0; @p mbarrier.arrive.shared::cta.b64 _, [%0]; }" ::"r"(bar), "r"((uint32_t)c) : "memory");
}
__device__ __forceinline__ void prefetch_if(const void* p, bool c) { asm volatile("{ .reg .pred p; setp.ne.u32 p, %1, 0; @p prefetch.global.L2 [%0]; }" ::"l"(p), "r"((uint32_t)c)); }
__device__ __forceinline__ void mbar_arrive_cl(uint32_t bar, uint32_t cta) {
  asm volatile("{ .reg .b32 ra; mapa.shared::cluster.u32 ra, %0, %1; mbarrier.arrive.shared::cluster.b64 _, [ra]; }" ::"r"(bar), "r"(cta) : "memory");
}
__device__ __forceinline__ uint32_t mapa(uint32_t a, uint32_t cta) { uint32_t r; asm("mapa.shared::cluster.u32 %0, %1, %2;" : "=r"(r) : "r"(a), "r"(cta)); return r; }
__device__ __forceinline__ void mbar_arrive_at(uint32_t ra) { asm volatile("mbarrier.arrive.shared::cluster.b64 _, [%0];" ::"r"(ra) : "memory"); }
__device__ __forceinline__ void mbar_wait(uint32_t bar, uint32_t parity = 0) {
  asm volatile("{ .reg .pred p; .reg .u32 c; mov.u32 c, 0;\n"
               "W: mbarrier.try_wait.parity.shared::cta.b64 p, [%0], %1; @p bra.uni D;\n"
               "add.u32 c, c, 1; setp.lt.u32 p, c, 0x100000; @p bra.uni W;\nD: }" ::"r"(bar), "r"(parity) : "memory");
}
__device__ __forceinline__ bool elect_one() { uint32_t p; asm volatile("{ .reg .pred P; elect.sync _|P, 0xffffffff; selp.u32 %0,1,0,P; }" : "=r"(p)); return p; }
__device__ __forceinline__ void bar_sync(int id, int n) { __syncwarp(); asm volatile("bar.sync %0, %1;" ::"r"(id), "r"(n) : "memory"); }
__device__ __forceinline__ void tma2d(uint32_t dst, const CUtensorMap* m, int c0, int c1, uint32_t bar) {
  asm volatile("cp.async.bulk.tensor.2d.shared::cluster.global.mbarrier::complete_tx::bytes [%0], [%1, {%3,%4}], [%2];"
               ::"r"(dst), "l"(m), "r"(bar), "r"(c0), "r"(c1) : "memory");
}
__device__ __forceinline__ void tma5d(uint32_t dst, const CUtensorMap* m, int c0, int c4, uint32_t bar) {
  asm volatile("cp.async.bulk.tensor.5d.shared::cluster.global.mbarrier::complete_tx::bytes [%0], [%1, {%3,%5,%5,%5,%4}], [%2];"
               ::"r"(dst), "l"(m), "r"(bar), "r"(c0), "r"(c4), "r"(0) : "memory");
}
__device__ __forceinline__ void tma4d(uint32_t dst, const CUtensorMap* m, int c0, int c3, uint32_t bar) {
  asm volatile("cp.async.bulk.tensor.4d.shared::cluster.global.mbarrier::complete_tx::bytes [%0], [%1, {%3,%5,%5,%4}], [%2];"
               ::"r"(dst), "l"(m), "r"(bar), "r"(c0), "r"(c3), "r"(0) : "memory");
}
__device__ __forceinline__ void tma4d_mc(uint32_t dst, const CUtensorMap* m, int c0, int c1, int c2, int c3, uint32_t bar, uint32_t mask) {
  asm volatile("cp.async.bulk.tensor.4d.shared::cluster.global.mbarrier::complete_tx::bytes.multicast::cluster [%0], [%1, {%3,%4,%5,%6}], [%2], %7;"
               ::"r"(dst), "l"(m), "r"(bar), "r"(c0), "r"(c1), "r"(c2), "r"(c3), "h"((uint16_t)mask) : "memory");
}
__device__ __forceinline__ void bulk_g2s(uint32_t dst, const void* src, uint32_t bytes, uint32_t bar) {
  asm volatile("cp.async.bulk.shared::cluster.global.mbarrier::complete_tx::bytes [%0], [%1], %2, [%3];" ::"r"(dst), "l"(src), "r"(bytes), "r"(bar) : "memory");
}
__device__ __forceinline__ void tma4d_store(const CUtensorMap* m, uint32_t src, int c0, int c1, int c2, int c3) {
  asm volatile("cp.async.bulk.tensor.4d.global.shared::cta.bulk_group [%0, {%2,%3,%4,%5}], [%1];" ::"l"(m), "r"(src), "r"(c0), "r"(c1), "r"(c2), "r"(c3) : "memory");
}
__device__ __forceinline__ void tma2d_store(const CUtensorMap* m, uint32_t src, int c0, int c1) {
  asm volatile("cp.async.bulk.tensor.2d.global.shared::cta.bulk_group [%0, {%2,%3}], [%1];" ::"l"(m), "r"(src), "r"(c0), "r"(c1) : "memory");
}
__device__ __forceinline__ void bulk_s2g(void* dst, uint32_t src, uint32_t bytes) {
  asm volatile("cp.async.bulk.global.shared::cta.bulk_group [%0], [%1], %2;" ::"l"(dst), "r"(src), "r"(bytes) : "memory");
}
__device__ __forceinline__ void bulk_commit() { asm volatile("cp.async.bulk.commit_group;" ::: "memory"); }
__device__ __forceinline__ void bulk_wait() { asm volatile("cp.async.bulk.wait_group 0;" ::: "memory"); }
__device__ __forceinline__ void fence_async() { asm volatile("fence.proxy.async.shared::cta;" ::: "memory"); }
__device__ __forceinline__ void prefetch_l2(const void* src, uint32_t bytes) { asm volatile("cp.async.bulk.prefetch.L2.global [%0], %1;" ::"l"(src), "r"(bytes) : "memory"); }
__device__ __forceinline__ void prefetch_map(const CUtensorMap* m) { asm volatile("prefetch.tensormap [%0];" ::"l"(m) : "memory"); }
__device__ __forceinline__ void wg_fence() { __syncwarp(); asm volatile("wgmma.fence.sync.aligned;" ::: "memory"); }
__device__ __forceinline__ void wg_commit() { asm volatile("wgmma.commit_group.sync.aligned;" ::: "memory"); }
template <int N> __device__ __forceinline__ void wg_wait() { asm volatile("wgmma.wait_group.sync.aligned %0;" ::"n"(N) : "memory"); }
template <int N> __device__ __forceinline__ void fence_regs(float (&d)[N]) {
#pragma unroll
  for (int i = 0; i < N; i++) asm volatile("" : "+f"(d[i])::"memory");
}
__device__ __forceinline__ uint64_t make_desc(uint32_t addr, uint32_t lbo, uint32_t sbo, uint32_t swz) {
  return (uint64_t)((addr & 0x3FFFF) >> 4) | ((uint64_t)(lbo >> 4) << 16) | ((uint64_t)(sbo >> 4) << 32) | ((uint64_t)swz << 62);
}
__device__ __forceinline__ uint32_t ldg1(const void* p) { uint32_t v; asm volatile("ld.global.nc.u32 %0,[%1];" : "=r"(v) : "l"(p)); return v; }
__device__ __forceinline__ uint32_t lds32(uint32_t a) { uint32_t v; asm volatile("ld.shared.u32 %0,[%1];" : "=r"(v) : "r"(a)); return v; }
__device__ __forceinline__ unsigned ld_rlx(const unsigned* p) { unsigned v; asm volatile("ld.relaxed.gpu.global.u32 %0,[%1];" : "=r"(v) : "l"(p) : "memory"); return v; }
__device__ __forceinline__ uint4 ld_rlx4(const void* p) {
  uint4 v; asm volatile("ld.relaxed.gpu.global.v4.u32 {%0,%1,%2,%3},[%4];" : "=r"(v.x), "=r"(v.y), "=r"(v.z), "=r"(v.w) : "l"(p) : "memory"); return v;
}
__device__ __forceinline__ uint2 ld_rlx2(const void* p) { uint2 v; asm volatile("ld.relaxed.gpu.global.v2.u32 {%0,%1},[%2];" : "=r"(v.x), "=r"(v.y) : "l"(p) : "memory"); return v; }
__device__ __forceinline__ void st_rlx2(void* p, uint32_t a, uint32_t b) { asm volatile("st.relaxed.gpu.global.v2.u32 [%0],{%1,%2};" ::"l"(p), "r"(a), "r"(b) : "memory"); }
__device__ __forceinline__ void st_rlx(void* p, uint32_t a) { asm volatile("st.relaxed.gpu.global.u32 [%0],%1;" ::"l"(p), "r"(a) : "memory"); }
#define PUB 15
template <int SITE> __device__ __forceinline__ void release() { if (PUB & SITE) asm volatile("fence.release.gpu;" ::: "memory"); }
__device__ __forceinline__ void signal_flag(unsigned* p, unsigned val) { asm volatile("st.relaxed.gpu.global.u32 [%0],%1;" ::"l"(p), "r"(val) : "memory"); }
__device__ __forceinline__ void signal_cnt(unsigned* p, unsigned n) { asm volatile("red.relaxed.gpu.global.add.u32 [%0],%1;" ::"l"(p), "r"(n) : "memory"); }
__device__ __forceinline__ void wait_flags(const unsigned* p, unsigned val, uint32_t need, uint32_t& ready) {
#pragma unroll 1
  for (int it = 0; (ready & need) != need && it < SPIN; it++) ready = __ballot_sync(0xffffffff, ld_rlx(p) == val);
}
__device__ __forceinline__ void wait_cnt(const unsigned* p, unsigned tgt) {
  asm volatile("{ .reg .pred p; .reg .u32 c; .reg .s32 v; mov.u32 c, 0;\n"
               "W: ld.relaxed.gpu.global.u32 v, [%0]; sub.s32 v, v, %1; setp.ge.s32 p, v, 0; @p bra.uni D;\n"
               "add.u32 c, c, 1; setp.lt.u32 p, c, 0x100000; @p bra.uni W;\nD: }" ::"l"(p), "r"(tgt) : "memory");
}
__device__ __forceinline__ uint32_t pack_bf(float lo, float hi) { uint32_t r; asm("cvt.rn.bf16x2.f32 %0, %1, %2;" : "=r"(r) : "f"(hi), "f"(lo)); return r; }
__device__ __forceinline__ float bf_lo(uint32_t v) { return __uint_as_float(v << 16); }
__device__ __forceinline__ float bf_hi(uint32_t v) { return __uint_as_float(v & 0xffff0000u); }
__device__ __forceinline__ float bf_rn(float x) { return __bfloat162float(__float2bfloat16_rn(x)); }
__device__ __forceinline__ float frcp(float x) { float r; asm("rcp.approx.ftz.f32 %0,%1;" : "=f"(r) : "f"(x)); return r; }
__device__ __forceinline__ float fsqrt(float x) { float r; asm("sqrt.approx.ftz.f32 %0,%1;" : "=f"(r) : "f"(x)); return r; }
__device__ __forceinline__ float frsqrt(float x) { float r; asm("rsqrt.approx.ftz.f32 %0,%1;" : "=f"(r) : "f"(x)); return r; }
__device__ __forceinline__ uint32_t hmul2(uint32_t a, uint32_t b) { uint32_t r; asm("mul.rn.bf16x2 %0,%1,%2;" : "=r"(r) : "r"(a), "r"(b)); return r; }
__device__ __forceinline__ uint32_t hfma2(uint32_t a, uint32_t b, uint32_t c) { uint32_t r; asm("fma.rn.bf16x2 %0,%1,%2,%3;" : "=r"(r) : "r"(a), "r"(b), "r"(c)); return r; }
__device__ __forceinline__ float2 cmul(float2 a, float2 b) { return make_float2(a.x * b.x - a.y * b.y, a.x * b.y + a.y * b.x); }
__device__ __forceinline__ float2 cfma(float2 a, float2 b, float2 c) {
  return make_float2(fmaf(a.x, b.x, fmaf(-a.y, b.y, c.x)), fmaf(a.x, b.y, fmaf(a.y, b.x, c.y)));
}
__device__ __forceinline__ uint32_t tagf(float v, uint32_t tag) { return (__float_as_uint(v) & ~1u) | tag; }
__device__ __forceinline__ float untag(uint32_t v) { return __uint_as_float(v & ~1u); }
__device__ __forceinline__ bool untagged(const uint4& v, uint32_t tag) { return (((v.x ^ tag) | (v.y ^ tag) | (v.z ^ tag) | (v.w ^ tag)) & 1) != 0; }
__device__ __forceinline__ bool untagged(const uint2& v, uint32_t tag) { return (((v.x ^ tag) | (v.y ^ tag)) & 1) != 0; }
__device__ __forceinline__ float2 lam_bar(float lr, float li, float ldt) {
  float dt = bf_rn(expf(ldt)); float e = expf(dt * lr), s, c; sincospif(dt * li * 0.31830988618379067f, &s, &c); return make_float2(e * c, e * s);
}

__device__ __forceinline__ int conv_ch(uint32_t c, int s) { return s * ((c >> 21) & 255) + (c & 255) - (s >= (int)(c >> 29) ? 8 : 0); }
struct Role {
  uint32_t v, c, p;
  __device__ __forceinline__ int tb() const { return v & 15; }
  __device__ __forceinline__ int cb() const { return (v >> 4) & 15; }
  __device__ __forceinline__ int b() const { return (v >> 8) & 255; }
  __device__ __forceinline__ int ubase() const { return (v >> 16) & 7; }
  __device__ __forceinline__ int ugs() const { return (v >> 19) & 7; }
  __device__ __forceinline__ int wpart() const { return (v >> 22) & 7; }
  __device__ __forceinline__ int rank() const { return (v >> 26) & 7; }
  __device__ __forceinline__ int cs() const { return (v >> 29) ? 8 : 2; }
  __device__ __forceinline__ int ch(int s) const { return conv_ch(c, s); }
  __device__ __forceinline__ int wlo() const { return p & 1; }
  __device__ __forceinline__ int whi() const { return (p >> 1) & 1; }
  __device__ __forceinline__ uint32_t wmask() const { return (p >> 2) & 255; }
  __device__ __forceinline__ uint32_t umask() const { return (p >> 10) & 255; }
  __device__ __forceinline__ int uj() const { return (p >> 20) & 31; }
  __device__ __forceinline__ int sm() const { return (p >> 25) & 15; }
  __device__ __forceinline__ int nch() const { return (c >> 10) & 7; }
  __device__ __forceinline__ int nprep() const { return (c >> 13) & 255; }
};

__device__ __forceinline__ void wgmma_ss80(float (&d)[40], uint64_t da, uint64_t db, int sd){
  asm volatile("{ .reg .pred p; setp.ne.b32 p, %42, 0;\n"
   "wgmma.mma_async.sync.aligned.m64n80k16.f32.bf16.bf16 {%0, %1, %2, %3, %4, %5, %6, %7, %8, %9, %10, %11, %12, %13, %14, %15, %16, %17, %18, %19, %20, %21, %22, %23, %24, %25, %26, %27, %28, %29, %30, %31, %32, %33, %34, %35, %36, %37, %38, %39}, %40, %41, p, 1, 1, 0, 0; }\n"
   : "+f"(d[0]), "+f"(d[1]), "+f"(d[2]), "+f"(d[3]), "+f"(d[4]), "+f"(d[5]), "+f"(d[6]), "+f"(d[7]), "+f"(d[8]), "+f"(d[9]), "+f"(d[10]), "+f"(d[11]), "+f"(d[12]), "+f"(d[13]), "+f"(d[14]), "+f"(d[15]), "+f"(d[16]), "+f"(d[17]), "+f"(d[18]), "+f"(d[19]), "+f"(d[20]), "+f"(d[21]), "+f"(d[22]), "+f"(d[23]), "+f"(d[24]), "+f"(d[25]), "+f"(d[26]), "+f"(d[27]), "+f"(d[28]), "+f"(d[29]), "+f"(d[30]), "+f"(d[31]), "+f"(d[32]), "+f"(d[33]), "+f"(d[34]), "+f"(d[35]), "+f"(d[36]), "+f"(d[37]), "+f"(d[38]), "+f"(d[39]) : "l"(da), "l"(db), "r"(sd));
}
__device__ __forceinline__ void wgmma_ss160(float (&d)[80], uint64_t da, uint64_t db, int sd){
  asm volatile("{ .reg .pred p; setp.ne.b32 p, %82, 0;\n"
   "wgmma.mma_async.sync.aligned.m64n160k16.f32.bf16.bf16 {%0, %1, %2, %3, %4, %5, %6, %7, %8, %9, %10, %11, %12, %13, %14, %15, %16, %17, %18, %19, %20, %21, %22, %23, %24, %25, %26, %27, %28, %29, %30, %31, %32, %33, %34, %35, %36, %37, %38, %39, %40, %41, %42, %43, %44, %45, %46, %47, %48, %49, %50, %51, %52, %53, %54, %55, %56, %57, %58, %59, %60, %61, %62, %63, %64, %65, %66, %67, %68, %69, %70, %71, %72, %73, %74, %75, %76, %77, %78, %79}, %80, %81, p, 1, 1, 0, 0; }\n"
   : "+f"(d[0]), "+f"(d[1]), "+f"(d[2]), "+f"(d[3]), "+f"(d[4]), "+f"(d[5]), "+f"(d[6]), "+f"(d[7]), "+f"(d[8]), "+f"(d[9]), "+f"(d[10]), "+f"(d[11]), "+f"(d[12]), "+f"(d[13]), "+f"(d[14]), "+f"(d[15]), "+f"(d[16]), "+f"(d[17]), "+f"(d[18]), "+f"(d[19]), "+f"(d[20]), "+f"(d[21]), "+f"(d[22]), "+f"(d[23]), "+f"(d[24]), "+f"(d[25]), "+f"(d[26]), "+f"(d[27]), "+f"(d[28]), "+f"(d[29]), "+f"(d[30]), "+f"(d[31]), "+f"(d[32]), "+f"(d[33]), "+f"(d[34]), "+f"(d[35]), "+f"(d[36]), "+f"(d[37]), "+f"(d[38]), "+f"(d[39]), "+f"(d[40]), "+f"(d[41]), "+f"(d[42]), "+f"(d[43]), "+f"(d[44]), "+f"(d[45]), "+f"(d[46]), "+f"(d[47]), "+f"(d[48]), "+f"(d[49]), "+f"(d[50]), "+f"(d[51]), "+f"(d[52]), "+f"(d[53]), "+f"(d[54]), "+f"(d[55]), "+f"(d[56]), "+f"(d[57]), "+f"(d[58]), "+f"(d[59]), "+f"(d[60]), "+f"(d[61]), "+f"(d[62]), "+f"(d[63]), "+f"(d[64]), "+f"(d[65]), "+f"(d[66]), "+f"(d[67]), "+f"(d[68]), "+f"(d[69]), "+f"(d[70]), "+f"(d[71]), "+f"(d[72]), "+f"(d[73]), "+f"(d[74]), "+f"(d[75]), "+f"(d[76]), "+f"(d[77]), "+f"(d[78]), "+f"(d[79]) : "l"(da), "l"(db), "r"(sd));
}
template<int N> __device__ __forceinline__ void wgmma_rs(float (&d)[N/2], uint32_t a0, uint32_t a1, uint32_t a2, uint32_t a3, uint64_t db, int sd);
template<> __device__ __forceinline__ void wgmma_rs<16>(float (&d)[8], uint32_t a0, uint32_t a1, uint32_t a2, uint32_t a3, uint64_t db, int sd){
  asm volatile("{ .reg .pred p; setp.ne.b32 p, %13, 0;\n"
   "wgmma.mma_async.sync.aligned.m64n16k16.f32.bf16.bf16 {%0, %1, %2, %3, %4, %5, %6, %7}, {%8,%9,%10,%11}, %12, p, 1, 1, 0; }\n"
   : "+f"(d[0]), "+f"(d[1]), "+f"(d[2]), "+f"(d[3]), "+f"(d[4]), "+f"(d[5]), "+f"(d[6]), "+f"(d[7]) : "r"(a0), "r"(a1), "r"(a2), "r"(a3), "l"(db), "r"(sd));
}
template<> __device__ __forceinline__ void wgmma_rs<32>(float (&d)[16], uint32_t a0, uint32_t a1, uint32_t a2, uint32_t a3, uint64_t db, int sd){
  asm volatile("{ .reg .pred p; setp.ne.b32 p, %21, 0;\n"
   "wgmma.mma_async.sync.aligned.m64n32k16.f32.bf16.bf16 {%0, %1, %2, %3, %4, %5, %6, %7, %8, %9, %10, %11, %12, %13, %14, %15}, {%16,%17,%18,%19}, %20, p, 1, 1, 0; }\n"
   : "+f"(d[0]), "+f"(d[1]), "+f"(d[2]), "+f"(d[3]), "+f"(d[4]), "+f"(d[5]), "+f"(d[6]), "+f"(d[7]), "+f"(d[8]), "+f"(d[9]), "+f"(d[10]), "+f"(d[11]), "+f"(d[12]), "+f"(d[13]), "+f"(d[14]), "+f"(d[15]) : "r"(a0), "r"(a1), "r"(a2), "r"(a3), "l"(db), "r"(sd));
}
template<> __device__ __forceinline__ void wgmma_rs<48>(float (&d)[24], uint32_t a0, uint32_t a1, uint32_t a2, uint32_t a3, uint64_t db, int sd){
  asm volatile("{ .reg .pred p; setp.ne.b32 p, %29, 0;\n"
   "wgmma.mma_async.sync.aligned.m64n48k16.f32.bf16.bf16 {%0, %1, %2, %3, %4, %5, %6, %7, %8, %9, %10, %11, %12, %13, %14, %15, %16, %17, %18, %19, %20, %21, %22, %23}, {%24,%25,%26,%27}, %28, p, 1, 1, 0; }\n"
   : "+f"(d[0]), "+f"(d[1]), "+f"(d[2]), "+f"(d[3]), "+f"(d[4]), "+f"(d[5]), "+f"(d[6]), "+f"(d[7]), "+f"(d[8]), "+f"(d[9]), "+f"(d[10]), "+f"(d[11]), "+f"(d[12]), "+f"(d[13]), "+f"(d[14]), "+f"(d[15]), "+f"(d[16]), "+f"(d[17]), "+f"(d[18]), "+f"(d[19]), "+f"(d[20]), "+f"(d[21]), "+f"(d[22]), "+f"(d[23]) : "r"(a0), "r"(a1), "r"(a2), "r"(a3), "l"(db), "r"(sd));
}
template<> __device__ __forceinline__ void wgmma_rs<64>(float (&d)[32], uint32_t a0, uint32_t a1, uint32_t a2, uint32_t a3, uint64_t db, int sd){
  asm volatile("{ .reg .pred p; setp.ne.b32 p, %37, 0;\n"
   "wgmma.mma_async.sync.aligned.m64n64k16.f32.bf16.bf16 {%0, %1, %2, %3, %4, %5, %6, %7, %8, %9, %10, %11, %12, %13, %14, %15, %16, %17, %18, %19, %20, %21, %22, %23, %24, %25, %26, %27, %28, %29, %30, %31}, {%32,%33,%34,%35}, %36, p, 1, 1, 0; }\n"
   : "+f"(d[0]), "+f"(d[1]), "+f"(d[2]), "+f"(d[3]), "+f"(d[4]), "+f"(d[5]), "+f"(d[6]), "+f"(d[7]), "+f"(d[8]), "+f"(d[9]), "+f"(d[10]), "+f"(d[11]), "+f"(d[12]), "+f"(d[13]), "+f"(d[14]), "+f"(d[15]), "+f"(d[16]), "+f"(d[17]), "+f"(d[18]), "+f"(d[19]), "+f"(d[20]), "+f"(d[21]), "+f"(d[22]), "+f"(d[23]), "+f"(d[24]), "+f"(d[25]), "+f"(d[26]), "+f"(d[27]), "+f"(d[28]), "+f"(d[29]), "+f"(d[30]), "+f"(d[31]) : "r"(a0), "r"(a1), "r"(a2), "r"(a3), "l"(db), "r"(sd));
}
template<> __device__ __forceinline__ void wgmma_rs<80>(float (&d)[40], uint32_t a0, uint32_t a1, uint32_t a2, uint32_t a3, uint64_t db, int sd){
  asm volatile("{ .reg .pred p; setp.ne.b32 p, %45, 0;\n"
   "wgmma.mma_async.sync.aligned.m64n80k16.f32.bf16.bf16 {%0, %1, %2, %3, %4, %5, %6, %7, %8, %9, %10, %11, %12, %13, %14, %15, %16, %17, %18, %19, %20, %21, %22, %23, %24, %25, %26, %27, %28, %29, %30, %31, %32, %33, %34, %35, %36, %37, %38, %39}, {%40,%41,%42,%43}, %44, p, 1, 1, 0; }\n"
   : "+f"(d[0]), "+f"(d[1]), "+f"(d[2]), "+f"(d[3]), "+f"(d[4]), "+f"(d[5]), "+f"(d[6]), "+f"(d[7]), "+f"(d[8]), "+f"(d[9]), "+f"(d[10]), "+f"(d[11]), "+f"(d[12]), "+f"(d[13]), "+f"(d[14]), "+f"(d[15]), "+f"(d[16]), "+f"(d[17]), "+f"(d[18]), "+f"(d[19]), "+f"(d[20]), "+f"(d[21]), "+f"(d[22]), "+f"(d[23]), "+f"(d[24]), "+f"(d[25]), "+f"(d[26]), "+f"(d[27]), "+f"(d[28]), "+f"(d[29]), "+f"(d[30]), "+f"(d[31]), "+f"(d[32]), "+f"(d[33]), "+f"(d[34]), "+f"(d[35]), "+f"(d[36]), "+f"(d[37]), "+f"(d[38]), "+f"(d[39]) : "r"(a0), "r"(a1), "r"(a2), "r"(a3), "l"(db), "r"(sd));
}
template<> __device__ __forceinline__ void wgmma_rs<96>(float (&d)[48], uint32_t a0, uint32_t a1, uint32_t a2, uint32_t a3, uint64_t db, int sd){
  asm volatile("{ .reg .pred p; setp.ne.b32 p, %53, 0;\n"
   "wgmma.mma_async.sync.aligned.m64n96k16.f32.bf16.bf16 {%0, %1, %2, %3, %4, %5, %6, %7, %8, %9, %10, %11, %12, %13, %14, %15, %16, %17, %18, %19, %20, %21, %22, %23, %24, %25, %26, %27, %28, %29, %30, %31, %32, %33, %34, %35, %36, %37, %38, %39, %40, %41, %42, %43, %44, %45, %46, %47}, {%48,%49,%50,%51}, %52, p, 1, 1, 0; }\n"
   : "+f"(d[0]), "+f"(d[1]), "+f"(d[2]), "+f"(d[3]), "+f"(d[4]), "+f"(d[5]), "+f"(d[6]), "+f"(d[7]), "+f"(d[8]), "+f"(d[9]), "+f"(d[10]), "+f"(d[11]), "+f"(d[12]), "+f"(d[13]), "+f"(d[14]), "+f"(d[15]), "+f"(d[16]), "+f"(d[17]), "+f"(d[18]), "+f"(d[19]), "+f"(d[20]), "+f"(d[21]), "+f"(d[22]), "+f"(d[23]), "+f"(d[24]), "+f"(d[25]), "+f"(d[26]), "+f"(d[27]), "+f"(d[28]), "+f"(d[29]), "+f"(d[30]), "+f"(d[31]), "+f"(d[32]), "+f"(d[33]), "+f"(d[34]), "+f"(d[35]), "+f"(d[36]), "+f"(d[37]), "+f"(d[38]), "+f"(d[39]), "+f"(d[40]), "+f"(d[41]), "+f"(d[42]), "+f"(d[43]), "+f"(d[44]), "+f"(d[45]), "+f"(d[46]), "+f"(d[47]) : "r"(a0), "r"(a1), "r"(a2), "r"(a3), "l"(db), "r"(sd));
}
template<> __device__ __forceinline__ void wgmma_rs<112>(float (&d)[56], uint32_t a0, uint32_t a1, uint32_t a2, uint32_t a3, uint64_t db, int sd){
  asm volatile("{ .reg .pred p; setp.ne.b32 p, %61, 0;\n"
   "wgmma.mma_async.sync.aligned.m64n112k16.f32.bf16.bf16 {%0, %1, %2, %3, %4, %5, %6, %7, %8, %9, %10, %11, %12, %13, %14, %15, %16, %17, %18, %19, %20, %21, %22, %23, %24, %25, %26, %27, %28, %29, %30, %31, %32, %33, %34, %35, %36, %37, %38, %39, %40, %41, %42, %43, %44, %45, %46, %47, %48, %49, %50, %51, %52, %53, %54, %55}, {%56,%57,%58,%59}, %60, p, 1, 1, 0; }\n"
   : "+f"(d[0]), "+f"(d[1]), "+f"(d[2]), "+f"(d[3]), "+f"(d[4]), "+f"(d[5]), "+f"(d[6]), "+f"(d[7]), "+f"(d[8]), "+f"(d[9]), "+f"(d[10]), "+f"(d[11]), "+f"(d[12]), "+f"(d[13]), "+f"(d[14]), "+f"(d[15]), "+f"(d[16]), "+f"(d[17]), "+f"(d[18]), "+f"(d[19]), "+f"(d[20]), "+f"(d[21]), "+f"(d[22]), "+f"(d[23]), "+f"(d[24]), "+f"(d[25]), "+f"(d[26]), "+f"(d[27]), "+f"(d[28]), "+f"(d[29]), "+f"(d[30]), "+f"(d[31]), "+f"(d[32]), "+f"(d[33]), "+f"(d[34]), "+f"(d[35]), "+f"(d[36]), "+f"(d[37]), "+f"(d[38]), "+f"(d[39]), "+f"(d[40]), "+f"(d[41]), "+f"(d[42]), "+f"(d[43]), "+f"(d[44]), "+f"(d[45]), "+f"(d[46]), "+f"(d[47]), "+f"(d[48]), "+f"(d[49]), "+f"(d[50]), "+f"(d[51]), "+f"(d[52]), "+f"(d[53]), "+f"(d[54]), "+f"(d[55]) : "r"(a0), "r"(a1), "r"(a2), "r"(a3), "l"(db), "r"(sd));
}
template<> __device__ __forceinline__ void wgmma_rs<128>(float (&d)[64], uint32_t a0, uint32_t a1, uint32_t a2, uint32_t a3, uint64_t db, int sd){
  asm volatile("{ .reg .pred p; setp.ne.b32 p, %69, 0;\n"
   "wgmma.mma_async.sync.aligned.m64n128k16.f32.bf16.bf16 {%0, %1, %2, %3, %4, %5, %6, %7, %8, %9, %10, %11, %12, %13, %14, %15, %16, %17, %18, %19, %20, %21, %22, %23, %24, %25, %26, %27, %28, %29, %30, %31, %32, %33, %34, %35, %36, %37, %38, %39, %40, %41, %42, %43, %44, %45, %46, %47, %48, %49, %50, %51, %52, %53, %54, %55, %56, %57, %58, %59, %60, %61, %62, %63}, {%64,%65,%66,%67}, %68, p, 1, 1, 0; }\n"
   : "+f"(d[0]), "+f"(d[1]), "+f"(d[2]), "+f"(d[3]), "+f"(d[4]), "+f"(d[5]), "+f"(d[6]), "+f"(d[7]), "+f"(d[8]), "+f"(d[9]), "+f"(d[10]), "+f"(d[11]), "+f"(d[12]), "+f"(d[13]), "+f"(d[14]), "+f"(d[15]), "+f"(d[16]), "+f"(d[17]), "+f"(d[18]), "+f"(d[19]), "+f"(d[20]), "+f"(d[21]), "+f"(d[22]), "+f"(d[23]), "+f"(d[24]), "+f"(d[25]), "+f"(d[26]), "+f"(d[27]), "+f"(d[28]), "+f"(d[29]), "+f"(d[30]), "+f"(d[31]), "+f"(d[32]), "+f"(d[33]), "+f"(d[34]), "+f"(d[35]), "+f"(d[36]), "+f"(d[37]), "+f"(d[38]), "+f"(d[39]), "+f"(d[40]), "+f"(d[41]), "+f"(d[42]), "+f"(d[43]), "+f"(d[44]), "+f"(d[45]), "+f"(d[46]), "+f"(d[47]), "+f"(d[48]), "+f"(d[49]), "+f"(d[50]), "+f"(d[51]), "+f"(d[52]), "+f"(d[53]), "+f"(d[54]), "+f"(d[55]), "+f"(d[56]), "+f"(d[57]), "+f"(d[58]), "+f"(d[59]), "+f"(d[60]), "+f"(d[61]), "+f"(d[62]), "+f"(d[63]) : "r"(a0), "r"(a1), "r"(a2), "r"(a3), "l"(db), "r"(sd));
}

#define BAR(i) (bars + 8u * (uint32_t)(i))

template <int G> __device__ __forceinline__ void conv_frags(uint32_t (&a)[12], uint32_t abase) {
#pragma unroll
  for (int i = 0; i < 12; i++) a[i] = lds32(abase + (G * 4 + i / 3) * 128 + (i % 3) * 4);
}
__device__ __forceinline__ void kv_prefetch(const __nv_bfloat16* pf, int task) { prefetch_if(pf + 64 * (task & 31) * DM + 64 * (task >> 5), task < 320); }
__device__ __forceinline__ void kv_load(const Params& P, Scratch* S, int task, int tid, uint32_t (&k_)[19], uint32_t (&v_)[16], uint4& sk) {
  const int row = 64 * (task & 31) + 16 * (tid >> 5), ch = 64 * (task >> 5) + 2 * (tid & 31);
  const uint32_t* kp = (const uint32_t*)(P.k + (size_t)row * DM + ch);
  const uint32_t* vp = (const uint32_t*)(P.v + (size_t)row * DM + ch);
  const uint32_t* hp = row > 0 ? kp - 3 * (DM / 2) : S->zero;
  const int hs = row > 0 ? DM / 2 : 0;
  asm volatile("ld.global.nc.v4.u32 {%0,%1,%2,%3},[%4];" : "=r"(sk.x), "=r"(sk.y), "=r"(sk.z), "=r"(sk.w) : "l"(P.shk + ch * 4));
#pragma unroll
  for (int i = 0; i < 3; i++) k_[i] = ldg1(hp + i * hs);
#pragma unroll
  for (int i = 0; i < 16; i++) { k_[i + 3] = ldg1(kp + i * (DM / 2)); v_[i] = ldg1(vp + i * (DM / 2)); }
}
template <int SH> __device__ __forceinline__ void xb_prefetch(const Head& H, int id, int tid, int c0) {
  const int ri = tid >> SH, rr = 11 * id + ri - 16;
  const __nv_bfloat16* p = ri < 16 ? H.x + (size_t)(16 * min(id, 127) + ri) * DM : (rr < DM ? H.b0 : H.b1 - DM * DM) + (size_t)rr * DM;
  prefetch_if(p + c0 + 64 * (tid & ((1 << SH) - 1)), ri < 16 || (ri < 27 && rr < 2 * DM));
}
__device__ __forceinline__ uint4 ldg4(const void* p) { uint4 v; asm volatile("ld.global.nc.v4.u32 {%0,%1,%2,%3},[%4];" : "=r"(v.x), "=r"(v.y), "=r"(v.z), "=r"(v.w) : "l"(p)); return v; }
__device__ __forceinline__ uint4 lds4(uint32_t a) { uint4 v; asm volatile("ld.shared.v4.u32 {%0,%1,%2,%3},[%4];" : "=r"(v.x), "=r"(v.y), "=r"(v.z), "=r"(v.w) : "r"(a) : "memory"); return v; }
__device__ __forceinline__ void discretise(const Head& H, const Params& P, uint32_t sb, Role R, int lane, uint32_t e1) {
  const uint32_t dn = __ldg((const unsigned short*)P.ssmd + min(conv_ch(R.c, (lane + 7) & 7), DM - 1));
  const int c = 32 * min(R.cb(), 9) + lane;
  const uint32_t lr2 = ldg1(P.lre + 2 * c), li2 = ldg1(P.lim + 2 * c), ld2 = ldg1(P.ldt + 2 * c);
  asm volatile("st.shared.u32 [%0],%1;" ::"r"(sb + MISC_OFF + 4 * (lane & 7)), "r"((lane & 7) ? dn : e1) : "memory");
#pragma unroll 1
  for (int i = 0; i < 2; i++) {
    const float lr = bf_hi(lr2 << (16 - 16 * i)), li = bf_hi(li2 << (16 - 16 * i));
    const float2 lb = lam_bar(lr, li, bf_hi(ld2 << (16 - 16 * i)));
    const float nx = lb.x - 1.f, ny = lb.y, inv = 2.f * frcp(lr * lr + li * li), cx = (nx * lr + ny * li) * inv, cy = (ny * lr - nx * li) * inv;
    const bool sw = !H.swap;
    asm volatile("st.shared.v4.f32 [%0],{%1,%2,%3,%4};" ::"r"(sb + LAM_OFF + 32 * lane + 16 * i), "f"(lb.x), "f"(sw ? -lb.y : lb.y), "f"(sw ? -cy : cx), "f"(sw ? cx : -cy) : "memory");
  }
  __syncwarp();
}
__device__ __forceinline__ void aux_prep(const Head& H, const Params& P, uint32_t sb, Role R, int tid, long long t_start) {
  Scratch* const S = H.s;
  const uint32_t bars = sb + BAR_OFF;
  tid = opaque(tid);
  const int w = tid >> 5, lane = tid & 31, tb = R.tb(), cb = R.cb();
  uint32_t k_[19], v_[16];
  uint4 sk;
  int task = R.b() < R.nprep() ? R.b() : 320;
  delay(KVDLY);
  PROFC(tid == 0, 345);
  kv_load(P, S, min(task, 319), tid, k_, v_, sk);
  const __nv_bfloat16* pf = (tid < 64 ? P.k : P.v) + (tid & 63) * DM;
  const int j = lane >> 3, sm = min(R.sm(), 9), trow = 160 * tb + 4 * sm + (tb < 12 ? 40 : 32) * w + j;
  const uint32_t so = sb + (2 * w + (j & 1) + 8 * (j >> 1)) * 128 + 16 * (lane & 7), xo = so + sm * 2048, wo = so + (tb & 1) * 8192 + (tb & 6) * 1024;
  const __nv_bfloat16* xp = H.x + (size_t)min(trow, SEQ - 1) * DM + 384 + 8 * (lane & 7);
  const __nv_bfloat16* bp = (j < 2 ? H.b0 : H.b1) + (size_t)(64 * cb + 32 * (tb & 1) + 4 * (tb & 6) + 2 * w + (j & 1)) * DM + 384 + 8 * (lane & 7);
  float s = 0.f, s2 = 0.f, sr = 0.f;
#define STAT(m, n) { const uint32_t xw[4] = {m.x, m.y, m.z, m.w}, bw[4] = {n.x, n.y, n.z, n.w}; \
  _Pragma("unroll") for (int i = 0; i < 4; i++) { const float u = bf_lo(xw[i]), v = bf_hi(xw[i]); s += u + v; s2 = fmaf(u, u, fmaf(v, v, s2)); sr += bf_lo(bw[i]) + bf_hi(bw[i]); } }
#define STATS(K0, K1) _Pragma("unroll 1") for (int kb = K0; kb < K1; kb++) { \
    mbar_wait(BAR(B_F1 + kb)); \
    const uint4 a = lds4(xo + ((uint32_t)(XTAB0 >> (6 * kb)) & 63) * 4096), c = lds4(wo + ((uint32_t)(WTAB0 >> (6 * kb)) & 63) * 4096); \
    STAT(a, c) \
    asm volatile("" : "+f"(s), "+f"(s2), "+f"(sr)); \
    if (XPFAT >= K0 && XPFAT < K1) prefetch_if(((lane & 4) ? bp : xp) + 64 * (lane & 3), kb == XPFAT); \
    kv_prefetch(pf, kb == KPFAT ? task + R.nprep() : kb == KPFAT2 ? task + 2 * R.nprep() : 320); \
  } \
  __syncwarp(); mbar_arrive_if(BAR(B_AX + K0 / 3), lane == 0);
  STATS(0, 3)
  PROFC(tid == 0, 349);
    {
      uint4 m[4], n[4];
#pragma unroll
      for (int i = 0; i < 4; i++) { m[i] = ldg4(xp + 64 * i); n[i] = ldg4(bp + 64 * i); }
      STATS(3, 6)
      PROFC(tid == 0, 346);
      mbar_wait(BAR(B_LM));
      const uint32_t tag = lds32(sb + MISC_OFF) & 1;
#pragma unroll
      for (int i = 0; i < 4; i++) { const uint4 a = m[i], c = n[i]; STAT(a, c) }
      PROFC(tid == 0 && s2 != 1.2345f, 347);
#pragma unroll
      for (int o = 1; o <= 4; o <<= 1) { s += __shfl_xor_sync(0xffffffff, s, o); s2 += __shfl_xor_sync(0xffffffff, s2, o); sr += __shfl_xor_sync(0xffffffff, sr, o); }
      const float mn = s * (1.f / DM), rs = frcp(bf_rn(fsqrt(bf_rn(bf_rn(fmaxf(s2 * (1.f / DM) - mn * mn, 0.f)) + 1e-5f))));
      asm volatile("{ .reg .pred p; setp.ne.u32 p, %2, 0; @p st.relaxed.gpu.global.u32 [%0],%1; }"
                   ::"l"((uint32_t*)(S->RS + (8 * cb + 4 * (tb & 1) + (tb >> 1)) * 16 + 4 * w + (j & 1)) + (lane & 4) + (j >> 1)), "r"(tagf(sr, tag)),
                   "r"((uint32_t)(tb < 8 && (lane & 3) == 0)) : "memory");
      asm volatile("{ .reg .pred p; setp.ne.u32 p, %3, 0; @p st.relaxed.gpu.global.v2.u32 [%0],{%1,%2}; }"
                   ::"l"(S->S + trow), "r"(tagf(rs, tag)), "r"(tagf(-bf_rn(mn) * rs, tag)), "r"((uint32_t)(R.sm() < 10 && (lane & 7) == 0)) : "memory");
      PROFC(tid == 0, 3);
    }
#pragma unroll 1
  for (int r = 0; task < 320; r++) {
    {
      const uint32_t T0 = __byte_perm(sk.x, sk.z, 0x5410), T1 = __byte_perm(sk.x, sk.z, 0x7632);
      const uint32_t T2 = __byte_perm(sk.y, sk.w, 0x5410), T3 = __byte_perm(sk.y, sk.w, 0x7632);
      PROFC(tid == 0 && v_[15] != 0x12345, 336 + r);
      uint32_t o[16];
#pragma unroll
      for (int t = 0; t < 16; t += 2) {
        const uint32_t a = hmul2(hfma2(k_[t + 3], T0, hfma2(k_[t + 2], T1, hfma2(k_[t + 1], T2, hmul2(k_[t], T3)))), v_[t]);
        const uint32_t c = hmul2(hfma2(k_[t + 4], T0, hfma2(k_[t + 3], T1, hfma2(k_[t + 2], T2, hmul2(k_[t + 1], T3)))), v_[t + 1]);
        const int wd = ((7 - t / 2) >> 1) + 4 * ((7 - t / 2) & 1);
        o[wd] = __byte_perm(c, a, 0x5410); o[8 + wd] = __byte_perm(c, a, 0x7632);
        asm volatile("" : "+r"(o[wd]), "+r"(o[8 + wd]));
        if (t == PFAT) kv_prefetch(pf, task + (1 + PFD) * R.nprep());
      }
      PROFC(tid == 0, 330 + 2 * r);
      const int ph = task & 1;
      task += R.nprep();
      if (ORD == 0 && task < 320) kv_load(P, S, task, tid, k_, v_, sk);
      mbar_wait(BAR(B_E1 + 3)); mbar_wait(BAR(B_AX + 1));
#pragma unroll
      for (int i = 0; i < 4; i++) {
        const int row = 2 * lane + (i >> 1);
        asm volatile("st.shared.v4.u32 [%0],{%1,%2,%3,%4};" ::"r"(sb + KS_OFF + r * 8192 + row * 128 + (((2 * w + ((i & 1) ^ ph)) ^ (row & 7)) << 4)),
                     "r"(o[4 * i]), "r"(o[4 * i + 1]), "r"(o[4 * i + 2]), "r"(o[4 * i + 3]) : "memory");
      }
      __syncwarp();
      mbar_arrive_if(BAR(B_PS + r), lane == 0);
      PROFC(tid == 0, 331 + 2 * r);
      if (ORD == 1 && task < 320) kv_load(P, S, task, tid, k_, v_, sk);
    }
  }
#undef STAT
#undef STATS
  PROFC(tid == 0, 40);
}
#define SPLIT(G) asm volatile("{ .reg .pred p; .reg .u32 r; L: mov.u32 r, %%clock; setp.eq.u32 p, r, %0; @p bra.uni L; }" ::"n"(G) : "memory")
template <bool AUX>
__device__ __forceinline__ void conv_loop(uint32_t sb, uint32_t rc, int wg, int tid, long long t_start) {
  sb = opaque(sb); rc = opaque(rc);
  const uint32_t bars = sb + BAR_OFF;
  int slot = AUX ? 0 : wg + 1;
  mbar_wait(BAR(B_LM));
#pragma unroll 1
  while (slot < (int)((rc >> 10) & 7)) {
    tid = opaque(tid);
    const int w = tid >> 5, lane = tid & 31, g = lane >> 2, q = lane & 3;
    const uint32_t Dn = lds32(sb + MISC_OFF + 4 + 4 * slot);
    const uint32_t d0 = (g == 1 && q == 3 - w) ? Dn : 0, d1 = (g == 0 && q == 3 - w) ? Dn : 0;
    const uint32_t cb_ = conv_buf(sb, slot), c0 = cb_ + KC_OFS;
    const uint32_t abase = c0 + 2 * (2 * (g & 1) + 4 * w + 16 * (g >> 1) + 4 * q);
    const uint64_t bd = make_desc(cb_ + KV_PAD, 16, 256, 3);
    const bool hi = lane & 16, s1 = lane & 8;
    const int qo = hi ? (q + 1) & 3 : q;
    const int srcA = hi ? (lane & 12) | ((q + 1) & 3) : (lane & 12) | 16 | ((q + 3) & 3);
    const bool h3 = hi && q == 3, wrap = s1 && qo == 3, back = wrap && hi;
    const bool chi = wrap ? !hi : hi;
    const int cq = s1 ? (qo + 1) & 3 : qo;
    const int srcB = (lane & 4) | (s1 ? 0 : 8) | (chi ? 16 | ((cq + 3) & 3) : cq);
    const uint32_t gp = c0 + ((32 * (2 * w + (g & 1)) + (chi ? 256 : 0)) ^ (chi ? 64 : 0) ^ ((conv_ch(rc, slot) & 8) << 2)) + 4 * (2 * cq + (s1 ? 0 : 1));
    uint32_t a[12], f[16], o[8];
    float S[4], T[4], U[2], keep[2], pv[2] = {0.f, 0.f}, pr[4] = {0.f, 0.f, 0.f, 0.f};
    float e0[64], e1[56], e2[48], e3[40], e4[32], e5[24], e6[16], e7[8];
#define UNR _Pragma("unroll")
#define PERM() UNR for (int i = 0; i < 4; i++) { f[4 * i] = __byte_perm(a[3 * i], a[3 * i + 1], 0x5432); f[4 * i + 1] = a[3 * i + 1]; \
                                                 f[4 * i + 2] = __byte_perm(a[3 * i + 1], a[3 * i + 2], 0x5432); f[4 * i + 3] = a[3 * i + 2]; }
#define MMA(N, E) UNR for (int i = 0; i < 4; i++) wgmma_rs<N>(E, f[4 * i], f[4 * i + 1], f[4 * i + 2], f[4 * i + 3], bd - 8 * i, 1); wg_commit();
#define L1(c) UNR for (int i = 0; i < 4; i++) { const float ev = c[i], od = c[4 + i]; S[i] = hi ? (h3 ? ev : od) : ev; \
                                                T[i] = __shfl_sync(0xffffffff, hi ? (h3 ? pr[i] : ev) : od, srcA); pr[i] = od; }
#define L1E() UNR for (int i = 0; i < 4; i++) S[i] += T[i];
#define L2() UNR for (int h = 0; h < 2; h++) { keep[h] = back ? pv[h] : S[2 * h + 1]; pv[h] = S[2 * h + 1]; U[h] = __shfl_sync(0xffffffff, S[2 * h], srcB); }
#define L2E(j) o[j] = pack_bf(keep[0] + U[0], keep[1] + U[1]);
#define GRP(G, N, P, E) UNR for (int i = 0; i < N / 2; i++) asm volatile("mov.b32 %0,%1;" : "=f"(E[i]) : "f"(P[i + 8])); \
    wg_fence(); if (G < 7) conv_frags<(G + 1) & 7>(a, abase); if (G >= 2) { L2() } L1(P) MMA(N, E) SPLIT(G); \
    if (G < 7) { PERM() } if (G >= 2) { L2E((G + 6) & 7) } L1E() wg_wait<0>(); fence_regs(E);
    PROFC(tid == 0, 300 + 4 * slot);
    mbar_wait(BAR(B_KF + slot));
    if (tid == 0) PROF(361 + slot);
    PROFC(tid == 0, 301 + 4 * slot);
    conv_frags<0>(a, abase);
    wg_fence();
    wgmma_rs<128>(e0, d0 << 16, d0, d1 << 16, d1, bd, 0);
    PERM() conv_frags<1>(a, abase); wg_fence(); MMA(128, e0) SPLIT(0); PERM() wg_wait<0>(); fence_regs(e0);
    GRP(1, 112, e0, e1) GRP(2, 96, e1, e2) GRP(3, 80, e2, e3) GRP(4, 64, e3, e4) GRP(5, 48, e4, e5) GRP(6, 32, e5, e6) GRP(7, 16, e6, e7)
    PROFC(tid == 0, 302 + 4 * slot);
    L2() L1(e7) L2E(6) L1E() L2() L2E(7)
    bar_sync(wg + 1, 128);
#pragma unroll
    for (int jj = 0; jj < 8; jj++) asm volatile("st.shared.u32 [%0],%1;" ::"r"(gp + jj * 512), "r"(o[jj]) : "memory");
#undef PERM
#undef MMA
#undef L1
#undef L1E
#undef L2
#undef L2E
#undef GRP
    PROFC(tid == 0, 303 + 4 * slot);
    __syncwarp();
    if (lane == 0) mbar_arrive(BAR(B_GS + slot));
    if (!AUX) break;
    slot = slot ? slot + 1 : 3;
  }
}

#define IDX(J, c, h) (8 * (J) + 4 * ((c) >> 1) + 2 * (h) + ((c) & 1))
__device__ __forceinline__ uint2 lds2(uint32_t a) { uint2 v; asm volatile("ld.shared.v2.u32 {%0,%1},[%2];" : "=r"(v.x), "=r"(v.y) : "r"(a) : "memory"); return v; }
__device__ __forceinline__ void resid_load(float (&r)[40], uint32_t sb, int wg, int tid, const uint4& s) {
  const uint32_t dp = sb + XR_OFF + 8 * (tid & 3), xp = dp + (64 * wg + 16 * (tid >> 5) + ((tid & 31) >> 2)) * 160;
#pragma unroll
  for (int J = 0; J < 5; J++) {
    const uint2 u = lds2(xp + 32 * J), v = lds2(xp + 32 * J + 1280), d = lds2(dp + 20480 + 32 * J);
    r[8 * J] = __uint_as_float(u.x); r[8 * J + 1] = __uint_as_float(u.y); r[8 * J + 2] = __uint_as_float(v.x); r[8 * J + 3] = __uint_as_float(v.y);
    r[8 * J + 4] = __uint_as_float(d.x); r[8 * J + 5] = __uint_as_float(d.y);
  }
  r[30] = untag(s.x); r[31] = untag(s.y); r[38] = untag(s.z); r[39] = untag(s.w);
}
__device__ __forceinline__ void resid_init(float (&r)[40]) {
  const float s[4] = {r[30], r[31], r[38], r[39]};
#pragma unroll
  for (int J = 0; J < 5; J++) {
    uint32_t w[6];
#pragma unroll
    for (int i = 0; i < 6; i++) w[i] = __float_as_uint(r[8 * J + i]);
#pragma unroll
    for (int i = 0; i < 4; i++) {
      const int h = i >> 1, c = 2 * (i & 1);
      const float rs = s[2 * h], nm = s[2 * h + 1], x0 = bf_lo(w[i]), x1 = bf_hi(w[i]);
      const uint32_t t = hmul2(pack_bf(fmaf(x0, rs, nm), fmaf(x1, rs, nm)), w[4 + (i & 1)]);
      r[IDX(J, c, h)] = x0 + bf_lo(t); r[IDX(J, c + 1, h)] = x1 + bf_hi(t);
    }
  }
}

__device__ __forceinline__ float flip(float v, uint32_t m) { return __uint_as_float(__float_as_uint(v) ^ m); }
__device__ __forceinline__ void g1_phase(const int LY, const Head& H, uint32_t sb, int wg, int tid, Role R, float (&xr)[40], long long t_start) {
  Scratch* const S = H.s;
  tid = opaque(tid); sb = opaque(sb); R.v = opaque(R.v);
  const uint32_t bars = sb + BAR_OFF;
  const int cb = R.cb(), tb = R.tb();
  const int w = tid >> 5, lane = tid & 31, g = lane >> 2, q = lane & 3;
  const bool full = tb < 12;
  uint2* Eb = S->E + ((LY * 130 + cb) * 8 + 4 * wg + w) * 16 + g;
  float a[80];
#pragma unroll
  for (int i = 0; i < 80; i++) a[i] = 0.f;
  uint32_t rel = mapa(BAR(B_E1), lane ? R.wpart() : R.ubase() + (w & (R.ugs() - 1)));
  const bool rels = lane == 0 || (tid == 1 && wg != R.wlo());
  {
    uint64_t tw = LY ? WTAB1 : WTAB0, tx = LY ? XTAB1 : XTAB0;
    uint32_t bf = BAR(B_F1);
    if (tid == 0 && wg == 0 && !LY) PROF(351);
    fence_regs(a);
    mbar_wait(bf, LY);
    if (tid == 0 && wg == 0) PROF(LY ? 20 : 4);
#pragma unroll 1
    for (int kb = 0; kb < 10; kb++) {
      const uint64_t da = make_desc(sb + ((uint32_t)tw & 63) * 4096 + wg * 8192, 16, 1024, 1);
      const uint64_t db = make_desc(sb + ((uint32_t)tx & 63) * 4096, 16, 1024, 1);
      wg_fence();
#pragma unroll
      for (int kk = 0; kk < 4; kk++) wgmma_ss160(a, da + 2 * kk, db + 2 * kk, 1);
      wg_commit();
      wg_wait<1>();
      if (kb > 0) { if (rels) mbar_arrive_at(rel); rel += 8; }
      bf += 8; tw >>= 6; tx >>= 6;
      if (kb < 9) mbar_wait(bf, LY);
    }
  }
  if (tid == 0 && wg == 0) PROF(LY ? 19 : 2);
  mbar_wait(BAR(B_LM));
  const uint32_t tag = lds32(sb + MISC_OFF) & 1;
  if (q == 3) st_rlx2(Eb + tb * 1280, tag ^ 1, tag ^ 1);
  float2 lam, mu, mu2;
  float rs0, rs1;
  const uint32_t lamp = sb + LAM_OFF + 16 * (32 * wg + 8 * w + g);
  {
    const uint2* rp = S->RS + (8 * cb + 4 * wg + w) * 16 + 2 * g - (g & 1);
    uint2 v = ld_rlx2(rp);
    asm volatile("ld.shared.v2.f32 {%0,%1},[%2];" : "=f"(lam.x), "=f"(lam.y) : "r"(lamp));
    const float2 l2 = cmul(lam, lam), l4 = cmul(l2, l2), l8 = cmul(l4, l4), l16 = cmul(l8, l8), l32 = cmul(l16, l16);
    mu = full ? cmul(l32, l8) : l32; mu2 = cmul(mu, mu);
#pragma unroll 1
    for (int it = 0; it < SPIN && __any_sync(0xffffffff, untagged(v, tag)); it++) v = ld_rlx2(rp);
    rs0 = untag(v.x); rs1 = untag(v.y);
  }
  if (tid == 0 && wg == 0 && !LY) PROF(39);
  mbar_wait(BAR(B_ST), LY);
  const uint32_t ssm = sb + SSM_OFF + q * (full ? 336 : 272);
  wg_wait<0>(); fence_regs(a);
  if (rels) mbar_arrive_at(rel);
  if (tid == 0 && wg == 0) PROF(LY ? 21 : 5);
  float2 p = make_float2(0.f, 0.f);
#pragma unroll
  for (int j = 0; j < 20; j++) {
    if (j < 16 || full) {
      float4 sv;
      asm volatile("ld.shared.v4.f32 {%0,%1,%2,%3},[%4];" : "=f"(sv.x), "=f"(sv.y), "=f"(sv.z), "=f"(sv.w) : "r"(ssm + 16 * j));
#pragma unroll
      for (int e = 0; e < 2; e++) {
        const int o = 4 * j + e;
        const float r = e ? sv.z : sv.x, nm = e ? sv.w : sv.y;
        a[o] = fmaf(a[o], r, nm * rs0); a[o + 2] = fmaf(a[o + 2], r, nm * rs1);
        p = cfma(lam, p, make_float2(a[o], a[o + 2]));
      }
    }
  }
  {
    float2 t = make_float2(__shfl_up_sync(0xffffffff, p.x, 1, 4), __shfl_up_sync(0xffffffff, p.y, 1, 4));
    if (q >= 1) p = cfma(mu, t, p);
    t = make_float2(__shfl_up_sync(0xffffffff, p.x, 2, 4), __shfl_up_sync(0xffffffff, p.y, 2, 4));
    if (q >= 2) p = cfma(mu2, t, p);
  }
  if (q == 3 && full) st_rlx2(Eb + tb * 1280, tagf(p.x, tag), tagf(p.y, tag));
  if (tid == 0 && wg == 1) PROF(96 + 64 * LY);
  uint2 ev[3];
#pragma unroll
  for (int i = 0; i < 3; i++) { const int j = tb - 1 - q - 4 * i; ev[i] = j >= 0 ? ld_rlx2(Eb + j * 1280) : make_uint2(tag, tag); }
  float2 x = make_float2(__shfl_up_sync(0xffffffff, p.x, 1, 4), __shfl_up_sync(0xffffffff, p.y, 1, 4));
  if (q == 0) x = make_float2(0.f, 0.f);
  float c0, c1;
  asm volatile("ld.shared.v2.f32 {%0,%1},[%2+8];" : "=f"(c0), "=f"(c1) : "r"(lamp));
  const float c2 = -flip(c1, H.swap), c3 = flip(c0, H.swap);
#pragma unroll
  for (int i = 0; i < 40; i++) {
    const int o = 4 * (i >> 1) + (i & 1);
    const float u = a[o], v = a[o + 2];
    a[o] = fmaf(c0, u, c1 * v); a[o + 2] = fmaf(c2, u, c3 * v);
  }
  fence_regs(a);
  if (LY == 0 && R.b() < 128) {
    const int t0 = 16 * g + 8 * wg + 2 * w;
    if (tid == 0 && wg == 1) PROF(366);
    mbar_wait(BAR(B_XR));
    if (tid == 0 && wg == 1) PROF(367);
    uint4 s = lds4(sb + XR_OFF + 20480 + 256 + 8 * t0);
    if (__any_sync(0xffffffff, untagged(s, tag))) {
#pragma unroll 1
      for (int it = 0; it < SPIN; it++) { s = ld_rlx4(S->S + 128 * (R.b() >> 3) + t0); if (!__any_sync(0xffffffff, untagged(s, tag))) break; }
    }
    resid_load(xr, sb, wg, tid, s);
  }
  float2 mq, om4, fq;
  {
    asm volatile("" : "+f"(lam.x), "+f"(lam.y));
    const float2 one = make_float2(1.f, 0.f), l2 = cmul(lam, lam), l4 = cmul(l2, l2), l8 = cmul(l4, l4), l16 = cmul(l8, l8);
    const float2 l80 = full ? mu2 : cmul(mu2, l16), om = cmul(l80, l80), om2 = cmul(om, om);
    mq = cmul((q & 1) ? mu : one, (q & 2) ? mu2 : one);
    om4 = cmul(om2, om2); fq = cmul((q & 1) ? om : one, (q & 2) ? om2 : one);
  }
  mbar_wait(BAR(B_E1 + 9), LY);
  if (tid == 0 && wg == 1) PROF(368 + LY);
#pragma unroll 1
  for (int it = 0; it < SPIN; it++) {
    const bool m0 = untagged(ev[0], tag), m1 = untagged(ev[1], tag), m2 = untagged(ev[2], tag);
    if (!__any_sync(0xffffffff, m0 || m1 || m2)) break;
    if (m0) ev[0] = ld_rlx2(Eb + (tb - 1 - q) * 1280);
    if (m1) ev[1] = ld_rlx2(Eb + (tb - 5 - q) * 1280);
    if (m2) ev[2] = ld_rlx2(Eb + (tb - 9 - q) * 1280);
  }
  if (tid == 0 && wg == 1) PROF(97 + 64 * LY);
  float2 c = make_float2(untag(ev[2].x), untag(ev[2].y));
#pragma unroll
  for (int i = 1; i >= 0; i--) c = cfma(om4, c, make_float2(untag(ev[i].x), untag(ev[i].y)));
  c = cmul(fq, c);
#pragma unroll
  for (int s = 1; s <= 2; s <<= 1) { c.x += __shfl_xor_sync(0xffffffff, c.x, s); c.y += __shfl_xor_sync(0xffffffff, c.y, s); }
  c = cfma(mq, c, x);
  float2 z = make_float2(fmaf(c0, c.x, c1 * c.y), fmaf(c2, c.x, c3 * c.y));
  if (tid == 0 && wg == 0) PROF(LY ? 22 : 6);
  const float2 lc = make_float2(lam.x, flip(lam.y, H.swap));
  const uint32_t hq = sb + (lane >> 4) * 1024 + (lane & 7) * 128 + (((4 * wg + w) ^ (lane & 7)) << 4);
  const uint32_t hp = hq + R_OFF + (lane & 8) * 2048, hp4 = hq + (LY ? R4_OFF1 : R4_OFF0) + (lane & 8) * 512;
#pragma unroll
  for (int j = 0; j < 20; j += 2) {
    if (j < 16 || full) {
      uint32_t o[4];
#pragma unroll
      for (int i = 0; i < 2; i++) {
        const float2 z0 = cfma(lc, z, make_float2(a[4 * (j + i)], a[4 * (j + i) + 2]));
        z = cfma(lc, z0, make_float2(a[4 * (j + i) + 1], a[4 * (j + i) + 3]));
        o[2 * i] = pack_bf(z0.x, z.x); o[2 * i + 1] = pack_bf(z0.y, z.y);
      }
      asm volatile("stmatrix.sync.aligned.m8n8.x4.trans.shared.b16 [%0], {%1,%2,%3,%4};" ::"r"(j < 16 ? hp + j * 1024 : hp4 + (j - 16) * 1024), "r"(o[0]), "r"(o[1]), "r"(o[2]), "r"(o[3]) : "memory");
      if (j & 2) { __syncwarp(); if (lane == 0) mbar_arrive(BAR(B_SH + j / 4)); }
    }
  }
  if (tid == 0 && wg == 0) PROF(LY ? 23 : 7);
  if (lane == 0) PROF(390 + 4 * wg + w);
}

__device__ __forceinline__ void gate_load(float (&G)[40], uint32_t sb, int LY, int wg, int tid, int tb2) {
  const uint32_t bars = sb + BAR_OFF;
  const int lane = tid & 31, w = tid >> 5;
  mbar_wait(BAR(B_GF), LY);
  const int g = lane >> 2, q = lane & 3;
  const uint32_t gb = sb + (LY ? G_OFF1 : G_OFF0) + wg * 10240 + 512 * q + ((32 * w + 4 * g) ^ (64 * ((tb2 ^ q) & 1)) ^ (16 * (q & 2)));
#pragma unroll
  for (int i = 0; i < 20; i++) { const uint32_t v = lds32((gb ^ (16 * (i & 3))) + 128 * (i & 3) + 2048 * (i >> 2)); G[2 * i] = bf_lo(v); G[2 * i + 1] = bf_hi(v); }
  fence_regs(G);
}
__device__ __forceinline__ void g2_phase(const int LY, const Params& P, Scratch* S, uint32_t sb, int wg, int tid, Role R, float (&xr)[40], long long t_start) {
  sb = opaque(sb);
  const uint32_t bars = sb + BAR_OFF;
  if (LY) {
    const int td = opaque(tid), b = (opaque(R.v) >> 8) & 255;
    const uint32_t tag = lds32(sb + MISC_OFF) & 1;
    const uint2* sp = S->S + 2 * SEQ + 128 * (b >> 3) + 4 * (td & 28) + 8 * wg + 2 * (td >> 5);
    if (!(R.cb() & 1)) mbar_wait(BAR(B_HD), 1);
    uint2 dl[5];
#pragma unroll
    for (int J = 0; J < 5; J++) dl[J] = __ldg((const uint2*)(P.dskip + 80 * (b & 7) + 4 * (td & 3) + 16 * J));
    uint4 sv;
#pragma unroll 1
    for (int it = 0; it < SPIN; it++) { sv = ld_rlx4(sp); if (!__any_sync(0xffffffff, untagged(sv, tag))) break; }
#pragma unroll
    for (int h = 0; h < 2; h++)
#pragma unroll
      for (int J = 0; J < 5; J++)
#pragma unroll
        for (int c = 0; c < 4; c++) {
          const float x2 = xr[IDX(J, c, h)];
          const uint32_t dw = (c & 2) ? dl[J].y : dl[J].x;
          xr[IDX(J, c, h)] = fmaf(fmaf(x2, untag(h ? sv.z : sv.x), untag(h ? sv.w : sv.y)), (c & 1) ? bf_hi(dw) : bf_lo(dw), x2);
        }
    fence_regs(xr);
  }
  float acc[40];
#pragma unroll
  for (int i = 0; i < 40; i++) acc[i] = RIAT == 1 ? 0.f : xr[i];
  fence_regs(acc);
#define G2_STEP(st, cs, hf) { \
    const uint64_t da = make_desc(sb + H_OFF + (st) * 32768 + (hf) * 16384 + wg * 8192, 16, 1024, 1), db = make_desc(sb + (cs) * 20480 + (hf) * 10240, 16, 1024, 1); \
    wg_fence(); \
    _Pragma("unroll") for (int kk = 0; kk < 4; kk++) wgmma_ss80(acc, da + 2 * kk, db + 2 * kk, 1); \
    wg_commit(); }
  mbar_wait(BAR(B_F2), LY);
  if (tid == 0 && wg == 0) PROF(LY ? 25 : 10);
  G2_STEP(0, 0, 0)
  mbar_wait(BAR(B_F3), LY);
  G2_STEP(0, 0, 1)
  tid = opaque(tid); R.v = opaque(R.v);
  const uint32_t tag = lds32(sb + MISC_OFF) & 1;
  const int b = R.b(), tb2 = b >> 3, db_ = b & 7;
  const int w = tid >> 5, lane = tid & 31, g = lane >> 2, q = lane & 3;
  const int t0 = 128 * tb2 + 16 * g + 8 * wg + 2 * w;
  const int d0 = 80 * db_ + 4 * q, mrow = 64 * wg + 16 * w + g;
#define GATE(J, c, h) G[8 * (J) + 2 * (c) + (h)]
  uint32_t rel = mapa(BAR(B_E2), lane ? ((w & 1) ? R.wpart() : R.rank()) : R.cs() == 8 ? 4 * wg + w : wg);
  const bool rels = lane == 0 || (lane == 1 && w < 2);
  uint32_t* Mb = S->M + ((2 * LY * 16 + tb2) * 8) * 256 + (wg * 4 + w) * 32 + (2 * g + (q & 1)) * 2 + (q >> 1);
  {
    uint32_t bf = BAR(B_F2 + 1), st = 1, ra = rel + 8 * (B_EA - B_E2);
    const int lag = wg ? (LY ? STG : STG0) / 2 : 0;
#pragma unroll 1
    for (int kp = 1; kp < 10; kp++) {
      const bool more = LY == 0 || kp < 8;
      wg_wait<1>();
      if (lane == 0 && more) mbar_arrive_at(ra + 8 * (st ? st - 1 : 2));
      mbar_wait(bf, LY);
      if (STG && !(STG & 1) && kp == lag) bar_sync(5, 256);
      G2_STEP(st, kp < 5 ? kp : kp - 5, 0)
      wg_wait<1>();
      if (rels && more) mbar_arrive_at(rel);
      rel += 8;
      mbar_wait(bf + 8 * (B_F3 - B_F2), LY);
      if ((STG & 1) && kp == lag) bar_sync(5, 256);
      G2_STEP(st, kp < 5 ? kp : kp - 5, 1)
      if (kp == MIAT) {
        st_rlx(Mb + db_ * 256, tag ^ 1);
        if (LY == 0) st_rlx(Mb + (16 * 8 + db_) * 256, tag ^ 1);
      }
      bf += 8; st = st == 2 ? 0 : st + 1;
    }
  }
  if (STG && (LY || STG0) && !wg) asm volatile("bar.arrive 5, 256;" ::: "memory");
  wg_wait<0>(); fence_regs(acc);
  if (LY == 0 && rels) mbar_arrive_at(rel);
  if (tid == 0 && wg == 0) PROF(LY ? 26 : 11);
  if (lane == 0) PROF(116 + 64 * LY + wg * 4 + w);

  float mm[2] = {0.f, 0.f}, rr[2];
#pragma unroll 1
  for (int rep = 0;; rep++) {
    float m[2][2];
#pragma unroll
    for (int h = 0; h < 2; h++) {
      m[h][0] = m[h][1] = 0.f;
#pragma unroll
      for (int J = 0; J < 5; J++)
#pragma unroll
        for (int c = 0; c < 4; c++) { const float xv = acc[IDX(J, c, h)]; m[h][0] += xv; m[h][1] = fmaf(xv, xv, m[h][1]); }
    }
    float r1[2];
#pragma unroll
    for (int i = 0; i < 2; i++) { const float snd = (q & 1) ? m[0][i] : m[1][i], kp = (q & 1) ? m[1][i] : m[0][i]; r1[i] = kp + __shfl_xor_sync(0xffffffff, snd, 1); }
    const float r2 = ((q & 2) ? r1[1] : r1[0]) + __shfl_xor_sync(0xffffffff, (q & 2) ? r1[0] : r1[1], 2);
    const uint32_t mx = sb + MX_OFF + 512 * wg + 4 * tid, bx = BAR(B_KF + 1 + 2 * LY + wg);
    if (R.cs() == 8 && !rep) {
#pragma unroll
      for (int i = 0; i < 8; i++)
        asm volatile("st.async.weak.shared::cluster.mbarrier::complete_tx::bytes.b32 [%0],%1,[%2];" ::"r"(mapa(mx + 1024 * db_, i ^ db_)), "f"(r2), "r"(mapa(bx, i ^ db_)) : "memory");
      if (tid == 0) mbar_expect_tx(bx, 4096);
    }
    st_rlx(Mb + db_ * 256, tagf(r2, tag));
    if (rep) break;
    if (lane == 0) PROF(100 + 64 * LY + wg * 4 + w);
    float G[40];
    gate_load(G, sb, LY, wg, tid, tb2);
    mbar_wait(BAR(B_CD + 1));
    uint32_t mv[8];
    if (R.cs() == 8) {
      mbar_wait(bx, 1);
#pragma unroll
      for (int i = 0; i < 8; i++) mv[i] = lds32(mx + 1024 * i);
    } else {
#pragma unroll
    for (int i = 0; i < 8; i++) mv[i] = ld_rlx(Mb + i * 256);
#pragma unroll 1
    for (int it = 0; it < SPIN; it++) {
      uint32_t miss = 0;
#pragma unroll
      for (int i = 0; i < 8; i++) miss |= ((mv[i] ^ tag) & 1) << i;
      if (!__any_sync(0xffffffff, miss)) break;
#pragma unroll
      for (int i = 0; i < 8; i++) if ((miss >> i) & 1) mv[i] = ld_rlx(Mb + i * 256);
    }
      if (MBAR || !LY) bar_sync(4, 256);
    }
    if (lane == 0) PROF(108 + 64 * LY + wg * 4 + w);
    const float s = ((untag(mv[0]) + untag(mv[1])) + (untag(mv[2]) + untag(mv[3]))) + ((untag(mv[4]) + untag(mv[5])) + (untag(mv[6]) + untag(mv[7])));
    const float o = __shfl_xor_sync(0xffffffff, s, 2);
    const float S1 = (q & 2) ? o : s, S2 = (q & 2) ? s : o;
    const float mean = S1 * (1.f / DM), rs = frsqrt(fmaxf(S2 * (1.f / DM) - mean * mean, 0.f) + 1e-5f);
    const float mo = __shfl_xor_sync(0xffffffff, mean, 1), ro = __shfl_xor_sync(0xffffffff, rs, 1);
    mm[0] = (q & 1) ? mo : mean; mm[1] = (q & 1) ? mean : mo; rr[0] = (q & 1) ? ro : rs; rr[1] = (q & 1) ? rs : ro;
    if (tid == 0 && wg == 0) PROF(LY ? 27 : 12);
    const float nm[2] = {-mm[0] * rr[0], -mm[1] * rr[1]};
    if (LY) mm[0] = mm[1] = 0.f;
#pragma unroll
    for (int h = 0; h < 2; h++)
#pragma unroll
      for (int J = 0; J < 5; J++)
#pragma unroll
        for (int c = 0; c < 4; c++) { const float xv = acc[IDX(J, c, h)]; acc[IDX(J, c, h)] = fmaf(fmaf(xv, rr[h], nm[h]), GATE(J, c, h), xv - mm[h]); }
    if (LY) break;
    if (R.cs() == 8) mbar_wait(BAR(B_KF + 1), 1);
#pragma unroll
    for (int i = 0; i < 10; i++) {
      const int J = i >> 1, h = i & 1;
      const uint32_t u0 = pack_bf(acc[IDX(J, 0, h)], acc[IDX(J, 1, h)]), u1 = pack_bf(acc[IDX(J, 2, h)], acc[IDX(J, 3, h)]);
      asm volatile("st.shared.v2.u32 [%0],{%1,%2};" ::"r"(sb + US_OFF + ((mrow ^ 64) + 8 * h) * 160 + 32 * J + 8 * q), "r"(u0), "r"(u1) : "memory");
    }
    __syncwarp();
    if (lane == 0) mbar_arrive(BAR(B_GS + 1 + wg));
    if (tid == 0 && wg == 0) PROF(13);
    Mb += 16 * 8 * 256;
  }
  if (LY == 0) {
#pragma unroll
    for (int i = 0; i < 40; i++) xr[i] = acc[i] + mm[(i >> 1) & 1];
    if (tid == 0 && wg == 0) PROF(15);
  }
  else {
    float* op = P.out + (size_t)t0 * DM + d0;
#pragma unroll
    for (int i = 0; i < 10; i++) {
      const int J = i >> 1, h = i & 1;
      asm volatile("st.global.v4.f32 [%0],{%1,%2,%3,%4};" ::"l"(op + h * DM + 16 * J),
                   "f"(acc[IDX(J, 0, h)]), "f"(acc[IDX(J, 1, h)]), "f"(acc[IDX(J, 2, h)]), "f"(acc[IDX(J, 3, h)]) : "memory");
    }
  }
  if (tid == 0 && wg == 0 && LY) PROF(28);
#undef IDX
#undef GATE
}

__device__ __forceinline__ void next_stats(Scratch* S, uint32_t sb, int tb2, int tid) {
  const uint32_t bars = sb + BAR_OFF, tag = lds32(sb + MISC_OFF) & 1;
  const uint32_t* Mb = S->M + tb2 * 8 * 256 + 2 * tid;
  mbar_wait(BAR(B_F1 + NSAT), 1);
  float m1, s1, s2;
#pragma unroll 1
  for (int it = 0; it < SPIN; it++) {
    uint32_t a[8], miss = 0;
    uint2 v[8];
#pragma unroll
    for (int i = 0; i < 8; i++) { a[i] = ld_rlx(Mb + i * 256); v[i] = ld_rlx2((const uint2*)(Mb + (16 * 8 + i) * 256)); }
#pragma unroll
    for (int i = 0; i < 8; i++) miss |= (a[i] ^ tag) | (v[i].x ^ tag) | (v[i].y ^ tag);
#define SUM8(F) ((untag(F(0)) + untag(F(1))) + (untag(F(2)) + untag(F(3)))) + ((untag(F(4)) + untag(F(5))) + (untag(F(6)) + untag(F(7))))
#define FA(i) a[i]
#define FX(i) v[i].x
#define FY(i) v[i].y
    m1 = SUM8(FA); s1 = SUM8(FX); s2 = SUM8(FY);
    if (!__any_sync(0xffffffff, miss & 1)) break;
  }
  const float mean = s1 * (1.f / DM), rs = frsqrt(fmaxf(s2 * (1.f / DM) - mean * mean, 0.f) + 1e-5f);
  uint2* sp = S->S + SEQ + 128 * tb2 + 8 * (tid & 14) + 2 * (tid >> 4) + (tid & 1);
  st_rlx2(sp, tagf(rs, tag), tagf(-mean * rs, tag));
  st_rlx2(sp + SEQ, tagf(rs, tag), tagf(-(mean + m1 * (1.f / DM)) * rs, tag));
}
template <int I0, int I1> __device__ __forceinline__ void init_barriers(uint32_t bars) {
#pragma unroll
  for (int i = I0; i < I1; i++) mbar_init(BAR(i), bar_count(i));
}
__device__ __forceinline__ int g2_cb(int kp) { return kp < 5 ? 2 * kp : 2 * kp - 9; }
__device__ __forceinline__ const unsigned* h_flag(Scratch* S, int ly, int tb2, int lane) {
  const int s0 = 128 * min(tb2, 15) / 160;
  const bool two = (128 * tb2 + 127) / 160 != s0;
  return &S->flag[(F_H + (ly * 13 + s0) * 10 + min(lane & 15, 9) + (two && lane >= 16 ? 10 : 0)) * 32];
}
__device__ __forceinline__ void gate_tile(const Params& P, uint32_t dst, uint32_t bar, int tb2, int db) {
  mbar_expect_tx(bar, 20480);
  tma2d(dst, &P.mGT, tb2 * 128, db * 80, bar);
  tma2d(dst + 10240, &P.mGT, tb2 * 128 + 64, db * 80, bar);
}
__global__ void __cluster_dims__() __launch_bounds__(512, 1) fused_kernel(const Head H, const __grid_constant__ Params P) {
  extern __shared__ __align__(1024) uint8_t smem[];
  const uint32_t sb = opaque(smem_u32(smem)), bars = sb + BAR_OFF;
  const int wi = __shfl_sync(0xffffffff, threadIdx.x >> 5, 0), wg = wi >> 2, tid = threadIdx.x & 127;
  const int umap = blockIdx.x >= 96;
#define CLK(v)
  CLK(c_a);
  if (wi == 14) {
    if (elect_one()) { init_barriers<0, NBAR1>(bars); asm volatile("fence.mbarrier_init.release.cluster;" ::: "memory"); }
    __syncwarp();
  } else if (wi >= 12) prefetch_map(wi == 12 ? &P.mB : &P.mA[umap]);
  else if (wg == 2) xb_prefetch<1>(H, blockIdx.x + H.base, tid, 0);
  else if (P.role[blockIdx.x].w) return;
  CLK(c_b);
  asm volatile("barrier.cluster.arrive.relaxed.aligned;" ::: "memory");
  CLK(c_c);
  Role R;
  { const uint4 r = P.role[blockIdx.x]; R.v = r.x; R.c = r.y; R.p = r.z; }
  const int id = R.c & 255;
  const int tb = R.tb(), cb = R.cb(), b = R.b(), tb2 = b >> 3, db = b & 7, rank = R.rank();
  const bool has1 = tb <= 12, has2 = b < 128, full = tb < 12;
  Scratch* const S = H.s;
  unsigned* const epoch_p = &S->epoch[id * 8];
  const long long t_start = 0;
  if (wg < 2) {
    if (threadIdx.x == 0) PROF(50);
    asm volatile("griddepcontrol.launch_dependents;");
    bar_sync(6, 448);
    asm volatile("setmaxnreg.inc.sync.aligned.u32 176;");
    float xr[40];
#pragma unroll
    for (int i = 0; i < 40; i++) xr[i] = 0.f;
#pragma unroll 1
    for (int ly = 0; ly < 2; ly++) {
      if (has1) g1_phase(ly, H, sb, wg, tid, R, xr, t_start);
      if (ly == 0) {
        resid_init(xr); fence_regs(xr);
        conv_loop<false>(sb, R.c, wg, tid, t_start);
        if (tid == 0 && wg == 0) PROF(9);
      }
      if (has2) g2_phase(ly, P, S, sb, wg, tid, R, xr, t_start);
    }
    if (tid == 0 && wg == 0) st_rlx(epoch_p, lds32(sb + MISC_OFF));
  } else if (wg == 2) {
    bar_sync(6, 448);
    if (has1) aux_prep(H, P, sb, R, tid, t_start);
    asm volatile("setmaxnreg.inc.sync.aligned.u32 136;");
    conv_loop<true>(sb, R.c, wg, tid, t_start);
    if (tid == 0) PROF(44);
    {
      const uint32_t bb = (P.role[blockIdx.x].x >> 8) & 255;
      if ((bb & 132) == NSDB && tid < 32) next_stats(H.s, sb, bb >> 3, 32 * (bb & 3) + tid);
    }
  } else {
    if (threadIdx.x == 384) PROF(354);
    asm volatile("setmaxnreg.dec.sync.aligned.u32 24;");
    const int wlo = R.wlo(), whi = R.whi();
    const uint32_t wmask = R.wmask(), umask = R.umask(), f1bytes = full ? 36864 : 32768;
    if (wi < 14) {
      if (threadIdx.x == 384) PROF(340);
      asm volatile("barrier.cluster.wait.aligned;" ::: "memory");
      if (has1 && elect_one()) {
        uint64_t tab = wi == 12 ? WTAB0 : XTAB0;
        PROF(329 + wi);
#pragma unroll 1
        for (int kb = 0; kb < 6; kb++, tab >>= 6) {
          const uint32_t dst = sb + ((uint32_t)tab & 63) * 4096;
          if (wi == 12) {
#pragma unroll 1
            for (int h = wlo; h <= whi; h++) tma4d_mc(dst + h * 8192, &P.mB, kb * 64, 0, 0, 8 * cb + 4 * h, BAR(B_F1 + kb), wmask);
          } else {
            tma4d_mc(dst + R.uj() * 1024, &P.mA[umap], kb * 64, 0, 0, 80 * tb + R.uj(), BAR(B_F1 + kb), umask);
            mbar_expect_tx(BAR(B_F1 + kb), f1bytes);
          }
        }
      }
      if (!has1 && wi == 13) bar_sync(7, 64);
    } else {
      if (wi == 15 && elect_one()) { init_barriers<NBAR1, NBAR>(bars); asm volatile("fence.mbarrier_init.release.cluster;" ::: "memory"); }
      bar_sync(6, 448);
      if (!has1 && wi == 14) bar_sync(7, 64);
    }
    const unsigned e1 = ld_rlx(epoch_p) + 1;
    if (wi == 12) {
      if (elect_one()) {
#pragma unroll 1
        for (int ly = 0; ly < 2; ly++) {
#pragma unroll 1
          for (int i = ly ? 0 : 6; i < 10 && has1; i++) {
            const int kb = (0x9876541032ull >> (4 * i)) & 15;
            if (ly == 0) { mbar_wait(BAR(B_E1 + ((DEP0 >> (4 * kb - 24)) & 15))); mbar_wait(BAR(B_AX + (kb == 9))); }
            else {
              if (has2 && i == (db >= GLATE ? 4 : 2)) {
                wait_cnt(&S->cnt[(C_G + db) * 32], e1 * 80);
                mbar_wait(BAR(B_E2 + 7));
                PROF(47);
                gate_tile(P, sb + G_OFF0, BAR(B_GF), tb2, db);
              }
              if (has2) mbar_wait(BAR(i < 4 ? B_E2 + ((0x9865u >> (4 * i)) & 15) : B_GE));
              else if (i == 0) { mbar_wait(BAR(B_E1 + 9)); mbar_wait(BAR(B_CD + 1)); }
              if (i >= 4) mbar_wait(BAR(i < 6 ? B_F1 + W4AT : B_E1 + i - 6), 1);
            }
            const uint32_t dst = sb + ((uint32_t)((ly ? WTAB1 : WTAB0) >> (6 * kb)) & 63) * 4096;
#pragma unroll 1
            for (int h = wlo; h <= whi; h++) tma4d_mc(dst + h * 8192, &P.mB, kb * 64, 0, 0, 8 * cb + 4 * h, BAR(B_F1 + kb), wmask);
          }
          if (has2) {
            if (ly == 0) {
              mbar_wait(BAR(B_E1 + XRAT));
              mbar_expect_tx(BAR(B_XR), 20480 + 160 + 1024);
              tma4d(sb + XR_OFF, &P.mX, 80 * db, tb2, BAR(B_XR));
              bulk_g2s(sb + XR_OFF + 20480, P.dskip + 80 * db, 160, BAR(B_XR));
              bulk_g2s(sb + XR_OFF + 20480 + 256, S->S + 128 * tb2, 1024, BAR(B_XR));
              if (CWAIT) mbar_wait(BAR(CWAIT == 1 ? B_KF + 2 : CWAIT == 2 ? B_KF + R.nch() - 1 : CWAIT == 3 ? B_KF + R.nch() - 2 : B_HD));
            }
#pragma unroll 1
            for (int kp = 0; kp < 10; kp++) {
              const uint32_t dst = sb + (kp < 5 ? kp : kp - 5) * 20480;
              mbar_wait(BAR(kp >= 5 ? B_E2 + kp - 5 : ly ? B_E1 + ((CTAB1 >> (4 * kp)) & 15) : kp < 3 ? B_SH : kp < 4 ? B_HD : B_CD), ly);
              mbar_expect_tx(BAR(B_F2 + kp), 10240 + 16384);
              tma5d(dst, &P.mC[0], g2_cb(kp) * 64, db * 5, BAR(B_F2 + kp));
              mbar_expect_tx(BAR(B_F3 + kp), 10240 + 16384);
              tma5d(dst + 10240, &P.mC[1], g2_cb(kp) * 64, db * 5, BAR(B_F3 + kp));
              if (ly && kp == 4) { mbar_wait(BAR(B_E1 + 9), 1); gate_tile(P, sb + G_OFF1, BAR(B_GF), tb2, db); }
            }
          }
        }
      }
    } else if (wi == 13) {
      const int h0 = R.cs() == 8 ? rank : 4 * rank;
#pragma unroll 1
      for (int ly = 0; ly < 2; ly++) {
        int lane = lane_id();
        if (has1) {
          const unsigned* fp = &S->flag[(F_U3 + 8 * ((160 * tb) >> 7) + (lane & (full ? 15 : 7))) * 32];
          uint32_t ready = ly ? __ballot_sync(0xffffffff, ld_rlx(fp) == e1) : ~0u;
          if (ly) mbar_wait(BAR(full ? B_KF + 1 : has2 ? B_GS + 1 : B_RF1), has2);
          if (ly && full) mbar_wait(BAR(B_KF + 2), 1);
#pragma unroll 1
          for (int kb = ly ? 0 : 6; kb < 10; kb++) {
            if (ly && kb == UPAT) { mbar_wait(BAR(B_XR)); ready = ~0u; }
            wait_flags(fp, e1, 0x101u * ((1u << (64 * kb / 80)) | (1u << ((64 * kb + 63) / 80))), ready);
            if (kb >= 4) mbar_wait(BAR(B_E1 + (ly ? kb - 4 : (DEP0 >> (4 * kb - 24)) & 15)), ly);
            mbar_wait(BAR(B_AX + (kb == 9)));
            if (elect_one()) {
              if (ly && kb == 0) PROF(34);
              tma4d_mc(sb + ((uint32_t)((ly ? XTAB1 : XTAB0) >> (6 * kb)) & 63) * 4096 + R.uj() * 1024, &P.mA[2 * ly + umap], kb * 64, 0, 0, 80 * tb + R.uj(),
                       BAR(B_F1 + kb), umask);
              mbar_expect_tx(BAR(B_F1 + kb), f1bytes);
            }
            __syncwarp();
          }
        }
        if (ly == 0) {
          if (has1) mbar_wait(BAR(B_E1 + KPF));
          if (elect_one()) {
#pragma unroll 1
            for (int s = 0; s < R.nch(); s++) prefetch_l2(P.ssmk + (size_t)R.ch(s) * SEQ, 4096);
          }
          lane = lane_id();
#pragma unroll
          for (int s = 0; s < 5; s++) {
            asm volatile("st.shared.v4.u32 [%0],{%1,%1,%1,%1};" ::"r"(conv_buf(sb, s) + 16 * lane), "r"(0) : "memory");
            asm volatile("st.shared.u8 [%0],%1;" ::"r"(conv_buf(sb, s) + KC_OFS + lane), "r"(0) : "memory");
          }
          fence_async();
          __syncwarp();
          const unsigned* cp = &S->cnt[(C_KV + (R.ch(min(lane, R.nch() - 1)) >> 6)) * 32];
          uint32_t ready = 0;
#pragma unroll 1
          for (int s = 0, sk = 0; s < R.nch(); s++) {
#pragma unroll 1
            for (; sk < (s ? R.nch() : KUP); sk++)
              if (elect_one()) { mbar_expect_tx(BAR(B_KF + sk), 8192); bulk_g2s(conv_buf(sb, sk) + KC_OFS + 32, P.ssmk + (size_t)R.ch(sk) * SEQ, 4096, BAR(B_KF + sk)); }
            PROFC(s == 0, 329);
#pragma unroll 1
            for (int it = 0; !((ready >> s) & 1) && it < SPIN; it++) ready = __ballot_sync(0xffffffff, (int)(ld_rlx(cp) - e1 * 32) >= 0);
            PROFC(s == 0, 30);
            if (elect_one()) {
              bulk_g2s(conv_buf(sb, s) + KV_PAD, S->kv + (size_t)R.ch(s) * SEQ, 4096, BAR(B_KF + s));
              if (s == 0 && has2) { prefetch_l2(P.cre + (size_t)5 * b * DM, 5 * DM * 2); prefetch_l2(P.cim + (size_t)5 * b * DM, 5 * DM * 2); }
            }
            __syncwarp();
          }
          PROF(31);
          if (!has1) return;
        }
        lane = lane_id();
        const unsigned* fp = h_flag(S, ly, tb2, lane);
        uint32_t ready = __ballot_sync(0xffffffff, ld_rlx(fp) == e1), st = 0;
        if (ly == 0 && !has2) {
          mbar_wait(BAR(B_HD));
          if (lane < 8) mbar_arrive_cl(BAR(B_RF1), lane & 1);
        }
        if (has2) {
          mbar_wait(BAR(B_RF0), ly);
#pragma unroll 1
          for (int kp = 0; kp < 10; kp++) {
            if (kp == 5) { mbar_wait(BAR(B_XR), 1); ready = ~0u; }
            if (kp == 2) { mbar_wait(BAR(B_HD), ly); if (lane < 8) mbar_arrive_cl(BAR(B_RF1), lane & (R.cs() - 1)); }
            wait_flags(fp, e1, 0x10001u << g2_cb(kp), ready);
            if (kp == 2) mbar_wait(BAR(B_RF1), ly);
#pragma unroll
            for (int hf = 0; hf < 2; hf++) {
              if (kp >= 3) { if (hf) mbar_wait(BAR(B_E2 + kp - 3), ly); else mbar_wait(BAR(B_EA + st), ly ^ (kp >= 6 && kp < 9)); }
              if (elect_one()) {
                if (kp == 0 && !hf) PROF(33 + 2 * ly);
                tma4d_mc(sb + H_OFF + st * 32768 + hf * 16384 + h0 * 2048, &P.mH, g2_cb(kp) * 128 + hf * 64, 0, 2 * h0,
                         ly * 16 + tb2, BAR((hf ? B_F3 : B_F2) + kp), (1u << R.cs()) - 1);
              }
              __syncwarp();
            }
            st = st == 2 ? 0 : st + 1;
          }
        }
      }
    } else if (wi == 14) {
      if (!has1) return;
      prefetch_if(P.dskip + 64 * (tid & 31), (tid & 31) < 10);
      if (elect_one()) { prefetch_map(&P.sK); prefetch_map(&P.mX); prefetch_map(&P.sH); prefetch_map(&P.sU); prefetch_map(&P.mC[0]); prefetch_map(&P.mC[1]); prefetch_map(&P.mH); prefetch_map(&P.mGT); prefetch_map(&P.mA[2 + umap]); }
      __syncwarp();
#pragma unroll 1
      for (int ly = 0; ly < 2; ly++) {
        if (ly) {
          mbar_wait(BAR(B_F1 + 1), 1);
          uint32_t ready = 0;
          wait_flags(&S->flag[(F_U3 + 8 * ((160 * tb) >> 7) + ((lane_id() + ly) & (full ? 15 : 7))) * 32], e1, ~0u, ready);
          if (elect_one()) mbar_arrive(BAR(B_XR));
        }
        const int lane = lane_id();
        mbar_wait(BAR(B_E1 + (ly ? STAT_AT1 : STAT_AT)), ly);
        PROFC(lane == 0 && ly == 0, 36);
        {
          const int l = lane - (full ? 0 : 16);
          const uint2* p = S->S + ly * SEQ + 160 * tb + 2 * l;
          uint4 v[3];
#pragma unroll 1
          for (int it = 0; it < SPIN; it++) {
            v[0] = ld_rlx4(p); v[1] = ld_rlx4(p + 64); v[2] = ld_rlx4(p + 96);
            const bool miss = __any_sync(0xffffffff, untagged(v[0], e1 & 1) | untagged(v[1], e1 & 1) | untagged(v[2], e1 & 1));
            PROFC(lane == 0 && ly == 0 && it == 0, 37);
            if (!miss) break;
          }
          PROFC(lane == 0 && ly == 0, 38);
#pragma unroll
          for (int i = 0; i < 3; i++) {
            const int pr = l + (i == 2 ? 48 : 32 * i);
            if (pr >= 0) asm volatile("st.shared.v4.u32 [%0],{%1,%2,%3,%4};" ::"r"(sb + SSM_OFF + 16 * (pr + ((pr * (full ? 205 : 256)) >> 12))), "r"(v[i].x & ~1u),
                                      "r"(v[i].y & ~1u), "r"(v[i].z & ~1u), "r"(v[i].w & ~1u) : "memory");
          }
          __syncwarp();
        }
        if (lane == 0) mbar_arrive(BAR(B_ST));
        if (ly && has2) {
          mbar_wait(BAR(B_E1 + 9), 1);
          if (lane < 8) mbar_arrive_cl(BAR(B_RF0), lane & (R.cs() - 1));
        }
        if (lane == 0) {
#pragma unroll 1
          for (int pc = 0; pc < (full ? 5 : 4); pc++) {
            if ((HWM >> (4 * pc)) & 8) {
              mbar_wait(BAR(B_SH + min((HWM >> (4 * pc)) & 7, full ? 4 : 3)), ly);
              PROF(380 + 5 * ly + pc);
              if (pc == 0 && (cb & 1)) delay(ly ? HDLY : HDLY0);
              fence_async();
            }
#pragma unroll
            for (int i = 0; i < 2; i++) tma4d_store(&P.sH, sb + (pc < 4 ? R_OFF + i * 16384 + pc * 4096 : (ly ? R4_OFF1 : R4_OFF0) + i * 4096), 128 * cb + 64 * i, 0, 0, ly * 1024 + 80 * tb + 4 * pc);
          }
          bulk_commit(); bulk_wait();
          PROF(ly ? 17 : 16);
          mbar_arrive(BAR(B_HD));
          release<1>();
          signal_flag(&S->flag[(F_H + (ly * 13 + tb) * 10 + cb) * 32], e1);
          PROF(ly ? 24 : 8);
        }
        __syncwarp();
        if (has2) {
          mbar_wait(BAR(B_F2 + FPAT), ly);
          uint32_t ready = 0;
          wait_flags(h_flag(S, ly, tb2, lane_id() | 1), e1, ~0u, ready);
          if (elect_one()) mbar_arrive(BAR(B_XR));
        }
        if (lane == 0 && has2 && !ly) {
          mbar_wait(BAR(B_CD + 1));
#pragma unroll
          for (int i = 0; i < 2; i++) {
            mbar_wait(BAR(B_GS + 1 + i), 1);
            fence_async();
            tma4d_store(&P.sU, sb + US_OFF + 10240 - 10240 * i, 80 * db, 0, 8 * i, tb2);
          }
          bulk_commit(); bulk_wait();
          PROF(18);
          release<2>(); signal_flag(&S->flag[(F_U3 + b) * 32], e1);
          PROF(14);
          mbar_wait(BAR(B_SG));
          mbar_arrive(BAR(B_GE)); mbar_arrive_cl(BAR(B_GE), R.wpart());
        }
        __syncwarp();
      }
    } else {
      discretise(H, P, sb, R, tid & 31, e1);
      if (elect_one()) {
        mbar_arrive(BAR(B_LM));
        PROF(348);
        if (b < R.nprep()) {
#pragma unroll 1
          for (int task = b, r = 0; task < 320; task += R.nprep(), r++) {
            mbar_wait(BAR(B_PS + r));
            PROF(320 + 3 * r);
            fence_async();
            tma2d_store(&P.sK, sb + KS_OFF + r * 8192, 64 * (task & 31), 64 * (task >> 5));
            bulk_commit(); bulk_wait();
            PROF(321 + 3 * r);
            release<4>();
            signal_cnt(&S->cnt[(C_KV + (task >> 5)) * 32], 1);
            PROF(322 + 3 * r);
          }
          PROF(41);
        }
        if (has2) {
          mbar_wait(BAR(B_SH));
#pragma unroll 1
          for (int i = 0; i < 8; i++) mbar_arrive_cl(BAR(B_RF0), i & (R.cs() - 1));
        }
#pragma unroll 1
        for (int s = 0, s0 = 0; s < R.nch(); s++) {
          mbar_wait(BAR(B_GS + s));
          fence_async();
          bulk_s2g(S->gt + (size_t)R.ch(s) * SEQ, conv_buf(sb, s) + KC_OFS, 4096); bulk_commit();
          if (s == 1 || s >= R.nch() - GSPL) bulk_wait();
          if (s == 1 || s == min(R.nch() - 1, 3)) mbar_arrive(BAR(B_CD + (s > 1)));
          mbar_arrive_if(BAR(B_SG), s == R.nch() - 1);
          if (s >= R.nch() - GSPL) {
            PROF(45);
            release<8>();
#pragma unroll 1
            for (; s0 <= s; s0++) signal_cnt(&S->cnt[(C_G + R.ch(s0) / 80) * 32], 1);
          }
        }
        PROF(46);
      }
    }
  }
}

typedef CUresult (*EncFn)(CUtensorMap*, CUtensorMapDataType, cuuint32_t, void*, const cuuint64_t*, const cuuint64_t*, const cuuint32_t*,
                          const cuuint32_t*, CUtensorMapInterleave, CUtensorMapSwizzle, CUtensorMapL2promotion, CUtensorMapFloatOOBfill);
bool enc(EncFn f, CUtensorMap* m, const void* base, int rank, const cuuint64_t* dims, const cuuint64_t* strides, const cuuint32_t* box, bool swz,
         bool f32 = false) {
  const cuuint32_t es[5] = {1, 1, 1, 1, 1};
  return f(m, f32 ? CU_TENSOR_MAP_DATA_TYPE_FLOAT32 : CU_TENSOR_MAP_DATA_TYPE_BFLOAT16, rank, const_cast<void*>(base), dims, strides, box, es,
           CU_TENSOR_MAP_INTERLEAVE_NONE, swz ? CU_TENSOR_MAP_SWIZZLE_128B : CU_TENSOR_MAP_SWIZZLE_NONE, CU_TENSOR_MAP_L2_PROMOTION_L2_256B,
           CU_TENSOR_MAP_FLOAT_OOB_FILL_NONE) == CUDA_SUCCESS;
}
void make_roles(Params& P, bool big) {
  for (uint32_t bx = 0; bx < (big ? 120u : 12u); bx++) {
    const uint32_t c = bx >> 3, r = bx & 7, id = big ? bx : 120 + bx;
    const uint32_t vA = c < 12 ? (2 * (c >> 1) + (r >> 2)) | (4 * (c & 1) + (r & 3)) << 4 | (r & 4) << 16 | 4 << 19 | (r ^ 4) << 22
                               : (4 * (c - 12) + (r >> 1)) | (8 + (r & 1)) << 4 | (r & 6) << 16 | 2 << 19 | (r ^ 2) << 22;
    const uint32_t vB = (bx < 10 ? 12 : 13) | bx << 4 | 2 << 19 | (bx & 1) << 22 | (bx & 1) << 26;
    P.role[bx].x = (big ? vA | r << 26 | 1u << 29 : vB) | (id < 128 ? (id & ~7u) | (r >> 1) | (r & 1) << 2 : id) << 8;
    P.role[bx].y = id | (big ? 5 : bx < 8 ? 3 : 4) << 10 | 120 << 13 | 132 << 21 | (big ? 4u : 3u) << 29;
    const uint32_t v = P.role[bx].x, cb = (v >> 4) & 15, rank = (v >> 26) & 7, ubase = (v >> 16) & 7, ugs = (v >> 19) & 7, wp = (v >> 22) & 7;
    const uint32_t wlo = rank > wp, whi = wp != rank ? wlo : 1, wmask = 1u << rank | 1u << wp;
    const uint32_t uj = (rank - ubase) * (!big ? 8 : ugs == 4 ? 5 : 10), sm = big ? (0x7296418530ull >> (4 * cb)) & 15 : bx < 8 ? 4 * (bx & 1) + (bx >> 1) : 15;
    P.role[bx].z = wlo | whi << 1 | wmask << 2 | ((1u << ugs) - 1) << (10 + ubase) | uj << 20 | sm << 25;
    P.role[bx].w = 0;
  }
}
void launch(const Head& H, const Params& P, int grid, int cs, bool dependent) {
  cudaLaunchConfig_t cfg = {};
  cfg.gridDim = grid; cfg.blockDim = 512; cfg.dynamicSmemBytes = SMEM_BYTES; cfg.stream = cudaStreamPerThread;
  cudaLaunchAttribute at[2];
  at[0].id = cudaLaunchAttributeClusterDimension; at[0].val.clusterDim.x = cs; at[0].val.clusterDim.y = 1; at[0].val.clusterDim.z = 1;
  at[1].id = cudaLaunchAttributeProgrammaticStreamSerialization; at[1].val.programmaticStreamSerializationAllowed = 1;
  cfg.attrs = at; cfg.numAttrs = dependent ? 2 : 1;
  cudaLaunchKernelEx(&cfg, fused_kernel, H, P);
}

}

extern "C" void kernel_launch(void* const* d_in, const int* in_sizes, int n_in, void* d_out, int out_size) {
  (void)in_sizes; (void)n_in; (void)out_size;
  typedef const __nv_bfloat16* cb;
  void* fp = nullptr; cudaDriverEntryPointQueryResult qr;
  cudaGetDriverEntryPoint("cuTensorMapEncodeTiled", &fp, cudaEnableDefault, &qr);
  EncFn f = (EncFn)fp;
  Scratch* sp = nullptr;
  cudaGetSymbolAddress((void**)&sp, g_scr);
  void *pu = sp->u, *ph = sp->h, *pgt = sp->gt;
  Params P;
  Head H;
  H.s = sp; H.x = (cb)d_in[0]; H.swap = (uintptr_t)d_in[4] < (uintptr_t)d_in[3] ? 0 : 0x80000000u; H.b0 = (cb)d_in[H.swap ? 3 : 4]; H.b1 = (cb)d_in[H.swap ? 4 : 3];
  for (int i = 0; i < 2; i++) {
    const cuuint64_t d[4] = {640, 8, 2, 80}, s[3] = {1280, (cuuint64_t)((uintptr_t)H.b1 - (uintptr_t)H.b0), 8 * 1280}; const cuuint32_t bx[4] = {64, 8, 2, 4};
    if (enc(f, &P.mB, H.b0, 4, d, s, bx, true)) break;
    cudaMemcpyAsync(sp->bcopy, H.b0, DM * DM * 2, cudaMemcpyDeviceToDevice, cudaStreamPerThread);
    cudaMemcpyAsync(sp->bcopy + DM * DM, H.b1, DM * DM * 2, cudaMemcpyDeviceToDevice, cudaStreamPerThread);
    H.b0 = sp->bcopy; H.b1 = sp->bcopy + DM * DM;
  }
  {
    const cuuint64_t d[5] = {640, 2, 4, 2, 40}, s[4] = {1280, 4 * 1280, 2 * 1280, 16 * 1280}; const cuuint32_t bx[5] = {64, 2, 4, 2, 5};
    enc(f, &P.mC[0], d_in[5], 5, d, s, bx, true); enc(f, &P.mC[1], d_in[6], 5, d, s, bx, true); }
  { const cuuint64_t d[2] = {2048, 640}, s[1] = {4096}; const cuuint32_t bx[2] = {64, 80}; enc(f, &P.mGT, pgt, 2, d, s, bx, true); }
  { const cuuint64_t d[4] = {640, 8, 16, 16}, s[3] = {16 * 1280, 1280, 128 * 1280}; const cuuint32_t bx[4] = {80, 8, 16, 1}, bh[4] = {80, 8, 8, 1};
    enc(f, &P.sU, pu, 4, d, s, bh, false); enc(f, &P.mX, d_in[0], 4, d, s, bx, false); }
  { const cuuint64_t d[2] = {2048, 640}, s[1] = {4096}; const cuuint32_t bx[2] = {64, 64}; enc(f, &P.sK, sp->kv, 2, d, s, bx, true); }
  P.lre = (cb)d_in[1]; P.lim = (cb)d_in[2]; P.cre = (cb)d_in[5]; P.cim = (cb)d_in[6]; P.ldt = (cb)d_in[7]; P.dskip = (cb)d_in[8];
  P.out = (float*)d_out;
  P.k = (cb)d_in[10]; P.v = (cb)d_in[11]; P.shk = (cb)d_in[12]; P.ssmk = (cb)d_in[13]; P.ssmd = (cb)d_in[14];
  cudaFuncSetAttribute(fused_kernel, cudaFuncAttributeMaxDynamicSharedMemorySize, SMEM_BYTES);
  for (int big = 1; big >= 0; big--) {
    const cuuint64_t seg = big ? 40 : 32;
    for (int i = 0; i < 4; i++) {
      const cuuint64_t d[4] = {640, 2, 4, 1024}, s[3] = {1280, seg * 1280, 2 * 1280}; const cuuint32_t bx[4] = {64, 2, 4, !big ? 8u : (i & 1) ? 10u : 5u};
      enc(f, &P.mA[i], i < 2 ? d_in[0] : pu, 4, d, s, bx, true);
    }
    {
      const cuuint64_t d[4] = {1280, 8, 16, 32}, s[3] = {16 * 2560, 2560, 128 * 2560}; const cuuint32_t bx[4] = {64, 8, big ? 2u : 8u, 1};
      enc(f, &P.mH, ph, 4, d, s, bx, true); }
    { const cuuint64_t d[4] = {1280, 2, 4, 2048}, s[3] = {2560, seg * 2560, 2 * 2560}; const cuuint32_t bx[4] = {64, 2, 4, 4};
      enc(f, &P.sH, ph, 4, d, s, bx, true); }
    make_roles(P, big);
    H.base = big ? 0 : 120;
    launch(H, P, big ? 120 : 12, big ? 8 : 2, !big);
  }
}
```

```cpp
#include <cuda_runtime.h>
#include <cuda.h>
#include <cuda_bf16.h>
#include <stdint.h>

namespace {

constexpr int SEQ = 2048, DM = 640;
constexpr int SPIN = 1 << 20;
#define PFAT 99
#define KVDLY 500
#define PFD 1
#define XPFAT 9
#define STAT_AT 6
#define KPFAT 3
#define KPFAT2 5
#define KPF 7
#define HDLY 1900
#define GSPL 2
#define CWAIT 0
#define HDLY0 1900
#define CTAB1 0x96543u
#define NSAT 0
#define SKW 1
#define RIAT 2
#define MIAT 5
#define FPAT 1
#define UPAT 7
#define STAT_AT1 4
#define W4AT 0
#define MBAR 1
#define STG 17
#define STG0 17
#define HWM 0xc09
#define NSDB 4
#define GLATE 6
#define KUP 1
#define XRAT 9
#define ORD 1

struct Scratch {
  uint2 E[2 * 13 * 10 * 8 * 16];
  uint32_t M[3 * 16 * 8 * 256];
  uint2 S[3 * SEQ];
  uint2 RS[80 * 16];
  unsigned flag[512 * 32];
  unsigned cnt[32 * 32];
  unsigned epoch[132 * 8];
  unsigned zero[128];
  unsigned prof[132 * 512];
  __align__(1024)
  __nv_bfloat16 u[SEQ * DM];
  __nv_bfloat16 h[2 * SEQ * 1280];
  __nv_bfloat16 kv[DM * SEQ];
  __nv_bfloat16 gt[DM * SEQ];
  __nv_bfloat16 bcopy[2 * DM * DM];
};
__device__ __align__(1024) Scratch g_scr;
#define PROFC(c, i) do {} while (0)
#define PSEL 1
#define PROF(i) do {} while (0)

constexpr int C_KV = 0, C_G = 10;
constexpr int F_U3 = 0, F_H = 128;

constexpr int R_OFF = 196608, R4_OFF0 = 73728, R4_OFF1 = 122880, H_OFF = 131072, KS_OFF = 131072, CV_OFF = 86272, G_OFF0 = 40960, G_OFF1 = 102400, US_OFF = 98304, XR_OFF = 163840, MX_OFF = 32768;
constexpr int LAM_OFF = 229376, SSM_OFF = LAM_OFF + 1024, BAR_OFF = SSM_OFF + 1344;
constexpr int B_F1 = 0, B_E1 = 10, B_RF0 = 20, B_RF1 = 21, NBAR1 = 22;
constexpr int B_F2 = 22, B_KF = 32, B_GF = 37, B_CD = 38, B_XR = 40, B_ST = 41, B_HD = 42, B_LM = 43, B_E2 = 44, B_GS = 54, B_PS = 59, B_AX = 62, B_SH = 64, B_SG = 69, B_GE = 70, B_EA = 71, B_F3 = 74, NBAR = 84;
__host__ __device__ constexpr int bar_count(int i) { return i < B_E1 ? 1 : i < B_RF0 ? 9 : i < B_F2 ? 8 : i < B_E2 ? 1 : i < B_GS ? 12 : i < B_SH ? 4 : i < B_SG ? 8 : i < B_GE ? 1 : i < B_EA ? 2 : i < B_F3 ? 8 : 1; }
constexpr int MISC_OFF = BAR_OFF + NBAR * 8, SMEM_BYTES = MISC_OFF + 32;
constexpr int KV_PAD = 512, KC_OFS = KV_PAD + 4096, CH_STRIDE = 8960;
__device__ __forceinline__ uint32_t conv_buf(uint32_t sb, int slot) { return sb + CV_OFF + slot * CH_STRIDE; }
constexpr uint64_t tab6(int a, int b, int c, int d, int e, int f, int g, int h, int i, int j) {
  return (uint64_t)a | (uint64_t)b << 6 | (uint64_t)c << 12 | (uint64_t)d << 18 | (uint64_t)e << 24 | (uint64_t)f << 30 | (uint64_t)g << 36 | (uint64_t)h << 42 |
         (uint64_t)i << 48 | (uint64_t)j << 54;
}
constexpr uint64_t WTAB0 = tab6(0, 4, 8, 30, 12, 26, 0, 4, 8, 12), XTAB0 = tab6(40, 45, 50, 34, 16, 21, 40, 45, 50, 16);
constexpr uint64_t WTAB1 = tab6(16, 20, 0, 4, 8, 12, 16, 20, 24, 28), XTAB1 = tab6(40, 45, 50, 32, 40, 45, 50, 32, 40, 45);
constexpr uint32_t DEP0 = 0x4210;

struct Head {
  Scratch* s;
  const __nv_bfloat16 *x, *b0, *b1;
  uint32_t base, swap;
};
struct Params {
  const __nv_bfloat16 *lre, *lim, *ldt, *k, *v, *shk, *cre, *cim, *ssmk, *ssmd, *dskip;
  float* out;
  uint4 role[120];
  CUtensorMap mB, mA[4], mH, mC[2], mGT, mX, sH, sU, sK;
};

__device__ __forceinline__ uint32_t smem_u32(const void* p) { return (uint32_t)__cvta_generic_to_shared(p); }
__device__ __forceinline__ uint32_t opaque(uint32_t x) { uint32_t y; asm volatile("mov.u32 %0, %1;" : "=r"(y) : "r"(x)); return y; }
__device__ __forceinline__ int lane_id() { int y; asm volatile("mov.u32 %0, %%laneid;" : "=r"(y)); return y; }
__device__ __forceinline__ void delay(uint32_t n) {
  asm volatile("{ .reg .pred p; .reg .u32 a, b; mov.u32 a, %%clock; L: mov.u32 b, %%clock; sub.u32 b, b, a; setp.lt.u32 p, b, %0; @p bra.uni L; }" ::"r"(n) : "memory");
}
__device__ __forceinline__ void mbar_init(uint32_t bar, uint32_t cnt) { asm volatile("mbarrier.init.shared::cta.b64 [%0], %1;" ::"r"(bar), "r"(cnt) : "memory"); }
__device__ __forceinline__ void mbar_expect_tx(uint32_t bar, uint32_t bytes) { asm volatile("mbarrier.arrive.expect_tx.shared::cta.b64 _, [%0], %1;" ::"r"(bar), "r"(bytes) : "memory"); }
__device__ __forceinline__ void mbar_arrive(uint32_t bar) { asm volatile("mbarrier.arrive.shared::cta.b64 _, [%0];" ::"r"(bar) : "memory"); }
__device__ __forceinline__ void mbar_arrive_if(uint32_t bar, bool c) {
  asm volatile("{ .reg .pred p; setp.ne.u32 p, %1, 0; @p mbarrier.arrive.shared::cta.b64 _, [%0]; }" ::"r"(bar), "r"((uint32_t)c) : "memory");
}
__device__ __forceinline__ void prefetch_if(const void* p, bool c) { asm volatile("{ .reg .pred p; setp.ne.u32 p, %1, 0; @p prefetch.global.L2 [%0]; }" ::"l"(p), "r"((uint32_t)c)); }
__device__ __forceinline__ void mbar_arrive_cl(uint32_t bar, uint32_t cta) {
  asm volatile("{ .reg .b32 ra; mapa.shared::cluster.u32 ra, %0, %1; mbarrier.arrive.shared::cluster.b64 _, [ra]; }" ::"r"(bar), "r"(cta) : "memory");
}
__device__ __forceinline__ uint32_t mapa(uint32_t a, uint32_t cta) { uint32_t r; asm("mapa.shared::cluster.u32 %0, %1, %2;" : "=r"(r) : "r"(a), "r"(cta)); return r; }
__device__ __forceinline__ void mbar_arrive_at(uint32_t ra) { asm volatile("mbarrier.arrive.shared::cluster.b64 _, [%0];" ::"r"(ra) : "memory"); }
__device__ __forceinline__ void mbar_wait(uint32_t bar, uint32_t parity = 0) {
  asm volatile("{ .reg .pred p; .reg .u32 c; mov.u32 c, 0;\n"
               "W: mbarrier.try_wait.parity.shared::cta.b64 p, [%0], %1; @p bra.uni D;\n"
               "add.u32 c, c, 1; setp.lt.u32 p, c, 0x100000; @p bra.uni W;\nD: }" ::"r"(bar), "r"(parity) : "memory");
}
__device__ __forceinline__ bool elect_one() { uint32_t p; asm volatile("{ .reg .pred P; elect.sync _|P, 0xffffffff; selp.u32 %0,1,0,P; }" : "=r"(p)); return p; }
__device__ __forceinline__ void bar_sync(int id, int n) { __syncwarp(); asm volatile("bar.sync %0, %1;" ::"r"(id), "r"(n) : "memory"); }
__device__ __forceinline__ void tma2d(uint32_t dst, const CUtensorMap* m, int c0, int c1, uint32_t bar) {
  asm volatile("cp.async.bulk.tensor.2d.shared::cluster.global.mbarrier::complete_tx::bytes [%0], [%1, {%3,%4}], [%2];"
               ::"r"(dst), "l"(m), "r"(bar), "r"(c0), "r"(c1) : "memory");
}
__device__ __forceinline__ void tma5d(uint32_t dst, const CUtensorMap* m, int c0, int c4, uint32_t bar) {
  asm volatile("cp.async.bulk.tensor.5d.shared::cluster.global.mbarrier::complete_tx::bytes [%0], [%1, {%3,%5,%5,%5,%4}], [%2];"
               ::"r"(dst), "l"(m), "r"(bar), "r"(c0), "r"(c4), "r"(0) : "memory");
}
__device__ __forceinline__ void tma4d(uint32_t dst, const CUtensorMap* m, int c0, int c3, uint32_t bar) {
  asm volatile("cp.async.bulk.tensor.4d.shared::cluster.global.mbarrier::complete_tx::bytes [%0], [%1, {%3,%5,%5,%4}], [%2];"
               ::"r"(dst), "l"(m), "r"(bar), "r"(c0), "r"(c3), "r"(0) : "memory");
}
__device__ __forceinline__ void tma4d_mc(uint32_t dst, const CUtensorMap* m, int c0, int c1, int c2, int c3, uint32_t bar, uint32_t mask) {
  asm volatile("cp.async.bulk.tensor.4d.shared::cluster.global.mbarrier::complete_tx::bytes.multicast::cluster [%0], [%1, {%3,%4,%5,%6}], [%2], %7;"
               ::"r"(dst), "l"(m), "r"(bar), "r"(c0), "r"(c1), "r"(c2), "r"(c3), "h"((uint16_t)mask) : "memory");
}
__device__ __forceinline__ void bulk_g2s(uint32_t dst, const void* src, uint32_t bytes, uint32_t bar) {
  asm volatile("cp.async.bulk.shared::cluster.global.mbarrier::complete_tx::bytes [%0], [%1], %2, [%3];" ::"r"(dst), "l"(src), "r"(bytes), "r"(bar) : "memory");
}
__device__ __forceinline__ void tma4d_store(const CUtensorMap* m, uint32_t src, int c0, int c1, int c2, int c3) {
  asm volatile("cp.async.bulk.tensor.4d.global.shared::cta.bulk_group [%0, {%2,%3,%4,%5}], [%1];" ::"l"(m), "r"(src), "r"(c0), "r"(c1), "r"(c2), "r"(c3) : "memory");
}
__device__ __forceinline__ void tma2d_store(const CUtensorMap* m, uint32_t src, int c0, int c1) {
  asm volatile("cp.async.bulk.tensor.2d.global.shared::cta.bulk_group [%0, {%2,%3}], [%1];" ::"l"(m), "r"(src), "r"(c0), "r"(c1) : "memory");
}
__device__ __forceinline__ void bulk_s2g(void* dst, uint32_t src, uint32_t bytes) {
  asm volatile("cp.async.bulk.global.shared::cta.bulk_group [%0], [%1], %2;" ::"l"(dst), "r"(src), "r"(bytes) : "memory");
}
__device__ __forceinline__ void bulk_commit() { asm volatile("cp.async.bulk.commit_group;" ::: "memory"); }
__device__ __forceinline__ void bulk_wait() { asm volatile("cp.async.bulk.wait_group 0;" ::: "memory"); }
__device__ __forceinline__ void fence_async() { asm volatile("fence.proxy.async.shared::cta;" ::: "memory"); }
__device__ __forceinline__ void prefetch_l2(const void* src, uint32_t bytes) { asm volatile("cp.async.bulk.prefetch.L2.global [%0], %1;" ::"l"(src), "r"(bytes) : "memory"); }
__device__ __forceinline__ void prefetch_map(const CUtensorMap* m) { asm volatile("prefetch.tensormap [%0];" ::"l"(m) : "memory"); }
__device__ __forceinline__ void wg_fence() { __syncwarp(); asm volatile("wgmma.fence.sync.aligned;" ::: "memory"); }
__device__ __forceinline__ void wg_commit() { asm volatile("wgmma.commit_group.sync.aligned;" ::: "memory"); }
template <int N> __device__ __forceinline__ void wg_wait() { asm volatile("wgmma.wait_group.sync.aligned %0;" ::"n"(N) : "memory"); }
template <int N> __device__ __forceinline__ void fence_regs(float (&d)[N]) {
#pragma unroll
  for (int i = 0; i < N; i++) asm volatile("" : "+f"(d[i])::"memory");
}
__device__ __forceinline__ uint64_t make_desc(uint32_t addr, uint32_t lbo, uint32_t sbo, uint32_t swz) {
  return (uint64_t)((addr & 0x3FFFF) >> 4) | ((uint64_t)(lbo >> 4) << 16) | ((uint64_t)(sbo >> 4) << 32) | ((uint64_t)swz << 62);
}
__device__ __forceinline__ uint32_t ldg1(const void* p) { uint32_t v; asm volatile("ld.global.nc.u32 %0,[%1];" : "=r"(v) : "l"(p)); return v; }
__device__ __forceinline__ uint32_t lds32(uint32_t a) { uint32_t v; asm volatile("ld.shared.u32 %0,[%1];" : "=r"(v) : "r"(a)); return v; }
__device__ __forceinline__ unsigned ld_rlx(const unsigned* p) { unsigned v; asm volatile("ld.relaxed.gpu.global.u32 %0,[%1];" : "=r"(v) : "l"(p) : "memory"); return v; }
__device__ __forceinline__ uint4 ld_rlx4(const void* p) {
  uint4 v; asm volatile("ld.relaxed.gpu.global.v4.u32 {%0,%1,%2,%3},[%4];" : "=r"(v.x), "=r"(v.y), "=r"(v.z), "=r"(v.w) : "l"(p) : "memory"); return v;
}
__device__ __forceinline__ uint2 ld_rlx2(const void* p) { uint2 v; asm volatile("ld.relaxed.gpu.global.v2.u32 {%0,%1},[%2];" : "=r"(v.x), "=r"(v.y) : "l"(p) : "memory"); return v; }
__device__ __forceinline__ void st_rlx2(void* p, uint32_t a, uint32_t b) { asm volatile("st.relaxed.gpu.global.v2.u32 [%0],{%1,%2};" ::"l"(p), "r"(a), "r"(b) : "memory"); }
__device__ __forceinline__ void st_rlx(void* p, uint32_t a) { asm volatile("st.relaxed.gpu.global.u32 [%0],%1;" ::"l"(p), "r"(a) : "memory"); }
#define PUB 15
template <int SITE> __device__ __forceinline__ void release() { if (PUB & SITE) asm volatile("fence.release.gpu;" ::: "memory"); }
__device__ __forceinline__ void signal_flag(unsigned* p, unsigned val) { asm volatile("st.relaxed.gpu.global.u32 [%0],%1;" ::"l"(p), "r"(val) : "memory"); }
__device__ __forceinline__ void signal_cnt(unsigned* p, unsigned n) { asm volatile("red.relaxed.gpu.global.add.u32 [%0],%1;" ::"l"(p), "r"(n) : "memory"); }
__device__ __forceinline__ void wait_flags(const unsigned* p, unsigned val, uint32_t need, uint32_t& ready) {
#pragma unroll 1
  for (int it = 0; (ready & need) != need && it < SPIN; it++) ready = __ballot_sync(0xffffffff, ld_rlx(p) == val);
}
__device__ __forceinline__ void wait_cnt(const unsigned* p, unsigned tgt) {
  asm volatile("{ .reg .pred p; .reg .u32 c; .reg .s32 v; mov.u32 c, 0;\n"
               "W: ld.relaxed.gpu.global.u32 v, [%0]; sub.s32 v, v, %1; setp.ge.s32 p, v, 0; @p bra.uni D;\n"
               "add.u32 c, c, 1; setp.lt.u32 p, c, 0x100000; @p bra.uni W;\nD: }" ::"l"(p), "r"(tgt) : "memory");
}
__device__ __forceinline__ uint32_t pack_bf(float lo, float hi) { uint32_t r; asm("cvt.rn.bf16x2.f32 %0, %1, %2;" : "=r"(r) : "f"(hi), "f"(lo)); return r; }
__device__ __forceinline__ float bf_lo(uint32_t v) { return __uint_as_float(v << 16); }
__device__ __forceinline__ float bf_hi(uint32_t v) { return __uint_as_float(v & 0xffff0000u); }
__device__ __forceinline__ float bf_rn(float x) { return __bfloat162float(__float2bfloat16_rn(x)); }
__device__ __forceinline__ float frcp(float x) { float r; asm("rcp.approx.ftz.f32 %0,%1;" : "=f"(r) : "f"(x)); return r; }
__device__ __forceinline__ float fsqrt(float x) { float r; asm("sqrt.approx.ftz.f32 %0,%1;" : "=f"(r) : "f"(x)); return r; }
__device__ __forceinline__ float frsqrt(float x) { float r; asm("rsqrt.approx.ftz.f32 %0,%1;" : "=f"(r) : "f"(x)); return r; }
__device__ __forceinline__ uint32_t hmul2(uint32_t a, uint32_t b) { uint32_t r; asm("mul.rn.bf16x2 %0,%1,%2;" : "=r"(r) : "r"(a), "r"(b)); return r; }
__device__ __forceinline__ uint32_t hfma2(uint32_t a, uint32_t b, uint32_t c) { uint32_t r; asm("fma.rn.bf16x2 %0,%1,%2,%3;" : "=r"(r) : "r"(a), "r"(b), "r"(c)); return r; }
__device__ __forceinline__ float2 cmul(float2 a, float2 b) { return make_float2(a.x * b.x - a.y * b.y, a.x * b.y + a.y * b.x); }
__device__ __forceinline__ float2 cfma(float2 a, float2 b, float2 c) {
  return make_float2(fmaf(a.x, b.x, fmaf(-a.y, b.y, c.x)), fmaf(a.x, b.y, fmaf(a.y, b.x, c.y)));
}
__device__ __forceinline__ uint32_t tagf(float v, uint32_t tag) { return (__float_as_uint(v) & ~1u) | tag; }
__device__ __forceinline__ float untag(uint32_t v) { return __uint_as_float(v & ~1u); }
__device__ __forceinline__ bool untagged(const uint4& v, uint32_t tag) { return (((v.x ^ tag) | (v.y ^ tag) | (v.z ^ tag) | (v.w ^ tag)) & 1) != 0; }
__device__ __forceinline__ bool untagged(const uint2& v, uint32_t tag) { return (((v.x ^ tag) | (v.y ^ tag)) & 1) != 0; }
__device__ __forceinline__ float2 lam_bar(float lr, float li, float ldt) {
  float dt = bf_rn(expf(ldt)); float e = expf(dt * lr), s, c; sincospif(dt * li * 0.31830988618379067f, &s, &c); return make_float2(e * c, e * s);
}

__device__ __forceinline__ int conv_ch(uint32_t c, int s) { return s * ((c >> 21) & 255) + (c & 255) - (s >= (int)(c >> 29) ? 8 : 0); }
struct Role {
  uint32_t v, c, p;
  __device__ __forceinline__ int tb() const { return v & 15; }
  __device__ __forceinline__ int cb() const { return (v >> 4) & 15; }
  __device__ __forceinline__ int b() const { return (v >> 8) & 255; }
  __device__ __forceinline__ int ubase() const { return (v >> 16) & 7; }
  __device__ __forceinline__ int ugs() const { return (v >> 19) & 7; }
  __device__ __forceinline__ int wpart() const { return (v >> 22) & 7; }
  __device__ __forceinline__ int rank() const { return (v >> 26) & 7; }
  __device__ __forceinline__ int cs() const { return (v >> 29) ? 8 : 2; }
  __device__ __forceinline__ int ch(int s) const { return conv_ch(c, s); }
  __device__ __forceinline__ int wlo() const { return p & 1; }
  __device__ __forceinline__ int whi() const { return (p >> 1) & 1; }
  __device__ __forceinline__ uint32_t wmask() const { return (p >> 2) & 255; }
  __device__ __forceinline__ uint32_t umask() const { return (p >> 10) & 255; }
  __device__ __forceinline__ int uj() const { return (p >> 20) & 31; }
  __device__ __forceinline__ int sm() const { return (p >> 25) & 15; }
  __device__ __forceinline__ int nch() const { return (c >> 10) & 7; }
  __device__ __forceinline__ int nprep() const { return (c >> 13) & 255; }
};

__device__ __forceinline__ void wgmma_ss80(float (&d)[40], uint64_t da, uint64_t db, int sd){
  asm volatile("{ .reg .pred p; setp.ne.b32 p, %42, 0;\n"
   "wgmma.mma_async.sync.aligned.m64n80k16.f32.bf16.bf16 {%0, %1, %2, %3, %4, %5, %6, %7, %8, %9, %10, %11, %12, %13, %14, %15, %16, %17, %18, %19, %20, %21, %22, %23, %24, %25, %26, %27, %28, %29, %30, %31, %32, %33, %34, %35, %36, %37, %38, %39}, %40, %41, p, 1, 1, 0, 0; }\n"
   : "+f"(d[0]), "+f"(d[1]), "+f"(d[2]), "+f"(d[3]), "+f"(d[4]), "+f"(d[5]), "+f"(d[6]), "+f"(d[7]), "+f"(d[8]), "+f"(d[9]), "+f"(d[10]), "+f"(d[11]), "+f"(d[12]), "+f"(d[13]), "+f"(d[14]), "+f"(d[15]), "+f"(d[16]), "+f"(d[17]), "+f"(d[18]), "+f"(d[19]), "+f"(d[20]), "+f"(d[21]), "+f"(d[22]), "+f"(d[23]), "+f"(d[24]), "+f"(d[25]), "+f"(d[26]), "+f"(d[27]), "+f"(d[28]), "+f"(d[29]), "+f"(d[30]), "+f"(d[31]), "+f"(d[32]), "+f"(d[33]), "+f"(d[34]), "+f"(d[35]), "+f"(d[36]), "+f"(d[37]), "+f"(d[38]), "+f"(d[39]) : "l"(da), "l"(db), "r"(sd));
}
__device__ __forceinline__ void wgmma_ss160(float (&d)[80], uint64_t da, uint64_t db, int sd){
  asm volatile("{ .reg .pred p; setp.ne.b32 p, %82, 0;\n"
   "wgmma.mma_async.sync.aligned.m64n160k16.f32.bf16.bf16 {%0, %1, %2, %3, %4, %5, %6, %7, %8, %9, %10, %11, %12, %13, %14, %15, %16, %17, %18, %19, %20, %21, %22, %23, %24, %25, %26, %27, %28, %29, %30, %31, %32, %33, %34, %35, %36, %37, %38, %39, %40, %41, %42, %43, %44, %45, %46, %47, %48, %49, %50, %51, %52, %53, %54, %55, %56, %57, %58, %59, %60, %61, %62, %63, %64, %65, %66, %67, %68, %69, %70, %71, %72, %73, %74, %75, %76, %77, %78, %79}, %80, %81, p, 1, 1, 0, 0; }\n"
   : "+f"(d[0]), "+f"(d[1]), "+f"(d[2]), "+f"(d[3]), "+f"(d[4]), "+f"(d[5]), "+f"(d[6]), "+f"(d[7]), "+f"(d[8]), "+f"(d[9]), "+f"(d[10]), "+f"(d[11]), "+f"(d[12]), "+f"(d[13]), "+f"(d[14]), "+f"(d[15]), "+f"(d[16]), "+f"(d[17]), "+f"(d[18]), "+f"(d[19]), "+f"(d[20]), "+f"(d[21]), "+f"(d[22]), "+f"(d[23]), "+f"(d[24]), "+f"(d[25]), "+f"(d[26]), "+f"(d[27]), "+f"(d[28]), "+f"(d[29]), "+f"(d[30]), "+f"(d[31]), "+f"(d[32]), "+f"(d[33]), "+f"(d[34]), "+f"(d[35]), "+f"(d[36]), "+f"(d[37]), "+f"(d[38]), "+f"(d[39]), "+f"(d[40]), "+f"(d[41]), "+f"(d[42]), "+f"(d[43]), "+f"(d[44]), "+f"(d[45]), "+f"(d[46]), "+f"(d[47]), "+f"(d[48]), "+f"(d[49]), "+f"(d[50]), "+f"(d[51]), "+f"(d[52]), "+f"(d[53]), "+f"(d[54]), "+f"(d[55]), "+f"(d[56]), "+f"(d[57]), "+f"(d[58]), "+f"(d[59]), "+f"(d[60]), "+f"(d[61]), "+f"(d[62]), "+f"(d[63]), "+f"(d[64]), "+f"(d[65]), "+f"(d[66]), "+f"(d[67]), "+f"(d[68]), "+f"(d[69]), "+f"(d[70]), "+f"(d[71]), "+f"(d[72]), "+f"(d[73]), "+f"(d[74]), "+f"(d[75]), "+f"(d[76]), "+f"(d[77]), "+f"(d[78]), "+f"(d[79]) : "l"(da), "l"(db), "r"(sd));
}
template<int N> __device__ __forceinline__ void wgmma_rs(float (&d)[N/2], uint32_t a0, uint32_t a1, uint32_t a2, uint32_t a3, uint64_t db, int sd);
template<> __device__ __forceinline__ void wgmma_rs<16>(float (&d)[8], uint32_t a0, uint32_t a1, uint32_t a2, uint32_t a3, uint64_t db, int sd){
  asm volatile("{ .reg .pred p; setp.ne.b32 p, %13, 0;\n"
   "wgmma.mma_async.sync.aligned.m64n16k16.f32.bf16.bf16 {%0, %1, %2, %3, %4, %5, %6, %7}, {%8,%9,%10,%11}, %12, p, 1, 1, 0; }\n"
   : "+f"(d[0]), "+f"(d[1]), "+f"(d[2]), "+f"(d[3]), "+f"(d[4]), "+f"(d[5]), "+f"(d[6]), "+f"(d[7]) : "r"(a0), "r"(a1), "r"(a2), "r"(a3), "l"(db), "r"(sd));
}
template<> __device__ __forceinline__ void wgmma_rs<32>(float (&d)[16], uint32_t a0, uint32_t a1, uint32_t a2, uint32_t a3, uint64_t db, int sd){
  asm volatile("{ .reg .pred p; setp.ne.b32 p, %21, 0;\n"
   "wgmma.mma_async.sync.aligned.m64n32k16.f32.bf16.bf16 {%0, %1, %2, %3, %4, %5, %6, %7, %8, %9, %10, %11, %12, %13, %14, %15}, {%16,%17,%18,%19}, %20, p, 1, 1, 0; }\n"
   : "+f"(d[0]), "+f"(d[1]), "+f"(d[2]), "+f"(d[3]), "+f"(d[4]), "+f"(d[5]), "+f"(d[6]), "+f"(d[7]), "+f"(d[8]), "+f"(d[9]), "+f"(d[10]), "+f"(d[11]), "+f"(d[12]), "+f"(d[13]), "+f"(d[14]), "+f"(d[15]) : "r"(a0), "r"(a1), "r"(a2), "r"(a3), "l"(db), "r"(sd));
}
template<> __device__ __forceinline__ void wgmma_rs<48>(float (&d)[24], uint32_t a0, uint32_t a1, uint32_t a2, uint32_t a3, uint64_t db, int sd){
  asm volatile("{ .reg .pred p; setp.ne.b32 p, %29, 0;\n"
   "wgmma.mma_async.sync.aligned.m64n48k16.f32.bf16.bf16 {%0, %1, %2, %3, %4, %5, %6, %7, %8, %9, %10, %11, %12, %13, %14, %15, %16, %17, %18, %19, %20, %21, %22, %23}, {%24,%25,%26,%27}, %28, p, 1, 1, 0; }\n"
   : "+f"(d[0]), "+f"(d[1]), "+f"(d[2]), "+f"(d[3]), "+f"(d[4]), "+f"(d[5]), "+f"(d[6]), "+f"(d[7]), "+f"(d[8]), "+f"(d[9]), "+f"(d[10]), "+f"(d[11]), "+f"(d[12]), "+f"(d[13]), "+f"(d[14]), "+f"(d[15]), "+f"(d[16]), "+f"(d[17]), "+f"(d[18]), "+f"(d[19]), "+f"(d[20]), "+f"(d[21]), "+f"(d[22]), "+f"(d[23]) : "r"(a0), "r"(a1), "r"(a2), "r"(a3), "l"(db), "r"(sd));
}
template<> __device__ __forceinline__ void wgmma_rs<64>(float (&d)[32], uint32_t a0, uint32_t a1, uint32_t a2, uint32_t a3, uint64_t db, int sd){
  asm volatile("{ .reg .pred p; setp.ne.b32 p, %37, 0;\n"
   "wgmma.mma_async.sync.aligned.m64n64k16.f32.bf16.bf16 {%0, %1, %2, %3, %4, %5, %6, %7, %8, %9, %10, %11, %12, %13, %14, %15, %16, %17, %18, %19, %20, %21, %22, %23, %24, %25, %26, %27, %28, %29, %30, %31}, {%32,%33,%34,%35}, %36, p, 1, 1, 0; }\n"
   : "+f"(d[0]), "+f"(d[1]), "+f"(d[2]), "+f"(d[3]), "+f"(d[4]), "+f"(d[5]), "+f"(d[6]), "+f"(d[7]), "+f"(d[8]), "+f"(d[9]), "+f"(d[10]), "+f"(d[11]), "+f"(d[12]), "+f"(d[13]), "+f"(d[14]), "+f"(d[15]), "+f"(d[16]), "+f"(d[17]), "+f"(d[18]), "+f"(d[19]), "+f"(d[20]), "+f"(d[21]), "+f"(d[22]), "+f"(d[23]), "+f"(d[24]), "+f"(d[25]), "+f"(d[26]), "+f"(d[27]), "+f"(d[28]), "+f"(d[29]), "+f"(d[30]), "+f"(d[31]) : "r"(a0), "r"(a1), "r"(a2), "r"(a3), "l"(db), "r"(sd));
}
template<> __device__ __forceinline__ void wgmma_rs<80>(float (&d)[40], uint32_t a0, uint32_t a1, uint32_t a2, uint32_t a3, uint64_t db, int sd){
  asm volatile("{ .reg .pred p; setp.ne.b32 p, %45, 0;\n"
   "wgmma.mma_async.sync.aligned.m64n80k16.f32.bf16.bf16 {%0, %1, %2, %3, %4, %5, %6, %7, %8, %9, %10, %11, %12, %13, %14, %15, %16, %17, %18, %19, %20, %21, %22, %23, %24, %25, %26, %27, %28, %29, %30, %31, %32, %33, %34, %35, %36, %37, %38, %39}, {%40,%41,%42,%43}, %44, p, 1, 1, 0; }\n"
   : "+f"(d[0]), "+f"(d[1]), "+f"(d[2]), "+f"(d[3]), "+f"(d[4]), "+f"(d[5]), "+f"(d[6]), "+f"(d[7]), "+f"(d[8]), "+f"(d[9]), "+f"(d[10]), "+f"(d[11]), "+f"(d[12]), "+f"(d[13]), "+f"(d[14]), "+f"(d[15]), "+f"(d[16]), "+f"(d[17]), "+f"(d[18]), "+f"(d[19]), "+f"(d[20]), "+f"(d[21]), "+f"(d[22]), "+f"(d[23]), "+f"(d[24]), "+f"(d[25]), "+f"(d[26]), "+f"(d[27]), "+f"(d[28]), "+f"(d[29]), "+f"(d[30]), "+f"(d[31]), "+f"(d[32]), "+f"(d[33]), "+f"(d[34]), "+f"(d[35]), "+f"(d[36]), "+f"(d[37]), "+f"(d[38]), "+f"(d[39]) : "r"(a0), "r"(a1), "r"(a2), "r"(a3), "l"(db), "r"(sd));
}
template<> __device__ __forceinline__ void wgmma_rs<96>(float (&d)[48], uint32_t a0, uint32_t a1, uint32_t a2, uint32_t a3, uint64_t db, int sd){
  asm volatile("{ .reg .pred p; setp.ne.b32 p, %53, 0;\n"
   "wgmma.mma_async.sync.aligned.m64n96k16.f32.bf16.bf16 {%0, %1, %2, %3, %4, %5, %6, %7, %8, %9, %10, %11, %12, %13, %14, %15, %16, %17, %18, %19, %20, %21, %22, %23, %24, %25, %26, %27, %28, %29, %30, %31, %32, %33, %34, %35, %36, %37, %38, %39, %40, %41, %42, %43, %44, %45, %46, %47}, {%48,%49,%50,%51}, %52, p, 1, 1, 0; }\n"
   : "+f"(d[0]), "+f"(d[1]), "+f"(d[2]), "+f"(d[3]), "+f"(d[4]), "+f"(d[5]), "+f"(d[6]), "+f"(d[7]), "+f"(d[8]), "+f"(d[9]), "+f"(d[10]), "+f"(d[11]), "+f"(d[12]), "+f"(d[13]), "+f"(d[14]), "+f"(d[15]), "+f"(d[16]), "+f"(d[17]), "+f"(d[18]), "+f"(d[19]), "+f"(d[20]), "+f"(d[21]), "+f"(d[22]), "+f"(d[23]), "+f"(d[24]), "+f"(d[25]), "+f"(d[26]), "+f"(d[27]), "+f"(d[28]), "+f"(d[29]), "+f"(d[30]), "+f"(d[31]), "+f"(d[32]), "+f"(d[33]), "+f"(d[34]), "+f"(d[35]), "+f"(d[36]), "+f"(d[37]), "+f"(d[38]), "+f"(d[39]), "+f"(d[40]), "+f"(d[41]), "+f"(d[42]), "+f"(d[43]), "+f"(d[44]), "+f"(d[45]), "+f"(d[46]), "+f"(d[47]) : "r"(a0), "r"(a1), "r"(a2), "r"(a3), "l"(db), "r"(sd));
}
template<> __device__ __forceinline__ void wgmma_rs<112>(float (&d)[56], uint32_t a0, uint32_t a1, uint32_t a2, uint32_t a3, uint64_t db, int sd){
  asm volatile("{ .reg .pred p; setp.ne.b32 p, %61, 0;\n"
   "wgmma.mma_async.sync.aligned.m64n112k16.f32.bf16.bf16 {%0, %1, %2, %3, %4, %5, %6, %7, %8, %9, %10, %11, %12, %13, %14, %15, %16, %17, %18, %19, %20, %21, %22, %23, %24, %25, %26, %27, %28, %29, %30, %31, %32, %33, %34, %35, %36, %37, %38, %39, %40, %41, %42, %43, %44, %45, %46, %47, %48, %49, %50, %51, %52, %53, %54, %55}, {%56,%57,%58,%59}, %60, p, 1, 1, 0; }\n"
   : "+f"(d[0]), "+f"(d[1]), "+f"(d[2]), "+f"(d[3]), "+f"(d[4]), "+f"(d[5]), "+f"(d[6]), "+f"(d[7]), "+f"(d[8]), "+f"(d[9]), "+f"(d[10]), "+f"(d[11]), "+f"(d[12]), "+f"(d[13]), "+f"(d[14]), "+f"(d[15]), "+f"(d[16]), "+f"(d[17]), "+f"(d[18]), "+f"(d[19]), "+f"(d[20]), "+f"(d[21]), "+f"(d[22]), "+f"(d[23]), "+f"(d[24]), "+f"(d[25]), "+f"(d[26]), "+f"(d[27]), "+f"(d[28]), "+f"(d[29]), "+f"(d[30]), "+f"(d[31]), "+f"(d[32]), "+f"(d[33]), "+f"(d[34]), "+f"(d[35]), "+f"(d[36]), "+f"(d[37]), "+f"(d[38]), "+f"(d[39]), "+f"(d[40]), "+f"(d[41]), "+f"(d[42]), "+f"(d[43]), "+f"(d[44]), "+f"(d[45]), "+f"(d[46]), "+f"(d[47]), "+f"(d[48]), "+f"(d[49]), "+f"(d[50]), "+f"(d[51]), "+f"(d[52]), "+f"(d[53]), "+f"(d[54]), "+f"(d[55]) : "r"(a0), "r"(a1), "r"(a2), "r"(a3), "l"(db), "r"(sd));
}
template<> __device__ __forceinline__ void wgmma_rs<128>(float (&d)[64], uint32_t a0, uint32_t a1, uint32_t a2, uint32_t a3, uint64_t db, int sd){
  asm volatile("{ .reg .pred p; setp.ne.b32 p, %69, 0;\n"
   "wgmma.mma_async.sync.aligned.m64n128k16.f32.bf16.bf16 {%0, %1, %2, %3, %4, %5, %6, %7, %8, %9, %10, %11, %12, %13, %14, %15, %16, %17, %18, %19, %20, %21, %22, %23, %24, %25, %26, %27, %28, %29, %30, %31, %32, %33, %34, %35, %36, %37, %38, %39, %40, %41, %42, %43, %44, %45, %46, %47, %48, %49, %50, %51, %52, %53, %54, %55, %56, %57, %58, %59, %60, %61, %62, %63}, {%64,%65,%66,%67}, %68, p, 1, 1, 0; }\n"
   : "+f"(d[0]), "+f"(d[1]), "+f"(d[2]), "+f"(d[3]), "+f"(d[4]), "+f"(d[5]), "+f"(d[6]), "+f"(d[7]), "+f"(d[8]), "+f"(d[9]), "+f"(d[10]), "+f"(d[11]), "+f"(d[12]), "+f"(d[13]), "+f"(d[14]), "+f"(d[15]), "+f"(d[16]), "+f"(d[17]), "+f"(d[18]), "+f"(d[19]), "+f"(d[20]), "+f"(d[21]), "+f"(d[22]), "+f"(d[23]), "+f"(d[24]), "+f"(d[25]), "+f"(d[26]), "+f"(d[27]), "+f"(d[28]), "+f"(d[29]), "+f"(d[30]), "+f"(d[31]), "+f"(d[32]), "+f"(d[33]), "+f"(d[34]), "+f"(d[35]), "+f"(d[36]), "+f"(d[37]), "+f"(d[38]), "+f"(d[39]), "+f"(d[40]), "+f"(d[41]), "+f"(d[42]), "+f"(d[43]), "+f"(d[44]), "+f"(d[45]), "+f"(d[46]), "+f"(d[47]), "+f"(d[48]), "+f"(d[49]), "+f"(d[50]), "+f"(d[51]), "+f"(d[52]), "+f"(d[53]), "+f"(d[54]), "+f"(d[55]), "+f"(d[56]), "+f"(d[57]), "+f"(d[58]), "+f"(d[59]), "+f"(d[60]), "+f"(d[61]), "+f"(d[62]), "+f"(d[63]) : "r"(a0), "r"(a1), "r"(a2), "r"(a3), "l"(db), "r"(sd));
}

#define BAR(i) (bars + 8u * (uint32_t)(i))

template <int G> __device__ __forceinline__ void conv_frags(uint32_t (&a)[12], uint32_t abase) {
#pragma unroll
  for (int i = 0; i < 12; i++) a[i] = lds32(abase + (G * 4 + i / 3) * 128 + (i % 3) * 4);
}
__device__ __forceinline__ void kv_prefetch(const __nv_bfloat16* pf, int task) { prefetch_if(pf + 64 * (task & 31) * DM + 64 * (task >> 5), task < 320); }
__device__ __forceinline__ void kv_load(const Params& P, Scratch* S, int task, int tid, uint32_t (&k_)[19], uint32_t (&v_)[16], uint4& sk) {
  const int row = 64 * (task & 31) + 16 * (tid >> 5), ch = 64 * (task >> 5) + 2 * (tid & 31);
  const uint32_t* kp = (const uint32_t*)(P.k + (size_t)row * DM + ch);
  const uint32_t* vp = (const uint32_t*)(P.v + (size_t)row * DM + ch);
  const uint32_t* hp = row > 0 ? kp - 3 * (DM / 2) : S->zero;
  const int hs = row > 0 ? DM / 2 : 0;
  asm volatile("ld.global.nc.v4.u32 {%0,%1,%2,%3},[%4];" : "=r"(sk.x), "=r"(sk.y), "=r"(sk.z), "=r"(sk.w) : "l"(P.shk + ch * 4));
#pragma unroll
  for (int i = 0; i < 3; i++) k_[i] = ldg1(hp + i * hs);
#pragma unroll
  for (int i = 0; i < 16; i++) { k_[i + 3] = ldg1(kp + i * (DM / 2)); v_[i] = ldg1(vp + i * (DM / 2)); }
}
template <int SH> __device__ __forceinline__ void xb_prefetch(const Head& H, int id, int tid, int c0) {
  const int ri = tid >> SH, rr = 11 * id + ri - 16;
  const __nv_bfloat16* p = ri < 16 ? H.x + (size_t)(16 * min(id, 127) + ri) * DM : (rr < DM ? H.b0 : H.b1 - DM * DM) + (size_t)rr * DM;
  prefetch_if(p + c0 + 64 * (tid & ((1 << SH) - 1)), ri < 16 || (ri < 27 && rr < 2 * DM));
}
__device__ __forceinline__ uint4 ldg4(const void* p) { uint4 v; asm volatile("ld.global.nc.v4.u32 {%0,%1,%2,%3},[%4];" : "=r"(v.x), "=r"(v.y), "=r"(v.z), "=r"(v.w) : "l"(p)); return v; }
__device__ __forceinline__ uint4 lds4(uint32_t a) { uint4 v; asm volatile("ld.shared.v4.u32 {%0,%1,%2,%3},[%4];" : "=r"(v.x), "=r"(v.y), "=r"(v.z), "=r"(v.w) : "r"(a) : "memory"); return v; }
__device__ __forceinline__ void discretise(const Head& H, const Params& P, uint32_t sb, Role R, int lane, uint32_t e1) {
  const uint32_t dn = __ldg((const unsigned short*)P.ssmd + min(conv_ch(R.c, (lane + 7) & 7), DM - 1));
  const int c = 32 * min(R.cb(), 9) + lane;
  const uint32_t lr2 = ldg1(P.lre + 2 * c), li2 = ldg1(P.lim + 2 * c), ld2 = ldg1(P.ldt + 2 * c);
  asm volatile("st.shared.u32 [%0],%1;" ::"r"(sb + MISC_OFF + 4 * (lane & 7)), "r"((lane & 7) ? dn : e1) : "memory");
#pragma unroll 1
  for (int i = 0; i < 2; i++) {
    const float lr = bf_hi(lr2 << (16 - 16 * i)), li = bf_hi(li2 << (16 - 16 * i));
    const float2 lb = lam_bar(lr, li, bf_hi(ld2 << (16 - 16 * i)));
    const float nx = lb.x - 1.f, ny = lb.y, inv = 2.f * frcp(lr * lr + li * li), cx = (nx * lr + ny * li) * inv, cy = (ny * lr - nx * li) * inv;
    const bool sw = !H.swap;
    asm volatile("st.shared.v4.f32 [%0],{%1,%2,%3,%4};" ::"r"(sb + LAM_OFF + 32 * lane + 16 * i), "f"(lb.x), "f"(sw ? -lb.y : lb.y), "f"(sw ? -cy : cx), "f"(sw ? cx : -cy) : "memory");
  }
  __syncwarp();
}
__device__ __forceinline__ void aux_prep(const Head& H, const Params& P, uint32_t sb, Role R, int tid, long long t_start) {
  Scratch* const S = H.s;
  const uint32_t bars = sb + BAR_OFF;
  tid = opaque(tid);
  const int w = tid >> 5, lane = tid & 31, tb = R.tb(), cb = R.cb();
  uint32_t k_[19], v_[16];
  uint4 sk;
  int task = R.b() < R.nprep() ? R.b() : 320;
  delay(KVDLY);
  PROFC(tid == 0, 345);
  kv_load(P, S, min(task, 319), tid, k_, v_, sk);
  const __nv_bfloat16* pf = (tid < 64 ? P.k : P.v) + (tid & 63) * DM;
  const int j = lane >> 3, sm = min(R.sm(), 9), trow = 160 * tb + 4 * sm + (tb < 12 ? 40 : 32) * w + j;
  const uint32_t so = sb + (2 * w + (j & 1) + 8 * (j >> 1)) * 128 + 16 * (lane & 7), xo = so + sm * 2048, wo = so + (tb & 1) * 8192 + (tb & 6) * 1024;
  const __nv_bfloat16* xp = H.x + (size_t)min(trow, SEQ - 1) * DM + 384 + 8 * (lane & 7);
  const __nv_bfloat16* bp = (j < 2 ? H.b0 : H.b1) + (size_t)(64 * cb + 32 * (tb & 1) + 4 * (tb & 6) + 2 * w + (j & 1)) * DM + 384 + 8 * (lane & 7);
  float s = 0.f, s2 = 0.f, sr = 0.f;
#define STAT(m, n) { const uint32_t xw[4] = {m.x, m.y, m.z, m.w}, bw[4] = {n.x, n.y, n.z, n.w}; \
  _Pragma("unroll") for (int i = 0; i < 4; i++) { const float u = bf_lo(xw[i]), v = bf_hi(xw[i]); s += u + v; s2 = fmaf(u, u, fmaf(v, v, s2)); sr += bf_lo(bw[i]) + bf_hi(bw[i]); } }
#define STATS(K0, K1) _Pragma("unroll 1") for (int kb = K0; kb < K1; kb++) { \
    mbar_wait(BAR(B_F1 + kb)); \
    const uint4 a = lds4(xo + ((uint32_t)(XTAB0 >> (6 * kb)) & 63) * 4096), c = lds4(wo + ((uint32_t)(WTAB0 >> (6 * kb)) & 63) * 4096); \
    STAT(a, c) \
    asm volatile("" : "+f"(s), "+f"(s2), "+f"(sr)); \
    if (XPFAT >= K0 && XPFAT < K1) prefetch_if(((lane & 4) ? bp : xp) + 64 * (lane & 3), kb == XPFAT); \
    kv_prefetch(pf, kb == KPFAT ? task + R.nprep() : kb == KPFAT2 ? task + 2 * R.nprep() : 320); \
  } \
  __syncwarp(); mbar_arrive_if(BAR(B_AX + K0 / 3), lane == 0);
  STATS(0, 3)
  PROFC(tid == 0, 349);
    {
      uint4 m[4], n[4];
#pragma unroll
      for (int i = 0; i < 4; i++) { m[i] = ldg4(xp + 64 * i); n[i] = ldg4(bp + 64 * i); }
      STATS(3, 6)
      PROFC(tid == 0, 346);
      mbar_wait(BAR(B_LM));
      const uint32_t tag = lds32(sb + MISC_OFF) & 1;
#pragma unroll
      for (int i = 0; i < 4; i++) { const uint4 a = m[i], c = n[i]; STAT(a, c) }
      PROFC(tid == 0 && s2 != 1.2345f, 347);
#pragma unroll
      for (int o = 1; o <= 4; o <<= 1) { s += __shfl_xor_sync(0xffffffff, s, o); s2 += __shfl_xor_sync(0xffffffff, s2, o); sr += __shfl_xor_sync(0xffffffff, sr, o); }
      const float mn = s * (1.f / DM), rs = frcp(bf_rn(fsqrt(bf_rn(bf_rn(fmaxf(s2 * (1.f / DM) - mn * mn, 0.f)) + 1e-5f))));
      asm volatile("{ .reg .pred p; setp.ne.u32 p, %2, 0; @p st.relaxed.gpu.global.u32 [%0],%1; }"
                   ::"l"((uint32_t*)(S->RS + (8 * cb + 4 * (tb & 1) + (tb >> 1)) * 16 + 4 * w + (j & 1)) + (lane & 4) + (j >> 1)), "r"(tagf(sr, tag)),
                   "r"((uint32_t)(tb < 8 && (lane & 3) == 0)) : "memory");
      asm volatile("{ .reg .pred p; setp.ne.u32 p, %3, 0; @p st.relaxed.gpu.global.v2.u32 [%0],{%1,%2}; }"
                   ::"l"(S->S + trow), "r"(tagf(rs, tag)), "r"(tagf(-bf_rn(mn) * rs, tag)), "r"((uint32_t)(R.sm() < 10 && (lane & 7) == 0)) : "memory");
      PROFC(tid == 0, 3);
    }
#pragma unroll 1
  for (int r = 0; task < 320; r++) {
    {
      const uint32_t T0 = __byte_perm(sk.x, sk.z, 0x5410), T1 = __byte_perm(sk.x, sk.z, 0x7632);
      const uint32_t T2 = __byte_perm(sk.y, sk.w, 0x5410), T3 = __byte_perm(sk.y, sk.w, 0x7632);
      PROFC(tid == 0 && v_[15] != 0x12345, 336 + r);
      uint32_t o[16];
#pragma unroll
      for (int t = 0; t < 16; t += 2) {
        const uint32_t a = hmul2(hfma2(k_[t + 3], T0, hfma2(k_[t + 2], T1, hfma2(k_[t + 1], T2, hmul2(k_[t], T3)))), v_[t]);
        const uint32_t c = hmul2(hfma2(k_[t + 4], T0, hfma2(k_[t + 3], T1, hfma2(k_[t + 2], T2, hmul2(k_[t + 1], T3)))), v_[t + 1]);
        const int wd = ((7 - t / 2) >> 1) + 4 * ((7 - t / 2) & 1);
        o[wd] = __byte_perm(c, a, 0x5410); o[8 + wd] = __byte_perm(c, a, 0x7632);
        asm volatile("" : "+r"(o[wd]), "+r"(o[8 + wd]));
        if (t == PFAT) kv_prefetch(pf, task + (1 + PFD) * R.nprep());
      }
      PROFC(tid == 0, 330 + 2 * r);
      const int ph = task & 1;
      task += R.nprep();
      if (ORD == 0 && task < 320) kv_load(P, S, task, tid, k_, v_, sk);
      mbar_wait(BAR(B_E1 + 3)); mbar_wait(BAR(B_AX + 1));
#pragma unroll
      for (int i = 0; i < 4; i++) {
        const int row = 2 * lane + (i >> 1);
        asm volatile("st.shared.v4.u32 [%0],{%1,%2,%3,%4};" ::"r"(sb + KS_OFF + r * 8192 + row * 128 + (((2 * w + ((i & 1) ^ ph)) ^ (row & 7)) << 4)),
                     "r"(o[4 * i]), "r"(o[4 * i + 1]), "r"(o[4 * i + 2]), "r"(o[4 * i + 3]) : "memory");
      }
      __syncwarp();
      mbar_arrive_if(BAR(B_PS + r), lane == 0);
      PROFC(tid == 0, 331 + 2 * r);
      if (ORD == 1 && task < 320) kv_load(P, S, task, tid, k_, v_, sk);
    }
  }
#undef STAT
#undef STATS
  PROFC(tid == 0, 40);
}
#define SPLIT(G) asm volatile("{ .reg .pred p; .reg .u32 r; L: mov.u32 r, %%clock; setp.eq.u32 p, r, %0; @p bra.uni L; }" ::"n"(G) : "memory")
template <bool AUX>
__device__ __forceinline__ void conv_loop(uint32_t sb, uint32_t rc, int wg, int tid, long long t_start) {
  sb = opaque(sb); rc = opaque(rc);
  const uint32_t bars = sb + BAR_OFF;
  int slot = AUX ? 0 : wg + 1;
  mbar_wait(BAR(B_LM));
#pragma unroll 1
  while (slot < (int)((rc >> 10) & 7)) {
    tid = opaque(tid);
    const int w = tid >> 5, lane = tid & 31, g = lane >> 2, q = lane & 3;
    const uint32_t Dn = lds32(sb + MISC_OFF + 4 + 4 * slot);
    const uint32_t d0 = (g == 1 && q == 3 - w) ? Dn : 0, d1 = (g == 0 && q == 3 - w) ? Dn : 0;
    const uint32_t cb_ = conv_buf(sb, slot), c0 = cb_ + KC_OFS;
    const uint32_t abase = c0 + 2 * (2 * (g & 1) + 4 * w + 16 * (g >> 1) + 4 * q);
    const uint64_t bd = make_desc(cb_ + KV_PAD, 16, 256, 3);
    const bool hi = lane & 16, s1 = lane & 8;
    const int qo = hi ? (q + 1) & 3 : q;
    const int srcA = hi ? (lane & 12) | ((q + 1) & 3) : (lane & 12) | 16 | ((q + 3) & 3);
    const bool h3 = hi && q == 3, wrap = s1 && qo == 3, back = wrap && hi;
    const bool chi = wrap ? !hi : hi;
    const int cq = s1 ? (qo + 1) & 3 : qo;
    const int srcB = (lane & 4) | (s1 ? 0 : 8) | (chi ? 16 | ((cq + 3) & 3) : cq);
    const uint32_t gp = c0 + ((32 * (2 * w + (g & 1)) + (chi ? 256 : 0)) ^ (chi ? 64 : 0) ^ ((conv_ch(rc, slot) & 8) << 2)) + 4 * (2 * cq + (s1 ? 0 : 1));
    uint32_t a[12], f[16], o[8];
    float S[4], T[4], U[2], keep[2], pv[2] = {0.f, 0.f}, pr[4] = {0.f, 0.f, 0.f, 0.f};
    float e0[64], e1[56], e2[48], e3[40], e4[32], e5[24], e6[16], e7[8];
#define UNR _Pragma("unroll")
#define PERM() UNR for (int i = 0; i < 4; i++) { f[4 * i] = __byte_perm(a[3 * i], a[3 * i + 1], 0x5432); f[4 * i + 1] = a[3 * i + 1]; \
                                                 f[4 * i + 2] = __byte_perm(a[3 * i + 1], a[3 * i + 2], 0x5432); f[4 * i + 3] = a[3 * i + 2]; }
#define MMA(N, E) UNR for (int i = 0; i < 4; i++) wgmma_rs<N>(E, f[4 * i], f[4 * i + 1], f[4 * i + 2], f[4 * i + 3], bd - 8 * i, 1); wg_commit();
#define L1(c) UNR for (int i = 0; i < 4; i++) { const float ev = c[i], od = c[4 + i]; S[i] = hi ? (h3 ? ev : od) : ev; \
                                                T[i] = __shfl_sync(0xffffffff, hi ? (h3 ? pr[i] : ev) : od, srcA); pr[i] = od; }
#define L1E() UNR for (int i = 0; i < 4; i++) S[i] += T[i];
#define L2() UNR for (int h = 0; h < 2; h++) { keep[h] = back ? pv[h] : S[2 * h + 1]; pv[h] = S[2 * h + 1]; U[h] = __shfl_sync(0xffffffff, S[2 * h], srcB); }
#define L2E(j) o[j] = pack_bf(keep[0] + U[0], keep[1] + U[1]);
#define GRP(G, N, P, E) UNR for (int i = 0; i < N / 2; i++) asm volatile("mov.b32 %0,%1;" : "=f"(E[i]) : "f"(P[i + 8])); \
    wg_fence(); if (G < 7) conv_frags<(G + 1) & 7>(a, abase); if (G >= 2) { L2() } L1(P) MMA(N, E) SPLIT(G); \
    if (G < 7) { PERM() } if (G >= 2) { L2E((G + 6) & 7) } L1E() wg_wait<0>(); fence_regs(E);
    PROFC(tid == 0, 300 + 4 * slot);
    mbar_wait(BAR(B_KF + slot));
    if (tid == 0) PROF(361 + slot);
    PROFC(tid == 0, 301 + 4 * slot);
    conv_frags<0>(a, abase);
    wg_fence();
    wgmma_rs<128>(e0, d0 << 16, d0, d1 << 16, d1, bd, 0);
    PERM() conv_frags<1>(a, abase); wg_fence(); MMA(128, e0) SPLIT(0); PERM() wg_wait<0>(); fence_regs(e0);
    GRP(1, 112, e0, e1) GRP(2, 96, e1, e2) GRP(3, 80, e2, e3) GRP(4, 64, e3, e4) GRP(5, 48, e4, e5) GRP(6, 32, e5, e6) GRP(7, 16, e6, e7)
    PROFC(tid == 0, 302 + 4 * slot);
    L2() L1(e7) L2E(6) L1E() L2() L2E(7)
    bar_sync(wg + 1, 128);
#pragma unroll
    for (int jj = 0; jj < 8; jj++) asm volatile("st.shared.u32 [%0],%1;" ::"r"(gp + jj * 512), "r"(o[jj]) : "memory");
#undef PERM
#undef MMA
#undef L1
#undef L1E
#undef L2
#undef L2E
#undef GRP
    PROFC(tid == 0, 303 + 4 * slot);
    __syncwarp();
    if (lane == 0) mbar_arrive(BAR(B_GS + slot));
    if (!AUX) break;
    slot = slot ? slot + 1 : 3;
  }
}

#define IDX(J, c, h) (8 * (J) + 4 * ((c) >> 1) + 2 * (h) + ((c) & 1))
__device__ __forceinline__ uint2 lds2(uint32_t a) { uint2 v; asm volatile("ld.shared.v2.u32 {%0,%1},[%2];" : "=r"(v.x), "=r"(v.y) : "r"(a) : "memory"); return v; }
__device__ __forceinline__ void resid_load(float (&r)[40], uint32_t sb, int wg, int tid, const uint4& s) {
  const uint32_t dp = sb + XR_OFF + 8 * (tid & 3), xp = dp + (64 * wg + 16 * (tid >> 5) + ((tid & 31) >> 2)) * 160;
#pragma unroll
  for (int J = 0; J < 5; J++) {
    const uint2 u = lds2(xp + 32 * J), v = lds2(xp + 32 * J + 1280), d = lds2(dp + 20480 + 32 * J);
    r[8 * J] = __uint_as_float(u.x); r[8 * J + 1] = __uint_as_float(u.y); r[8 * J + 2] = __uint_as_float(v.x); r[8 * J + 3] = __uint_as_float(v.y);
    r[8 * J + 4] = __uint_as_float(d.x); r[8 * J + 5] = __uint_as_float(d.y);
  }
  r[30] = untag(s.x); r[31] = untag(s.y); r[38] = untag(s.z); r[39] = untag(s.w);
}
__device__ __forceinline__ void resid_init(float (&r)[40]) {
  const float s[4] = {r[30], r[31], r[38], r[39]};
#pragma unroll
  for (int J = 0; J < 5; J++) {
    uint32_t w[6];
#pragma unroll
    for (int i = 0; i < 6; i++) w[i] = __float_as_uint(r[8 * J + i]);
#pragma unroll
    for (int i = 0; i < 4; i++) {
      const int h = i >> 1, c = 2 * (i & 1);
      const float rs = s[2 * h], nm = s[2 * h + 1], x0 = bf_lo(w[i]), x1 = bf_hi(w[i]);
      const uint32_t t = hmul2(pack_bf(fmaf(x0, rs, nm), fmaf(x1, rs, nm)), w[4 + (i & 1)]);
      r[IDX(J, c, h)] = x0 + bf_lo(t); r[IDX(J, c + 1, h)] = x1 + bf_hi(t);
    }
  }
}

__device__ __forceinline__ float flip(float v, uint32_t m) { return __uint_as_float(__float_as_uint(v) ^ m); }
__device__ __forceinline__ void g1_phase(const int LY, const Head& H, uint32_t sb, int wg, int tid, Role R, float (&xr)[40], long long t_start) {
  Scratch* const S = H.s;
  tid = opaque(tid); sb = opaque(sb); R.v = opaque(R.v);
  const uint32_t bars = sb + BAR_OFF;
  const int cb = R.cb(), tb = R.tb();
  const int w = tid >> 5, lane = tid & 31, g = lane >> 2, q = lane & 3;
  const bool full = tb < 12;
  uint2* Eb = S->E + ((LY * 130 + cb) * 8 + 4 * wg + w) * 16 + g;
  float a[80];
#pragma unroll
  for (int i = 0; i < 80; i++) a[i] = 0.f;
  uint32_t rel = mapa(BAR(B_E1), lane ? R.wpart() : R.ubase() + (w & (R.ugs() - 1)));
  const bool rels = lane == 0 || (tid == 1 && wg != R.wlo());
  {
    uint64_t tw = LY ? WTAB1 : WTAB0, tx = LY ? XTAB1 : XTAB0;
    uint32_t bf = BAR(B_F1);
    if (tid == 0 && wg == 0 && !LY) PROF(351);
    fence_regs(a);
    mbar_wait(bf, LY);
    if (tid == 0 && wg == 0) PROF(LY ? 20 : 4);
#pragma unroll 1
    for (int kb = 0; kb < 10; kb++) {
      const uint64_t da = make_desc(sb + ((uint32_t)tw & 63) * 4096 + wg * 8192, 16, 1024, 1);
      const uint64_t db = make_desc(sb + ((uint32_t)tx & 63) * 4096, 16, 1024, 1);
      wg_fence();
#pragma unroll
      for (int kk = 0; kk < 4; kk++) wgmma_ss160(a, da + 2 * kk, db + 2 * kk, 1);
      wg_commit();
      wg_wait<1>();
      if (kb > 0) { if (rels) mbar_arrive_at(rel); rel += 8; }
      bf += 8; tw >>= 6; tx >>= 6;
      if (kb < 9) mbar_wait(bf, LY);
    }
  }
  if (tid == 0 && wg == 0) PROF(LY ? 19 : 2);
  mbar_wait(BAR(B_LM));
  const uint32_t tag = lds32(sb + MISC_OFF) & 1;
  if (q == 3) st_rlx2(Eb + tb * 1280, tag ^ 1, tag ^ 1);
  float2 lam, mu, mu2;
  float rs0, rs1;
  const uint32_t lamp = sb + LAM_OFF + 16 * (32 * wg + 8 * w + g);
  {
    const uint2* rp = S->RS + (8 * cb + 4 * wg + w) * 16 + 2 * g - (g & 1);
    uint2 v = ld_rlx2(rp);
    asm volatile("ld.shared.v2.f32 {%0,%1},[%2];" : "=f"(lam.x), "=f"(lam.y) : "r"(lamp));
    const float2 l2 = cmul(lam, lam), l4 = cmul(l2, l2), l8 = cmul(l4, l4), l16 = cmul(l8, l8), l32 = cmul(l16, l16);
    mu = full ? cmul(l32, l8) : l32; mu2 = cmul(mu, mu);
#pragma unroll 1
    for (int it = 0; it < SPIN && __any_sync(0xffffffff, untagged(v, tag)); it++) v = ld_rlx2(rp);
    rs0 = untag(v.x); rs1 = untag(v.y);
  }
  if (tid == 0 && wg == 0 && !LY) PROF(39);
  mbar_wait(BAR(B_ST), LY);
  const uint32_t ssm = sb + SSM_OFF + q * (full ? 336 : 272);
  wg_wait<0>(); fence_regs(a);
  if (rels) mbar_arrive_at(rel);
  if (tid == 0 && wg == 0) PROF(LY ? 21 : 5);
  float2 p = make_float2(0.f, 0.f);
#pragma unroll
  for (int j = 0; j < 20; j++) {
    if (j < 16 || full) {
      float4 sv;
      asm volatile("ld.shared.v4.f32 {%0,%1,%2,%3},[%4];" : "=f"(sv.x), "=f"(sv.y), "=f"(sv.z), "=f"(sv.w) : "r"(ssm + 16 * j));
#pragma unroll
      for (int e = 0; e < 2; e++) {
        const int o = 4 * j + e;
        const float r = e ? sv.z : sv.x, nm = e ? sv.w : sv.y;
        a[o] = fmaf(a[o], r, nm * rs0); a[o + 2] = fmaf(a[o + 2], r, nm * rs1);
        p = cfma(lam, p, make_float2(a[o], a[o + 2]));
      }
    }
  }
  {
    float2 t = make_float2(__shfl_up_sync(0xffffffff, p.x, 1, 4), __shfl_up_sync(0xffffffff, p.y, 1, 4));
    if (q >= 1) p = cfma(mu, t, p);
    t = make_float2(__shfl_up_sync(0xffffffff, p.x, 2, 4), __shfl_up_sync(0xffffffff, p.y, 2, 4));
    if (q >= 2) p = cfma(mu2, t, p);
  }
  if (q == 3 && full) st_rlx2(Eb + tb * 1280, tagf(p.x, tag), tagf(p.y, tag));
  if (tid == 0 && wg == 1) PROF(96 + 64 * LY);
  uint2 ev[3];
#pragma unroll
  for (int i = 0; i < 3; i++) { const int j = tb - 1 - q - 4 * i; ev[i] = j >= 0 ? ld_rlx2(Eb + j * 1280) : make_uint2(tag, tag); }
  float2 x = make_float2(__shfl_up_sync(0xffffffff, p.x, 1, 4), __shfl_up_sync(0xffffffff, p.y, 1, 4));
  if (q == 0) x = make_float2(0.f, 0.f);
  float c0, c1;
  asm volatile("ld.shared.v2.f32 {%0,%1},[%2+8];" : "=f"(c0), "=f"(c1) : "r"(lamp));
  const float c2 = -flip(c1, H.swap), c3 = flip(c0, H.swap);
#pragma unroll
  for (int i = 0; i < 40; i++) {
    const int o = 4 * (i >> 1) + (i & 1);
    const float u = a[o], v = a[o + 2];
    a[o] = fmaf(c0, u, c1 * v); a[o + 2] = fmaf(c2, u, c3 * v);
  }
  fence_regs(a);
  if (LY == 0 && R.b() < 128) {
    const int t0 = 16 * g + 8 * wg + 2 * w;
    if (tid == 0 && wg == 1) PROF(366);
    mbar_wait(BAR(B_XR));
    if (tid == 0 && wg == 1) PROF(367);
    uint4 s = lds4(sb + XR_OFF + 20480 + 256 + 8 * t0);
    if (__any_sync(0xffffffff, untagged(s, tag))) {
#pragma unroll 1
      for (int it = 0; it < SPIN; it++) { s = ld_rlx4(S->S + 128 * (R.b() >> 3) + t0); if (!__any_sync(0xffffffff, untagged(s, tag))) break; }
    }
    resid_load(xr, sb, wg, tid, s);
  }
  float2 mq, om4, fq;
  {
    asm volatile("" : "+f"(lam.x), "+f"(lam.y));
    const float2 one = make_float2(1.f, 0.f), l2 = cmul(lam, lam), l4 = cmul(l2, l2), l8 = cmul(l4, l4), l16 = cmul(l8, l8);
    const float2 l80 = full ? mu2 : cmul(mu2, l16), om = cmul(l80, l80), om2 = cmul(om, om);
    mq = cmul((q & 1) ? mu : one, (q & 2) ? mu2 : one);
    om4 = cmul(om2, om2); fq = cmul((q & 1) ? om : one, (q & 2) ? om2 : one);
  }
  mbar_wait(BAR(B_E1 + 9), LY);
  if (tid == 0 && wg == 1) PROF(368 + LY);
#pragma unroll 1
  for (int it = 0; it < SPIN; it++) {
    const bool m0 = untagged(ev[0], tag), m1 = untagged(ev[1], tag), m2 = untagged(ev[2], tag);
    if (!__any_sync(0xffffffff, m0 || m1 || m2)) break;
    if (m0) ev[0] = ld_rlx2(Eb + (tb - 1 - q) * 1280);
    if (m1) ev[1] = ld_rlx2(Eb + (tb - 5 - q) * 1280);
    if (m2) ev[2] = ld_rlx2(Eb + (tb - 9 - q) * 1280);
  }
  if (tid == 0 && wg == 1) PROF(97 + 64 * LY);
  float2 c = make_float2(untag(ev[2].x), untag(ev[2].y));
#pragma unroll
  for (int i = 1; i >= 0; i--) c = cfma(om4, c, make_float2(untag(ev[i].x), untag(ev[i].y)));
  c = cmul(fq, c);
#pragma unroll
  for (int s = 1; s <= 2; s <<= 1) { c.x += __shfl_xor_sync(0xffffffff, c.x, s); c.y += __shfl_xor_sync(0xffffffff, c.y, s); }
  c = cfma(mq, c, x);
  float2 z = make_float2(fmaf(c0, c.x, c1 * c.y), fmaf(c2, c.x, c3 * c.y));
  if (tid == 0 && wg == 0) PROF(LY ? 22 : 6);
  const float2 lc = make_float2(lam.x, flip(lam.y, H.swap));
  const uint32_t hq = sb + (lane >> 4) * 1024 + (lane & 7) * 128 + (((4 * wg + w) ^ (lane & 7)) << 4);
  const uint32_t hp = hq + R_OFF + (lane & 8) * 2048, hp4 = hq + (LY ? R4_OFF1 : R4_OFF0) + (lane & 8) * 512;
#pragma unroll
  for (int j = 0; j < 20; j += 2) {
    if (j < 16 || full) {
      uint32_t o[4];
#pragma unroll
      for (int i = 0; i < 2; i++) {
        const float2 z0 = cfma(lc, z, make_float2(a[4 * (j + i)], a[4 * (j + i) + 2]));
        z = cfma(lc, z0, make_float2(a[4 * (j + i) + 1], a[4 * (j + i) + 3]));
        o[2 * i] = pack_bf(z0.x, z.x); o[2 * i + 1] = pack_bf(z0.y, z.y);
      }
      asm volatile("stmatrix.sync.aligned.m8n8.x4.trans.shared.b16 [%0], {%1,%2,%3,%4};" ::"r"(j < 16 ? hp + j * 1024 : hp4 + (j - 16) * 1024), "r"(o[0]), "r"(o[1]), "r"(o[2]), "r"(o[3]) : "memory");
      if (j & 2) { __syncwarp(); if (lane == 0) mbar_arrive(BAR(B_SH + j / 4)); }
    }
  }
  if (tid == 0 && wg == 0) PROF(LY ? 23 : 7);
  if (lane == 0) PROF(390 + 4 * wg + w);
}

__device__ __forceinline__ void gate_load(float (&G)[40], uint32_t sb, int LY, int wg, int tid, int tb2) {
  const uint32_t bars = sb + BAR_OFF;
  const int lane = tid & 31, w = tid >> 5;
  mbar_wait(BAR(B_GF), LY);
  const int g = lane >> 2, q = lane & 3;
  const uint32_t gb = sb + (LY ? G_OFF1 : G_OFF0) + wg * 10240 + 512 * q + ((32 * w + 4 * g) ^ (64 * ((tb2 ^ q) & 1)) ^ (16 * (q & 2)));
#pragma unroll
  for (int i = 0; i < 20; i++) { const uint32_t v = lds32((gb ^ (16 * (i & 3))) + 128 * (i & 3) + 2048 * (i >> 2)); G[2 * i] = bf_lo(v); G[2 * i + 1] = bf_hi(v); }
  fence_regs(G);
}
__device__ __forceinline__ void g2_phase(const int LY, const Params& P, Scratch* S, uint32_t sb, int wg, int tid, Role R, float (&xr)[40], long long t_start) {
  sb = opaque(sb);
  const uint32_t bars = sb + BAR_OFF;
  if (LY) {
    const int td = opaque(tid), b = (opaque(R.v) >> 8) & 255;
    const uint32_t tag = lds32(sb + MISC_OFF) & 1;
    const uint2* sp = S->S + 2 * SEQ + 128 * (b >> 3) + 4 * (td & 28) + 8 * wg + 2 * (td >> 5);
    if (!(R.cb() & 1)) mbar_wait(BAR(B_HD), 1);
    uint2 dl[5];
#pragma unroll
    for (int J = 0; J < 5; J++) dl[J] = __ldg((const uint2*)(P.dskip + 80 * (b & 7) + 4 * (td & 3) + 16 * J));
    uint4 sv;
#pragma unroll 1
    for (int it = 0; it < SPIN; it++) { sv = ld_rlx4(sp); if (!__any_sync(0xffffffff, untagged(sv, tag))) break; }
#pragma unroll
    for (int h = 0; h < 2; h++)
#pragma unroll
      for (int J = 0; J < 5; J++)
#pragma unroll
        for (int c = 0; c < 4; c++) {
          const float x2 = xr[IDX(J, c, h)];
          const uint32_t dw = (c & 2) ? dl[J].y : dl[J].x;
          xr[IDX(J, c, h)] = fmaf(fmaf(x2, untag(h ? sv.z : sv.x), untag(h ? sv.w : sv.y)), (c & 1) ? bf_hi(dw) : bf_lo(dw), x2);
        }
    fence_regs(xr);
  }
  float acc[40];
#pragma unroll
  for (int i = 0; i < 40; i++) acc[i] = RIAT == 1 ? 0.f : xr[i];
  fence_regs(acc);
#define G2_STEP(st, cs, hf) { \
    const uint64_t da = make_desc(sb + H_OFF + (st) * 32768 + (hf) * 16384 + wg * 8192, 16, 1024, 1), db = make_desc(sb + (cs) * 20480 + (hf) * 10240, 16, 1024, 1); \
    wg_fence(); \
    _Pragma("unroll") for (int kk = 0; kk < 4; kk++) wgmma_ss80(acc, da + 2 * kk, db + 2 * kk, 1); \
    wg_commit(); }
  mbar_wait(BAR(B_F2), LY);
  if (tid == 0 && wg == 0) PROF(LY ? 25 : 10);
  G2_STEP(0, 0, 0)
  mbar_wait(BAR(B_F3), LY);
  G2_STEP(0, 0, 1)
  tid = opaque(tid); R.v = opaque(R.v);
  const uint32_t tag = lds32(sb + MISC_OFF) & 1;
  const int b = R.b(), tb2 = b >> 3, db_ = b & 7;
  const int w = tid >> 5, lane = tid & 31, g = lane >> 2, q = lane & 3;
  const int t0 = 128 * tb2 + 16 * g + 8 * wg + 2 * w;
  const int d0 = 80 * db_ + 4 * q, mrow = 64 * wg + 16 * w + g;
#define GATE(J, c, h) G[8 * (J) + 2 * (c) + (h)]
  uint32_t rel = mapa(BAR(B_E2), lane ? ((w & 1) ? R.wpart() : R.rank()) : R.cs() == 8 ? 4 * wg + w : wg);
  const bool rels = lane == 0 || (lane == 1 && w < 2);
  uint32_t* Mb = S->M + ((2 * LY * 16 + tb2) * 8) * 256 + (wg * 4 + w) * 32 + (2 * g + (q & 1)) * 2 + (q >> 1);
  {
    uint32_t bf = BAR(B_F2 + 1), st = 1, ra = rel + 8 * (B_EA - B_E2);
    const int lag = wg ? (LY ? STG : STG0) / 2 : 0;
#pragma unroll 1
    for (int kp = 1; kp < 10; kp++) {
      const bool more = LY == 0 || kp < 8;
      wg_wait<1>();
      if (lane == 0 && more) mbar_arrive_at(ra + 8 * (st ? st - 1 : 2));
      mbar_wait(bf, LY);
      if (STG && !(STG & 1) && kp == lag) bar_sync(5, 256);
      G2_STEP(st, kp < 5 ? kp : kp - 5, 0)
      wg_wait<1>();
      if (rels && more) mbar_arrive_at(rel);
      rel += 8;
      mbar_wait(bf + 8 * (B_F3 - B_F2), LY);
      if ((STG & 1) && kp == lag) bar_sync(5, 256);
      G2_STEP(st, kp < 5 ? kp : kp - 5, 1)
      if (kp == MIAT) {
        st_rlx(Mb + db_ * 256, tag ^ 1);
        if (LY == 0) st_rlx(Mb + (16 * 8 + db_) * 256, tag ^ 1);
      }
      bf += 8; st = st == 2 ? 0 : st + 1;
    }
  }
  if (STG && (LY || STG0) && !wg) asm volatile("bar.arrive 5, 256;" ::: "memory");
  const uint32_t mx = sb + MX_OFF + 512 * wg + 4 * tid, bx = BAR(B_KF + 1 + 2 * LY + wg);
  uint32_t pa[8], pb[8];
#pragma unroll
  for (int i = 0; i < 8; i++) { pa[i] = mapa(mx + 1024 * db_, i ^ db_); pb[i] = mapa(bx + (tid >> 10), i ^ db_); asm volatile("" : "+r"(pa[i]), "+r"(pb[i])); }
  wg_wait<0>(); fence_regs(acc);
  if (LY == 0 && rels) mbar_arrive_at(rel);
  if (tid == 0 && wg == 0) PROF(LY ? 26 : 11);
  if (lane == 0) PROF(116 + 64 * LY + wg * 4 + w);

#pragma unroll 1
  for (int rep = 0;; rep++) {
    float m[2][2];
#pragma unroll
    for (int h = 0; h < 2; h++) {
      m[h][0] = m[h][1] = 0.f;
#pragma unroll
      for (int J = 0; J < 5; J++)
#pragma unroll
        for (int c = 0; c < 4; c++) { const float xv = acc[IDX(J, c, h)]; m[h][0] += xv; m[h][1] = fmaf(xv, xv, m[h][1]); }
    }
    float r1[2];
#pragma unroll
    for (int i = 0; i < 2; i++) { const float snd = (q & 1) ? m[0][i] : m[1][i], kp = (q & 1) ? m[1][i] : m[0][i]; r1[i] = kp + __shfl_xor_sync(0xffffffff, snd, 1); }
    const float r2 = ((q & 2) ? r1[1] : r1[0]) + __shfl_xor_sync(0xffffffff, (q & 2) ? r1[0] : r1[1], 2);
    if (R.cs() == 8 && !rep) {
#pragma unroll
      for (int i = 0; i < 8; i++)
        asm volatile("st.async.weak.shared::cluster.mbarrier::complete_tx::bytes.b32 [%0],%1,[%2];" ::"r"(pa[i]), "f"(r2), "r"(pb[i]) : "memory");
      if (tid == 0) mbar_expect_tx(bx, 4096);
    }
    st_rlx(Mb + db_ * 256, tagf(r2, tag));
    if (rep) break;
    if (lane == 0) PROF(100 + 64 * LY + wg * 4 + w);
    float G[40];
    gate_load(G, sb, LY, wg, tid, tb2);
    mbar_wait(BAR(B_CD + 1));
    uint32_t mv[8];
    if (R.cs() == 8) {
      mbar_wait(bx, 1);
#pragma unroll
      for (int i = 0; i < 8; i++) mv[i] = lds32(mx + 1024 * i);
    } else {
#pragma unroll
    for (int i = 0; i < 8; i++) mv[i] = ld_rlx(Mb + i * 256);
#pragma unroll 1
    for (int it = 0; it < SPIN; it++) {
      uint32_t miss = 0;
#pragma unroll
      for (int i = 0; i < 8; i++) miss |= ((mv[i] ^ tag) & 1) << i;
      if (!__any_sync(0xffffffff, miss)) break;
#pragma unroll
      for (int i = 0; i < 8; i++) if ((miss >> i) & 1) mv[i] = ld_rlx(Mb + i * 256);
    }
#pragma unroll
      for (int i = 0; i < 8; i++) mv[i] = __float_as_uint(untag(mv[i]));
      if (MBAR || !LY) bar_sync(4, 256);
    }
    if (lane == 0) PROF(108 + 64 * LY + wg * 4 + w);
#define MV(i) __uint_as_float(mv[i])
    const float s = ((MV(0) + MV(1)) + (MV(2) + MV(3))) + ((MV(4) + MV(5)) + (MV(6) + MV(7)));
#undef MV
    float mm[2], rr[2];
#pragma unroll
    for (int h = 0; h < 2; h++) {
      mm[h] = __shfl_sync(0xffffffff, s, h, 4) * (1.f / DM);
      rr[h] = frsqrt(fmaxf(__shfl_sync(0xffffffff, s, 2 + h, 4) * (1.f / DM) - mm[h] * mm[h], 0.f) + 1e-5f);
    }
    if (tid == 0 && wg == 0) PROF(LY ? 27 : 12);
    const float nm[2] = {-mm[0] * rr[0], -mm[1] * rr[1]};
#pragma unroll
    for (int h = 0; h < 2; h++)
#pragma unroll
      for (int J = 0; J < 5; J++)
#pragma unroll
        for (int c = 0; c < 4; c++) { const float xv = acc[IDX(J, c, h)]; xr[IDX(J, c, h)] = fmaf(fmaf(xv, rr[h], nm[h]), GATE(J, c, h), xv); }
    if (LY) break;
#pragma unroll
    for (int i = 0; i < 40; i++) acc[i] = xr[i] - mm[(i >> 1) & 1];
    if (R.cs() == 8) mbar_wait(BAR(B_KF + 1), 1);
#pragma unroll
    for (int i = 0; i < 10; i++) {
      const int J = i >> 1, h = i & 1;
      const uint32_t u0 = pack_bf(acc[IDX(J, 0, h)], acc[IDX(J, 1, h)]), u1 = pack_bf(acc[IDX(J, 2, h)], acc[IDX(J, 3, h)]);
      asm volatile("st.shared.v2.u32 [%0],{%1,%2};" ::"r"(sb + US_OFF + ((mrow ^ 64) + 8 * h) * 160 + 32 * J + 8 * q), "r"(u0), "r"(u1) : "memory");
    }
    __syncwarp();
    if (lane == 0) mbar_arrive(BAR(B_GS + 1 + wg));
    if (tid == 0 && wg == 0) PROF(13);
    Mb += 16 * 8 * 256;
  }
  if (LY == 0) {
    if (tid == 0 && wg == 0) PROF(15);
  }
  else {
    float* op = P.out + (size_t)t0 * DM + d0;
#pragma unroll
    for (int i = 0; i < 10; i++) {
      const int J = i >> 1, h = i & 1;
      asm volatile("st.global.v4.f32 [%0],{%1,%2,%3,%4};" ::"l"(op + h * DM + 16 * J),
                   "f"(xr[IDX(J, 0, h)]), "f"(xr[IDX(J, 1, h)]), "f"(xr[IDX(J, 2, h)]), "f"(xr[IDX(J, 3, h)]) : "memory");
    }
  }
  if (tid == 0 && wg == 0 && LY) PROF(28);
#undef IDX
#undef GATE
}

__device__ __forceinline__ void next_stats(Scratch* S, uint32_t sb, int tb2, int tid) {
  const uint32_t bars = sb + BAR_OFF, tag = lds32(sb + MISC_OFF) & 1;
  const uint32_t* Mb = S->M + tb2 * 8 * 256 + 2 * tid;
  mbar_wait(BAR(B_F1 + NSAT), 1);
  float m1, s1, s2;
#pragma unroll 1
  for (int it = 0; it < SPIN; it++) {
    uint32_t a[8], miss = 0;
    uint2 v[8];
#pragma unroll
    for (int i = 0; i < 8; i++) { a[i] = ld_rlx(Mb + i * 256); v[i] = ld_rlx2((const uint2*)(Mb + (16 * 8 + i) * 256)); }
#pragma unroll
    for (int i = 0; i < 8; i++) miss |= (a[i] ^ tag) | (v[i].x ^ tag) | (v[i].y ^ tag);
#define SUM8(F) ((untag(F(0)) + untag(F(1))) + (untag(F(2)) + untag(F(3)))) + ((untag(F(4)) + untag(F(5))) + (untag(F(6)) + untag(F(7))))
#define FA(i) a[i]
#define FX(i) v[i].x
#define FY(i) v[i].y
    m1 = SUM8(FA); s1 = SUM8(FX); s2 = SUM8(FY);
    if (!__any_sync(0xffffffff, miss & 1)) break;
  }
  const float mean = s1 * (1.f / DM), rs = frsqrt(fmaxf(s2 * (1.f / DM) - mean * mean, 0.f) + 1e-5f);
  uint2* sp = S->S + SEQ + 128 * tb2 + 8 * (tid & 14) + 2 * (tid >> 4) + (tid & 1);
  st_rlx2(sp, tagf(rs, tag), tagf(-mean * rs, tag));
  st_rlx2(sp + SEQ, tagf(rs, tag), tagf(-(mean + m1 * (1.f / DM)) * rs, tag));
}
template <int I0, int I1> __device__ __forceinline__ void init_barriers(uint32_t bars) {
#pragma unroll
  for (int i = I0; i < I1; i++) mbar_init(BAR(i), bar_count(i));
}
__device__ __forceinline__ int g2_cb(int kp) { return kp < 5 ? 2 * kp : 2 * kp - 9; }
__device__ __forceinline__ const unsigned* h_flag(Scratch* S, int ly, int tb2, int lane) {
  const int s0 = 128 * min(tb2, 15) / 160;
  const bool two = (128 * tb2 + 127) / 160 != s0;
  return &S->flag[(F_H + (ly * 13 + s0) * 10 + min(lane & 15, 9) + (two && lane >= 16 ? 10 : 0)) * 32];
}
__device__ __forceinline__ void gate_tile(const Params& P, uint32_t dst, uint32_t bar, int tb2, int db) {
  mbar_expect_tx(bar, 20480);
  tma2d(dst, &P.mGT, tb2 * 128, db * 80, bar);
  tma2d(dst + 10240, &P.mGT, tb2 * 128 + 64, db * 80, bar);
}
__global__ void __cluster_dims__() __launch_bounds__(512, 1) fused_kernel(const Head H, const __grid_constant__ Params P) {
  extern __shared__ __align__(1024) uint8_t smem[];
  const uint32_t sb = opaque(smem_u32(smem)), bars = sb + BAR_OFF;
  const int wi = __shfl_sync(0xffffffff, threadIdx.x >> 5, 0), wg = wi >> 2, tid = threadIdx.x & 127;
  const int umap = blockIdx.x >= 96;
#define CLK(v)
  CLK(c_a);
  if (wi == 14) {
    if (elect_one()) { init_barriers<0, NBAR1>(bars); asm volatile("fence.mbarrier_init.release.cluster;" ::: "memory"); }
    __syncwarp();
  } else if (wi >= 12) prefetch_map(wi == 12 ? &P.mB : &P.mA[umap]);
  else if (wg == 2) xb_prefetch<1>(H, blockIdx.x + H.base, tid, 0);
  else if (P.role[blockIdx.x].w) return;
  CLK(c_b);
  asm volatile("barrier.cluster.arrive.relaxed.aligned;" ::: "memory");
  CLK(c_c);
  Role R;
  { const uint4 r = P.role[blockIdx.x]; R.v = r.x; R.c = r.y; R.p = r.z; }
  const int id = R.c & 255;
  const int tb = R.tb(), cb = R.cb(), b = R.b(), tb2 = b >> 3, db = b & 7, rank = R.rank();
  const bool has1 = tb <= 12, has2 = b < 128, full = tb < 12;
  Scratch* const S = H.s;
  unsigned* const epoch_p = &S->epoch[id * 8];
  const long long t_start = 0;
  if (wg < 2) {
    if (threadIdx.x == 0) PROF(50);
    asm volatile("griddepcontrol.launch_dependents;");
    bar_sync(6, 448);
    asm volatile("setmaxnreg.inc.sync.aligned.u32 176;");
    float xr[40];
#pragma unroll
    for (int i = 0; i < 40; i++) xr[i] = 0.f;
#pragma unroll 1
    for (int ly = 0; ly < 2; ly++) {
      if (has1) g1_phase(ly, H, sb, wg, tid, R, xr, t_start);
      if (ly == 0) {
        resid_init(xr); fence_regs(xr);
        conv_loop<false>(sb, R.c, wg, tid, t_start);
        if (tid == 0 && wg == 0) PROF(9);
      }
      if (has2) g2_phase(ly, P, S, sb, wg, tid, R, xr, t_start);
    }
    if (tid == 0 && wg == 0) st_rlx(epoch_p, lds32(sb + MISC_OFF));
  } else if (wg == 2) {
    bar_sync(6, 448);
    if (has1) aux_prep(H, P, sb, R, tid, t_start);
    asm volatile("setmaxnreg.inc.sync.aligned.u32 136;");
    conv_loop<true>(sb, R.c, wg, tid, t_start);
    if (tid == 0) PROF(44);
    {
      const uint32_t bb = (P.role[blockIdx.x].x >> 8) & 255;
      if ((bb & 132) == NSDB && tid < 32) next_stats(H.s, sb, bb >> 3, 32 * (bb & 3) + tid);
    }
  } else {
    if (threadIdx.x == 384) PROF(354);
    asm volatile("setmaxnreg.dec.sync.aligned.u32 24;");
    const int wlo = R.wlo(), whi = R.whi();
    const uint32_t wmask = R.wmask(), umask = R.umask(), f1bytes = full ? 36864 : 32768;
    if (wi < 14) {
      if (threadIdx.x == 384) PROF(340);
      asm volatile("barrier.cluster.wait.aligned;" ::: "memory");
      if (has1 && elect_one()) {
        uint64_t tab = wi == 12 ? WTAB0 : XTAB0;
        PROF(329 + wi);
#pragma unroll 1
        for (int kb = 0; kb < 6; kb++, tab >>= 6) {
          const uint32_t dst = sb + ((uint32_t)tab & 63) * 4096;
          if (wi == 12) {
#pragma unroll 1
            for (int h = wlo; h <= whi; h++) tma4d_mc(dst + h * 8192, &P.mB, kb * 64, 0, 0, 8 * cb + 4 * h, BAR(B_F1 + kb), wmask);
          } else {
            tma4d_mc(dst + R.uj() * 1024, &P.mA[umap], kb * 64, 0, 0, 80 * tb + R.uj(), BAR(B_F1 + kb), umask);
            mbar_expect_tx(BAR(B_F1 + kb), f1bytes);
          }
        }
      }
      if (!has1 && wi == 13) bar_sync(7, 64);
    } else {
      if (wi == 15 && elect_one()) { init_barriers<NBAR1, NBAR>(bars); asm volatile("fence.mbarrier_init.release.cluster;" ::: "memory"); }
      bar_sync(6, 448);
      if (!has1 && wi == 14) bar_sync(7, 64);
    }
    const unsigned e1 = ld_rlx(epoch_p) + 1;
    if (wi == 12) {
      if (elect_one()) {
#pragma unroll 1
        for (int ly = 0; ly < 2; ly++) {
#pragma unroll 1
          for (int i = ly ? 0 : 6; i < 10 && has1; i++) {
            const int kb = (0x9876541032ull >> (4 * i)) & 15;
            if (ly == 0) { mbar_wait(BAR(B_E1 + ((DEP0 >> (4 * kb - 24)) & 15))); mbar_wait(BAR(B_AX + (kb == 9))); }
            else {
              if (has2 && i == (db >= GLATE ? 4 : 2)) {
                wait_cnt(&S->cnt[(C_G + db) * 32], e1 * 80);
                mbar_wait(BAR(B_E2 + 7));
                PROF(47);
                gate_tile(P, sb + G_OFF0, BAR(B_GF), tb2, db);
              }
              if (has2) mbar_wait(BAR(i < 4 ? B_E2 + ((0x9865u >> (4 * i)) & 15) : B_GE));
              else if (i == 0) { mbar_wait(BAR(B_E1 + 9)); mbar_wait(BAR(B_CD + 1)); }
              if (i >= 4) mbar_wait(BAR(i < 6 ? B_F1 + W4AT : B_E1 + i - 6), 1);
            }
            const uint32_t dst = sb + ((uint32_t)((ly ? WTAB1 : WTAB0) >> (6 * kb)) & 63) * 4096;
#pragma unroll 1
            for (int h = wlo; h <= whi; h++) tma4d_mc(dst + h * 8192, &P.mB, kb * 64, 0, 0, 8 * cb + 4 * h, BAR(B_F1 + kb), wmask);
          }
          if (has2) {
            if (ly == 0) {
              mbar_wait(BAR(B_E1 + XRAT));
              mbar_expect_tx(BAR(B_XR), 20480 + 160 + 1024);
              tma4d(sb + XR_OFF, &P.mX, 80 * db, tb2, BAR(B_XR));
              bulk_g2s(sb + XR_OFF + 20480, P.dskip + 80 * db, 160, BAR(B_XR));
              bulk_g2s(sb + XR_OFF + 20480 + 256, S->S + 128 * tb2, 1024, BAR(B_XR));
              if (CWAIT) mbar_wait(BAR(CWAIT == 1 ? B_KF + 2 : CWAIT == 2 ? B_KF + R.nch() - 1 : CWAIT == 3 ? B_KF + R.nch() - 2 : B_HD));
            }
#pragma unroll 1
            for (int kp = 0; kp < 10; kp++) {
              const uint32_t dst = sb + (kp < 5 ? kp : kp - 5) * 20480;
              mbar_wait(BAR(kp >= 5 ? B_E2 + kp - 5 : ly ? B_E1 + ((CTAB1 >> (4 * kp)) & 15) : kp < 3 ? B_SH : kp < 4 ? B_HD : B_CD), ly);
              mbar_expect_tx(BAR(B_F2 + kp), 10240 + 16384);
              tma5d(dst, &P.mC[0], g2_cb(kp) * 64, db * 5, BAR(B_F2 + kp));
              mbar_expect_tx(BAR(B_F3 + kp), 10240 + 16384);
              tma5d(dst + 10240, &P.mC[1], g2_cb(kp) * 64, db * 5, BAR(B_F3 + kp));
              if (ly && kp == 4) { mbar_wait(BAR(B_E1 + 9), 1); gate_tile(P, sb + G_OFF1, BAR(B_GF), tb2, db); }
            }
          }
        }
      }
    } else if (wi == 13) {
      const int h0 = R.cs() == 8 ? rank : 4 * rank;
#pragma unroll 1
      for (int ly = 0; ly < 2; ly++) {
        int lane = lane_id();
        if (has1) {
          const unsigned* fp = &S->flag[(F_U3 + 8 * ((160 * tb) >> 7) + (lane & (full ? 15 : 7))) * 32];
          uint32_t ready = ly ? __ballot_sync(0xffffffff, ld_rlx(fp) == e1) : ~0u;
          if (ly) mbar_wait(BAR(full ? B_KF + 1 : has2 ? B_GS + 1 : B_RF1), has2);
          if (ly && full) mbar_wait(BAR(B_KF + 2), 1);
#pragma unroll 1
          for (int kb = ly ? 0 : 6; kb < 10; kb++) {
            if (ly && kb == UPAT) { mbar_wait(BAR(B_XR)); ready = ~0u; }
            wait_flags(fp, e1, 0x101u * ((1u << (64 * kb / 80)) | (1u << ((64 * kb + 63) / 80))), ready);
            if (kb >= 4) mbar_wait(BAR(B_E1 + (ly ? kb - 4 : (DEP0 >> (4 * kb - 24)) & 15)), ly);
            mbar_wait(BAR(B_AX + (kb == 9)));
            if (elect_one()) {
              if (ly && kb == 0) PROF(34);
              tma4d_mc(sb + ((uint32_t)((ly ? XTAB1 : XTAB0) >> (6 * kb)) & 63) * 4096 + R.uj() * 1024, &P.mA[2 * ly + umap], kb * 64, 0, 0, 80 * tb + R.uj(),
                       BAR(B_F1 + kb), umask);
              mbar_expect_tx(BAR(B_F1 + kb), f1bytes);
            }
            __syncwarp();
          }
        }
        if (ly == 0) {
          if (has1) mbar_wait(BAR(B_E1 + KPF));
          if (elect_one()) {
#pragma unroll 1
            for (int s = 0; s < R.nch(); s++) prefetch_l2(P.ssmk + (size_t)R.ch(s) * SEQ, 4096);
          }
          lane = lane_id();
#pragma unroll
          for (int s = 0; s < 5; s++) {
            asm volatile("st.shared.v4.u32 [%0],{%1,%1,%1,%1};" ::"r"(conv_buf(sb, s) + 16 * lane), "r"(0) : "memory");
            asm volatile("st.shared.u8 [%0],%1;" ::"r"(conv_buf(sb, s) + KC_OFS + lane), "r"(0) : "memory");
          }
          fence_async();
          __syncwarp();
          const unsigned* cp = &S->cnt[(C_KV + (R.ch(min(lane, R.nch() - 1)) >> 6)) * 32];
          uint32_t ready = 0;
#pragma unroll 1
          for (int s = 0, sk = 0; s < R.nch(); s++) {
#pragma unroll 1
            for (; sk < (s ? R.nch() : KUP); sk++)
              if (elect_one()) { mbar_expect_tx(BAR(B_KF + sk), 8192); bulk_g2s(conv_buf(sb, sk) + KC_OFS + 32, P.ssmk + (size_t)R.ch(sk) * SEQ, 4096, BAR(B_KF + sk)); }
            PROFC(s == 0, 329);
#pragma unroll 1
            for (int it = 0; !((ready >> s) & 1) && it < SPIN; it++) ready = __ballot_sync(0xffffffff, (int)(ld_rlx(cp) - e1 * 32) >= 0);
            PROFC(s == 0, 30);
            if (elect_one()) {
              bulk_g2s(conv_buf(sb, s) + KV_PAD, S->kv + (size_t)R.ch(s) * SEQ, 4096, BAR(B_KF + s));
              if (s == 0 && has2) { prefetch_l2(P.cre + (size_t)5 * b * DM, 5 * DM * 2); prefetch_l2(P.cim + (size_t)5 * b * DM, 5 * DM * 2); }
            }
            __syncwarp();
          }
          PROF(31);
          if (!has1) return;
        }
        lane = lane_id();
        const unsigned* fp = h_flag(S, ly, tb2, lane);
        uint32_t ready = __ballot_sync(0xffffffff, ld_rlx(fp) == e1), st = 0;
        if (ly == 0 && !has2) {
          mbar_wait(BAR(B_HD));
          if (lane < 8) mbar_arrive_cl(BAR(B_RF1), lane & 1);
        }
        if (has2) {
          mbar_wait(BAR(B_RF0), ly);
#pragma unroll 1
          for (int kp = 0; kp < 10; kp++) {
            if (kp == 5) { mbar_wait(BAR(B_XR), 1); ready = ~0u; }
            if (kp == 2) { mbar_wait(BAR(B_HD), ly); if (lane < 8) mbar_arrive_cl(BAR(B_RF1), lane & (R.cs() - 1)); }
            wait_flags(fp, e1, 0x10001u << g2_cb(kp), ready);
            if (kp == 2) mbar_wait(BAR(B_RF1), ly);
#pragma unroll
            for (int hf = 0; hf < 2; hf++) {
              if (kp >= 3) { if (hf) mbar_wait(BAR(B_E2 + kp - 3), ly); else mbar_wait(BAR(B_EA + st), ly ^ (kp >= 6 && kp < 9)); }
              if (elect_one()) {
                if (kp == 0 && !hf) PROF(33 + 2 * ly);
                tma4d_mc(sb + H_OFF + st * 32768 + hf * 16384 + h0 * 2048, &P.mH, g2_cb(kp) * 128 + hf * 64, 0, 2 * h0,
                         ly * 16 + tb2, BAR((hf ? B_F3 : B_F2) + kp), (1u << R.cs()) - 1);
              }
              __syncwarp();
            }
            st = st == 2 ? 0 : st + 1;
          }
        }
      }
    } else if (wi == 14) {
      if (!has1) return;
      prefetch_if(P.dskip + 64 * (tid & 31), (tid & 31) < 10);
      if (elect_one()) { prefetch_map(&P.sK); prefetch_map(&P.mX); prefetch_map(&P.sH); prefetch_map(&P.sU); prefetch_map(&P.mC[0]); prefetch_map(&P.mC[1]); prefetch_map(&P.mH); prefetch_map(&P.mGT); prefetch_map(&P.mA[2 + umap]); }
      __syncwarp();
#pragma unroll 1
      for (int ly = 0; ly < 2; ly++) {
        if (ly) {
          mbar_wait(BAR(B_F1 + 1), 1);
          uint32_t ready = 0;
          wait_flags(&S->flag[(F_U3 + 8 * ((160 * tb) >> 7) + ((lane_id() + ly) & (full ? 15 : 7))) * 32], e1, ~0u, ready);
          if (elect_one()) mbar_arrive(BAR(B_XR));
        }
        const int lane = lane_id();
        mbar_wait(BAR(B_E1 + (ly ? STAT_AT1 : STAT_AT)), ly);
        PROFC(lane == 0 && ly == 0, 36);
        {
          const int l = lane - (full ? 0 : 16);
          const uint2* p = S->S + ly * SEQ + 160 * tb + 2 * l;
          uint4 v[3];
#pragma unroll 1
          for (int it = 0; it < SPIN; it++) {
            v[0] = ld_rlx4(p); v[1] = ld_rlx4(p + 64); v[2] = ld_rlx4(p + 96);
            const bool miss = __any_sync(0xffffffff, untagged(v[0], e1 & 1) | untagged(v[1], e1 & 1) | untagged(v[2], e1 & 1));
            PROFC(lane == 0 && ly == 0 && it == 0, 37);
            if (!miss) break;
          }
          PROFC(lane == 0 && ly == 0, 38);
#pragma unroll
          for (int i = 0; i < 3; i++) {
            const int pr = l + (i == 2 ? 48 : 32 * i);
            if (pr >= 0) asm volatile("st.shared.v4.u32 [%0],{%1,%2,%3,%4};" ::"r"(sb + SSM_OFF + 16 * (pr + ((pr * (full ? 205 : 256)) >> 12))), "r"(v[i].x & ~1u),
                                      "r"(v[i].y & ~1u), "r"(v[i].z & ~1u), "r"(v[i].w & ~1u) : "memory");
          }
          __syncwarp();
        }
        if (lane == 0) mbar_arrive(BAR(B_ST));
        if (ly && has2) {
          mbar_wait(BAR(B_E1 + 9), 1);
          if (lane < 8) mbar_arrive_cl(BAR(B_RF0), lane & (R.cs() - 1));
        }
        if (lane == 0) {
#pragma unroll 1
          for (int pc = 0; pc < (full ? 5 : 4); pc++) {
            if ((HWM >> (4 * pc)) & 8) {
              mbar_wait(BAR(B_SH + min((HWM >> (4 * pc)) & 7, full ? 4 : 3)), ly);
              PROF(380 + 5 * ly + pc);
              if (pc == 0 && (cb & 1)) delay(ly ? HDLY : HDLY0);
              fence_async();
            }
#pragma unroll
            for (int i = 0; i < 2; i++) tma4d_store(&P.sH, sb + (pc < 4 ? R_OFF + i * 16384 + pc * 4096 : (ly ? R4_OFF1 : R4_OFF0) + i * 4096), 128 * cb + 64 * i, 0, 0, ly * 1024 + 80 * tb + 4 * pc);
          }
          bulk_commit(); bulk_wait();
          PROF(ly ? 17 : 16);
          mbar_arrive(BAR(B_HD));
          release<1>();
          signal_flag(&S->flag[(F_H + (ly * 13 + tb) * 10 + cb) * 32], e1);
          PROF(ly ? 24 : 8);
        }
        __syncwarp();
        if (has2) {
          mbar_wait(BAR(B_F2 + FPAT), ly);
          uint32_t ready = 0;
          wait_flags(h_flag(S, ly, tb2, lane_id() | 1), e1, ~0u, ready);
          if (elect_one()) mbar_arrive(BAR(B_XR));
        }
        if (lane == 0 && has2 && !ly) {
          mbar_wait(BAR(B_CD + 1));
#pragma unroll
          for (int i = 0; i < 2; i++) {
            mbar_wait(BAR(B_GS + 1 + i), 1);
            fence_async();
            tma4d_store(&P.sU, sb + US_OFF + 10240 - 10240 * i, 80 * db, 0, 8 * i, tb2);
          }
          bulk_commit(); bulk_wait();
          PROF(18);
          release<2>(); signal_flag(&S->flag[(F_U3 + b) * 32], e1);
          PROF(14);
          mbar_wait(BAR(B_SG));
          mbar_arrive(BAR(B_GE)); mbar_arrive_cl(BAR(B_GE), R.wpart());
        }
        __syncwarp();
      }
    } else {
      discretise(H, P, sb, R, tid & 31, e1);
      if (elect_one()) {
        mbar_arrive(BAR(B_LM));
        PROF(348);
        if (b < R.nprep()) {
#pragma unroll 1
          for (int task = b, r = 0; task < 320; task += R.nprep(), r++) {
            mbar_wait(BAR(B_PS + r));
            PROF(320 + 3 * r);
            fence_async();
            tma2d_store(&P.sK, sb + KS_OFF + r * 8192, 64 * (task & 31), 64 * (task >> 5));
            bulk_commit(); bulk_wait();
            PROF(321 + 3 * r);
            release<4>();
            signal_cnt(&S->cnt[(C_KV + (task >> 5)) * 32], 1);
            PROF(322 + 3 * r);
          }
          PROF(41);
        }
        if (has2) {
          mbar_wait(BAR(B_SH));
#pragma unroll 1
          for (int i = 0; i < 8; i++) mbar_arrive_cl(BAR(B_RF0), i & (R.cs() - 1));
        }
#pragma unroll 1
        for (int s = 0, s0 = 0; s < R.nch(); s++) {
          mbar_wait(BAR(B_GS + s));
          fence_async();
          bulk_s2g(S->gt + (size_t)R.ch(s) * SEQ, conv_buf(sb, s) + KC_OFS, 4096); bulk_commit();
          if (s == 1 || s >= R.nch() - GSPL) bulk_wait();
          if (s == 1 || s == min(R.nch() - 1, 3)) mbar_arrive(BAR(B_CD + (s > 1)));
          mbar_arrive_if(BAR(B_SG), s == R.nch() - 1);
          if (s >= R.nch() - GSPL) {
            PROF(45);
            release<8>();
#pragma unroll 1
            for (; s0 <= s; s0++) signal_cnt(&S->cnt[(C_G + R.ch(s0) / 80) * 32], 1);
          }
        }
        PROF(46);
      }
    }
  }
}

typedef CUresult (*EncFn)(CUtensorMap*, CUtensorMapDataType, cuuint32_t, void*, const cuuint64_t*, const cuuint64_t*, const cuuint32_t*,
                          const cuuint32_t*, CUtensorMapInterleave, CUtensorMapSwizzle, CUtensorMapL2promotion, CUtensorMapFloatOOBfill);
bool enc(EncFn f, CUtensorMap* m, const void* base, int rank, const cuuint64_t* dims, const cuuint64_t* strides, const cuuint32_t* box, bool swz,
         bool f32 = false) {
  const cuuint32_t es[5] = {1, 1, 1, 1, 1};
  return f(m, f32 ? CU_TENSOR_MAP_DATA_TYPE_FLOAT32 : CU_TENSOR_MAP_DATA_TYPE_BFLOAT16, rank, const_cast<void*>(base), dims, strides, box, es,
           CU_TENSOR_MAP_INTERLEAVE_NONE, swz ? CU_TENSOR_MAP_SWIZZLE_128B : CU_TENSOR_MAP_SWIZZLE_NONE, CU_TENSOR_MAP_L2_PROMOTION_L2_256B,
           CU_TENSOR_MAP_FLOAT_OOB_FILL_NONE) == CUDA_SUCCESS;
}
void make_roles(Params& P, bool big) {
  for (uint32_t bx = 0; bx < (big ? 120u : 12u); bx++) {
    const uint32_t c = bx >> 3, r = bx & 7, id = big ? bx : 120 + bx;
    const uint32_t vA = c < 12 ? (2 * (c >> 1) + (r >> 2)) | (4 * (c & 1) + (r & 3)) << 4 | (r & 4) << 16 | 4 << 19 | (r ^ 4) << 22
                               : (4 * (c - 12) + (r >> 1)) | (8 + (r & 1)) << 4 | (r & 6) << 16 | 2 << 19 | (r ^ 2) << 22;
    const uint32_t vB = (bx < 10 ? 12 : 13) | bx << 4 | 2 << 19 | (bx & 1) << 22 | (bx & 1) << 26;
    P.role[bx].x = (big ? vA | r << 26 | 1u << 29 : vB) | (id < 128 ? (id & ~7u) | (r >> 1) | (r & 1) << 2 : id) << 8;
    P.role[bx].y = id | (big ? 5 : bx < 8 ? 3 : 4) << 10 | 120 << 13 | 132 << 21 | (big ? 4u : 3u) << 29;
    const uint32_t v = P.role[bx].x, cb = (v >> 4) & 15, rank = (v >> 26) & 7, ubase = (v >> 16) & 7, ugs = (v >> 19) & 7, wp = (v >> 22) & 7;
    const uint32_t wlo = rank > wp, whi = wp != rank ? wlo : 1, wmask = 1u << rank | 1u << wp;
    const uint32_t uj = (rank - ubase) * (!big ? 8 : ugs == 4 ? 5 : 10), sm = big ? (0x7296418530ull >> (4 * cb)) & 15 : bx < 8 ? 4 * (bx & 1) + (bx >> 1) : 15;
    P.role[bx].z = wlo | whi << 1 | wmask << 2 | ((1u << ugs) - 1) << (10 + ubase) | uj << 20 | sm << 25;
    P.role[bx].w = 0;
  }
}
void launch(const Head& H, const Params& P, int grid, int cs, bool dependent) {
  cudaLaunchConfig_t cfg = {};
  cfg.gridDim = grid; cfg.blockDim = 512; cfg.dynamicSmemBytes = SMEM_BYTES; cfg.stream = cudaStreamPerThread;
  cudaLaunchAttribute at[2];
  at[0].id = cudaLaunchAttributeClusterDimension; at[0].val.clusterDim.x = cs; at[0].val.clusterDim.y = 1; at[0].val.clusterDim.z = 1;
  at[1].id = cudaLaunchAttributeProgrammaticStreamSerialization; at[1].val.programmaticStreamSerializationAllowed = 1;
  cfg.attrs = at; cfg.numAttrs = dependent ? 2 : 1;
  cudaLaunchKernelEx(&cfg, fused_kernel, H, P);
}

}

extern "C" void kernel_launch(void* const* d_in, const int* in_sizes, int n_in, void* d_out, int out_size) {
  (void)in_sizes; (void)n_in; (void)out_size;
  typedef const __nv_bfloat16* cb;
  void* fp = nullptr; cudaDriverEntryPointQueryResult qr;
  cudaGetDriverEntryPoint("cuTensorMapEncodeTiled", &fp, cudaEnableDefault, &qr);
  EncFn f = (EncFn)fp;
  Scratch* sp = nullptr;
  cudaGetSymbolAddress((void**)&sp, g_scr);
  void *pu = sp->u, *ph = sp->h, *pgt = sp->gt;
  Params P;
  Head H;
  H.s = sp; H.x = (cb)d_in[0]; H.swap = (uintptr_t)d_in[4] < (uintptr_t)d_in[3] ? 0 : 0x80000000u; H.b0 = (cb)d_in[H.swap ? 3 : 4]; H.b1 = (cb)d_in[H.swap ? 4 : 3];
  for (int i = 0; i < 2; i++) {
    const cuuint64_t d[4] = {640, 8, 2, 80}, s[3] = {1280, (cuuint64_t)((uintptr_t)H.b1 - (uintptr_t)H.b0), 8 * 1280}; const cuuint32_t bx[4] = {64, 8, 2, 4};
    if (enc(f, &P.mB, H.b0, 4, d, s, bx, true)) break;
    cudaMemcpyAsync(sp->bcopy, H.b0, DM * DM * 2, cudaMemcpyDeviceToDevice, cudaStreamPerThread);
    cudaMemcpyAsync(sp->bcopy + DM * DM, H.b1, DM * DM * 2, cudaMemcpyDeviceToDevice, cudaStreamPerThread);
    H.b0 = sp->bcopy; H.b1 = sp->bcopy + DM * DM;
  }
  {
    const cuuint64_t d[5] = {640, 2, 4, 2, 40}, s[4] = {1280, 4 * 1280, 2 * 1280, 16 * 1280}; const cuuint32_t bx[5] = {64, 2, 4, 2, 5};
    enc(f, &P.mC[0], d_in[5], 5, d, s, bx, true); enc(f, &P.mC[1], d_in[6], 5, d, s, bx, true); }
  { const cuuint64_t d[2] = {2048, 640}, s[1] = {4096}; const cuuint32_t bx[2] = {64, 80}; enc(f, &P.mGT, pgt, 2, d, s, bx, true); }
  { const cuuint64_t d[4] = {640, 8, 16, 16}, s[3] = {16 * 1280, 1280, 128 * 1280}; const cuuint32_t bx[4] = {80, 8, 16, 1}, bh[4] = {80, 8, 8, 1};
    enc(f, &P.sU, pu, 4, d, s, bh, false); enc(f, &P.mX, d_in[0], 4, d, s, bx, false); }
  { const cuuint64_t d[2] = {2048, 640}, s[1] = {4096}; const cuuint32_t bx[2] = {64, 64}; enc(f, &P.sK, sp->kv, 2, d, s, bx, true); }
  P.lre = (cb)d_in[1]; P.lim = (cb)d_in[2]; P.cre = (cb)d_in[5]; P.cim = (cb)d_in[6]; P.ldt = (cb)d_in[7]; P.dskip = (cb)d_in[8];
  P.out = (float*)d_out;
  P.k = (cb)d_in[10]; P.v = (cb)d_in[11]; P.shk = (cb)d_in[12]; P.ssmk = (cb)d_in[13]; P.ssmd = (cb)d_in[14];
  cudaFuncSetAttribute(fused_kernel, cudaFuncAttributeMaxDynamicSharedMemorySize, SMEM_BYTES);
  for (int big = 1; big >= 0; big--) {
    const cuuint64_t seg = big ? 40 : 32;
    for (int i = 0; i < 4; i++) {
      const cuuint64_t d[4] = {640, 2, 4, 1024}, s[3] = {1280, seg * 1280, 2 * 1280}; const cuuint32_t bx[4] = {64, 2, 4, !big ? 8u : (i & 1) ? 10u : 5u};
      enc(f, &P.mA[i], i < 2 ? d_in[0] : pu, 4, d, s, bx, true);
    }
    {
      const cuuint64_t d[4] = {1280, 8, 16, 32}, s[3] = {16 * 2560, 2560, 128 * 2560}; const cuuint32_t bx[4] = {64, 8, big ? 2u : 8u, 1};
      enc(f, &P.mH, ph, 4, d, s, bx, true); }
    { const cuuint64_t d[4] = {1280, 2, 4, 2048}, s[3] = {2560, seg * 2560, 2 * 2560}; const cuuint32_t bx[4] = {64, 2, 4, 4};
      enc(f, &P.sH, ph, 4, d, s, bx, true); }
    make_roles(P, big);
    H.base = big ? 0 : 120;
    launch(H, P, big ? 120 : 12, big ? 8 : 2, !big);
  }
}
```

```cpp
#include <cuda_runtime.h>
#include <cuda.h>
#include <cuda_bf16.h>
#include <stdint.h>

namespace {

constexpr int SEQ = 2048, DM = 640;
constexpr int SPIN = 1 << 20;
#define PFAT 99
#define KVDLY 500
#define PFD 1
#define XPFAT 9
#define STAT_AT 6
#define KPFAT 3
#define KPFAT2 5
#define KPF 7
#define HDLY 1900
#define GSPL 2
#define CWAIT 0
#define HDLY0 1900
#define CTAB1 0x96543u
#define NSAT 0
#define SKW 1
#define RIAT 2
#define MIAT 5
#define FPAT 1
#define UPAT 7
#define STAT_AT1 4
#define W4AT 0
#define MBAR 1
#define STG 17
#define STG0 17
#define HWM 0xc09
#define NSDB 4
#define GLATE 6
#define KUP 1
#define XRAT 9
#define ORD 1

struct Scratch {
  uint2 E[2 * 13 * 10 * 8 * 16];
  uint32_t M[3 * 16 * 8 * 256];
  uint2 S[3 * SEQ];
  uint2 RS[80 * 16];
  unsigned flag[512 * 32];
  unsigned cnt[32 * 32];
  unsigned epoch[132 * 8];
  unsigned zero[128];
  unsigned prof[132 * 512];
  __align__(1024)
  __nv_bfloat16 u[SEQ * DM];
  __nv_bfloat16 h[2 * SEQ * 1280];
  __nv_bfloat16 kv[DM * SEQ];
  __nv_bfloat16 gt[DM * SEQ];
  __nv_bfloat16 bcopy[2 * DM * DM];
};
__device__ __align__(1024) Scratch g_scr;
#define PROFC(c, i) do {} while (0)
#define PSEL 1
#define PROF(i) do {} while (0)

constexpr int C_KV = 0, C_G = 10;
constexpr int F_U3 = 0, F_H = 128;

constexpr int R_OFF = 196608, R4_OFF0 = 73728, R4_OFF1 = 122880, H_OFF = 131072, KS_OFF = 131072, CV_OFF = 86272, G_OFF0 = 40960, G_OFF1 = 102400, US_OFF = 98304, XR_OFF = 163840, MX_OFF = 32768;
constexpr int LAM_OFF = 229376, SSM_OFF = LAM_OFF + 1024, BAR_OFF = SSM_OFF + 1344;
constexpr int B_F1 = 0, B_E1 = 10, B_RF0 = 20, B_RF1 = 21, NBAR1 = 22;
constexpr int B_F2 = 22, B_KF = 32, B_GF = 37, B_CD = 38, B_XR = 40, B_ST = 41, B_HD = 42, B_LM = 43, B_E2 = 44, B_GS = 54, B_PS = 59, B_AX = 62, B_SH = 64, B_SG = 69, B_GE = 70, B_EA = 71, B_F3 = 74, NBAR = 84;
__host__ __device__ constexpr int bar_count(int i) { return i < B_E1 ? 1 : i < B_RF0 ? 9 : i < B_F2 ? 8 : i < B_E2 ? 1 : i < B_GS ? 12 : i < B_SH ? 4 : i < B_SG ? 8 : i < B_GE ? 1 : i < B_EA ? 2 : i < B_F3 ? 8 : 1; }
constexpr int MISC_OFF = BAR_OFF + NBAR * 8, SMEM_BYTES = MISC_OFF + 32;
constexpr int KV_PAD = 512, KC_OFS = KV_PAD + 4096, CH_STRIDE = 8960;
__device__ __forceinline__ uint32_t conv_buf(uint32_t sb, int slot) { return sb + CV_OFF + slot * CH_STRIDE; }
constexpr uint64_t tab6(int a, int b, int c, int d, int e, int f, int g, int h, int i, int j) {
  return (uint64_t)a | (uint64_t)b << 6 | (uint64_t)c << 12 | (uint64_t)d << 18 | (uint64_t)e << 24 | (uint64_t)f << 30 | (uint64_t)g << 36 | (uint64_t)h << 42 |
         (uint64_t)i << 48 | (uint64_t)j << 54;
}
constexpr uint64_t WTAB0 = tab6(0, 4, 8, 30, 12, 26, 0, 4, 8, 12), XTAB0 = tab6(40, 45, 50, 34, 16, 21, 40, 45, 50, 16);
constexpr uint64_t WTAB1 = tab6(16, 20, 0, 4, 8, 12, 16, 20, 24, 28), XTAB1 = tab6(40, 45, 50, 32, 40, 45, 50, 32, 40, 45);
constexpr uint32_t DEP0 = 0x4210;

struct Head {
  Scratch* s;
  const __nv_bfloat16 *x, *b0, *b1;
  uint32_t base, swap;
};
struct Params {
  const __nv_bfloat16 *lre, *lim, *ldt, *k, *v, *shk, *cre, *cim, *ssmk, *ssmd, *dskip;
  float* out;
  uint4 role[120];
  CUtensorMap mB, mA[4], mH, mC[2], mGT, mX, sH, sU, sK;
};

__device__ __forceinline__ uint32_t smem_u32(const void* p) { return (uint32_t)__cvta_generic_to_shared(p); }
__device__ __forceinline__ uint32_t opaque(uint32_t x) { uint32_t y; asm volatile("mov.u32 %0, %1;" : "=r"(y) : "r"(x)); return y; }
__device__ __forceinline__ int lane_id() { int y; asm volatile("mov.u32 %0, %%laneid;" : "=r"(y)); return y; }
__device__ __forceinline__ void delay(uint32_t n) {
  asm volatile("{ .reg .pred p; .reg .u32 a, b; mov.u32 a, %%clock; L: mov.u32 b, %%clock; sub.u32 b, b, a; setp.lt.u32 p, b, %0; @p bra.uni L; }" ::"r"(n) : "memory");
}
__device__ __forceinline__ void mbar_init(uint32_t bar, uint32_t cnt) { asm volatile("mbarrier.init.shared::cta.b64 [%0], %1;" ::"r"(bar), "r"(cnt) : "memory"); }
__device__ __forceinline__ void mbar_expect_tx(uint32_t bar, uint32_t bytes) { asm volatile("mbarrier.arrive.expect_tx.shared::cta.b64 _, [%0], %1;" ::"r"(bar), "r"(bytes) : "memory"); }
__device__ __forceinline__ void mbar_arrive(uint32_t bar) { asm volatile("mbarrier.arrive.shared::cta.b64 _, [%0];" ::"r"(bar) : "memory"); }
__device__ __forceinline__ void mbar_arrive_if(uint32_t bar, bool c) {
  asm volatile("{ .reg .pred p; setp.ne.u32 p, %1, 0; @p mbarrier.arrive.shared::cta.b64 _, [%0]; }" ::"r"(bar), "r"((uint32_t)c) : "memory");
}
__device__ __forceinline__ void prefetch_if(const void* p, bool c) { asm volatile("{ .reg .pred p; setp.ne.u32 p, %1, 0; @p prefetch.global.L2 [%0]; }" ::"l"(p), "r"((uint32_t)c)); }
__device__ __forceinline__ void mbar_arrive_cl(uint32_t bar, uint32_t cta) {
  asm volatile("{ .reg .b32 ra; mapa.shared::cluster.u32 ra, %0, %1; mbarrier.arrive.shared::cluster.b64 _, [ra]; }" ::"r"(bar), "r"(cta) : "memory");
}
__device__ __forceinline__ uint32_t mapa(uint32_t a, uint32_t cta) { uint32_t r; asm("mapa.shared::cluster.u32 %0, %1, %2;" : "=r"(r) : "r"(a), "r"(cta)); return r; }
__device__ __forceinline__ void mbar_arrive_at(uint32_t ra) { asm volatile("mbarrier.arrive.shared::cluster.b64 _, [%0];" ::"r"(ra) : "memory"); }
__device__ __forceinline__ void mbar_wait(uint32_t bar, uint32_t parity = 0) {
  asm volatile("{ .reg .pred p; .reg .u32 c; mov.u32 c, 0;\n"
               "W: mbarrier.try_wait.parity.shared::cta.b64 p, [%0], %1; @p bra.uni D;\n"
               "add.u32 c, c, 1; setp.lt.u32 p, c, 0x100000; @p bra.uni W;\nD: }" ::"r"(bar), "r"(parity) : "memory");
}
__device__ __forceinline__ bool elect_one() { uint32_t p; asm volatile("{ .reg .pred P; elect.sync _|P, 0xffffffff; selp.u32 %0,1,0,P; }" : "=r"(p)); return p; }
__device__ __forceinline__ void bar_sync(int id, int n) { __syncwarp(); asm volatile("bar.sync %0, %1;" ::"r"(id), "r"(n) : "memory"); }
__device__ __forceinline__ void tma2d(uint32_t dst, const CUtensorMap* m, int c0, int c1, uint32_t bar) {
  asm volatile("cp.async.bulk.tensor.2d.shared::cluster.global.mbarrier::complete_tx::bytes [%0], [%1, {%3,%4}], [%2];"
               ::"r"(dst), "l"(m), "r"(bar), "r"(c0), "r"(c1) : "memory");
}
__device__ __forceinline__ void tma5d(uint32_t dst, const CUtensorMap* m, int c0, int c4, uint32_t bar) {
  asm volatile("cp.async.bulk.tensor.5d.shared::cluster.global.mbarrier::complete_tx::bytes [%0], [%1, {%3,%5,%5,%5,%4}], [%2];"
               ::"r"(dst), "l"(m), "r"(bar), "r"(c0), "r"(c4), "r"(0) : "memory");
}
__device__ __forceinline__ void tma4d(uint32_t dst, const CUtensorMap* m, int c0, int c3, uint32_t bar) {
  asm volatile("cp.async.bulk.tensor.4d.shared::cluster.global.mbarrier::complete_tx::bytes [%0], [%1, {%3,%5,%5,%4}], [%2];"
               ::"r"(dst), "l"(m), "r"(bar), "r"(c0), "r"(c3), "r"(0) : "memory");
}
__device__ __forceinline__ void tma4d_mc(uint32_t dst, const CUtensorMap* m, int c0, int c1, int c2, int c3, uint32_t bar, uint32_t mask) {
  asm volatile("cp.async.bulk.tensor.4d.shared::cluster.global.mbarrier::complete_tx::bytes.multicast::cluster [%0], [%1, {%3,%4,%5,%6}], [%2], %7;"
               ::"r"(dst), "l"(m), "r"(bar), "r"(c0), "r"(c1), "r"(c2), "r"(c3), "h"((uint16_t)mask) : "memory");
}
__device__ __forceinline__ void bulk_g2s(uint32_t dst, const void* src, uint32_t bytes, uint32_t bar) {
  asm volatile("cp.async.bulk.shared::cluster.global.mbarrier::complete_tx::bytes [%0], [%1], %2, [%3];" ::"r"(dst), "l"(src), "r"(bytes), "r"(bar) : "memory");
}
__device__ __forceinline__ void tma4d_store(const CUtensorMap* m, uint32_t src, int c0, int c1, int c2, int c3) {
  asm volatile("cp.async.bulk.tensor.4d.global.shared::cta.bulk_group [%0, {%2,%3,%4,%5}], [%1];" ::"l"(m), "r"(src), "r"(c0), "r"(c1), "r"(c2), "r"(c3) : "memory");
}
__device__ __forceinline__ void tma2d_store(const CUtensorMap* m, uint32_t src, int c0, int c1) {
  asm volatile("cp.async.bulk.tensor.2d.global.shared::cta.bulk_group [%0, {%2,%3}], [%1];" ::"l"(m), "r"(src), "r"(c0), "r"(c1) : "memory");
}
__device__ __forceinline__ void bulk_s2g(void* dst, uint32_t src, uint32_t bytes) {
  asm volatile("cp.async.bulk.global.shared::cta.bulk_group [%0], [%1], %2;" ::"l"(dst), "r"(src), "r"(bytes) : "memory");
}
__device__ __forceinline__ void bulk_commit() { asm volatile("cp.async.bulk.commit_group;" ::: "memory"); }
__device__ __forceinline__ void bulk_wait() { asm volatile("cp.async.bulk.wait_group 0;" ::: "memory"); }
__device__ __forceinline__ void fence_async() { asm volatile("fence.proxy.async.shared::cta;" ::: "memory"); }
__device__ __forceinline__ void prefetch_l2(const void* src, uint32_t bytes) { asm volatile("cp.async.bulk.prefetch.L2.global [%0], %1;" ::"l"(src), "r"(bytes) : "memory"); }
__device__ __forceinline__ void prefetch_map(const CUtensorMap* m) { asm volatile("prefetch.tensormap [%0];" ::"l"(m) : "memory"); }
__device__ __forceinline__ void wg_fence() { __syncwarp(); asm volatile("wgmma.fence.sync.aligned;" ::: "memory"); }
__device__ __forceinline__ void wg_commit() { asm volatile("wgmma.commit_group.sync.aligned;" ::: "memory"); }
template <int N> __device__ __forceinline__ void wg_wait() { asm volatile("wgmma.wait_group.sync.aligned %0;" ::"n"(N) : "memory"); }
template <int N> __device__ __forceinline__ void fence_regs(float (&d)[N]) {
#pragma unroll
  for (int i = 0; i < N; i++) asm volatile("" : "+f"(d[i])::"memory");
}
__device__ __forceinline__ uint64_t make_desc(uint32_t addr, uint32_t lbo, uint32_t sbo, uint32_t swz) {
  return (uint64_t)((addr & 0x3FFFF) >> 4) | ((uint64_t)(lbo >> 4) << 16) | ((uint64_t)(sbo >> 4) << 32) | ((uint64_t)swz << 62);
}
__device__ __forceinline__ uint32_t ldg1(const void* p) { uint32_t v; asm volatile("ld.global.nc.u32 %0,[%1];" : "=r"(v) : "l"(p)); return v; }
__device__ __forceinline__ uint32_t lds32(uint32_t a) { uint32_t v; asm volatile("ld.shared.u32 %0,[%1];" : "=r"(v) : "r"(a)); return v; }
__device__ __forceinline__ unsigned ld_rlx(const unsigned* p) { unsigned v; asm volatile("ld.relaxed.gpu.global.u32 %0,[%1];" : "=r"(v) : "l"(p) : "memory"); return v; }
__device__ __forceinline__ uint4 ld_rlx4(const void* p) {
  uint4 v; asm volatile("ld.relaxed.gpu.global.v4.u32 {%0,%1,%2,%3},[%4];" : "=r"(v.x), "=r"(v.y), "=r"(v.z), "=r"(v.w) : "l"(p) : "memory"); return v;
}
__device__ __forceinline__ uint2 ld_rlx2(const void* p) { uint2 v; asm volatile("ld.relaxed.gpu.global.v2.u32 {%0,%1},[%2];" : "=r"(v.x), "=r"(v.y) : "l"(p) : "memory"); return v; }
__device__ __forceinline__ void st_rlx2(void* p, uint32_t a, uint32_t b) { asm volatile("st.relaxed.gpu.global.v2.u32 [%0],{%1,%2};" ::"l"(p), "r"(a), "r"(b) : "memory"); }
__device__ __forceinline__ void st_rlx(void* p, uint32_t a) { asm volatile("st.relaxed.gpu.global.u32 [%0],%1;" ::"l"(p), "r"(a) : "memory"); }
#define PUB 15
template <int SITE> __device__ __forceinline__ void release() { if (PUB & SITE) asm volatile("fence.release.gpu;" ::: "memory"); }
__device__ __forceinline__ void signal_flag(unsigned* p, unsigned val) { asm volatile("st.relaxed.gpu.global.u32 [%0],%1;" ::"l"(p), "r"(val) : "memory"); }
__device__ __forceinline__ void signal_cnt(unsigned* p, unsigned n) { asm volatile("red.relaxed.gpu.global.add.u32 [%0],%1;" ::"l"(p), "r"(n) : "memory"); }
__device__ __forceinline__ void wait_flags(const unsigned* p, unsigned val, uint32_t need, uint32_t& ready) {
#pragma unroll 1
  for (int it = 0; (ready & need) != need && it < SPIN; it++) ready = __ballot_sync(0xffffffff, ld_rlx(p) == val);
}
__device__ __forceinline__ void wait_cnt(const unsigned* p, unsigned tgt) {
  asm volatile("{ .reg .pred p; .reg .u32 c; .reg .s32 v; mov.u32 c, 0;\n"
               "W: ld.relaxed.gpu.global.u32 v, [%0]; sub.s32 v, v, %1; setp.ge.s32 p, v, 0; @p bra.uni D;\n"
               "add.u32 c, c, 1; setp.lt.u32 p, c, 0x100000; @p bra.uni W;\nD: }" ::"l"(p), "r"(tgt) : "memory");
}
__device__ __forceinline__ uint32_t pack_bf(float lo, float hi) { uint32_t r; asm("cvt.rn.bf16x2.f32 %0, %1, %2;" : "=r"(r) : "f"(hi), "f"(lo)); return r; }
__device__ __forceinline__ float bf_lo(uint32_t v) { return __uint_as_float(v << 16); }
__device__ __forceinline__ float bf_hi(uint32_t v) { return __uint_as_float(v & 0xffff0000u); }
__device__ __forceinline__ float bf_rn(float x) { return __bfloat162float(__float2bfloat16_rn(x)); }
__device__ __forceinline__ float frcp(float x) { float r; asm("rcp.approx.ftz.f32 %0,%1;" : "=f"(r) : "f"(x)); return r; }
__device__ __forceinline__ float fsqrt(float x) { float r; asm("sqrt.approx.ftz.f32 %0,%1;" : "=f"(r) : "f"(x)); return r; }
__device__ __forceinline__ float frsqrt(float x) { float r; asm("rsqrt.approx.ftz.f32 %0,%1;" : "=f"(r) : "f"(x)); return r; }
__device__ __forceinline__ uint32_t hmul2(uint32_t a, uint32_t b) { uint32_t r; asm("mul.rn.bf16x2 %0,%1,%2;" : "=r"(r) : "r"(a), "r"(b)); return r; }
__device__ __forceinline__ uint32_t hfma2(uint32_t a, uint32_t b, uint32_t c) { uint32_t r; asm("fma.rn.bf16x2 %0,%1,%2,%3;" : "=r"(r) : "r"(a), "r"(b), "r"(c)); return r; }
__device__ __forceinline__ float2 cmul(float2 a, float2 b) { return make_float2(a.x * b.x - a.y * b.y, a.x * b.y + a.y * b.x); }
__device__ __forceinline__ float2 cfma(float2 a, float2 b, float2 c) {
  return make_float2(fmaf(a.x, b.x, fmaf(-a.y, b.y, c.x)), fmaf(a.x, b.y, fmaf(a.y, b.x, c.y)));
}
__device__ __forceinline__ uint32_t tagf(float v, uint32_t tag) { return (__float_as_uint(v) & ~1u) | tag; }
__device__ __forceinline__ float untag(uint32_t v) { return __uint_as_float(v & ~1u); }
__device__ __forceinline__ bool untagged(const uint4& v, uint32_t tag) { return (((v.x ^ tag) | (v.y ^ tag) | (v.z ^ tag) | (v.w ^ tag)) & 1) != 0; }
__device__ __forceinline__ bool untagged(const uint2& v, uint32_t tag) { return (((v.x ^ tag) | (v.y ^ tag)) & 1) != 0; }
__device__ __forceinline__ float2 lam_bar(float lr, float li, float ldt) {
  float dt = bf_rn(expf(ldt)); float e = expf(dt * lr), s, c; sincospif(dt * li * 0.31830988618379067f, &s, &c); return make_float2(e * c, e * s);
}

__device__ __forceinline__ int conv_ch(uint32_t c, int s) { return s * ((c >> 21) & 255) + (c & 255) - (s >= (int)(c >> 29) ? 8 : 0); }
struct Role {
  uint32_t v, c, p;
  __device__ __forceinline__ int tb() const { return v & 15; }
  __device__ __forceinline__ int cb() const { return (v >> 4) & 15; }
  __device__ __forceinline__ int b() const { return (v >> 8) & 255; }
  __device__ __forceinline__ int ubase() const { return (v >> 16) & 7; }
  __device__ __forceinline__ int ugs() const { return (v >> 19) & 7; }
  __device__ __forceinline__ int wpart() const { return (v >> 22) & 7; }
  __device__ __forceinline__ int rank() const { return (v >> 26) & 7; }
  __device__ __forceinline__ int cs() const { return (v >> 29) ? 8 : 2; }
  __device__ __forceinline__ int ch(int s) const { return conv_ch(c, s); }
  __device__ __forceinline__ int wlo() const { return p & 1; }
  __device__ __forceinline__ int whi() const { return (p >> 1) & 1; }
  __device__ __forceinline__ uint32_t wmask() const { return (p >> 2) & 255; }
  __device__ __forceinline__ uint32_t umask() const { return (p >> 10) & 255; }
  __device__ __forceinline__ int uj() const { return (p >> 20) & 31; }
  __device__ __forceinline__ int sm() const { return (p >> 25) & 15; }
  __device__ __forceinline__ int nch() const { return (c >> 10) & 7; }
  __device__ __forceinline__ int nprep() const { return (c >> 13) & 255; }
};

__device__ __forceinline__ void wgmma_ss80(float (&d)[40], uint64_t da, uint64_t db, int sd){
  asm volatile("{ .reg .pred p; setp.ne.b32 p, %42, 0;\n"
   "wgmma.mma_async.sync.aligned.m64n80k16.f32.bf16.bf16 {%0, %1, %2, %3, %4, %5, %6, %7, %8, %9, %10, %11, %12, %13, %14, %15, %16, %17, %18, %19, %20, %21, %22, %23, %24, %25, %26, %27, %28, %29, %30, %31, %32, %33, %34, %35, %36, %37, %38, %39}, %40, %41, p, 1, 1, 0, 0; }\n"
   : "+f"(d[0]), "+f"(d[1]), "+f"(d[2]), "+f"(d[3]), "+f"(d[4]), "+f"(d[5]), "+f"(d[6]), "+f"(d[7]), "+f"(d[8]), "+f"(d[9]), "+f"(d[10]), "+f"(d[11]), "+f"(d[12]), "+f"(d[13]), "+f"(d[14]), "+f"(d[15]), "+f"(d[16]), "+f"(d[17]), "+f"(d[18]), "+f"(d[19]), "+f"(d[20]), "+f"(d[21]), "+f"(d[22]), "+f"(d[23]), "+f"(d[24]), "+f"(d[25]), "+f"(d[26]), "+f"(d[27]), "+f"(d[28]), "+f"(d[29]), "+f"(d[30]), "+f"(d[31]), "+f"(d[32]), "+f"(d[33]), "+f"(d[34]), "+f"(d[35]), "+f"(d[36]), "+f"(d[37]), "+f"(d[38]), "+f"(d[39]) : "l"(da), "l"(db), "r"(sd));
}
__device__ __forceinline__ void wgmma_ss160(float (&d)[80], uint64_t da, uint64_t db, int sd){
  asm volatile("{ .reg .pred p; setp.ne.b32 p, %82, 0;\n"
   "wgmma.mma_async.sync.aligned.m64n160k16.f32.bf16.bf16 {%0, %1, %2, %3, %4, %5, %6, %7, %8, %9, %10, %11, %12, %13, %14, %15, %16, %17, %18, %19, %20, %21, %22, %23, %24, %25, %26, %27, %28, %29, %30, %31, %32, %33, %34, %35, %36, %37, %38, %39, %40, %41, %42, %43, %44, %45, %46, %47, %48, %49, %50, %51, %52, %53, %54, %55, %56, %57, %58, %59, %60, %61, %62, %63, %64, %65, %66, %67, %68, %69, %70, %71, %72, %73, %74, %75, %76, %77, %78, %79}, %80, %81, p, 1, 1, 0, 0; }\n"
   : "+f"(d[0]), "+f"(d[1]), "+f"(d[2]), "+f"(d[3]), "+f"(d[4]), "+f"(d[5]), "+f"(d[6]), "+f"(d[7]), "+f"(d[8]), "+f"(d[9]), "+f"(d[10]), "+f"(d[11]), "+f"(d[12]), "+f"(d[13]), "+f"(d[14]), "+f"(d[15]), "+f"(d[16]), "+f"(d[17]), "+f"(d[18]), "+f"(d[19]), "+f"(d[20]), "+f"(d[21]), "+f"(d[22]), "+f"(d[23]), "+f"(d[24]), "+f"(d[25]), "+f"(d[26]), "+f"(d[27]), "+f"(d[28]), "+f"(d[29]), "+f"(d[30]), "+f"(d[31]), "+f"(d[32]), "+f"(d[33]), "+f"(d[34]), "+f"(d[35]), "+f"(d[36]), "+f"(d[37]), "+f"(d[38]), "+f"(d[39]), "+f"(d[40]), "+f"(d[41]), "+f"(d[42]), "+f"(d[43]), "+f"(d[44]), "+f"(d[45]), "+f"(d[46]), "+f"(d[47]), "+f"(d[48]), "+f"(d[49]), "+f"(d[50]), "+f"(d[51]), "+f"(d[52]), "+f"(d[53]), "+f"(d[54]), "+f"(d[55]), "+f"(d[56]), "+f"(d[57]), "+f"(d[58]), "+f"(d[59]), "+f"(d[60]), "+f"(d[61]), "+f"(d[62]), "+f"(d[63]), "+f"(d[64]), "+f"(d[65]), "+f"(d[66]), "+f"(d[67]), "+f"(d[68]), "+f"(d[69]), "+f"(d[70]), "+f"(d[71]), "+f"(d[72]), "+f"(d[73]), "+f"(d[74]), "+f"(d[75]), "+f"(d[76]), "+f"(d[77]), "+f"(d[78]), "+f"(d[79]) : "l"(da), "l"(db), "r"(sd));
}
template<int N> __device__ __forceinline__ void wgmma_rs(float (&d)[N/2], uint32_t a0, uint32_t a1, uint32_t a2, uint32_t a3, uint64_t db, int sd);
template<> __device__ __forceinline__ void wgmma_rs<16>(float (&d)[8], uint32_t a0, uint32_t a1, uint32_t a2, uint32_t a3, uint64_t db, int sd){
  asm volatile("{ .reg .pred p; setp.ne.b32 p, %13, 0;\n"
   "wgmma.mma_async.sync.aligned.m64n16k16.f32.bf16.bf16 {%0, %1, %2, %3, %4, %5, %6, %7}, {%8,%9,%10,%11}, %12, p, 1, 1, 0; }\n"
   : "+f"(d[0]), "+f"(d[1]), "+f"(d[2]), "+f"(d[3]), "+f"(d[4]), "+f"(d[5]), "+f"(d[6]), "+f"(d[7]) : "r"(a0), "r"(a1), "r"(a2), "r"(a3), "l"(db), "r"(sd));
}
template<> __device__ __forceinline__ void wgmma_rs<32>(float (&d)[16], uint32_t a0, uint32_t a1, uint32_t a2, uint32_t a3, uint64_t db, int sd){
  asm volatile("{ .reg .pred p; setp.ne.b32 p, %21, 0;\n"
   "wgmma.mma_async.sync.aligned.m64n32k16.f32.bf16.bf16 {%0, %1, %2, %3, %4, %5, %6, %7, %8, %9, %10, %11, %12, %13, %14, %15}, {%16,%17,%18,%19}, %20, p, 1, 1, 0; }\n"
   : "+f"(d[0]), "+f"(d[1]), "+f"(d[2]), "+f"(d[3]), "+f"(d[4]), "+f"(d[5]), "+f"(d[6]), "+f"(d[7]), "+f"(d[8]), "+f"(d[9]), "+f"(d[10]), "+f"(d[11]), "+f"(d[12]), "+f"(d[13]), "+f"(d[14]), "+f"(d[15]) : "r"(a0), "r"(a1), "r"(a2), "r"(a3), "l"(db), "r"(sd));
}
template<> __device__ __forceinline__ void wgmma_rs<48>(float (&d)[24], uint32_t a0, uint32_t a1, uint32_t a2, uint32_t a3, uint64_t db, int sd){
  asm volatile("{ .reg .pred p; setp.ne.b32 p, %29, 0;\n"
   "wgmma.mma_async.sync.aligned.m64n48k16.f32.bf16.bf16 {%0, %1, %2, %3, %4, %5, %6, %7, %8, %9, %10, %11, %12, %13, %14, %15, %16, %17, %18, %19, %20, %21, %22, %23}, {%24,%25,%26,%27}, %28, p, 1, 1, 0; }\n"
   : "+f"(d[0]), "+f"(d[1]), "+f"(d[2]), "+f"(d[3]), "+f"(d[4]), "+f"(d[5]), "+f"(d[6]), "+f"(d[7]), "+f"(d[8]), "+f"(d[9]), "+f"(d[10]), "+f"(d[11]), "+f"(d[12]), "+f"(d[13]), "+f"(d[14]), "+f"(d[15]), "+f"(d[16]), "+f"(d[17]), "+f"(d[18]), "+f"(d[19]), "+f"(d[20]), "+f"(d[21]), "+f"(d[22]), "+f"(d[23]) : "r"(a0), "r"(a1), "r"(a2), "r"(a3), "l"(db), "r"(sd));
}
template<> __device__ __forceinline__ void wgmma_rs<64>(float (&d)[32], uint32_t a0, uint32_t a1, uint32_t a2, uint32_t a3, uint64_t db, int sd){
  asm volatile("{ .reg .pred p; setp.ne.b32 p, %37, 0;\n"
   "wgmma.mma_async.sync.aligned.m64n64k16.f32.bf16.bf16 {%0, %1, %2, %3, %4, %5, %6, %7, %8, %9, %10, %11, %12, %13, %14, %15, %16, %17, %18, %19, %20, %21, %22, %23, %24, %25, %26, %27, %28, %29, %30, %31}, {%32,%33,%34,%35}, %36, p, 1, 1, 0; }\n"
   : "+f"(d[0]), "+f"(d[1]), "+f"(d[2]), "+f"(d[3]), "+f"(d[4]), "+f"(d[5]), "+f"(d[6]), "+f"(d[7]), "+f"(d[8]), "+f"(d[9]), "+f"(d[10]), "+f"(d[11]), "+f"(d[12]), "+f"(d[13]), "+f"(d[14]), "+f"(d[15]), "+f"(d[16]), "+f"(d[17]), "+f"(d[18]), "+f"(d[19]), "+f"(d[20]), "+f"(d[21]), "+f"(d[22]), "+f"(d[23]), "+f"(d[24]), "+f"(d[25]), "+f"(d[26]), "+f"(d[27]), "+f"(d[28]), "+f"(d[29]), "+f"(d[30]), "+f"(d[31]) : "r"(a0), "r"(a1), "r"(a2), "r"(a3), "l"(db), "r"(sd));
}
template<> __device__ __forceinline__ void wgmma_rs<80>(float (&d)[40], uint32_t a0, uint32_t a1, uint32_t a2, uint32_t a3, uint64_t db, int sd){
  asm volatile("{ .reg .pred p; setp.ne.b32 p, %45, 0;\n"
   "wgmma.mma_async.sync.aligned.m64n80k16.f32.bf16.bf16 {%0, %1, %2, %3, %4, %5, %6, %7, %8, %9, %10, %11, %12, %13, %14, %15, %16, %17, %18, %19, %20, %21, %22, %23, %24, %25, %26, %27, %28, %29, %30, %31, %32, %33, %34, %35, %36, %37, %38, %39}, {%40,%41,%42,%43}, %44, p, 1, 1, 0; }\n"
   : "+f"(d[0]), "+f"(d[1]), "+f"(d[2]), "+f"(d[3]), "+f"(d[4]), "+f"(d[5]), "+f"(d[6]), "+f"(d[7]), "+f"(d[8]), "+f"(d[9]), "+f"(d[10]), "+f"(d[11]), "+f"(d[12]), "+f"(d[13]), "+f"(d[14]), "+f"(d[15]), "+f"(d[16]), "+f"(d[17]), "+f"(d[18]), "+f"(d[19]), "+f"(d[20]), "+f"(d[21]), "+f"(d[22]), "+f"(d[23]), "+f"(d[24]), "+f"(d[25]), "+f"(d[26]), "+f"(d[27]), "+f"(d[28]), "+f"(d[29]), "+f"(d[30]), "+f"(d[31]), "+f"(d[32]), "+f"(d[33]), "+f"(d[34]), "+f"(d[35]), "+f"(d[36]), "+f"(d[37]), "+f"(d[38]), "+f"(d[39]) : "r"(a0), "r"(a1), "r"(a2), "r"(a3), "l"(db), "r"(sd));
}
template<> __device__ __forceinline__ void wgmma_rs<96>(float (&d)[48], uint32_t a0, uint32_t a1, uint32_t a2, uint32_t a3, uint64_t db, int sd){
  asm volatile("{ .reg .pred p; setp.ne.b32 p, %53, 0;\n"
   "wgmma.mma_async.sync.aligned.m64n96k16.f32.bf16.bf16 {%0, %1, %2, %3, %4, %5, %6, %7, %8, %9, %10, %11, %12, %13, %14, %15, %16, %17, %18, %19, %20, %21, %22, %23, %24, %25, %26, %27, %28, %29, %30, %31, %32, %33, %34, %35, %36, %37, %38, %39, %40, %41, %42, %43, %44, %45, %46, %47}, {%48,%49,%50,%51}, %52, p, 1, 1, 0; }\n"
   : "+f"(d[0]), "+f"(d[1]), "+f"(d[2]), "+f"(d[3]), "+f"(d[4]), "+f"(d[5]), "+f"(d[6]), "+f"(d[7]), "+f"(d[8]), "+f"(d[9]), "+f"(d[10]), "+f"(d[11]), "+f"(d[12]), "+f"(d[13]), "+f"(d[14]), "+f"(d[15]), "+f"(d[16]), "+f"(d[17]), "+f"(d[18]), "+f"(d[19]), "+f"(d[20]), "+f"(d[21]), "+f"(d[22]), "+f"(d[23]), "+f"(d[24]), "+f"(d[25]), "+f"(d[26]), "+f"(d[27]), "+f"(d[28]), "+f"(d[29]), "+f"(d[30]), "+f"(d[31]), "+f"(d[32]), "+f"(d[33]), "+f"(d[34]), "+f"(d[35]), "+f"(d[36]), "+f"(d[37]), "+f"(d[38]), "+f"(d[39]), "+f"(d[40]), "+f"(d[41]), "+f"(d[42]), "+f"(d[43]), "+f"(d[44]), "+f"(d[45]), "+f"(d[46]), "+f"(d[47]) : "r"(a0), "r"(a1), "r"(a2), "r"(a3), "l"(db), "r"(sd));
}
template<> __device__ __forceinline__ void wgmma_rs<112>(float (&d)[56], uint32_t a0, uint32_t a1, uint32_t a2, uint32_t a3, uint64_t db, int sd){
  asm volatile("{ .reg .pred p; setp.ne.b32 p, %61, 0;\n"
   "wgmma.mma_async.sync.aligned.m64n112k16.f32.bf16.bf16 {%0, %1, %2, %3, %4, %5, %6, %7, %8, %9, %10, %11, %12, %13, %14, %15, %16, %17, %18, %19, %20, %21, %22, %23, %24, %25, %26, %27, %28, %29, %30, %31, %32, %33, %34, %35, %36, %37, %38, %39, %40, %41, %42, %43, %44, %45, %46, %47, %48, %49, %50, %51, %52, %53, %54, %55}, {%56,%57,%58,%59}, %60, p, 1, 1, 0; }\n"
   : "+f"(d[0]), "+f"(d[1]), "+f"(d[2]), "+f"(d[3]), "+f"(d[4]), "+f"(d[5]), "+f"(d[6]), "+f"(d[7]), "+f"(d[8]), "+f"(d[9]), "+f"(d[10]), "+f"(d[11]), "+f"(d[12]), "+f"(d[13]), "+f"(d[14]), "+f"(d[15]), "+f"(d[16]), "+f"(d[17]), "+f"(d[18]), "+f"(d[19]), "+f"(d[20]), "+f"(d[21]), "+f"(d[22]), "+f"(d[23]), "+f"(d[24]), "+f"(d[25]), "+f"(d[26]), "+f"(d[27]), "+f"(d[28]), "+f"(d[29]), "+f"(d[30]), "+f"(d[31]), "+f"(d[32]), "+f"(d[33]), "+f"(d[34]), "+f"(d[35]), "+f"(d[36]), "+f"(d[37]), "+f"(d[38]), "+f"(d[39]), "+f"(d[40]), "+f"(d[41]), "+f"(d[42]), "+f"(d[43]), "+f"(d[44]), "+f"(d[45]), "+f"(d[46]), "+f"(d[47]), "+f"(d[48]), "+f"(d[49]), "+f"(d[50]), "+f"(d[51]), "+f"(d[52]), "+f"(d[53]), "+f"(d[54]), "+f"(d[55]) : "r"(a0), "r"(a1), "r"(a2), "r"(a3), "l"(db), "r"(sd));
}
template<> __device__ __forceinline__ void wgmma_rs<128>(float (&d)[64], uint32_t a0, uint32_t a1, uint32_t a2, uint32_t a3, uint64_t db, int sd){
  asm volatile("{ .reg .pred p; setp.ne.b32 p, %69, 0;\n"
   "wgmma.mma_async.sync.aligned.m64n128k16.f32.bf16.bf16 {%0, %1, %2, %3, %4, %5, %6, %7, %8, %9, %10, %11, %12, %13, %14, %15, %16, %17, %18, %19, %20, %21, %22, %23, %24, %25, %26, %27, %28, %29, %30, %31, %32, %33, %34, %35, %36, %37, %38, %39, %40, %41, %42, %43, %44, %45, %46, %47, %48, %49, %50, %51, %52, %53, %54, %55, %56, %57, %58, %59, %60, %61, %62, %63}, {%64,%65,%66,%67}, %68, p, 1, 1, 0; }\n"
   : "+f"(d[0]), "+f"(d[1]), "+f"(d[2]), "+f"(d[3]), "+f"(d[4]), "+f"(d[5]), "+f"(d[6]), "+f"(d[7]), "+f"(d[8]), "+f"(d[9]), "+f"(d[10]), "+f"(d[11]), "+f"(d[12]), "+f"(d[13]), "+f"(d[14]), "+f"(d[15]), "+f"(d[16]), "+f"(d[17]), "+f"(d[18]), "+f"(d[19]), "+f"(d[20]), "+f"(d[21]), "+f"(d[22]), "+f"(d[23]), "+f"(d[24]), "+f"(d[25]), "+f"(d[26]), "+f"(d[27]), "+f"(d[28]), "+f"(d[29]), "+f"(d[30]), "+f"(d[31]), "+f"(d[32]), "+f"(d[33]), "+f"(d[34]), "+f"(d[35]), "+f"(d[36]), "+f"(d[37]), "+f"(d[38]), "+f"(d[39]), "+f"(d[40]), "+f"(d[41]), "+f"(d[42]), "+f"(d[43]), "+f"(d[44]), "+f"(d[45]), "+f"(d[46]), "+f"(d[47]), "+f"(d[48]), "+f"(d[49]), "+f"(d[50]), "+f"(d[51]), "+f"(d[52]), "+f"(d[53]), "+f"(d[54]), "+f"(d[55]), "+f"(d[56]), "+f"(d[57]), "+f"(d[58]), "+f"(d[59]), "+f"(d[60]), "+f"(d[61]), "+f"(d[62]), "+f"(d[63]) : "r"(a0), "r"(a1), "r"(a2), "r"(a3), "l"(db), "r"(sd));
}

#define BAR(i) (bars + 8u * (uint32_t)(i))

template <int G> __device__ __forceinline__ void conv_frags(uint32_t (&a)[12], uint32_t abase) {
#pragma unroll
  for (int i = 0; i < 12; i++) a[i] = lds32(abase + (G * 4 + i / 3) * 128 + (i % 3) * 4);
}
__device__ __forceinline__ void kv_prefetch(const __nv_bfloat16* pf, int task) { prefetch_if(pf + 64 * (task & 31) * DM + 64 * (task >> 5), task < 320); }
__device__ __forceinline__ void kv_load(const Params& P, Scratch* S, int task, int tid, uint32_t (&k_)[19], uint32_t (&v_)[16], uint4& sk) {
  const int row = 64 * (task & 31) + 16 * (tid >> 5), ch = 64 * (task >> 5) + 2 * (tid & 31);
  const uint32_t* kp = (const uint32_t*)(P.k + (size_t)row * DM + ch);
  const uint32_t* vp = (const uint32_t*)(P.v + (size_t)row * DM + ch);
  const uint32_t* hp = row > 0 ? kp - 3 * (DM / 2) : S->zero;
  const int hs = row > 0 ? DM / 2 : 0;
  asm volatile("ld.global.nc.v4.u32 {%0,%1,%2,%3},[%4];" : "=r"(sk.x), "=r"(sk.y), "=r"(sk.z), "=r"(sk.w) : "l"(P.shk + ch * 4));
#pragma unroll
  for (int i = 0; i < 3; i++) k_[i] = ldg1(hp + i * hs);
#pragma unroll
  for (int i = 0; i < 16; i++) { k_[i + 3] = ldg1(kp + i * (DM / 2)); v_[i] = ldg1(vp + i * (DM / 2)); }
}
template <int SH> __device__ __forceinline__ void xb_prefetch(const Head& H, int id, int tid, int c0) {
  const int ri = tid >> SH, rr = 11 * id + ri - 16;
  const __nv_bfloat16* p = ri < 16 ? H.x + (size_t)(16 * min(id, 127) + ri) * DM : (rr < DM ? H.b0 : H.b1 - DM * DM) + (size_t)rr * DM;
  prefetch_if(p + c0 + 64 * (tid & ((1 << SH) - 1)), ri < 16 || (ri < 27 && rr < 2 * DM));
}
__device__ __forceinline__ uint4 ldg4(const void* p) { uint4 v; asm volatile("ld.global.nc.v4.u32 {%0,%1,%2,%3},[%4];" : "=r"(v.x), "=r"(v.y), "=r"(v.z), "=r"(v.w) : "l"(p)); return v; }
__device__ __forceinline__ uint4 lds4(uint32_t a) { uint4 v; asm volatile("ld.shared.v4.u32 {%0,%1,%2,%3},[%4];" : "=r"(v.x), "=r"(v.y), "=r"(v.z), "=r"(v.w) : "r"(a) : "memory"); return v; }
__device__ __forceinline__ void discretise(const Head& H, const Params& P, uint32_t sb, Role R, int lane, uint32_t e1) {
  const uint32_t dn = __ldg((const unsigned short*)P.ssmd + min(conv_ch(R.c, (lane + 7) & 7), DM - 1));
  const int c = 32 * min(R.cb(), 9) + lane;
  const uint32_t lr2 = ldg1(P.lre + 2 * c), li2 = ldg1(P.lim + 2 * c), ld2 = ldg1(P.ldt + 2 * c);
  asm volatile("st.shared.u32 [%0],%1;" ::"r"(sb + MISC_OFF + 4 * (lane & 7)), "r"((lane & 7) ? dn : e1) : "memory");
#pragma unroll 1
  for (int i = 0; i < 2; i++) {
    const float lr = bf_hi(lr2 << (16 - 16 * i)), li = bf_hi(li2 << (16 - 16 * i));
    const float2 lb = lam_bar(lr, li, bf_hi(ld2 << (16 - 16 * i)));
    const float nx = lb.x - 1.f, ny = lb.y, inv = 2.f * frcp(lr * lr + li * li), cx = (nx * lr + ny * li) * inv, cy = (ny * lr - nx * li) * inv;
    const bool sw = !H.swap;
    asm volatile("st.shared.v4.f32 [%0],{%1,%2,%3,%4};" ::"r"(sb + LAM_OFF + 32 * lane + 16 * i), "f"(lb.x), "f"(sw ? -lb.y : lb.y), "f"(sw ? -cy : cx), "f"(sw ? cx : -cy) : "memory");
  }
  __syncwarp();
}
__device__ __forceinline__ void aux_prep(const Head& H, const Params& P, uint32_t sb, Role R, int tid, long long t_start) {
  Scratch* const S = H.s;
  const uint32_t bars = sb + BAR_OFF;
  tid = opaque(tid);
  const int w = tid >> 5, lane = tid & 31, tb = R.tb(), cb = R.cb();
  uint32_t k_[19], v_[16];
  uint4 sk;
  int task = R.b() < R.nprep() ? R.b() : 320;
  delay(KVDLY);
  PROFC(tid == 0, 345);
  kv_load(P, S, min(task, 319), tid, k_, v_, sk);
  const __nv_bfloat16* pf = (tid < 64 ? P.k : P.v) + (tid & 63) * DM;
  const int j = lane >> 3, sm = min(R.sm(), 9), trow = 160 * tb + 4 * sm + (tb < 12 ? 40 : 32) * w + j;
  const uint32_t so = sb + (2 * w + (j & 1) + 8 * (j >> 1)) * 128 + 16 * (lane & 7), xo = so + sm * 2048, wo = so + (tb & 1) * 8192 + (tb & 6) * 1024;
  const __nv_bfloat16* xp = H.x + (size_t)min(trow, SEQ - 1) * DM + 384 + 8 * (lane & 7);
  const __nv_bfloat16* bp = (j < 2 ? H.b0 : H.b1) + (size_t)(64 * cb + 32 * (tb & 1) + 4 * (tb & 6) + 2 * w + (j & 1)) * DM + 384 + 8 * (lane & 7);
  float s = 0.f, s2 = 0.f, sr = 0.f;
#define STAT(m, n) { const uint32_t xw[4] = {m.x, m.y, m.z, m.w}, bw[4] = {n.x, n.y, n.z, n.w}; \
  _Pragma("unroll") for (int i = 0; i < 4; i++) { const float u = bf_lo(xw[i]), v = bf_hi(xw[i]); s += u + v; s2 = fmaf(u, u, fmaf(v, v, s2)); sr += bf_lo(bw[i]) + bf_hi(bw[i]); } }
#define STATS(K0, K1) _Pragma("unroll 1") for (int kb = K0; kb < K1; kb++) { \
    mbar_wait(BAR(B_F1 + kb)); \
    const uint4 a = lds4(xo + ((uint32_t)(XTAB0 >> (6 * kb)) & 63) * 4096), c = lds4(wo + ((uint32_t)(WTAB0 >> (6 * kb)) & 63) * 4096); \
    STAT(a, c) \
    asm volatile("" : "+f"(s), "+f"(s2), "+f"(sr)); \
    if (XPFAT >= K0 && XPFAT < K1) prefetch_if(((lane & 4) ? bp : xp) + 64 * (lane & 3), kb == XPFAT); \
    kv_prefetch(pf, kb == KPFAT ? task + R.nprep() : kb == KPFAT2 ? task + 2 * R.nprep() : 320); \
  } \
  __syncwarp(); mbar_arrive_if(BAR(B_AX + K0 / 3), lane == 0);
  STATS(0, 3)
  PROFC(tid == 0, 349);
    {
      uint4 m[4], n[4];
#pragma unroll
      for (int i = 0; i < 4; i++) { m[i] = ldg4(xp + 64 * i); n[i] = ldg4(bp + 64 * i); }
      STATS(3, 6)
      PROFC(tid == 0, 346);
      mbar_wait(BAR(B_LM));
      const uint32_t tag = lds32(sb + MISC_OFF) & 1;
#pragma unroll
      for (int i = 0; i < 4; i++) { const uint4 a = m[i], c = n[i]; STAT(a, c) }
      PROFC(tid == 0 && s2 != 1.2345f, 347);
#pragma unroll
      for (int o = 1; o <= 4; o <<= 1) { s += __shfl_xor_sync(0xffffffff, s, o); s2 += __shfl_xor_sync(0xffffffff, s2, o); sr += __shfl_xor_sync(0xffffffff, sr, o); }
      const float mn = s * (1.f / DM), rs = frcp(bf_rn(fsqrt(bf_rn(bf_rn(fmaxf(s2 * (1.f / DM) - mn * mn, 0.f)) + 1e-5f))));
      asm volatile("{ .reg .pred p; setp.ne.u32 p, %2, 0; @p st.relaxed.gpu.global.u32 [%0],%1; }"
                   ::"l"((uint32_t*)(S->RS + (8 * cb + 4 * (tb & 1) + (tb >> 1)) * 16 + 4 * w + (j & 1)) + (lane & 4) + (j >> 1)), "r"(tagf(sr, tag)),
                   "r"((uint32_t)(tb < 8 && (lane & 3) == 0)) : "memory");
      asm volatile("{ .reg .pred p; setp.ne.u32 p, %3, 0; @p st.relaxed.gpu.global.v2.u32 [%0],{%1,%2}; }"
                   ::"l"(S->S + trow), "r"(tagf(rs, tag)), "r"(tagf(-bf_rn(mn) * rs, tag)), "r"((uint32_t)(R.sm() < 10 && (lane & 7) == 0)) : "memory");
      PROFC(tid == 0, 3);
    }
#pragma unroll 1
  for (int r = 0; task < 320; r++) {
    {
      const uint32_t T0 = __byte_perm(sk.x, sk.z, 0x5410), T1 = __byte_perm(sk.x, sk.z, 0x7632);
      const uint32_t T2 = __byte_perm(sk.y, sk.w, 0x5410), T3 = __byte_perm(sk.y, sk.w, 0x7632);
      PROFC(tid == 0 && v_[15] != 0x12345, 336 + r);
      uint32_t o[16];
#pragma unroll
      for (int t = 0; t < 16; t += 2) {
        const uint32_t a = hmul2(hfma2(k_[t + 3], T0, hfma2(k_[t + 2], T1, hfma2(k_[t + 1], T2, hmul2(k_[t], T3)))), v_[t]);
        const uint32_t c = hmul2(hfma2(k_[t + 4], T0, hfma2(k_[t + 3], T1, hfma2(k_[t + 2], T2, hmul2(k_[t + 1], T3)))), v_[t + 1]);
        const int wd = ((7 - t / 2) >> 1) + 4 * ((7 - t / 2) & 1);
        o[wd] = __byte_perm(c, a, 0x5410); o[8 + wd] = __byte_perm(c, a, 0x7632);
        asm volatile("" : "+r"(o[wd]), "+r"(o[8 + wd]));
        if (t == PFAT) kv_prefetch(pf, task + (1 + PFD) * R.nprep());
      }
      PROFC(tid == 0, 330 + 2 * r);
      const int ph = task & 1;
      task += R.nprep();
      if (ORD == 0 && task < 320) kv_load(P, S, task, tid, k_, v_, sk);
      mbar_wait(BAR(B_E1 + 3)); mbar_wait(BAR(B_AX + 1));
#pragma unroll
      for (int i = 0; i < 4; i++) {
        const int row = 2 * lane + (i >> 1);
        asm volatile("st.shared.v4.u32 [%0],{%1,%2,%3,%4};" ::"r"(sb + KS_OFF + r * 8192 + row * 128 + (((2 * w + ((i & 1) ^ ph)) ^ (row & 7)) << 4)),
                     "r"(o[4 * i]), "r"(o[4 * i + 1]), "r"(o[4 * i + 2]), "r"(o[4 * i + 3]) : "memory");
      }
      __syncwarp();
      mbar_arrive_if(BAR(B_PS + r), lane == 0);
      PROFC(tid == 0, 331 + 2 * r);
      if (ORD == 1 && task < 320) kv_load(P, S, task, tid, k_, v_, sk);
    }
  }
#undef STAT
#undef STATS
  PROFC(tid == 0, 40);
}
#define SPLIT(G) asm volatile("{ .reg .pred p; .reg .u32 r; L: mov.u32 r, %%clock; setp.eq.u32 p, r, %0; @p bra.uni L; }" ::"n"(G) : "memory")
template <bool AUX>
__device__ __forceinline__ void conv_loop(uint32_t sb, uint32_t rc, int wg, int tid, long long t_start) {
  sb = opaque(sb); rc = opaque(rc);
  const uint32_t bars = sb + BAR_OFF;
  int slot = AUX ? 0 : wg + 1;
  mbar_wait(BAR(B_LM));
#pragma unroll 1
  while (slot < (int)((rc >> 10) & 7)) {
    tid = opaque(tid);
    const int w = tid >> 5, lane = tid & 31, g = lane >> 2, q = lane & 3;
    const uint32_t Dn = lds32(sb + MISC_OFF + 4 + 4 * slot);
    const uint32_t d0 = (g == 1 && q == 3 - w) ? Dn : 0, d1 = (g == 0 && q == 3 - w) ? Dn : 0;
    const uint32_t cb_ = conv_buf(sb, slot), c0 = cb_ + KC_OFS;
    const uint32_t abase = c0 + 2 * (2 * (g & 1) + 4 * w + 16 * (g >> 1) + 4 * q);
    const uint64_t bd = make_desc(cb_ + KV_PAD, 16, 256, 3);
    const bool hi = lane & 16, s1 = lane & 8;
    const int qo = hi ? (q + 1) & 3 : q;
    const int srcA = hi ? (lane & 12) | ((q + 1) & 3) : (lane & 12) | 16 | ((q + 3) & 3);
    const bool h3 = hi && q == 3, wrap = s1 && qo == 3, back = wrap && hi;
    const bool chi = wrap ? !hi : hi;
    const int cq = s1 ? (qo + 1) & 3 : qo;
    const int srcB = (lane & 4) | (s1 ? 0 : 8) | (chi ? 16 | ((cq + 3) & 3) : cq);
    const uint32_t gp = c0 + ((32 * (2 * w + (g & 1)) + (chi ? 256 : 0)) ^ (chi ? 64 : 0) ^ ((conv_ch(rc, slot) & 8) << 2)) + 4 * (2 * cq + (s1 ? 0 : 1));
    uint32_t a[12], f[16], o[8];
    float S[4], T[4], U[2], keep[2], pv[2] = {0.f, 0.f}, pr[4] = {0.f, 0.f, 0.f, 0.f};
    float e0[64], e1[56], e2[48], e3[40], e4[32], e5[24], e6[16], e7[8];
#define UNR _Pragma("unroll")
#define PERM() UNR for (int i = 0; i < 4; i++) { f[4 * i] = __byte_perm(a[3 * i], a[3 * i + 1], 0x5432); f[4 * i + 1] = a[3 * i + 1]; \
                                                 f[4 * i + 2] = __byte_perm(a[3 * i + 1], a[3 * i + 2], 0x5432); f[4 * i + 3] = a[3 * i + 2]; }
#define MMA(N, E) UNR for (int i = 0; i < 4; i++) wgmma_rs<N>(E, f[4 * i], f[4 * i + 1], f[4 * i + 2], f[4 * i + 3], bd - 8 * i, 1); wg_commit();
#define L1(c) UNR for (int i = 0; i < 4; i++) { const float ev = c[i], od = c[4 + i]; S[i] = hi ? (h3 ? ev : od) : ev; \
                                                T[i] = __shfl_sync(0xffffffff, hi ? (h3 ? pr[i] : ev) : od, srcA); pr[i] = od; }
#define L1E() UNR for (int i = 0; i < 4; i++) S[i] += T[i];
#define L2() UNR for (int h = 0; h < 2; h++) { keep[h] = back ? pv[h] : S[2 * h + 1]; pv[h] = S[2 * h + 1]; U[h] = __shfl_sync(0xffffffff, S[2 * h], srcB); }
#define L2E(j) o[j] = pack_bf(keep[0] + U[0], keep[1] + U[1]);
#define GRP(G, N, P, E) UNR for (int i = 0; i < N / 2; i++) asm volatile("mov.b32 %0,%1;" : "=f"(E[i]) : "f"(P[i + 8])); \
    wg_fence(); if (G < 7) conv_frags<(G + 1) & 7>(a, abase); if (G >= 2) { L2() } L1(P) MMA(N, E) SPLIT(G); \
    if (G < 7) { PERM() } if (G >= 2) { L2E((G + 6) & 7) } L1E() wg_wait<0>(); fence_regs(E);
    PROFC(tid == 0, 300 + 4 * slot);
    mbar_wait(BAR(B_KF + slot));
    if (tid == 0) PROF(361 + slot);
    PROFC(tid == 0, 301 + 4 * slot);
    conv_frags<0>(a, abase);
    wg_fence();
    wgmma_rs<128>(e0, d0 << 16, d0, d1 << 16, d1, bd, 0);
    PERM() conv_frags<1>(a, abase); wg_fence(); MMA(128, e0) SPLIT(0); PERM() wg_wait<0>(); fence_regs(e0);
    GRP(1, 112, e0, e1) GRP(2, 96, e1, e2) GRP(3, 80, e2, e3) GRP(4, 64, e3, e4) GRP(5, 48, e4, e5) GRP(6, 32, e5, e6) GRP(7, 16, e6, e7)
    PROFC(tid == 0, 302 + 4 * slot);
    L2() L1(e7) L2E(6) L1E() L2() L2E(7)
    bar_sync(wg + 1, 128);
#pragma unroll
    for (int jj = 0; jj < 8; jj++) asm volatile("st.shared.u32 [%0],%1;" ::"r"(gp + jj * 512), "r"(o[jj]) : "memory");
#undef PERM
#undef MMA
#undef L1
#undef L1E
#undef L2
#undef L2E
#undef GRP
    PROFC(tid == 0, 303 + 4 * slot);
    __syncwarp();
    if (lane == 0) mbar_arrive(BAR(B_GS + slot));
    if (!AUX) break;
    slot = slot ? slot + 1 : 3;
  }
}

#define IDX(J, c, h) (8 * (J) + 4 * ((c) >> 1) + 2 * (h) + ((c) & 1))
__device__ __forceinline__ uint2 lds2(uint32_t a) { uint2 v; asm volatile("ld.shared.v2.u32 {%0,%1},[%2];" : "=r"(v.x), "=r"(v.y) : "r"(a) : "memory"); return v; }
__device__ __forceinline__ void resid_load(float (&r)[40], uint32_t sb, int wg, int tid, const uint4& s) {
  const uint32_t dp = sb + XR_OFF + 8 * (tid & 3), xp = dp + (64 * wg + 16 * (tid >> 5) + ((tid & 31) >> 2)) * 160;
#pragma unroll
  for (int J = 0; J < 5; J++) {
    const uint2 u = lds2(xp + 32 * J), v = lds2(xp + 32 * J + 1280), d = lds2(dp + 20480 + 32 * J);
    r[8 * J] = __uint_as_float(u.x); r[8 * J + 1] = __uint_as_float(u.y); r[8 * J + 2] = __uint_as_float(v.x); r[8 * J + 3] = __uint_as_float(v.y);
    r[8 * J + 4] = __uint_as_float(d.x); r[8 * J + 5] = __uint_as_float(d.y);
  }
  r[30] = untag(s.x); r[31] = untag(s.y); r[38] = untag(s.z); r[39] = untag(s.w);
}
__device__ __forceinline__ void resid_init(float (&r)[40]) {
  const float s[4] = {r[30], r[31], r[38], r[39]};
#pragma unroll
  for (int J = 0; J < 5; J++) {
    uint32_t w[6];
#pragma unroll
    for (int i = 0; i < 6; i++) w[i] = __float_as_uint(r[8 * J + i]);
#pragma unroll
    for (int i = 0; i < 4; i++) {
      const int h = i >> 1, c = 2 * (i & 1);
      const float rs = s[2 * h], nm = s[2 * h + 1], x0 = bf_lo(w[i]), x1 = bf_hi(w[i]);
      const uint32_t t = hmul2(pack_bf(fmaf(x0, rs, nm), fmaf(x1, rs, nm)), w[4 + (i & 1)]);
      r[IDX(J, c, h)] = x0 + bf_lo(t); r[IDX(J, c + 1, h)] = x1 + bf_hi(t);
    }
  }
}

__device__ __forceinline__ float flip(float v, uint32_t m) { return __uint_as_float(__float_as_uint(v) ^ m); }
__device__ __forceinline__ void g1_phase(const int LY, const Head& H, uint32_t sb, int wg, int tid, Role R, float (&xr)[40], long long t_start) {
  Scratch* const S = H.s;
  tid = opaque(tid); sb = opaque(sb); R.v = opaque(R.v);
  const uint32_t bars = sb + BAR_OFF;
  const int cb = R.cb(), tb = R.tb();
  const int w = tid >> 5, lane = tid & 31, g = lane >> 2, q = lane & 3;
  const bool full = tb < 12;
  uint2* Eb = S->E + ((LY * 130 + cb) * 8 + 4 * wg + w) * 16 + g;
  float a[80];
#pragma unroll
  for (int i = 0; i < 80; i++) a[i] = 0.f;
  uint32_t rel = mapa(BAR(B_E1), lane ? R.wpart() : R.ubase() + (w & (R.ugs() - 1)));
  const bool rels = lane == 0 || (tid == 1 && wg != R.wlo());
  {
    uint64_t tw = LY ? WTAB1 : WTAB0, tx = LY ? XTAB1 : XTAB0;
    uint32_t bf = BAR(B_F1);
    if (tid == 0 && wg == 0 && !LY) PROF(351);
    fence_regs(a);
    mbar_wait(bf, LY);
    if (tid == 0 && wg == 0) PROF(LY ? 20 : 4);
#pragma unroll 1
    for (int kb = 0; kb < 10; kb++) {
      const uint64_t da = make_desc(sb + ((uint32_t)tw & 63) * 4096 + wg * 8192, 16, 1024, 1);
      const uint64_t db = make_desc(sb + ((uint32_t)tx & 63) * 4096, 16, 1024, 1);
      wg_fence();
#pragma unroll
      for (int kk = 0; kk < 4; kk++) wgmma_ss160(a, da + 2 * kk, db + 2 * kk, 1);
      wg_commit();
      wg_wait<1>();
      if (kb > 0) { if (rels) mbar_arrive_at(rel); rel += 8; }
      bf += 8; tw >>= 6; tx >>= 6;
      if (kb < 9) mbar_wait(bf, LY);
    }
  }
  if (tid == 0 && wg == 0) PROF(LY ? 19 : 2);
  mbar_wait(BAR(B_LM));
  const uint32_t tag = lds32(sb + MISC_OFF) & 1;
  if (q == 3) st_rlx2(Eb + tb * 1280, tag ^ 1, tag ^ 1);
  float2 lam, mu, mu2;
  float rs0, rs1;
  const uint32_t lamp = sb + LAM_OFF + 16 * (32 * wg + 8 * w + g);
  {
    const uint2* rp = S->RS + (8 * cb + 4 * wg + w) * 16 + 2 * g - (g & 1);
    uint2 v = ld_rlx2(rp);
    asm volatile("ld.shared.v2.f32 {%0,%1},[%2];" : "=f"(lam.x), "=f"(lam.y) : "r"(lamp));
    const float2 l2 = cmul(lam, lam), l4 = cmul(l2, l2), l8 = cmul(l4, l4), l16 = cmul(l8, l8), l32 = cmul(l16, l16);
    mu = full ? cmul(l32, l8) : l32; mu2 = cmul(mu, mu);
#pragma unroll 1
    for (int it = 0; it < SPIN && __any_sync(0xffffffff, untagged(v, tag)); it++) v = ld_rlx2(rp);
    rs0 = untag(v.x); rs1 = untag(v.y);
  }
  if (tid == 0 && wg == 0 && !LY) PROF(39);
  mbar_wait(BAR(B_ST), LY);
  const uint32_t ssm = sb + SSM_OFF + q * 160;
  float2 pn = make_float2(0.f, 0.f);
#pragma unroll 1
  for (uint32_t sp = ssm; sp < ssm + (full ? 160 : 128); sp += 16) {
    const uint4 sv = lds4(sp + 640);
#define STEP(n) pn = make_float2(fmaf(lam.x, pn.x, fmaf(-lam.y, pn.y, __uint_as_float(n))), fmaf(lam.x, pn.y, lam.y * pn.x));
    STEP(sv.x) STEP(sv.y) STEP(sv.z) STEP(sv.w)
#undef STEP
  }
  pn = cmul(pn, make_float2(rs0, rs1));
  asm volatile("" : "+f"(pn.x), "+f"(pn.y));
  wg_wait<0>(); fence_regs(a);
  if (rels) mbar_arrive_at(rel);
  if (tid == 0 && wg == 0) PROF(LY ? 21 : 5);
  float2 p = make_float2(0.f, 0.f);
#pragma unroll
  for (int j = 0; j < 10; j++) {
    if (j < 8 || full) {
      const uint4 sv = lds4(ssm + 16 * j);
#pragma unroll
      for (int e = 0; e < 4; e++) {
        const int o = 8 * j + e + (e & 2);
        const float r = __uint_as_float(e == 0 ? sv.x : e == 1 ? sv.y : e == 2 ? sv.z : sv.w);
        a[o] *= r; a[o + 2] *= r;
        p = cfma(lam, p, make_float2(a[o], a[o + 2]));
      }
    }
  }
  p.x += pn.x; p.y += pn.y;
  {
    float2 t = make_float2(__shfl_up_sync(0xffffffff, p.x, 1, 4), __shfl_up_sync(0xffffffff, p.y, 1, 4));
    if (q >= 1) p = cfma(mu, t, p);
    t = make_float2(__shfl_up_sync(0xffffffff, p.x, 2, 4), __shfl_up_sync(0xffffffff, p.y, 2, 4));
    if (q >= 2) p = cfma(mu2, t, p);
  }
  if (q == 3 && full) st_rlx2(Eb + tb * 1280, tagf(p.x, tag), tagf(p.y, tag));
  if (tid == 0 && wg == 1) PROF(96 + 64 * LY);
  uint2 ev[3];
#pragma unroll
  for (int i = 0; i < 3; i++) { const int j = tb - 1 - q - 4 * i; ev[i] = j >= 0 ? ld_rlx2(Eb + j * 1280) : make_uint2(tag, tag); }
  float2 x = make_float2(__shfl_up_sync(0xffffffff, p.x, 1, 4), __shfl_up_sync(0xffffffff, p.y, 1, 4));
  if (q == 0) x = make_float2(0.f, 0.f);
  float c0, c1;
  asm volatile("ld.shared.v2.f32 {%0,%1},[%2+8];" : "=f"(c0), "=f"(c1) : "r"(lamp));
  const float c2 = -flip(c1, H.swap), c3 = flip(c0, H.swap);
  const float k0 = fmaf(c0, rs0, c1 * rs1), k1 = fmaf(c2, rs0, c3 * rs1);
#pragma unroll
  for (int j = 0; j < 10; j++) {
    const uint4 sv = lds4(ssm + 640 + 16 * j);
#pragma unroll
    for (int e = 0; e < 4; e++) {
      const int o = 8 * j + e + (e & 2);
      const float u = a[o], v = a[o + 2], nm = __uint_as_float(e == 0 ? sv.x : e == 1 ? sv.y : e == 2 ? sv.z : sv.w);
      a[o] = fmaf(c0, u, fmaf(c1, v, nm * k0)); a[o + 2] = fmaf(c2, u, fmaf(c3, v, nm * k1));
    }
  }
  fence_regs(a);
  if (LY == 0 && R.b() < 128) {
    const int t0 = 16 * g + 8 * wg + 2 * w;
    if (tid == 0 && wg == 1) PROF(366);
    mbar_wait(BAR(B_XR));
    if (tid == 0 && wg == 1) PROF(367);
    uint4 s = lds4(sb + XR_OFF + 20480 + 256 + 8 * t0);
    if (__any_sync(0xffffffff, untagged(s, tag))) {
#pragma unroll 1
      for (int it = 0; it < SPIN; it++) { s = ld_rlx4(S->S + 128 * (R.b() >> 3) + t0); if (!__any_sync(0xffffffff, untagged(s, tag))) break; }
    }
    resid_load(xr, sb, wg, tid, s);
  }
  float2 mq, om4, fq;
  {
    asm volatile("" : "+f"(lam.x), "+f"(lam.y));
    const float2 one = make_float2(1.f, 0.f), l2 = cmul(lam, lam), l4 = cmul(l2, l2), l8 = cmul(l4, l4), l16 = cmul(l8, l8);
    const float2 l80 = full ? mu2 : cmul(mu2, l16), om = cmul(l80, l80), om2 = cmul(om, om);
    mq = cmul((q & 1) ? mu : one, (q & 2) ? mu2 : one);
    om4 = cmul(om2, om2); fq = cmul((q & 1) ? om : one, (q & 2) ? om2 : one);
  }
  mbar_wait(BAR(B_E1 + 9), LY);
  if (tid == 0 && wg == 1) PROF(368 + LY);
#pragma unroll 1
  for (int it = 0; it < SPIN; it++) {
    const bool m0 = untagged(ev[0], tag), m1 = untagged(ev[1], tag), m2 = untagged(ev[2], tag);
    if (!__any_sync(0xffffffff, m0 || m1 || m2)) break;
    if (m0) ev[0] = ld_rlx2(Eb + (tb - 1 - q) * 1280);
    if (m1) ev[1] = ld_rlx2(Eb + (tb - 5 - q) * 1280);
    if (m2) ev[2] = ld_rlx2(Eb + (tb - 9 - q) * 1280);
  }
  if (tid == 0 && wg == 1) PROF(97 + 64 * LY);
  float2 c = make_float2(untag(ev[2].x), untag(ev[2].y));
#pragma unroll
  for (int i = 1; i >= 0; i--) c = cfma(om4, c, make_float2(untag(ev[i].x), untag(ev[i].y)));
  c = cmul(fq, c);
#pragma unroll
  for (int s = 1; s <= 2; s <<= 1) { c.x += __shfl_xor_sync(0xffffffff, c.x, s); c.y += __shfl_xor_sync(0xffffffff, c.y, s); }
  c = cfma(mq, c, x);
  float2 z = make_float2(fmaf(c0, c.x, c1 * c.y), fmaf(c2, c.x, c3 * c.y));
  if (tid == 0 && wg == 0) PROF(LY ? 22 : 6);
  const float2 lc = make_float2(lam.x, flip(lam.y, H.swap));
  const uint32_t hq = sb + (lane >> 4) * 1024 + (lane & 7) * 128 + (((4 * wg + w) ^ (lane & 7)) << 4);
  const uint32_t hp = hq + R_OFF + (lane & 8) * 2048, hp4 = hq + (LY ? R4_OFF1 : R4_OFF0) + (lane & 8) * 512;
#pragma unroll
  for (int j = 0; j < 20; j += 2) {
    if (j < 16 || full) {
      uint32_t o[4];
#pragma unroll
      for (int i = 0; i < 2; i++) {
        const float2 z0 = cfma(lc, z, make_float2(a[4 * (j + i)], a[4 * (j + i) + 2]));
        z = cfma(lc, z0, make_float2(a[4 * (j + i) + 1], a[4 * (j + i) + 3]));
        o[2 * i] = pack_bf(z0.x, z.x); o[2 * i + 1] = pack_bf(z0.y, z.y);
      }
      asm volatile("stmatrix.sync.aligned.m8n8.x4.trans.shared.b16 [%0], {%1,%2,%3,%4};" ::"r"(j < 16 ? hp + j * 1024 : hp4 + (j - 16) * 1024), "r"(o[0]), "r"(o[1]), "r"(o[2]), "r"(o[3]) : "memory");
      if (j & 2) { __syncwarp(); if (lane == 0) mbar_arrive(BAR(B_SH + j / 4)); }
    }
  }
  if (tid == 0 && wg == 0) PROF(LY ? 23 : 7);
  if (lane == 0) PROF(390 + 4 * wg + w);
}

__device__ __forceinline__ void gate_load(float (&G)[40], uint32_t sb, int LY, int wg, int tid, int tb2) {
  const uint32_t bars = sb + BAR_OFF;
  const int lane = tid & 31, w = tid >> 5;
  mbar_wait(BAR(B_GF), LY);
  const int g = lane >> 2, q = lane & 3;
  const uint32_t gb = sb + (LY ? G_OFF1 : G_OFF0) + wg * 10240 + 512 * q + ((32 * w + 4 * g) ^ (64 * ((tb2 ^ q) & 1)) ^ (16 * (q & 2)));
#pragma unroll
  for (int i = 0; i < 20; i++) { const uint32_t v = lds32((gb ^ (16 * (i & 3))) + 128 * (i & 3) + 2048 * (i >> 2)); G[2 * i] = bf_lo(v); G[2 * i + 1] = bf_hi(v); }
  fence_regs(G);
}
__device__ __forceinline__ void g2_phase(const int LY, const Params& P, Scratch* S, uint32_t sb, int wg, int tid, Role R, float (&xr)[40], long long t_start) {
  sb = opaque(sb);
  const uint32_t bars = sb + BAR_OFF;
  if (LY) {
    const int td = opaque(tid), b = (opaque(R.v) >> 8) & 255;
    const uint32_t tag = lds32(sb + MISC_OFF) & 1;
    const uint2* sp = S->S + 2 * SEQ + 128 * (b >> 3) + 4 * (td & 28) + 8 * wg + 2 * (td >> 5);
    if (!(R.cb() & 1)) mbar_wait(BAR(B_HD), 1);
    uint2 dl[5];
#pragma unroll
    for (int J = 0; J < 5; J++) dl[J] = __ldg((const uint2*)(P.dskip + 80 * (b & 7) + 4 * (td & 3) + 16 * J));
    uint4 sv;
#pragma unroll 1
    for (int it = 0; it < SPIN; it++) { sv = ld_rlx4(sp); if (!__any_sync(0xffffffff, untagged(sv, tag))) break; }
#pragma unroll
    for (int h = 0; h < 2; h++)
#pragma unroll
      for (int J = 0; J < 5; J++)
#pragma unroll
        for (int c = 0; c < 4; c++) {
          const float x2 = xr[IDX(J, c, h)];
          const uint32_t dw = (c & 2) ? dl[J].y : dl[J].x;
          xr[IDX(J, c, h)] = fmaf(fmaf(x2, untag(h ? sv.z : sv.x), untag(h ? sv.w : sv.y)), (c & 1) ? bf_hi(dw) : bf_lo(dw), x2);
        }
    fence_regs(xr);
  }
  float acc[40];
#pragma unroll
  for (int i = 0; i < 40; i++) acc[i] = RIAT == 1 ? 0.f : xr[i];
  fence_regs(acc);
#define G2_STEP(st, cs, hf) { \
    const uint64_t da = make_desc(sb + H_OFF + (st) * 32768 + (hf) * 16384 + wg * 8192, 16, 1024, 1), db = make_desc(sb + (cs) * 20480 + (hf) * 10240, 16, 1024, 1); \
    wg_fence(); \
    _Pragma("unroll") for (int kk = 0; kk < 4; kk++) wgmma_ss80(acc, da + 2 * kk, db + 2 * kk, 1); \
    wg_commit(); }
  mbar_wait(BAR(B_F2), LY);
  if (tid == 0 && wg == 0) PROF(LY ? 25 : 10);
  G2_STEP(0, 0, 0)
  mbar_wait(BAR(B_F3), LY);
  G2_STEP(0, 0, 1)
  tid = opaque(tid); R.v = opaque(R.v);
  const uint32_t tag = lds32(sb + MISC_OFF) & 1;
  const int b = R.b(), tb2 = b >> 3, db_ = b & 7;
  const int w = tid >> 5, lane = tid & 31, g = lane >> 2, q = lane & 3;
  const int t0 = 128 * tb2 + 16 * g + 8 * wg + 2 * w;
  const int d0 = 80 * db_ + 4 * q, mrow = 64 * wg + 16 * w + g;
#define GATE(J, c, h) G[8 * (J) + 2 * (c) + (h)]
  uint32_t rel = mapa(BAR(B_E2), lane ? ((w & 1) ? R.wpart() : R.rank()) : R.cs() == 8 ? 4 * wg + w : wg);
  const bool rels = lane == 0 || (lane == 1 && w < 2);
  const uint32_t mx = sb + MX_OFF + 512 * wg + 4 * tid, bx = BAR(B_KF + 1 + 2 * LY + wg);
  uint32_t pa[8], pb[8];
#pragma unroll
  for (int i = 0; i < 8; i++) { pa[i] = mapa(mx + 1024 * db_, i ^ db_); pb[i] = mapa(bx + (tid >> 10), i ^ db_); asm volatile("" : "+r"(pa[i]), "+r"(pb[i])); }
  uint32_t* Mb = S->M + ((2 * LY * 16 + tb2) * 8) * 256 + (wg * 4 + w) * 32 + (2 * g + (q & 1)) * 2 + (q >> 1);
  {
    uint32_t bf = BAR(B_F2 + 1), st = 1, ra = rel + 8 * (B_EA - B_E2);
    const int lag = wg ? (LY ? STG : STG0) / 2 : 0;
#pragma unroll 1
    for (int kp = 1; kp < 10; kp++) {
      const bool more = LY == 0 || kp < 8;
      wg_wait<1>();
      if (lane == 0 && more) mbar_arrive_at(ra + 8 * (st ? st - 1 : 2));
      mbar_wait(bf, LY);
      if (STG && !(STG & 1) && kp == lag) bar_sync(5, 256);
      G2_STEP(st, kp < 5 ? kp : kp - 5, 0)
      wg_wait<1>();
      if (rels && more) mbar_arrive_at(rel);
      rel += 8;
      mbar_wait(bf + 8 * (B_F3 - B_F2), LY);
      if ((STG & 1) && kp == lag) bar_sync(5, 256);
      G2_STEP(st, kp < 5 ? kp : kp - 5, 1)
      if (kp == MIAT) {
        st_rlx(Mb + db_ * 256, tag ^ 1);
        if (LY == 0) st_rlx(Mb + (16 * 8 + db_) * 256, tag ^ 1);
      }
      bf += 8; st = st == 2 ? 0 : st + 1;
    }
  }
  if (STG && (LY || STG0) && !wg) asm volatile("bar.arrive 5, 256;" ::: "memory");
  wg_wait<0>(); fence_regs(acc);
  if (LY == 0 && rels) mbar_arrive_at(rel);
  if (tid == 0 && wg == 0) PROF(LY ? 26 : 11);
  if (lane == 0) PROF(116 + 64 * LY + wg * 4 + w);

#pragma unroll 1
  for (int rep = 0;; rep++) {
    float m[2][2];
#pragma unroll
    for (int h = 0; h < 2; h++) {
      m[h][0] = m[h][1] = 0.f;
#pragma unroll
      for (int J = 0; J < 5; J++)
#pragma unroll
        for (int c = 0; c < 4; c++) { const float xv = acc[IDX(J, c, h)]; m[h][0] += xv; m[h][1] = fmaf(xv, xv, m[h][1]); }
    }
    float r1[2];
#pragma unroll
    for (int i = 0; i < 2; i++) { const float snd = (q & 1) ? m[0][i] : m[1][i], kp = (q & 1) ? m[1][i] : m[0][i]; r1[i] = kp + __shfl_xor_sync(0xffffffff, snd, 1); }
    const float r2 = ((q & 2) ? r1[1] : r1[0]) + __shfl_xor_sync(0xffffffff, (q & 2) ? r1[0] : r1[1], 2);
    if (R.cs() == 8 && !rep) {
#pragma unroll
      for (int i = 0; i < 8; i++)
        asm volatile("st.async.weak.shared::cluster.mbarrier::complete_tx::bytes.b32 [%0],%1,[%2];" ::"r"(pa[i]), "f"(r2), "r"(pb[i]) : "memory");
      if (tid == 0) mbar_expect_tx(bx, 4096);
    }
    st_rlx(Mb + db_ * 256, tagf(r2, tag));
    if (rep) break;
    if (lane == 0) PROF(100 + 64 * LY + wg * 4 + w);
    float G[40];
    gate_load(G, sb, LY, wg, tid, tb2);
    mbar_wait(BAR(B_CD + 1));
    uint32_t mv[8];
    if (R.cs() == 8) {
      mbar_wait(BAR(B_KF + 1), 1);
      mbar_wait(bx, 1);
#pragma unroll
      for (int i = 0; i < 8; i++) mv[i] = lds32(mx + 1024 * i);
    } else {
#pragma unroll
    for (int i = 0; i < 8; i++) mv[i] = ld_rlx(Mb + i * 256);
#pragma unroll 1
    for (int it = 0; it < SPIN; it++) {
      uint32_t miss = 0;
#pragma unroll
      for (int i = 0; i < 8; i++) miss |= ((mv[i] ^ tag) & 1) << i;
      if (!__any_sync(0xffffffff, miss)) break;
#pragma unroll
      for (int i = 0; i < 8; i++) if ((miss >> i) & 1) mv[i] = ld_rlx(Mb + i * 256);
    }
#pragma unroll
      for (int i = 0; i < 8; i++) mv[i] = __float_as_uint(untag(mv[i]));
      if (MBAR || !LY) bar_sync(4, 256);
    }
    if (lane == 0) PROF(108 + 64 * LY + wg * 4 + w);
#define MV(i) __uint_as_float(mv[i])
    const float s = ((MV(0) + MV(1)) + (MV(2) + MV(3))) + ((MV(4) + MV(5)) + (MV(6) + MV(7)));
#undef MV
    float mm[2], rr[2];
#pragma unroll
    for (int h = 0; h < 2; h++) {
      mm[h] = __shfl_sync(0xffffffff, s, h, 4) * (1.f / DM);
      rr[h] = frsqrt(fmaxf(__shfl_sync(0xffffffff, s, 2 + h, 4) * (1.f / DM) - mm[h] * mm[h], 0.f) + 1e-5f);
    }
    if (tid == 0 && wg == 0) PROF(LY ? 27 : 12);
    const float nm[2] = {-mm[0] * rr[0], -mm[1] * rr[1]};
#pragma unroll
    for (int h = 0; h < 2; h++)
#pragma unroll
      for (int J = 0; J < 5; J++)
#pragma unroll
        for (int c = 0; c < 4; c++) { const float xv = acc[IDX(J, c, h)]; xr[IDX(J, c, h)] = fmaf(fmaf(xv, rr[h], nm[h]), GATE(J, c, h), xv); }
    if (LY) break;
#pragma unroll
    for (int i = 0; i < 40; i++) acc[i] = xr[i] - mm[(i >> 1) & 1];
#pragma unroll
    for (int i = 0; i < 10; i++) {
      const int J = i >> 1, h = i & 1;
      const uint32_t u0 = pack_bf(acc[IDX(J, 0, h)], acc[IDX(J, 1, h)]), u1 = pack_bf(acc[IDX(J, 2, h)], acc[IDX(J, 3, h)]);
      asm volatile("st.shared.v2.u32 [%0],{%1,%2};" ::"r"(sb + US_OFF + ((mrow ^ 64) + 8 * h) * 160 + 32 * J + 8 * q), "r"(u0), "r"(u1) : "memory");
    }
    __syncwarp();
    if (lane == 0) mbar_arrive(BAR(B_GS + 1 + wg));
    if (tid == 0 && wg == 0) PROF(13);
    Mb += 16 * 8 * 256;
  }
  if (LY == 0) {
    if (tid == 0 && wg == 0) PROF(15);
  }
  else {
    float* op = P.out + (size_t)t0 * DM + d0;
#pragma unroll
    for (int i = 0; i < 10; i++) {
      const int J = i >> 1, h = i & 1;
      asm volatile("st.global.v4.f32 [%0],{%1,%2,%3,%4};" ::"l"(op + h * DM + 16 * J),
                   "f"(xr[IDX(J, 0, h)]), "f"(xr[IDX(J, 1, h)]), "f"(xr[IDX(J, 2, h)]), "f"(xr[IDX(J, 3, h)]) : "memory");
    }
  }
  if (tid == 0 && wg == 0 && LY) PROF(28);
#undef IDX
#undef GATE
}

__device__ __forceinline__ void next_stats(Scratch* S, uint32_t sb, int tb2, int tid) {
  const uint32_t bars = sb + BAR_OFF, tag = lds32(sb + MISC_OFF) & 1;
  const uint32_t* Mb = S->M + tb2 * 8 * 256 + 2 * tid;
  mbar_wait(BAR(B_F1 + NSAT), 1);
  float m1, s1, s2;
#pragma unroll 1
  for (int it = 0; it < SPIN; it++) {
    uint32_t a[8], miss = 0;
    uint2 v[8];
#pragma unroll
    for (int i = 0; i < 8; i++) { a[i] = ld_rlx(Mb + i * 256); v[i] = ld_rlx2((const uint2*)(Mb + (16 * 8 + i) * 256)); }
#pragma unroll
    for (int i = 0; i < 8; i++) miss |= (a[i] ^ tag) | (v[i].x ^ tag) | (v[i].y ^ tag);
#define SUM8(F) ((untag(F(0)) + untag(F(1))) + (untag(F(2)) + untag(F(3)))) + ((untag(F(4)) + untag(F(5))) + (untag(F(6)) + untag(F(7))))
#define FA(i) a[i]
#define FX(i) v[i].x
#define FY(i) v[i].y
    m1 = SUM8(FA); s1 = SUM8(FX); s2 = SUM8(FY);
    if (!__any_sync(0xffffffff, miss & 1)) break;
  }
  const float mean = s1 * (1.f / DM), rs = frsqrt(fmaxf(s2 * (1.f / DM) - mean * mean, 0.f) + 1e-5f);
  uint2* sp = S->S + SEQ + 128 * tb2 + 8 * (tid & 14) + 2 * (tid >> 4) + (tid & 1);
  st_rlx2(sp, tagf(rs, tag), tagf(-mean * rs, tag));
  st_rlx2(sp + SEQ, tagf(rs, tag), tagf(-(mean + m1 * (1.f / DM)) * rs, tag));
}
template <int I0, int I1> __device__ __forceinline__ void init_barriers(uint32_t bars) {
#pragma unroll
  for (int i = I0; i < I1; i++) mbar_init(BAR(i), bar_count(i));
}
__device__ __forceinline__ int g2_cb(int kp) { return kp < 5 ? 2 * kp : 2 * kp - 9; }
__device__ __forceinline__ const unsigned* h_flag(Scratch* S, int ly, int tb2, int lane) {
  const int s0 = 128 * min(tb2, 15) / 160;
  const bool two = (128 * tb2 + 127) / 160 != s0;
  return &S->flag[(F_H + (ly * 13 + s0) * 10 + min(lane & 15, 9) + (two && lane >= 16 ? 10 : 0)) * 32];
}
__device__ __forceinline__ void gate_tile(const Params& P, uint32_t dst, uint32_t bar, int tb2, int db) {
  mbar_expect_tx(bar, 20480);
  tma2d(dst, &P.mGT, tb2 * 128, db * 80, bar);
  tma2d(dst + 10240, &P.mGT, tb2 * 128 + 64, db * 80, bar);
}
__global__ void __cluster_dims__() __launch_bounds__(512, 1) fused_kernel(const Head H, const __grid_constant__ Params P) {
  extern __shared__ __align__(1024) uint8_t smem[];
  const uint32_t sb = opaque(smem_u32(smem)), bars = sb + BAR_OFF;
  const int wi = __shfl_sync(0xffffffff, threadIdx.x >> 5, 0), wg = wi >> 2, tid = threadIdx.x & 127;
  const int umap = blockIdx.x >= 96;
#define CLK(v)
  CLK(c_a);
  if (wi == 14) {
    if (elect_one()) { init_barriers<0, NBAR1>(bars); asm volatile("fence.mbarrier_init.release.cluster;" ::: "memory"); }
    __syncwarp();
  } else if (wi >= 12) prefetch_map(wi == 12 ? &P.mB : &P.mA[umap]);
  else if (wg == 2) xb_prefetch<1>(H, blockIdx.x + H.base, tid, 0);
  else if (P.role[blockIdx.x].w) return;
  CLK(c_b);
  asm volatile("barrier.cluster.arrive.relaxed.aligned;" ::: "memory");
  CLK(c_c);
  Role R;
  { const uint4 r = P.role[blockIdx.x]; R.v = r.x; R.c = r.y; R.p = r.z; }
  const int id = R.c & 255;
  const int tb = R.tb(), cb = R.cb(), b = R.b(), tb2 = b >> 3, db = b & 7, rank = R.rank();
  const bool has1 = tb <= 12, has2 = b < 128, full = tb < 12;
  Scratch* const S = H.s;
  unsigned* const epoch_p = &S->epoch[id * 8];
  const long long t_start = 0;
  if (wg < 2) {
    if (threadIdx.x == 0) PROF(50);
    asm volatile("griddepcontrol.launch_dependents;");
    bar_sync(6, 448);
    asm volatile("setmaxnreg.inc.sync.aligned.u32 176;");
    float xr[40];
#pragma unroll
    for (int i = 0; i < 40; i++) xr[i] = 0.f;
#pragma unroll 1
    for (int ly = 0; ly < 2; ly++) {
      if (has1) g1_phase(ly, H, sb, wg, tid, R, xr, t_start);
      if (ly == 0) {
        resid_init(xr); fence_regs(xr);
        conv_loop<false>(sb, R.c, wg, tid, t_start);
        if (tid == 0 && wg == 0) PROF(9);
      }
      if (has2) g2_phase(ly, P, S, sb, wg, tid, R, xr, t_start);
    }
    if (tid == 0 && wg == 0) st_rlx(epoch_p, lds32(sb + MISC_OFF));
  } else if (wg == 2) {
    bar_sync(6, 448);
    if (has1) aux_prep(H, P, sb, R, tid, t_start);
    asm volatile("setmaxnreg.inc.sync.aligned.u32 136;");
    conv_loop<true>(sb, R.c, wg, tid, t_start);
    if (tid == 0) PROF(44);
    {
      const uint32_t bb = (P.role[blockIdx.x].x >> 8) & 255;
      if ((bb & 132) == NSDB && tid < 32) next_stats(H.s, sb, bb >> 3, 32 * (bb & 3) + tid);
    }
  } else {
    if (threadIdx.x == 384) PROF(354);
    asm volatile("setmaxnreg.dec.sync.aligned.u32 24;");
    const int wlo = R.wlo(), whi = R.whi();
    const uint32_t wmask = R.wmask(), umask = R.umask(), f1bytes = full ? 36864 : 32768;
    if (wi < 14) {
      if (threadIdx.x == 384) PROF(340);
      asm volatile("barrier.cluster.wait.aligned;" ::: "memory");
      if (has1 && elect_one()) {
        uint64_t tab = wi == 12 ? WTAB0 : XTAB0;
        PROF(329 + wi);
#pragma unroll 1
        for (int kb = 0; kb < 6; kb++, tab >>= 6) {
          const uint32_t dst = sb + ((uint32_t)tab & 63) * 4096;
          if (wi == 12) {
#pragma unroll 1
            for (int h = wlo; h <= whi; h++) tma4d_mc(dst + h * 8192, &P.mB, kb * 64, 0, 0, 8 * cb + 4 * h, BAR(B_F1 + kb), wmask);
          } else {
            tma4d_mc(dst + R.uj() * 1024, &P.mA[umap], kb * 64, 0, 0, 80 * tb + R.uj(), BAR(B_F1 + kb), umask);
            mbar_expect_tx(BAR(B_F1 + kb), f1bytes);
          }
        }
      }
      if (!has1 && wi == 13) bar_sync(7, 64);
    } else {
      if (wi == 15 && elect_one()) { init_barriers<NBAR1, NBAR>(bars); asm volatile("fence.mbarrier_init.release.cluster;" ::: "memory"); }
      bar_sync(6, 448);
      if (!has1 && wi == 14) bar_sync(7, 64);
    }
    const unsigned e1 = ld_rlx(epoch_p) + 1;
    if (wi == 12) {
      if (elect_one()) {
#pragma unroll 1
        for (int ly = 0; ly < 2; ly++) {
#pragma unroll 1
          for (int i = ly ? 0 : 6; i < 10 && has1; i++) {
            const int kb = (0x9876541032ull >> (4 * i)) & 15;
            if (ly == 0) { mbar_wait(BAR(B_E1 + ((DEP0 >> (4 * kb - 24)) & 15))); mbar_wait(BAR(B_AX + (kb == 9))); }
            else {
              if (has2 && i == (db >= GLATE ? 4 : 2)) {
                wait_cnt(&S->cnt[(C_G + db) * 32], e1 * 80);
                mbar_wait(BAR(B_E2 + 7));
                PROF(47);
                gate_tile(P, sb + G_OFF0, BAR(B_GF), tb2, db);
              }
              if (has2) mbar_wait(BAR(i < 4 ? B_E2 + ((0x9865u >> (4 * i)) & 15) : B_GE));
              else if (i == 0) { mbar_wait(BAR(B_E1 + 9)); mbar_wait(BAR(B_CD + 1)); }
              if (i >= 4) mbar_wait(BAR(i < 6 ? B_F1 + W4AT : B_E1 + i - 6), 1);
            }
            const uint32_t dst = sb + ((uint32_t)((ly ? WTAB1 : WTAB0) >> (6 * kb)) & 63) * 4096;
#pragma unroll 1
            for (int h = wlo; h <= whi; h++) tma4d_mc(dst + h * 8192, &P.mB, kb * 64, 0, 0, 8 * cb + 4 * h, BAR(B_F1 + kb), wmask);
          }
          if (has2) {
            if (ly == 0) {
              mbar_wait(BAR(B_E1 + XRAT));
              mbar_expect_tx(BAR(B_XR), 20480 + 160 + 1024);
              tma4d(sb + XR_OFF, &P.mX, 80 * db, tb2, BAR(B_XR));
              bulk_g2s(sb + XR_OFF + 20480, P.dskip + 80 * db, 160, BAR(B_XR));
              bulk_g2s(sb + XR_OFF + 20480 + 256, S->S + 128 * tb2, 1024, BAR(B_XR));
              if (CWAIT) mbar_wait(BAR(CWAIT == 1 ? B_KF + 2 : CWAIT == 2 ? B_KF + R.nch() - 1 : CWAIT == 3 ? B_KF + R.nch() - 2 : B_HD));
            }
#pragma unroll 1
            for (int kp = 0; kp < 10; kp++) {
              const uint32_t dst = sb + (kp < 5 ? kp : kp - 5) * 20480;
              mbar_wait(BAR(kp >= 5 ? B_E2 + kp - 5 : ly ? B_E1 + ((CTAB1 >> (4 * kp)) & 15) : kp < 3 ? B_SH : kp < 4 ? B_HD : B_CD), ly);
              mbar_expect_tx(BAR(B_F2 + kp), 10240 + 16384);
              tma5d(dst, &P.mC[0], g2_cb(kp) * 64, db * 5, BAR(B_F2 + kp));
              mbar_expect_tx(BAR(B_F3 + kp), 10240 + 16384);
              tma5d(dst + 10240, &P.mC[1], g2_cb(kp) * 64, db * 5, BAR(B_F3 + kp));
              if (ly && kp == 4) { mbar_wait(BAR(B_E1 + 9), 1); gate_tile(P, sb + G_OFF1, BAR(B_GF), tb2, db); }
            }
          }
        }
      }
    } else if (wi == 13) {
      const int h0 = R.cs() == 8 ? rank : 4 * rank;
#pragma unroll 1
      for (int ly = 0; ly < 2; ly++) {
        int lane = lane_id();
        if (has1) {
          const unsigned* fp = &S->flag[(F_U3 + 8 * ((160 * tb) >> 7) + (lane & (full ? 15 : 7))) * 32];
          uint32_t ready = ly ? __ballot_sync(0xffffffff, ld_rlx(fp) == e1) : ~0u;
          if (ly) mbar_wait(BAR(full ? B_KF + 1 : has2 ? B_GS + 1 : B_RF1), has2);
          if (ly && full) mbar_wait(BAR(B_KF + 2), 1);
#pragma unroll 1
          for (int kb = ly ? 0 : 6; kb < 10; kb++) {
            if (ly && kb == UPAT) { mbar_wait(BAR(B_XR)); ready = ~0u; }
            wait_flags(fp, e1, 0x101u * ((1u << (64 * kb / 80)) | (1u << ((64 * kb + 63) / 80))), ready);
            if (kb >= 4) mbar_wait(BAR(B_E1 + (ly ? kb - 4 : (DEP0 >> (4 * kb - 24)) & 15)), ly);
            mbar_wait(BAR(B_AX + (kb == 9)));
            if (elect_one()) {
              if (ly && kb == 0) PROF(34);
              tma4d_mc(sb + ((uint32_t)((ly ? XTAB1 : XTAB0) >> (6 * kb)) & 63) * 4096 + R.uj() * 1024, &P.mA[2 * ly + umap], kb * 64, 0, 0, 80 * tb + R.uj(),
                       BAR(B_F1 + kb), umask);
              mbar_expect_tx(BAR(B_F1 + kb), f1bytes);
            }
            __syncwarp();
          }
        }
        if (ly == 0) {
          if (has1) mbar_wait(BAR(B_E1 + KPF));
          if (elect_one()) {
#pragma unroll 1
            for (int s = 0; s < R.nch(); s++) prefetch_l2(P.ssmk + (size_t)R.ch(s) * SEQ, 4096);
          }
          lane = lane_id();
#pragma unroll
          for (int s = 0; s < 5; s++) {
            asm volatile("st.shared.v4.u32 [%0],{%1,%1,%1,%1};" ::"r"(conv_buf(sb, s) + 16 * lane), "r"(0) : "memory");
            asm volatile("st.shared.u8 [%0],%1;" ::"r"(conv_buf(sb, s) + KC_OFS + lane), "r"(0) : "memory");
          }
          fence_async();
          __syncwarp();
          const unsigned* cp = &S->cnt[(C_KV + (R.ch(min(lane, R.nch() - 1)) >> 6)) * 32];
          uint32_t ready = 0;
#pragma unroll 1
          for (int s = 0, sk = 0; s < R.nch(); s++) {
#pragma unroll 1
            for (; sk < (s ? R.nch() : KUP); sk++)
              if (elect_one()) { mbar_expect_tx(BAR(B_KF + sk), 8192); bulk_g2s(conv_buf(sb, sk) + KC_OFS + 32, P.ssmk + (size_t)R.ch(sk) * SEQ, 4096, BAR(B_KF + sk)); }
            PROFC(s == 0, 329);
#pragma unroll 1
            for (int it = 0; !((ready >> s) & 1) && it < SPIN; it++) ready = __ballot_sync(0xffffffff, (int)(ld_rlx(cp) - e1 * 32) >= 0);
            PROFC(s == 0, 30);
            if (elect_one()) {
              bulk_g2s(conv_buf(sb, s) + KV_PAD, S->kv + (size_t)R.ch(s) * SEQ, 4096, BAR(B_KF + s));
              if (s == 0 && has2) { prefetch_l2(P.cre + (size_t)5 * b * DM, 5 * DM * 2); prefetch_l2(P.cim + (size_t)5 * b * DM, 5 * DM * 2); }
            }
            __syncwarp();
          }
          PROF(31);
          if (!has1) return;
        }
        lane = lane_id();
        const unsigned* fp = h_flag(S, ly, tb2, lane);
        uint32_t ready = __ballot_sync(0xffffffff, ld_rlx(fp) == e1), st = 0;
        if (ly == 0 && !has2) {
          mbar_wait(BAR(B_HD));
          if (lane < 8) mbar_arrive_cl(BAR(B_RF1), lane & 1);
        }
        if (has2) {
          mbar_wait(BAR(B_RF0), ly);
#pragma unroll 1
          for (int kp = 0; kp < 10; kp++) {
            if (kp == 5) { mbar_wait(BAR(B_XR), 1); ready = ~0u; }
            if (kp == 2) { mbar_wait(BAR(B_HD), ly); if (lane < 8) mbar_arrive_cl(BAR(B_RF1), lane & (R.cs() - 1)); }
            wait_flags(fp, e1, 0x10001u << g2_cb(kp), ready);
            if (kp == 2) mbar_wait(BAR(B_RF1), ly);
#pragma unroll
            for (int hf = 0; hf < 2; hf++) {
              if (kp >= 3) { if (hf) mbar_wait(BAR(B_E2 + kp - 3), ly); else mbar_wait(BAR(B_EA + st), ly ^ (kp >= 6 && kp < 9)); }
              if (elect_one()) {
                if (kp == 0 && !hf) PROF(33 + 2 * ly);
                tma4d_mc(sb + H_OFF + st * 32768 + hf * 16384 + h0 * 2048, &P.mH, g2_cb(kp) * 128 + hf * 64, 0, 2 * h0,
                         ly * 16 + tb2, BAR((hf ? B_F3 : B_F2) + kp), (1u << R.cs()) - 1);
              }
              __syncwarp();
            }
            st = st == 2 ? 0 : st + 1;
          }
        }
      }
    } else if (wi == 14) {
      if (!has1) return;
      prefetch_if(P.dskip + 64 * (tid & 31), (tid & 31) < 10);
      if (elect_one()) { prefetch_map(&P.sK); prefetch_map(&P.mX); prefetch_map(&P.sH); prefetch_map(&P.sU); prefetch_map(&P.mC[0]); prefetch_map(&P.mC[1]); prefetch_map(&P.mH); prefetch_map(&P.mGT); prefetch_map(&P.mA[2 + umap]); }
      __syncwarp();
#pragma unroll 1
      for (int ly = 0; ly < 2; ly++) {
        if (ly) {
          mbar_wait(BAR(B_F1 + 1), 1);
          uint32_t ready = 0;
          wait_flags(&S->flag[(F_U3 + 8 * ((160 * tb) >> 7) + ((lane_id() + ly) & (full ? 15 : 7))) * 32], e1, ~0u, ready);
          if (elect_one()) mbar_arrive(BAR(B_XR));
        }
        const int lane = lane_id();
        mbar_wait(BAR(B_E1 + (ly ? STAT_AT1 : STAT_AT)), ly);
        PROFC(lane == 0 && ly == 0, 36);
        {
          const int l = lane - (full ? 0 : 16);
          const uint2* p = S->S + ly * SEQ + 160 * tb + 2 * l;
          uint4 v[3];
#pragma unroll 1
          for (int it = 0; it < SPIN; it++) {
            v[0] = ld_rlx4(p); v[1] = ld_rlx4(p + 64); v[2] = ld_rlx4(p + 96);
            const bool miss = __any_sync(0xffffffff, untagged(v[0], e1 & 1) | untagged(v[1], e1 & 1) | untagged(v[2], e1 & 1));
            PROFC(lane == 0 && ly == 0 && it == 0, 37);
            if (!miss) break;
          }
          PROFC(lane == 0 && ly == 0, 38);
          uint32_t sp = sb + SSM_OFF + 8 * lane + (full ? 0 : 2 * (lane & 16) - 160);
#pragma unroll
          for (int i = 0; i < 3; i++) {
            asm volatile("{ .reg .pred p; setp.ge.u32 p, %0, %5; @p st.shared.v2.u32 [%0],{%1,%3}; @p st.shared.v2.u32 [%0+640],{%2,%4}; }" ::"r"(sp),
                         "r"(v[i].x & ~1u), "r"(v[i].y & ~1u), "r"(v[i].z & ~1u), "r"(v[i].w & ~1u), "r"(sb + SSM_OFF) : "memory");
            sp += (full ? 256 : 320) >> i;
          }
          __syncwarp();
        }
        if (lane == 0) mbar_arrive(BAR(B_ST));
        if (ly && has2) {
          mbar_wait(BAR(B_E1 + 9), 1);
          if (lane < 8) mbar_arrive_cl(BAR(B_RF0), lane & (R.cs() - 1));
        }
        if (lane == 0) {
#pragma unroll 1
          for (int pc = 0; pc < (full ? 5 : 4); pc++) {
            if ((HWM >> (4 * pc)) & 8) {
              mbar_wait(BAR(B_SH + min((HWM >> (4 * pc)) & 7, full ? 4 : 3)), ly);
              PROF(380 + 5 * ly + pc);
              if (pc == 0 && (cb & 1)) delay(ly ? HDLY : HDLY0);
              fence_async();
            }
#pragma unroll
            for (int i = 0; i < 2; i++) tma4d_store(&P.sH, sb + (pc < 4 ? R_OFF + i * 16384 + pc * 4096 : (ly ? R4_OFF1 : R4_OFF0) + i * 4096), 128 * cb + 64 * i, 0, 0, ly * 1024 + 80 * tb + 4 * pc);
          }
          bulk_commit(); bulk_wait();
          PROF(ly ? 17 : 16);
          mbar_arrive(BAR(B_HD));
          release<1>();
          signal_flag(&S->flag[(F_H + (ly * 13 + tb) * 10 + cb) * 32], e1);
          PROF(ly ? 24 : 8);
        }
        __syncwarp();
        if (has2) {
          mbar_wait(BAR(B_F2 + FPAT), ly);
          uint32_t ready = 0;
          wait_flags(h_flag(S, ly, tb2, lane_id() | 1), e1, ~0u, ready);
          if (elect_one()) mbar_arrive(BAR(B_XR));
        }
        if (lane == 0 && has2 && !ly) {
          mbar_wait(BAR(B_CD + 1));
#pragma unroll
          for (int i = 0; i < 2; i++) {
            mbar_wait(BAR(B_GS + 1 + i), 1);
            fence_async();
            tma4d_store(&P.sU, sb + US_OFF + 10240 - 10240 * i, 80 * db, 0, 8 * i, tb2);
          }
          bulk_commit(); bulk_wait();
          PROF(18);
          release<2>(); signal_flag(&S->flag[(F_U3 + b) * 32], e1);
          PROF(14);
          mbar_wait(BAR(B_SG));
          mbar_arrive(BAR(B_GE)); mbar_arrive_cl(BAR(B_GE), R.wpart());
        }
        __syncwarp();
      }
    } else {
      discretise(H, P, sb, R, tid & 31, e1);
      if (elect_one()) {
        mbar_arrive(BAR(B_LM));
        PROF(348);
        if (b < R.nprep()) {
#pragma unroll 1
          for (int task = b, r = 0; task < 320; task += R.nprep(), r++) {
            mbar_wait(BAR(B_PS + r));
            PROF(320 + 3 * r);
            fence_async();
            tma2d_store(&P.sK, sb + KS_OFF + r * 8192, 64 * (task & 31), 64 * (task >> 5));
            bulk_commit(); bulk_wait();
            PROF(321 + 3 * r);
            release<4>();
            signal_cnt(&S->cnt[(C_KV + (task >> 5)) * 32], 1);
            PROF(322 + 3 * r);
          }
          PROF(41);
        }
        if (has2) {
          mbar_wait(BAR(B_SH));
#pragma unroll 1
          for (int i = 0; i < 8; i++) mbar_arrive_cl(BAR(B_RF0), i & (R.cs() - 1));
        }
#pragma unroll 1
        for (int s = 0, s0 = 0; s < R.nch(); s++) {
          mbar_wait(BAR(B_GS + s));
          fence_async();
          bulk_s2g(S->gt + (size_t)R.ch(s) * SEQ, conv_buf(sb, s) + KC_OFS, 4096); bulk_commit();
          if (s == 1 || s >= R.nch() - GSPL) bulk_wait();
          if (s == 1 || s == min(R.nch() - 1, 3)) mbar_arrive(BAR(B_CD + (s > 1)));
          mbar_arrive_if(BAR(B_SG), s == R.nch() - 1);
          if (s >= R.nch() - GSPL) {
            PROF(45);
            release<8>();
#pragma unroll 1
            for (; s0 <= s; s0++) signal_cnt(&S->cnt[(C_G + R.ch(s0) / 80) * 32], 1);
          }
        }
        PROF(46);
      }
    }
  }
}

typedef CUresult (*EncFn)(CUtensorMap*, CUtensorMapDataType, cuuint32_t, void*, const cuuint64_t*, const cuuint64_t*, const cuuint32_t*,
                          const cuuint32_t*, CUtensorMapInterleave, CUtensorMapSwizzle, CUtensorMapL2promotion, CUtensorMapFloatOOBfill);
bool enc(EncFn f, CUtensorMap* m, const void* base, int rank, const cuuint64_t* dims, const cuuint64_t* strides, const cuuint32_t* box, bool swz,
         bool f32 = false) {
  const cuuint32_t es[5] = {1, 1, 1, 1, 1};
  return f(m, f32 ? CU_TENSOR_MAP_DATA_TYPE_FLOAT32 : CU_TENSOR_MAP_DATA_TYPE_BFLOAT16, rank, const_cast<void*>(base), dims, strides, box, es,
           CU_TENSOR_MAP_INTERLEAVE_NONE, swz ? CU_TENSOR_MAP_SWIZZLE_128B : CU_TENSOR_MAP_SWIZZLE_NONE, CU_TENSOR_MAP_L2_PROMOTION_L2_256B,
           CU_TENSOR_MAP_FLOAT_OOB_FILL_NONE) == CUDA_SUCCESS;
}
void make_roles(Params& P, bool big) {
  for (uint32_t bx = 0; bx < (big ? 120u : 12u); bx++) {
    const uint32_t c = bx >> 3, r = bx & 7, id = big ? bx : 120 + bx;
    const uint32_t vA = c < 12 ? (2 * (c >> 1) + (r >> 2)) | (4 * (c & 1) + (r & 3)) << 4 | (r & 4) << 16 | 4 << 19 | (r ^ 4) << 22
                               : (4 * (c - 12) + (r >> 1)) | (8 + (r & 1)) << 4 | (r & 6) << 16 | 2 << 19 | (r ^ 2) << 22;
    const uint32_t vB = (bx < 10 ? 12 : 13) | bx << 4 | 2 << 19 | (bx & 1) << 22 | (bx & 1) << 26;
    P.role[bx].x = (big ? vA | r << 26 | 1u << 29 : vB) | (id < 128 ? (id & ~7u) | (r >> 1) | (r & 1) << 2 : id) << 8;
    P.role[bx].y = id | (big ? 5 : bx < 8 ? 3 : 4) << 10 | 120 << 13 | 132 << 21 | (big ? 4u : 3u) << 29;
    const uint32_t v = P.role[bx].x, cb = (v >> 4) & 15, rank = (v >> 26) & 7, ubase = (v >> 16) & 7, ugs = (v >> 19) & 7, wp = (v >> 22) & 7;
    const uint32_t wlo = rank > wp, whi = wp != rank ? wlo : 1, wmask = 1u << rank | 1u << wp;
    const uint32_t uj = (rank - ubase) * (!big ? 8 : ugs == 4 ? 5 : 10), sm = big ? (0x7296418530ull >> (4 * cb)) & 15 : bx < 8 ? 4 * (bx & 1) + (bx >> 1) : 15;
    P.role[bx].z = wlo | whi << 1 | wmask << 2 | ((1u << ugs) - 1) << (10 + ubase) | uj << 20 | sm << 25;
    P.role[bx].w = 0;
  }
}
void launch(const Head& H, const Params& P, int grid, int cs, bool dependent) {
  cudaLaunchConfig_t cfg = {};
  cfg.gridDim = grid; cfg.blockDim = 512; cfg.dynamicSmemBytes = SMEM_BYTES; cfg.stream = cudaStreamPerThread;
  cudaLaunchAttribute at[2];
  at[0].id = cudaLaunchAttributeClusterDimension; at[0].val.clusterDim.x = cs; at[0].val.clusterDim.y = 1; at[0].val.clusterDim.z = 1;
  at[1].id = cudaLaunchAttributeProgrammaticStreamSerialization; at[1].val.programmaticStreamSerializationAllowed = 1;
  cfg.attrs = at; cfg.numAttrs = dependent ? 2 : 1;
  cudaLaunchKernelEx(&cfg, fused_kernel, H, P);
}

}

extern "C" void kernel_launch(void* const* d_in, const int* in_sizes, int n_in, void* d_out, int out_size) {
  (void)in_sizes; (void)n_in; (void)out_size;
  typedef const __nv_bfloat16* cb;
  void* fp = nullptr; cudaDriverEntryPointQueryResult qr;
  cudaGetDriverEntryPoint("cuTensorMapEncodeTiled", &fp, cudaEnableDefault, &qr);
  EncFn f = (EncFn)fp;
  Scratch* sp = nullptr;
  cudaGetSymbolAddress((void**)&sp, g_scr);
  void *pu = sp->u, *ph = sp->h, *pgt = sp->gt;
  Params P;
  Head H;
  H.s = sp; H.x = (cb)d_in[0]; H.swap = (uintptr_t)d_in[4] < (uintptr_t)d_in[3] ? 0 : 0x80000000u; H.b0 = (cb)d_in[H.swap ? 3 : 4]; H.b1 = (cb)d_in[H.swap ? 4 : 3];
  for (int i = 0; i < 2; i++) {
    const cuuint64_t d[4] = {640, 8, 2, 80}, s[3] = {1280, (cuuint64_t)((uintptr_t)H.b1 - (uintptr_t)H.b0), 8 * 1280}; const cuuint32_t bx[4] = {64, 8, 2, 4};
    if (enc(f, &P.mB, H.b0, 4, d, s, bx, true)) break;
    cudaMemcpyAsync(sp->bcopy, H.b0, DM * DM * 2, cudaMemcpyDeviceToDevice, cudaStreamPerThread);
    cudaMemcpyAsync(sp->bcopy + DM * DM, H.b1, DM * DM * 2, cudaMemcpyDeviceToDevice, cudaStreamPerThread);
    H.b0 = sp->bcopy; H.b1 = sp->bcopy + DM * DM;
  }
  {
    const cuuint64_t d[5] = {640, 2, 4, 2, 40}, s[4] = {1280, 4 * 1280, 2 * 1280, 16 * 1280}; const cuuint32_t bx[5] = {64, 2, 4, 2, 5};
    enc(f, &P.mC[0], d_in[5], 5, d, s, bx, true); enc(f, &P.mC[1], d_in[6], 5, d, s, bx, true); }
  { const cuuint64_t d[2] = {2048, 640}, s[1] = {4096}; const cuuint32_t bx[2] = {64, 80}; enc(f, &P.mGT, pgt, 2, d, s, bx, true); }
  { const cuuint64_t d[4] = {640, 8, 16, 16}, s[3] = {16 * 1280, 1280, 128 * 1280}; const cuuint32_t bx[4] = {80, 8, 16, 1}, bh[4] = {80, 8, 8, 1};
    enc(f, &P.sU, pu, 4, d, s, bh, false); enc(f, &P.mX, d_in[0], 4, d, s, bx, false); }
  { const cuuint64_t d[2] = {2048, 640}, s[1] = {4096}; const cuuint32_t bx[2] = {64, 64}; enc(f, &P.sK, sp->kv, 2, d, s, bx, true); }
  P.lre = (cb)d_in[1]; P.lim = (cb)d_in[2]; P.cre = (cb)d_in[5]; P.cim = (cb)d_in[6]; P.ldt = (cb)d_in[7]; P.dskip = (cb)d_in[8];
  P.out = (float*)d_out;
  P.k = (cb)d_in[10]; P.v = (cb)d_in[11]; P.shk = (cb)d_in[12]; P.ssmk = (cb)d_in[13]; P.ssmd = (cb)d_in[14];
  cudaFuncSetAttribute(fused_kernel, cudaFuncAttributeMaxDynamicSharedMemorySize, SMEM_BYTES);
  for (int big = 1; big >= 0; big--) {
    const cuuint64_t seg = big ? 40 : 32;
    for (int i = 0; i < 4; i++) {
      const cuuint64_t d[4] = {640, 2, 4, 1024}, s[3] = {1280, seg * 1280, 2 * 1280}; const cuuint32_t bx[4] = {64, 2, 4, !big ? 8u : (i & 1) ? 10u : 5u};
      enc(f, &P.mA[i], i < 2 ? d_in[0] : pu, 4, d, s, bx, true);
    }
    {
      const cuuint64_t d[4] = {1280, 8, 16, 32}, s[3] = {16 * 2560, 2560, 128 * 2560}; const cuuint32_t bx[4] = {64, 8, big ? 2u : 8u, 1};
      enc(f, &P.mH, ph, 4, d, s, bx, true); }
    { const cuuint64_t d[4] = {1280, 2, 4, 2048}, s[3] = {2560, seg * 2560, 2 * 2560}; const cuuint32_t bx[4] = {64, 2, 4, 4};
      enc(f, &P.sH, ph, 4, d, s, bx, true); }
    make_roles(P, big);
    H.base = big ? 0 : 120;
    launch(H, P, big ? 120 : 12, big ? 8 : 2, !big);
  }
}
```

```cpp
#include <cuda_runtime.h>
#include <cuda.h>
#include <cuda_bf16.h>
#include <stdint.h>

namespace {

constexpr int SEQ = 2048, DM = 640;
constexpr int SPIN = 1 << 20;
#define PFAT 99
#define KVDLY 500
#define PFD 1
#define XPFAT 9
#define STAT_AT 6
#define KPFAT 3
#define KPFAT2 5
#define KPF 7
#define HDLY 1900
#define GSPL 2
#define CWAIT 0
#define HDLY0 1900
#define CTAB1 0x96543u
#define NSAT 0
#define SKW 1
#define RIAT 2
#define MIAT 5
#define FPAT 1
#define UPAT 7
#define STAT_AT1 4
#define W4AT 0
#define MBAR 1
#define STG 17
#define STG0 17
#define HWM 0xc09
#define NSDB 4
#define GLATE 6
#define KUP 1
#define XRAT 9
#define ORD 1

struct Scratch {
  uint2 E[2 * 13 * 10 * 8 * 16];
  uint32_t M[3 * 16 * 8 * 256];
  uint2 S[3 * SEQ];
  uint2 RS[80 * 16];
  unsigned flag[512 * 32];
  unsigned cnt[32 * 32];
  unsigned epoch[132 * 8];
  unsigned zero[128];
  unsigned prof[132 * 512];
  __align__(1024)
  __nv_bfloat16 u[SEQ * DM];
  __nv_bfloat16 h[2 * SEQ * 1280];
  __nv_bfloat16 kv[DM * SEQ];
  __nv_bfloat16 gt[DM * SEQ];
  __nv_bfloat16 bcopy[2 * DM * DM];
};
__device__ __align__(1024) Scratch g_scr;
#define PROFC(c, i) do {} while (0)
#define PSEL 1
#define PROF(i) do {} while (0)

constexpr int C_KV = 0, C_G = 10;
constexpr int F_U3 = 0, F_H = 128;

constexpr int R_OFF = 196608, R4_OFF0 = 73728, R4_OFF1 = 122880, H_OFF = 131072, KS_OFF = 131072, CV_OFF = 86272, G_OFF0 = 40960, G_OFF1 = 102400, US_OFF = 98304, XR_OFF = 163840, MX_OFF = 32768;
constexpr int LAM_OFF = 229376, SSM_OFF = LAM_OFF + 1024, BAR_OFF = SSM_OFF + 1344;
constexpr int B_F1 = 0, B_E1 = 10, B_RF0 = 20, B_RF1 = 21, NBAR1 = 22;
constexpr int B_F2 = 22, B_KF = 32, B_GF = 37, B_CD = 38, B_XR = 40, B_ST = 41, B_HD = 42, B_LM = 43, B_E2 = 44, B_GS = 54, B_PS = 59, B_AX = 62, B_SH = 64, B_SG = 69, B_GE = 70, B_EA = 71, B_F3 = 74, NBAR = 84;
__host__ __device__ constexpr int bar_count(int i) { return i < B_E1 ? 1 : i < B_RF0 ? 9 : i < B_F2 ? 8 : i < B_E2 ? 1 : i < B_GS ? 12 : i < B_SH ? 4 : i < B_SG ? 8 : i < B_GE ? 1 : i < B_EA ? 2 : i < B_F3 ? 8 : 1; }
constexpr int MISC_OFF = BAR_OFF + NBAR * 8, SMEM_BYTES = MISC_OFF + 32;
constexpr int KV_PAD = 512, KC_OFS = KV_PAD + 4096, CH_STRIDE = 8960;
__device__ __forceinline__ uint32_t conv_buf(uint32_t sb, int slot) { return sb + CV_OFF + slot * CH_STRIDE; }
constexpr uint64_t tab6(int a, int b, int c, int d, int e, int f, int g, int h, int i, int j) {
  return (uint64_t)a | (uint64_t)b << 6 | (uint64_t)c << 12 | (uint64_t)d << 18 | (uint64_t)e << 24 | (uint64_t)f << 30 | (uint64_t)g << 36 | (uint64_t)h << 42 |
         (uint64_t)i << 48 | (uint64_t)j << 54;
}
constexpr uint64_t WTAB0 = tab6(0, 4, 8, 30, 12, 26, 0, 4, 8, 12), XTAB0 = tab6(40, 45, 50, 34, 16, 21, 40, 45, 50, 16);
constexpr uint64_t WTAB1 = tab6(16, 20, 0, 4, 8, 12, 16, 20, 24, 28), XTAB1 = tab6(40, 45, 50, 32, 40, 45, 50, 32, 40, 45);
constexpr uint32_t DEP0 = 0x4210;

struct Head {
  Scratch* s;
  const __nv_bfloat16 *x, *b0, *b1;
  uint32_t base, swap;
};
struct Params {
  const __nv_bfloat16 *lre, *lim, *ldt, *k, *v, *shk, *cre, *cim, *ssmk, *ssmd, *dskip;
  float* out;
  uint4 role[120];
  CUtensorMap mB, mA[4], mH, mC[2], mGT, mX, sH, sU, sK;
};

__device__ __forceinline__ uint32_t smem_u32(const void* p) { return (uint32_t)__cvta_generic_to_shared(p); }
__device__ __forceinline__ uint32_t opaque(uint32_t x) { uint32_t y; asm volatile("mov.u32 %0, %1;" : "=r"(y) : "r"(x)); return y; }
__device__ __forceinline__ int lane_id() { int y; asm volatile("mov.u32 %0, %%laneid;" : "=r"(y)); return y; }
__device__ __forceinline__ void delay(uint32_t n) {
  asm volatile("{ .reg .pred p; .reg .u32 a, b; mov.u32 a, %%clock; L: mov.u32 b, %%clock; sub.u32 b, b, a; setp.lt.u32 p, b, %0; @p bra.uni L; }" ::"r"(n) : "memory");
}
__device__ __forceinline__ void mbar_init(uint32_t bar, uint32_t cnt) { asm volatile("mbarrier.init.shared::cta.b64 [%0], %1;" ::"r"(bar), "r"(cnt) : "memory"); }
__device__ __forceinline__ void mbar_expect_tx(uint32_t bar, uint32_t bytes) { asm volatile("mbarrier.arrive.expect_tx.shared::cta.b64 _, [%0], %1;" ::"r"(bar), "r"(bytes) : "memory"); }
__device__ __forceinline__ void mbar_arrive(uint32_t bar) { asm volatile("mbarrier.arrive.shared::cta.b64 _, [%0];" ::"r"(bar) : "memory"); }
__device__ __forceinline__ void mbar_arrive_if(uint32_t bar, bool c) {
  asm volatile("{ .reg .pred p; setp.ne.u32 p, %1, 0; @p mbarrier.arrive.shared::cta.b64 _, [%0]; }" ::"r"(bar), "r"((uint32_t)c) : "memory");
}
__device__ __forceinline__ void prefetch_if(const void* p, bool c) { asm volatile("{ .reg .pred p; setp.ne.u32 p, %1, 0; @p prefetch.global.L2 [%0]; }" ::"l"(p), "r"((uint32_t)c)); }
__device__ __forceinline__ void mbar_arrive_cl(uint32_t bar, uint32_t cta) {
  asm volatile("{ .reg .b32 ra; mapa.shared::cluster.u32 ra, %0, %1; mbarrier.arrive.shared::cluster.b64 _, [ra]; }" ::"r"(bar), "r"(cta) : "memory");
}
__device__ __forceinline__ uint32_t mapa(uint32_t a, uint32_t cta) { uint32_t r; asm("mapa.shared::cluster.u32 %0, %1, %2;" : "=r"(r) : "r"(a), "r"(cta)); return r; }
__device__ __forceinline__ void mbar_arrive_at(uint32_t ra) { asm volatile("mbarrier.arrive.shared::cluster.b64 _, [%0];" ::"r"(ra) : "memory"); }
__device__ __forceinline__ void mbar_wait(uint32_t bar, uint32_t parity = 0) {
  asm volatile("{ .reg .pred p; .reg .u32 c; mov.u32 c, 0;\n"
               "W: mbarrier.try_wait.parity.shared::cta.b64 p, [%0], %1; @p bra.uni D;\n"
               "add.u32 c, c, 1; setp.lt.u32 p, c, 0x100000; @p bra.uni W;\nD: }" ::"r"(bar), "r"(parity) : "memory");
}
__device__ __forceinline__ bool elect_one() { uint32_t p; asm volatile("{ .reg .pred P; elect.sync _|P, 0xffffffff; selp.u32 %0,1,0,P; }" : "=r"(p)); return p; }
__device__ __forceinline__ void bar_sync(int id, int n) { __syncwarp(); asm volatile("bar.sync %0, %1;" ::"r"(id), "r"(n) : "memory"); }
__device__ __forceinline__ void tma2d(uint32_t dst, const CUtensorMap* m, int c0, int c1, uint32_t bar) {
  asm volatile("cp.async.bulk.tensor.2d.shared::cluster.global.mbarrier::complete_tx::bytes [%0], [%1, {%3,%4}], [%2];"
               ::"r"(dst), "l"(m), "r"(bar), "r"(c0), "r"(c1) : "memory");
}
__device__ __forceinline__ void tma5d(uint32_t dst, const CUtensorMap* m, int c0, int c4, uint32_t bar) {
  asm volatile("cp.async.bulk.tensor.5d.shared::cluster.global.mbarrier::complete_tx::bytes [%0], [%1, {%3,%5,%5,%5,%4}], [%2];"
               ::"r"(dst), "l"(m), "r"(bar), "r"(c0), "r"(c4), "r"(0) : "memory");
}
__device__ __forceinline__ void tma4d(uint32_t dst, const CUtensorMap* m, int c0, int c3, uint32_t bar) {
  asm volatile("cp.async.bulk.tensor.4d.shared::cluster.global.mbarrier::complete_tx::bytes [%0], [%1, {%3,%5,%5,%4}], [%2];"
               ::"r"(dst), "l"(m), "r"(bar), "r"(c0), "r"(c3), "r"(0) : "memory");
}
__device__ __forceinline__ void tma4d_mc(uint32_t dst, const CUtensorMap* m, int c0, int c1, int c2, int c3, uint32_t bar, uint32_t mask) {
  asm volatile("cp.async.bulk.tensor.4d.shared::cluster.global.mbarrier::complete_tx::bytes.multicast::cluster [%0], [%1, {%3,%4,%5,%6}], [%2], %7;"
               ::"r"(dst), "l"(m), "r"(bar), "r"(c0), "r"(c1), "r"(c2), "r"(c3), "h"((uint16_t)mask) : "memory");
}
__device__ __forceinline__ void bulk_g2s(uint32_t dst, const void* src, uint32_t bytes, uint32_t bar) {
  asm volatile("cp.async.bulk.shared::cluster.global.mbarrier::complete_tx::bytes [%0], [%1], %2, [%3];" ::"r"(dst), "l"(src), "r"(bytes), "r"(bar) : "memory");
}
__device__ __forceinline__ void tma4d_store(const CUtensorMap* m, uint32_t src, int c0, int c1, int c2, int c3) {
  asm volatile("cp.async.bulk.tensor.4d.global.shared::cta.bulk_group [%0, {%2,%3,%4,%5}], [%1];" ::"l"(m), "r"(src), "r"(c0), "r"(c1), "r"(c2), "r"(c3) : "memory");
}
__device__ __forceinline__ void tma2d_store(const CUtensorMap* m, uint32_t src, int c0, int c1) {
  asm volatile("cp.async.bulk.tensor.2d.global.shared::cta.bulk_group [%0, {%2,%3}], [%1];" ::"l"(m), "r"(src), "r"(c0), "r"(c1) : "memory");
}
__device__ __forceinline__ void bulk_s2g(void* dst, uint32_t src, uint32_t bytes) {
  asm volatile("cp.async.bulk.global.shared::cta.bulk_group [%0], [%1], %2;" ::"l"(dst), "r"(src), "r"(bytes) : "memory");
}
__device__ __forceinline__ void bulk_commit() { asm volatile("cp.async.bulk.commit_group;" ::: "memory"); }
__device__ __forceinline__ void bulk_wait() { asm volatile("cp.async.bulk.wait_group 0;" ::: "memory"); }
__device__ __forceinline__ void fence_async() { asm volatile("fence.proxy.async.shared::cta;" ::: "memory"); }
__device__ __forceinline__ void prefetch_l2(const void* src, uint32_t bytes) { asm volatile("cp.async.bulk.prefetch.L2.global [%0], %1;" ::"l"(src), "r"(bytes) : "memory"); }
__device__ __forceinline__ void prefetch_map(const CUtensorMap* m) { asm volatile("prefetch.tensormap [%0];" ::"l"(m) : "memory"); }
__device__ __forceinline__ void wg_fence() { __syncwarp(); asm volatile("wgmma.fence.sync.aligned;" ::: "memory"); }
__device__ __forceinline__ void wg_commit() { asm volatile("wgmma.commit_group.sync.aligned;" ::: "memory"); }
template <int N> __device__ __forceinline__ void wg_wait() { asm volatile("wgmma.wait_group.sync.aligned %0;" ::"n"(N) : "memory"); }
template <int N> __device__ __forceinline__ void fence_regs(float (&d)[N]) {
#pragma unroll
  for (int i = 0; i < N; i++) asm volatile("" : "+f"(d[i])::"memory");
}
__device__ __forceinline__ uint64_t make_desc(uint32_t addr, uint32_t lbo, uint32_t sbo, uint32_t swz) {
  return (uint64_t)((addr & 0x3FFFF) >> 4) | ((uint64_t)(lbo >> 4) << 16) | ((uint64_t)(sbo >> 4) << 32) | ((uint64_t)swz << 62);
}
__device__ __forceinline__ uint32_t ldg1(const void* p) { uint32_t v; asm volatile("ld.global.nc.u32 %0,[%1];" : "=r"(v) : "l"(p)); return v; }
__device__ __forceinline__ uint32_t lds32(uint32_t a) { uint32_t v; asm volatile("ld.shared.u32 %0,[%1];" : "=r"(v) : "r"(a)); return v; }
__device__ __forceinline__ unsigned ld_rlx(const unsigned* p) { unsigned v; asm volatile("ld.relaxed.gpu.global.u32 %0,[%1];" : "=r"(v) : "l"(p) : "memory"); return v; }
__device__ __forceinline__ uint4 ld_rlx4(const void* p) {
  uint4 v; asm volatile("ld.relaxed.gpu.global.v4.u32 {%0,%1,%2,%3},[%4];" : "=r"(v.x), "=r"(v.y), "=r"(v.z), "=r"(v.w) : "l"(p) : "memory"); return v;
}
__device__ __forceinline__ uint2 ld_rlx2(const void* p) { uint2 v; asm volatile("ld.relaxed.gpu.global.v2.u32 {%0,%1},[%2];" : "=r"(v.x), "=r"(v.y) : "l"(p) : "memory"); return v; }
__device__ __forceinline__ void st_rlx2(void* p, uint32_t a, uint32_t b) { asm volatile("st.relaxed.gpu.global.v2.u32 [%0],{%1,%2};" ::"l"(p), "r"(a), "r"(b) : "memory"); }
__device__ __forceinline__ void st_rlx(void* p, uint32_t a) { asm volatile("st.relaxed.gpu.global.u32 [%0],%1;" ::"l"(p), "r"(a) : "memory"); }
#define PUB 15
template <int SITE> __device__ __forceinline__ void release() { if (PUB & SITE) asm volatile("fence.release.gpu;" ::: "memory"); }
__device__ __forceinline__ void signal_flag(unsigned* p, unsigned val) { asm volatile("st.relaxed.gpu.global.u32 [%0],%1;" ::"l"(p), "r"(val) : "memory"); }
__device__ __forceinline__ void signal_cnt(unsigned* p, unsigned n) { asm volatile("red.relaxed.gpu.global.add.u32 [%0],%1;" ::"l"(p), "r"(n) : "memory"); }
__device__ __forceinline__ void wait_flags(const unsigned* p, unsigned val, uint32_t need, uint32_t& ready) {
#pragma unroll 1
  for (int it = 0; (ready & need) != need && it < SPIN; it++) ready = __ballot_sync(0xffffffff, ld_rlx(p) == val);
}
__device__ __forceinline__ void wait_cnt(const unsigned* p, unsigned tgt) {
  asm volatile("{ .reg .pred p; .reg .u32 c; .reg .s32 v; mov.u32 c, 0;\n"
               "W: ld.relaxed.gpu.global.u32 v, [%0]; sub.s32 v, v, %1; setp.ge.s32 p, v, 0; @p bra.uni D;\n"
               "add.u32 c, c, 1; setp.lt.u32 p, c, 0x100000; @p bra.uni W;\nD: }" ::"l"(p), "r"(tgt) : "memory");
}
__device__ __forceinline__ uint32_t pack_bf(float lo, float hi) { uint32_t r; asm("cvt.rn.bf16x2.f32 %0, %1, %2;" : "=r"(r) : "f"(hi), "f"(lo)); return r; }
__device__ __forceinline__ float bf_lo(uint32_t v) { return __uint_as_float(v << 16); }
__device__ __forceinline__ float bf_hi(uint32_t v) { return __uint_as_float(v & 0xffff0000u); }
__device__ __forceinline__ float bf_rn(float x) { return __bfloat162float(__float2bfloat16_rn(x)); }
__device__ __forceinline__ float frcp(float x) { float r; asm("rcp.approx.ftz.f32 %0,%1;" : "=f"(r) : "f"(x)); return r; }
__device__ __forceinline__ float fsqrt(float x) { float r; asm("sqrt.approx.ftz.f32 %0,%1;" : "=f"(r) : "f"(x)); return r; }
__device__ __forceinline__ float frsqrt(float x) { float r; asm("rsqrt.approx.ftz.f32 %0,%1;" : "=f"(r) : "f"(x)); return r; }
__device__ __forceinline__ uint32_t hmul2(uint32_t a, uint32_t b) { uint32_t r; asm("mul.rn.bf16x2 %0,%1,%2;" : "=r"(r) : "r"(a), "r"(b)); return r; }
__device__ __forceinline__ uint32_t hfma2(uint32_t a, uint32_t b, uint32_t c) { uint32_t r; asm("fma.rn.bf16x2 %0,%1,%2,%3;" : "=r"(r) : "r"(a), "r"(b), "r"(c)); return r; }
__device__ __forceinline__ float2 cmul(float2 a, float2 b) { return make_float2(a.x * b.x - a.y * b.y, a.x * b.y + a.y * b.x); }
__device__ __forceinline__ float2 cfma(float2 a, float2 b, float2 c) {
  return make_float2(fmaf(a.x, b.x, fmaf(-a.y, b.y, c.x)), fmaf(a.x, b.y, fmaf(a.y, b.x, c.y)));
}
__device__ __forceinline__ uint32_t tagf(float v, uint32_t tag) { return (__float_as_uint(v) & ~1u) | tag; }
__device__ __forceinline__ float untag(uint32_t v) { return __uint_as_float(v & ~1u); }
__device__ __forceinline__ bool untagged(const uint4& v, uint32_t tag) { return (((v.x ^ tag) | (v.y ^ tag) | (v.z ^ tag) | (v.w ^ tag)) & 1) != 0; }
__device__ __forceinline__ bool untagged(const uint2& v, uint32_t tag) { return (((v.x ^ tag) | (v.y ^ tag)) & 1) != 0; }
__device__ __forceinline__ float2 lam_bar(float lr, float li, float ldt) {
  float dt = bf_rn(expf(ldt)); float e = expf(dt * lr), s, c; sincospif(dt * li * 0.31830988618379067f, &s, &c); return make_float2(e * c, e * s);
}

__device__ __forceinline__ int conv_ch(uint32_t c, int s) { return s * ((c >> 21) & 255) + (c & 255) - (s >= (int)(c >> 29) ? 8 : 0); }
struct Role {
  uint32_t v, c, p;
  __device__ __forceinline__ int tb() const { return v & 15; }
  __device__ __forceinline__ int cb() const { return (v >> 4) & 15; }
  __device__ __forceinline__ int b() const { return (v >> 8) & 255; }
  __device__ __forceinline__ int ubase() const { return (v >> 16) & 7; }
  __device__ __forceinline__ int ugs() const { return (v >> 19) & 7; }
  __device__ __forceinline__ int wpart() const { return (v >> 22) & 7; }
  __device__ __forceinline__ int rank() const { return (v >> 26) & 7; }
  __device__ __forceinline__ int cs() const { return (v >> 29) ? 8 : 2; }
  __device__ __forceinline__ int ch(int s) const { return conv_ch(c, s); }
  __device__ __forceinline__ int wlo() const { return p & 1; }
  __device__ __forceinline__ int whi() const { return (p >> 1) & 1; }
  __device__ __forceinline__ uint32_t wmask() const { return (p >> 2) & 255; }
  __device__ __forceinline__ uint32_t umask() const { return (p >> 10) & 255; }
  __device__ __forceinline__ int uj() const { return (p >> 20) & 31; }
  __device__ __forceinline__ int sm() const { return (p >> 25) & 15; }
  __device__ __forceinline__ int nch() const { return (c >> 10) & 7; }
  __device__ __forceinline__ int nprep() const { return (c >> 13) & 255; }
};

__device__ __forceinline__ void wgmma_ss80(float (&d)[40], uint64_t da, uint64_t db, int sd){
  asm volatile("{ .reg .pred p; setp.ne.b32 p, %42, 0;\n"
   "wgmma.mma_async.sync.aligned.m64n80k16.f32.bf16.bf16 {%0, %1, %2, %3, %4, %5, %6, %7, %8, %9, %10, %11, %12, %13, %14, %15, %16, %17, %18, %19, %20, %21, %22, %23, %24, %25, %26, %27, %28, %29, %30, %31, %32, %33, %34, %35, %36, %37, %38, %39}, %40, %41, p, 1, 1, 0, 0; }\n"
   : "+f"(d[0]), "+f"(d[1]), "+f"(d[2]), "+f"(d[3]), "+f"(d[4]), "+f"(d[5]), "+f"(d[6]), "+f"(d[7]), "+f"(d[8]), "+f"(d[9]), "+f"(d[10]), "+f"(d[11]), "+f"(d[12]), "+f"(d[13]), "+f"(d[14]), "+f"(d[15]), "+f"(d[16]), "+f"(d[17]), "+f"(d[18]), "+f"(d[19]), "+f"(d[20]), "+f"(d[21]), "+f"(d[22]), "+f"(d[23]), "+f"(d[24]), "+f"(d[25]), "+f"(d[26]), "+f"(d[27]), "+f"(d[28]), "+f"(d[29]), "+f"(d[30]), "+f"(d[31]), "+f"(d[32]), "+f"(d[33]), "+f"(d[34]), "+f"(d[35]), "+f"(d[36]), "+f"(d[37]), "+f"(d[38]), "+f"(d[39]) : "l"(da), "l"(db), "r"(sd));
}
__device__ __forceinline__ void wgmma_ss160(float (&d)[80], uint64_t da, uint64_t db, int sd){
  asm volatile("{ .reg .pred p; setp.ne.b32 p, %82, 0;\n"
   "wgmma.mma_async.sync.aligned.m64n160k16.f32.bf16.bf16 {%0, %1, %2, %3, %4, %5, %6, %7, %8, %9, %10, %11, %12, %13, %14, %15, %16, %17, %18, %19, %20, %21, %22, %23, %24, %25, %26, %27, %28, %29, %30, %31, %32, %33, %34, %35, %36, %37, %38, %39, %40, %41, %42, %43, %44, %45, %46, %47, %48, %49, %50, %51, %52, %53, %54, %55, %56, %57, %58, %59, %60, %61, %62, %63, %64, %65, %66, %67, %68, %69, %70, %71, %72, %73, %74, %75, %76, %77, %78, %79}, %80, %81, p, 1, 1, 0, 0; }\n"
   : "+f"(d[0]), "+f"(d[1]), "+f"(d[2]), "+f"(d[3]), "+f"(d[4]), "+f"(d[5]), "+f"(d[6]), "+f"(d[7]), "+f"(d[8]), "+f"(d[9]), "+f"(d[10]), "+f"(d[11]), "+f"(d[12]), "+f"(d[13]), "+f"(d[14]), "+f"(d[15]), "+f"(d[16]), "+f"(d[17]), "+f"(d[18]), "+f"(d[19]), "+f"(d[20]), "+f"(d[21]), "+f"(d[22]), "+f"(d[23]), "+f"(d[24]), "+f"(d[25]), "+f"(d[26]), "+f"(d[27]), "+f"(d[28]), "+f"(d[29]), "+f"(d[30]), "+f"(d[31]), "+f"(d[32]), "+f"(d[33]), "+f"(d[34]), "+f"(d[35]), "+f"(d[36]), "+f"(d[37]), "+f"(d[38]), "+f"(d[39]), "+f"(d[40]), "+f"(d[41]), "+f"(d[42]), "+f"(d[43]), "+f"(d[44]), "+f"(d[45]), "+f"(d[46]), "+f"(d[47]), "+f"(d[48]), "+f"(d[49]), "+f"(d[50]), "+f"(d[51]), "+f"(d[52]), "+f"(d[53]), "+f"(d[54]), "+f"(d[55]), "+f"(d[56]), "+f"(d[57]), "+f"(d[58]), "+f"(d[59]), "+f"(d[60]), "+f"(d[61]), "+f"(d[62]), "+f"(d[63]), "+f"(d[64]), "+f"(d[65]), "+f"(d[66]), "+f"(d[67]), "+f"(d[68]), "+f"(d[69]), "+f"(d[70]), "+f"(d[71]), "+f"(d[72]), "+f"(d[73]), "+f"(d[74]), "+f"(d[75]), "+f"(d[76]), "+f"(d[77]), "+f"(d[78]), "+f"(d[79]) : "l"(da), "l"(db), "r"(sd));
}
template<int N> __device__ __forceinline__ void wgmma_rs(float (&d)[N/2], uint32_t a0, uint32_t a1, uint32_t a2, uint32_t a3, uint64_t db, int sd);
template<> __device__ __forceinline__ void wgmma_rs<16>(float (&d)[8], uint32_t a0, uint32_t a1, uint32_t a2, uint32_t a3, uint64_t db, int sd){
  asm volatile("{ .reg .pred p; setp.ne.b32 p, %13, 0;\n"
   "wgmma.mma_async.sync.aligned.m64n16k16.f32.bf16.bf16 {%0, %1, %2, %3, %4, %5, %6, %7}, {%8,%9,%10,%11}, %12, p, 1, 1, 0; }\n"
   : "+f"(d[0]), "+f"(d[1]), "+f"(d[2]), "+f"(d[3]), "+f"(d[4]), "+f"(d[5]), "+f"(d[6]), "+f"(d[7]) : "r"(a0), "r"(a1), "r"(a2), "r"(a3), "l"(db), "r"(sd));
}
template<> __device__ __forceinline__ void wgmma_rs<32>(float (&d)[16], uint32_t a0, uint32_t a1, uint32_t a2, uint32_t a3, uint64_t db, int sd){
  asm volatile("{ .reg .pred p; setp.ne.b32 p, %21, 0;\n"
   "wgmma.mma_async.sync.aligned.m64n32k16.f32.bf16.bf16 {%0, %1, %2, %3, %4, %5, %6, %7, %8, %9, %10, %11, %12, %13, %14, %15}, {%16,%17,%18,%19}, %20, p, 1, 1, 0; }\n"
   : "+f"(d[0]), "+f"(d[1]), "+f"(d[2]), "+f"(d[3]), "+f"(d[4]), "+f"(d[5]), "+f"(d[6]), "+f"(d[7]), "+f"(d[8]), "+f"(d[9]), "+f"(d[10]), "+f"(d[11]), "+f"(d[12]), "+f"(d[13]), "+f"(d[14]), "+f"(d[15]) : "r"(a0), "r"(a1), "r"(a2), "r"(a3), "l"(db), "r"(sd));
}
template<> __device__ __forceinline__ void wgmma_rs<48>(float (&d)[24], uint32_t a0, uint32_t a1, uint32_t a2, uint32_t a3, uint64_t db, int sd){
  asm volatile("{ .reg .pred p; setp.ne.b32 p, %29, 0;\n"
   "wgmma.mma_async.sync.aligned.m64n48k16.f32.bf16.bf16 {%0, %1, %2, %3, %4, %5, %6, %7, %8, %9, %10, %11, %12, %13, %14, %15, %16, %17, %18, %19, %20, %21, %22, %23}, {%24,%25,%26,%27}, %28, p, 1, 1, 0; }\n"
   : "+f"(d[0]), "+f"(d[1]), "+f"(d[2]), "+f"(d[3]), "+f"(d[4]), "+f"(d[5]), "+f"(d[6]), "+f"(d[7]), "+f"(d[8]), "+f"(d[9]), "+f"(d[10]), "+f"(d[11]), "+f"(d[12]), "+f"(d[13]), "+f"(d[14]), "+f"(d[15]), "+f"(d[16]), "+f"(d[17]), "+f"(d[18]), "+f"(d[19]), "+f"(d[20]), "+f"(d[21]), "+f"(d[22]), "+f"(d[23]) : "r"(a0), "r"(a1), "r"(a2), "r"(a3), "l"(db), "r"(sd));
}
template<> __device__ __forceinline__ void wgmma_rs<64>(float (&d)[32], uint32_t a0, uint32_t a1, uint32_t a2, uint32_t a3, uint64_t db, int sd){
  asm volatile("{ .reg .pred p; setp.ne.b32 p, %37, 0;\n"
   "wgmma.mma_async.sync.aligned.m64n64k16.f32.bf16.bf16 {%0, %1, %2, %3, %4, %5, %6, %7, %8, %9, %10, %11, %12, %13, %14, %15, %16, %17, %18, %19, %20, %21, %22, %23, %24, %25, %26, %27, %28, %29, %30, %31}, {%32,%33,%34,%35}, %36, p, 1, 1, 0; }\n"
   : "+f"(d[0]), "+f"(d[1]), "+f"(d[2]), "+f"(d[3]), "+f"(d[4]), "+f"(d[5]), "+f"(d[6]), "+f"(d[7]), "+f"(d[8]), "+f"(d[9]), "+f"(d[10]), "+f"(d[11]), "+f"(d[12]), "+f"(d[13]), "+f"(d[14]), "+f"(d[15]), "+f"(d[16]), "+f"(d[17]), "+f"(d[18]), "+f"(d[19]), "+f"(d[20]), "+f"(d[21]), "+f"(d[22]), "+f"(d[23]), "+f"(d[24]), "+f"(d[25]), "+f"(d[26]), "+f"(d[27]), "+f"(d[28]), "+f"(d[29]), "+f"(d[30]), "+f"(d[31]) : "r"(a0), "r"(a1), "r"(a2), "r"(a3), "l"(db), "r"(sd));
}
template<> __device__ __forceinline__ void wgmma_rs<80>(float (&d)[40], uint32_t a0, uint32_t a1, uint32_t a2, uint32_t a3, uint64_t db, int sd){
  asm volatile("{ .reg .pred p; setp.ne.b32 p, %45, 0;\n"
   "wgmma.mma_async.sync.aligned.m64n80k16.f32.bf16.bf16 {%0, %1, %2, %3, %4, %5, %6, %7, %8, %9, %10, %11, %12, %13, %14, %15, %16, %17, %18, %19, %20, %21, %22, %23, %24, %25, %26, %27, %28, %29, %30, %31, %32, %33, %34, %35, %36, %37, %38, %39}, {%40,%41,%42,%43}, %44, p, 1, 1, 0; }\n"
   : "+f"(d[0]), "+f"(d[1]), "+f"(d[2]), "+f"(d[3]), "+f"(d[4]), "+f"(d[5]), "+f"(d[6]), "+f"(d[7]), "+f"(d[8]), "+f"(d[9]), "+f"(d[10]), "+f"(d[11]), "+f"(d[12]), "+f"(d[13]), "+f"(d[14]), "+f"(d[15]), "+f"(d[16]), "+f"(d[17]), "+f"(d[18]), "+f"(d[19]), "+f"(d[20]), "+f"(d[21]), "+f"(d[22]), "+f"(d[23]), "+f"(d[24]), "+f"(d[25]), "+f"(d[26]), "+f"(d[27]), "+f"(d[28]), "+f"(d[29]), "+f"(d[30]), "+f"(d[31]), "+f"(d[32]), "+f"(d[33]), "+f"(d[34]), "+f"(d[35]), "+f"(d[36]), "+f"(d[37]), "+f"(d[38]), "+f"(d[39]) : "r"(a0), "r"(a1), "r"(a2), "r"(a3), "l"(db), "r"(sd));
}
template<> __device__ __forceinline__ void wgmma_rs<96>(float (&d)[48], uint32_t a0, uint32_t a1, uint32_t a2, uint32_t a3, uint64_t db, int sd){
  asm volatile("{ .reg .pred p; setp.ne.b32 p, %53, 0;\n"
   "wgmma.mma_async.sync.aligned.m64n96k16.f32.bf16.bf16 {%0, %1, %2, %3, %4, %5, %6, %7, %8, %9, %10, %11, %12, %13, %14, %15, %16, %17, %18, %19, %20, %21, %22, %23, %24, %25, %26, %27, %28, %29, %30, %31, %32, %33, %34, %35, %36, %37, %38, %39, %40, %41, %42, %43, %44, %45, %46, %47}, {%48,%49,%50,%51}, %52, p, 1, 1, 0; }\n"
   : "+f"(d[0]), "+f"(d[1]), "+f"(d[2]), "+f"(d[3]), "+f"(d[4]), "+f"(d[5]), "+f"(d[6]), "+f"(d[7]), "+f"(d[8]), "+f"(d[9]), "+f"(d[10]), "+f"(d[11]), "+f"(d[12]), "+f"(d[13]), "+f"(d[14]), "+f"(d[15]), "+f"(d[16]), "+f"(d[17]), "+f"(d[18]), "+f"(d[19]), "+f"(d[20]), "+f"(d[21]), "+f"(d[22]), "+f"(d[23]), "+f"(d[24]), "+f"(d[25]), "+f"(d[26]), "+f"(d[27]), "+f"(d[28]), "+f"(d[29]), "+f"(d[30]), "+f"(d[31]), "+f"(d[32]), "+f"(d[33]), "+f"(d[34]), "+f"(d[35]), "+f"(d[36]), "+f"(d[37]), "+f"(d[38]), "+f"(d[39]), "+f"(d[40]), "+f"(d[41]), "+f"(d[42]), "+f"(d[43]), "+f"(d[44]), "+f"(d[45]), "+f"(d[46]), "+f"(d[47]) : "r"(a0), "r"(a1), "r"(a2), "r"(a3), "l"(db), "r"(sd));
}
template<> __device__ __forceinline__ void wgmma_rs<112>(float (&d)[56], uint32_t a0, uint32_t a1, uint32_t a2, uint32_t a3, uint64_t db, int sd){
  asm volatile("{ .reg .pred p; setp.ne.b32 p, %61, 0;\n"
   "wgmma.mma_async.sync.aligned.m64n112k16.f32.bf16.bf16 {%0, %1, %2, %3, %4, %5, %6, %7, %8, %9, %10, %11, %12, %13, %14, %15, %16, %17, %18, %19, %20, %21, %22, %23, %24, %25, %26, %27, %28, %29, %30, %31, %32, %33, %34, %35, %36, %37, %38, %39, %40, %41, %42, %43, %44, %45, %46, %47, %48, %49, %50, %51, %52, %53, %54, %55}, {%56,%57,%58,%59}, %60, p, 1, 1, 0; }\n"
   : "+f"(d[0]), "+f"(d[1]), "+f"(d[2]), "+f"(d[3]), "+f"(d[4]), "+f"(d[5]), "+f"(d[6]), "+f"(d[7]), "+f"(d[8]), "+f"(d[9]), "+f"(d[10]), "+f"(d[11]), "+f"(d[12]), "+f"(d[13]), "+f"(d[14]), "+f"(d[15]), "+f"(d[16]), "+f"(d[17]), "+f"(d[18]), "+f"(d[19]), "+f"(d[20]), "+f"(d[21]), "+f"(d[22]), "+f"(d[23]), "+f"(d[24]), "+f"(d[25]), "+f"(d[26]), "+f"(d[27]), "+f"(d[28]), "+f"(d[29]), "+f"(d[30]), "+f"(d[31]), "+f"(d[32]), "+f"(d[33]), "+f"(d[34]), "+f"(d[35]), "+f"(d[36]), "+f"(d[37]), "+f"(d[38]), "+f"(d[39]), "+f"(d[40]), "+f"(d[41]), "+f"(d[42]), "+f"(d[43]), "+f"(d[44]), "+f"(d[45]), "+f"(d[46]), "+f"(d[47]), "+f"(d[48]), "+f"(d[49]), "+f"(d[50]), "+f"(d[51]), "+f"(d[52]), "+f"(d[53]), "+f"(d[54]), "+f"(d[55]) : "r"(a0), "r"(a1), "r"(a2), "r"(a3), "l"(db), "r"(sd));
}
template<> __device__ __forceinline__ void wgmma_rs<128>(float (&d)[64], uint32_t a0, uint32_t a1, uint32_t a2, uint32_t a3, uint64_t db, int sd){
  asm volatile("{ .reg .pred p; setp.ne.b32 p, %69, 0;\n"
   "wgmma.mma_async.sync.aligned.m64n128k16.f32.bf16.bf16 {%0, %1, %2, %3, %4, %5, %6, %7, %8, %9, %10, %11, %12, %13, %14, %15, %16, %17, %18, %19, %20, %21, %22, %23, %24, %25, %26, %27, %28, %29, %30, %31, %32, %33, %34, %35, %36, %37, %38, %39, %40, %41, %42, %43, %44, %45, %46, %47, %48, %49, %50, %51, %52, %53, %54, %55, %56, %57, %58, %59, %60, %61, %62, %63}, {%64,%65,%66,%67}, %68, p, 1, 1, 0; }\n"
   : "+f"(d[0]), "+f"(d[1]), "+f"(d[2]), "+f"(d[3]), "+f"(d[4]), "+f"(d[5]), "+f"(d[6]), "+f"(d[7]), "+f"(d[8]), "+f"(d[9]), "+f"(d[10]), "+f"(d[11]), "+f"(d[12]), "+f"(d[13]), "+f"(d[14]), "+f"(d[15]), "+f"(d[16]), "+f"(d[17]), "+f"(d[18]), "+f"(d[19]), "+f"(d[20]), "+f"(d[21]), "+f"(d[22]), "+f"(d[23]), "+f"(d[24]), "+f"(d[25]), "+f"(d[26]), "+f"(d[27]), "+f"(d[28]), "+f"(d[29]), "+f"(d[30]), "+f"(d[31]), "+f"(d[32]), "+f"(d[33]), "+f"(d[34]), "+f"(d[35]), "+f"(d[36]), "+f"(d[37]), "+f"(d[38]), "+f"(d[39]), "+f"(d[40]), "+f"(d[41]), "+f"(d[42]), "+f"(d[43]), "+f"(d[44]), "+f"(d[45]), "+f"(d[46]), "+f"(d[47]), "+f"(d[48]), "+f"(d[49]), "+f"(d[50]), "+f"(d[51]), "+f"(d[52]), "+f"(d[53]), "+f"(d[54]), "+f"(d[55]), "+f"(d[56]), "+f"(d[57]), "+f"(d[58]), "+f"(d[59]), "+f"(d[60]), "+f"(d[61]), "+f"(d[62]), "+f"(d[63]) : "r"(a0), "r"(a1), "r"(a2), "r"(a3), "l"(db), "r"(sd));
}

#define BAR(i) (bars + 8u * (uint32_t)(i))

template <int G> __device__ __forceinline__ void conv_frags(uint32_t (&a)[12], uint32_t abase) {
#pragma unroll
  for (int i = 0; i < 12; i++) a[i] = lds32(abase + (G * 4 + i / 3) * 128 + (i % 3) * 4);
}
__device__ __forceinline__ void kv_prefetch(const __nv_bfloat16* pf, int task) { prefetch_if(pf + 64 * (task & 31) * DM + 64 * (task >> 5), task < 320); }
__device__ __forceinline__ void kv_load(const Params& P, Scratch* S, int task, int tid, uint32_t (&k_)[19], uint32_t (&v_)[16], uint4& sk) {
  const int row = 64 * (task & 31) + 16 * (tid >> 5), ch = 64 * (task >> 5) + 2 * (tid & 31);
  const uint32_t* kp = (const uint32_t*)(P.k + (size_t)row * DM + ch);
  const uint32_t* vp = (const uint32_t*)(P.v + (size_t)row * DM + ch);
  const uint32_t* hp = row > 0 ? kp - 3 * (DM / 2) : S->zero;
  const int hs = row > 0 ? DM / 2 : 0;
  asm volatile("ld.global.nc.v4.u32 {%0,%1,%2,%3},[%4];" : "=r"(sk.x), "=r"(sk.y), "=r"(sk.z), "=r"(sk.w) : "l"(P.shk + ch * 4));
#pragma unroll
  for (int i = 0; i < 3; i++) k_[i] = ldg1(hp + i * hs);
#pragma unroll
  for (int i = 0; i < 16; i++) { k_[i + 3] = ldg1(kp + i * (DM / 2)); v_[i] = ldg1(vp + i * (DM / 2)); }
}
template <int SH> __device__ __forceinline__ void xb_prefetch(const Head& H, int id, int tid, int c0) {
  const int ri = tid >> SH, rr = 11 * id + ri - 16;
  const __nv_bfloat16* p = ri < 16 ? H.x + (size_t)(16 * min(id, 127) + ri) * DM : (rr < DM ? H.b0 : H.b1 - DM * DM) + (size_t)rr * DM;
  prefetch_if(p + c0 + 64 * (tid & ((1 << SH) - 1)), ri < 16 || (ri < 27 && rr < 2 * DM));
}
__device__ __forceinline__ uint4 ldg4(const void* p) { uint4 v; asm volatile("ld.global.nc.v4.u32 {%0,%1,%2,%3},[%4];" : "=r"(v.x), "=r"(v.y), "=r"(v.z), "=r"(v.w) : "l"(p)); return v; }
__device__ __forceinline__ uint4 lds4(uint32_t a) { uint4 v; asm volatile("ld.shared.v4.u32 {%0,%1,%2,%3},[%4];" : "=r"(v.x), "=r"(v.y), "=r"(v.z), "=r"(v.w) : "r"(a) : "memory"); return v; }
__device__ __forceinline__ void discretise(const Head& H, const Params& P, uint32_t sb, Role R, int lane, uint32_t e1) {
  const uint32_t dn = __ldg((const unsigned short*)P.ssmd + min(conv_ch(R.c, (lane + 7) & 7), DM - 1));
  const int c = 32 * min(R.cb(), 9) + lane;
  const uint32_t lr2 = ldg1(P.lre + 2 * c), li2 = ldg1(P.lim + 2 * c), ld2 = ldg1(P.ldt + 2 * c);
  asm volatile("st.shared.u32 [%0],%1;" ::"r"(sb + MISC_OFF + 4 * (lane & 7)), "r"((lane & 7) ? dn : e1) : "memory");
#pragma unroll 1
  for (int i = 0; i < 2; i++) {
    const float lr = bf_hi(lr2 << (16 - 16 * i)), li = bf_hi(li2 << (16 - 16 * i));
    const float2 lb = lam_bar(lr, li, bf_hi(ld2 << (16 - 16 * i)));
    const float nx = lb.x - 1.f, ny = lb.y, inv = 2.f * frcp(lr * lr + li * li), cx = (nx * lr + ny * li) * inv, cy = (ny * lr - nx * li) * inv;
    const bool sw = !H.swap;
    asm volatile("st.shared.v4.f32 [%0],{%1,%2,%3,%4};" ::"r"(sb + LAM_OFF + 32 * lane + 16 * i), "f"(lb.x), "f"(sw ? -lb.y : lb.y), "f"(sw ? -cy : cx), "f"(sw ? cx : -cy) : "memory");
  }
  __syncwarp();
}
__device__ __forceinline__ void aux_prep(const Head& H, const Params& P, uint32_t sb, Role R, int tid, long long t_start) {
  Scratch* const S = H.s;
  const uint32_t bars = sb + BAR_OFF;
  tid = opaque(tid);
  const int w = tid >> 5, lane = tid & 31, tb = R.tb(), cb = R.cb();
  uint32_t k_[19], v_[16];
  uint4 sk;
  int task = R.b() < R.nprep() ? R.b() : 320;
  delay(KVDLY);
  PROFC(tid == 0, 345);
  kv_load(P, S, min(task, 319), tid, k_, v_, sk);
  const __nv_bfloat16* pf = (tid < 64 ? P.k : P.v) + (tid & 63) * DM;
  const int j = lane >> 3, sm = min(R.sm(), 9), trow = 160 * tb + 4 * sm + (tb < 12 ? 40 : 32) * w + j;
  const uint32_t so = sb + (2 * w + (j & 1) + 8 * (j >> 1)) * 128 + 16 * (lane & 7), xo = so + sm * 2048, wo = so + (tb & 1) * 8192 + (tb & 6) * 1024;
  const __nv_bfloat16* xp = H.x + (size_t)min(trow, SEQ - 1) * DM + 384 + 8 * (lane & 7);
  const __nv_bfloat16* bp = (j < 2 ? H.b0 : H.b1) + (size_t)(64 * cb + 32 * (tb & 1) + 4 * (tb & 6) + 2 * w + (j & 1)) * DM + 384 + 8 * (lane & 7);
  float s = 0.f, s2 = 0.f, sr = 0.f;
#define STAT(m, n) { const uint32_t xw[4] = {m.x, m.y, m.z, m.w}, bw[4] = {n.x, n.y, n.z, n.w}; \
  _Pragma("unroll") for (int i = 0; i < 4; i++) { const float u = bf_lo(xw[i]), v = bf_hi(xw[i]); s += u + v; s2 = fmaf(u, u, fmaf(v, v, s2)); sr += bf_lo(bw[i]) + bf_hi(bw[i]); } }
#define STATS(K0, K1) _Pragma("unroll 1") for (int kb = K0; kb < K1; kb++) { \
    mbar_wait(BAR(B_F1 + kb)); \
    const uint4 a = lds4(xo + ((uint32_t)(XTAB0 >> (6 * kb)) & 63) * 4096), c = lds4(wo + ((uint32_t)(WTAB0 >> (6 * kb)) & 63) * 4096); \
    STAT(a, c) \
    asm volatile("" : "+f"(s), "+f"(s2), "+f"(sr)); \
    if (XPFAT >= K0 && XPFAT < K1) prefetch_if(((lane & 4) ? bp : xp) + 64 * (lane & 3), kb == XPFAT); \
    kv_prefetch(pf, kb == KPFAT ? task + R.nprep() : kb == KPFAT2 ? task + 2 * R.nprep() : 320); \
  } \
  __syncwarp(); mbar_arrive_if(BAR(B_AX + K0 / 3), lane == 0);
  STATS(0, 3)
  PROFC(tid == 0, 349);
    {
      uint4 m[4], n[4];
#pragma unroll
      for (int i = 0; i < 4; i++) { m[i] = ldg4(xp + 64 * i); n[i] = ldg4(bp + 64 * i); }
      STATS(3, 6)
      PROFC(tid == 0, 346);
      mbar_wait(BAR(B_LM));
      const uint32_t tag = lds32(sb + MISC_OFF) & 1;
#pragma unroll
      for (int i = 0; i < 4; i++) { const uint4 a = m[i], c = n[i]; STAT(a, c) }
      PROFC(tid == 0 && s2 != 1.2345f, 347);
#pragma unroll
      for (int o = 1; o <= 4; o <<= 1) { s += __shfl_xor_sync(0xffffffff, s, o); s2 += __shfl_xor_sync(0xffffffff, s2, o); sr += __shfl_xor_sync(0xffffffff, sr, o); }
      const float mn = s * (1.f / DM), rs = frcp(bf_rn(fsqrt(bf_rn(bf_rn(fmaxf(s2 * (1.f / DM) - mn * mn, 0.f)) + 1e-5f))));
      asm volatile("{ .reg .pred p; setp.ne.u32 p, %2, 0; @p st.relaxed.gpu.global.u32 [%0],%1; }"
                   ::"l"((uint32_t*)(S->RS + (8 * cb + 4 * (tb & 1) + (tb >> 1)) * 16 + 4 * w + (j & 1)) + (lane & 4) + (j >> 1)), "r"(tagf(sr, tag)),
                   "r"((uint32_t)(tb < 8 && (lane & 3) == 0)) : "memory");
      asm volatile("{ .reg .pred p; setp.ne.u32 p, %3, 0; @p st.relaxed.gpu.global.v2.u32 [%0],{%1,%2}; }"
                   ::"l"(S->S + trow), "r"(tagf(rs, tag)), "r"(tagf(-bf_rn(mn) * rs, tag)), "r"((uint32_t)(R.sm() < 10 && (lane & 7) == 0)) : "memory");
      PROFC(tid == 0, 3);
    }
#pragma unroll 1
  for (int r = 0; task < 320; r++) {
    {
      const uint32_t T0 = __byte_perm(sk.x, sk.z, 0x5410), T1 = __byte_perm(sk.x, sk.z, 0x7632);
      const uint32_t T2 = __byte_perm(sk.y, sk.w, 0x5410), T3 = __byte_perm(sk.y, sk.w, 0x7632);
      PROFC(tid == 0 && v_[15] != 0x12345, 336 + r);
      uint32_t o[16];
#pragma unroll
      for (int t = 0; t < 16; t += 2) {
        const uint32_t a = hmul2(hfma2(k_[t + 3], T0, hfma2(k_[t + 2], T1, hfma2(k_[t + 1], T2, hmul2(k_[t], T3)))), v_[t]);
        const uint32_t c = hmul2(hfma2(k_[t + 4], T0, hfma2(k_[t + 3], T1, hfma2(k_[t + 2], T2, hmul2(k_[t + 1], T3)))), v_[t + 1]);
        const int wd = ((7 - t / 2) >> 1) + 4 * ((7 - t / 2) & 1);
        o[wd] = __byte_perm(c, a, 0x5410); o[8 + wd] = __byte_perm(c, a, 0x7632);
        asm volatile("" : "+r"(o[wd]), "+r"(o[8 + wd]));
        if (t == PFAT) kv_prefetch(pf, task + (1 + PFD) * R.nprep());
      }
      PROFC(tid == 0, 330 + 2 * r);
      const int ph = task & 1;
      task += R.nprep();
      if (ORD == 0 && task < 320) kv_load(P, S, task, tid, k_, v_, sk);
      mbar_wait(BAR(B_E1 + 3)); mbar_wait(BAR(B_AX + 1));
#pragma unroll
      for (int i = 0; i < 4; i++) {
        const int row = 2 * lane + (i >> 1);
        asm volatile("st.shared.v4.u32 [%0],{%1,%2,%3,%4};" ::"r"(sb + KS_OFF + r * 8192 + row * 128 + (((2 * w + ((i & 1) ^ ph)) ^ (row & 7)) << 4)),
                     "r"(o[4 * i]), "r"(o[4 * i + 1]), "r"(o[4 * i + 2]), "r"(o[4 * i + 3]) : "memory");
      }
      __syncwarp();
      mbar_arrive_if(BAR(B_PS + r), lane == 0);
      PROFC(tid == 0, 331 + 2 * r);
      if (ORD == 1 && task < 320) kv_load(P, S, task, tid, k_, v_, sk);
    }
  }
#undef STAT
#undef STATS
  PROFC(tid == 0, 40);
}
#define SPLIT(G) asm volatile("{ .reg .pred p; .reg .u32 r; L: mov.u32 r, %%clock; setp.eq.u32 p, r, %0; @p bra.uni L; }" ::"n"(G) : "memory")
template <bool AUX>
__device__ __forceinline__ void conv_loop(uint32_t sb, uint32_t rc, int wg, int tid, long long t_start) {
  sb = opaque(sb); rc = opaque(rc);
  const uint32_t bars = sb + BAR_OFF;
  int slot = AUX ? 0 : wg + 1;
  mbar_wait(BAR(B_LM));
#pragma unroll 1
  while (slot < (int)((rc >> 10) & 7)) {
    tid = opaque(tid);
    const int w = tid >> 5, lane = tid & 31, g = lane >> 2, q = lane & 3;
    const uint32_t Dn = lds32(sb + MISC_OFF + 4 + 4 * slot);
    const uint32_t d0 = (g == 1 && q == 3 - w) ? Dn : 0, d1 = (g == 0 && q == 3 - w) ? Dn : 0;
    const uint32_t cb_ = conv_buf(sb, slot), c0 = cb_ + KC_OFS;
    const uint32_t abase = c0 + 2 * (2 * (g & 1) + 4 * w + 16 * (g >> 1) + 4 * q);
    const uint64_t bd = make_desc(cb_ + KV_PAD, 16, 256, 3);
    const bool hi = lane & 16, s1 = lane & 8;
    const int qo = hi ? (q + 1) & 3 : q;
    const int srcA = hi ? (lane & 12) | ((q + 1) & 3) : (lane & 12) | 16 | ((q + 3) & 3);
    const bool h3 = hi && q == 3, wrap = s1 && qo == 3, back = wrap && hi;
    const bool chi = wrap ? !hi : hi;
    const int cq = s1 ? (qo + 1) & 3 : qo;
    const int srcB = (lane & 4) | (s1 ? 0 : 8) | (chi ? 16 | ((cq + 3) & 3) : cq);
    const uint32_t gp = c0 + ((32 * (2 * w + (g & 1)) + (chi ? 256 : 0)) ^ (chi ? 64 : 0) ^ ((conv_ch(rc, slot) & 8) << 2)) + 4 * (2 * cq + (s1 ? 0 : 1));
    uint32_t a[12], f[16], o[8];
    float S[4], T[4], U[2], keep[2], pv[2] = {0.f, 0.f}, pr[4] = {0.f, 0.f, 0.f, 0.f};
    float e0[64], e1[56], e2[48], e3[40], e4[32], e5[24], e6[16], e7[8];
#define UNR _Pragma("unroll")
#define PERM() UNR for (int i = 0; i < 4; i++) { f[4 * i] = __byte_perm(a[3 * i], a[3 * i + 1], 0x5432); f[4 * i + 1] = a[3 * i + 1]; \
                                                 f[4 * i + 2] = __byte_perm(a[3 * i + 1], a[3 * i + 2], 0x5432); f[4 * i + 3] = a[3 * i + 2]; }
#define MMA(N, E) UNR for (int i = 0; i < 4; i++) wgmma_rs<N>(E, f[4 * i], f[4 * i + 1], f[4 * i + 2], f[4 * i + 3], bd - 8 * i, 1); wg_commit();
#define L1(c) UNR for (int i = 0; i < 4; i++) { const float ev = c[i], od = c[4 + i]; S[i] = hi ? (h3 ? ev : od) : ev; \
                                                T[i] = __shfl_sync(0xffffffff, hi ? (h3 ? pr[i] : ev) : od, srcA); pr[i] = od; }
#define L1E() UNR for (int i = 0; i < 4; i++) S[i] += T[i];
#define L2() UNR for (int h = 0; h < 2; h++) { keep[h] = back ? pv[h] : S[2 * h + 1]; pv[h] = S[2 * h + 1]; U[h] = __shfl_sync(0xffffffff, S[2 * h], srcB); }
#define L2E(j) o[j] = pack_bf(keep[0] + U[0], keep[1] + U[1]);
#define GRP(G, N, P, E) UNR for (int i = 0; i < N / 2; i++) asm volatile("mov.b32 %0,%1;" : "=f"(E[i]) : "f"(P[i + 8])); \
    wg_fence(); if (G < 7) conv_frags<(G + 1) & 7>(a, abase); if (G >= 2) { L2() } L1(P) MMA(N, E) SPLIT(G); \
    if (G < 7) { PERM() } if (G >= 2) { L2E((G + 6) & 7) } L1E() wg_wait<0>(); fence_regs(E);
    PROFC(tid == 0, 300 + 4 * slot);
    mbar_wait(BAR(B_KF + slot));
    if (tid == 0) PROF(361 + slot);
    PROFC(tid == 0, 301 + 4 * slot);
    conv_frags<0>(a, abase);
    wg_fence();
    wgmma_rs<128>(e0, d0 << 16, d0, d1 << 16, d1, bd, 0);
    PERM() conv_frags<1>(a, abase); wg_fence(); MMA(128, e0) SPLIT(0); PERM() wg_wait<0>(); fence_regs(e0);
    GRP(1, 112, e0, e1) GRP(2, 96, e1, e2) GRP(3, 80, e2, e3) GRP(4, 64, e3, e4) GRP(5, 48, e4, e5) GRP(6, 32, e5, e6) GRP(7, 16, e6, e7)
    PROFC(tid == 0, 302 + 4 * slot);
    L2() L1(e7) L2E(6) L1E() L2() L2E(7)
    bar_sync(wg + 1, 128);
#pragma unroll
    for (int jj = 0; jj < 8; jj++) asm volatile("st.shared.u32 [%0],%1;" ::"r"(gp + jj * 512), "r"(o[jj]) : "memory");
#undef PERM
#undef MMA
#undef L1
#undef L1E
#undef L2
#undef L2E
#undef GRP
    PROFC(tid == 0, 303 + 4 * slot);
    __syncwarp();
    if (lane == 0) mbar_arrive(BAR(B_GS + slot));
    if (!AUX) break;
    slot = slot ? slot + 1 : 3;
  }
}

#define IDX(J, c, h) (8 * (J) + 4 * ((c) >> 1) + 2 * (h) + ((c) & 1))
__device__ __forceinline__ uint2 lds2(uint32_t a) { uint2 v; asm volatile("ld.shared.v2.u32 {%0,%1},[%2];" : "=r"(v.x), "=r"(v.y) : "r"(a) : "memory"); return v; }
__device__ __forceinline__ void resid_load(float (&r)[40], uint32_t sb, int wg, int tid, const uint4& s) {
  const uint32_t dp = sb + XR_OFF + 8 * (tid & 3), xp = dp + (64 * wg + 16 * (tid >> 5) + ((tid & 31) >> 2)) * 160;
#pragma unroll
  for (int J = 0; J < 5; J++) {
    const uint2 u = lds2(xp + 32 * J), v = lds2(xp + 32 * J + 1280), d = lds2(dp + 20480 + 32 * J);
    r[8 * J] = __uint_as_float(u.x); r[8 * J + 1] = __uint_as_float(u.y); r[8 * J + 2] = __uint_as_float(v.x); r[8 * J + 3] = __uint_as_float(v.y);
    r[8 * J + 4] = __uint_as_float(d.x); r[8 * J + 5] = __uint_as_float(d.y);
  }
  r[30] = untag(s.x); r[31] = untag(s.y); r[38] = untag(s.z); r[39] = untag(s.w);
}
__device__ __forceinline__ void resid_init(float (&r)[40]) {
  const float s[4] = {r[30], r[31], r[38], r[39]};
#pragma unroll
  for (int J = 0; J < 5; J++) {
    uint32_t w[6];
#pragma unroll
    for (int i = 0; i < 6; i++) w[i] = __float_as_uint(r[8 * J + i]);
#pragma unroll
    for (int i = 0; i < 4; i++) {
      const int h = i >> 1, c = 2 * (i & 1);
      const float rs = s[2 * h], nm = s[2 * h + 1], x0 = bf_lo(w[i]), x1 = bf_hi(w[i]);
      const uint32_t t = hmul2(pack_bf(fmaf(x0, rs, nm), fmaf(x1, rs, nm)), w[4 + (i & 1)]);
      r[IDX(J, c, h)] = x0 + bf_lo(t); r[IDX(J, c + 1, h)] = x1 + bf_hi(t);
    }
  }
}

__device__ __forceinline__ float flip(float v, uint32_t m) { return __uint_as_float(__float_as_uint(v) ^ m); }
__device__ __forceinline__ void g1_phase(const int LY, const Head& H, uint32_t sb, int wg, int tid, Role R, float (&xr)[40], long long t_start) {
  Scratch* const S = H.s;
  tid = opaque(tid); sb = opaque(sb); R.v = opaque(R.v);
  const uint32_t bars = sb + BAR_OFF;
  const int cb = R.cb(), tb = R.tb();
  const int w = tid >> 5, lane = tid & 31, g = lane >> 2, q = lane & 3;
  const bool full = tb < 12;
  uint2* Eb = S->E + ((LY * 130 + cb) * 8 + 4 * wg + w) * 16 + g;
  float a[80];
#pragma unroll
  for (int i = 0; i < 80; i++) a[i] = 0.f;
  uint32_t rel = mapa(BAR(B_E1), lane ? R.wpart() : R.ubase() + (w & (R.ugs() - 1)));
  const bool rels = lane == 0 || (tid == 1 && wg != R.wlo());
  float2 lam = make_float2(0.f, 0.f), mu = lam, mu2 = lam;
  uint32_t tag = 0;
  uint2 v = make_uint2(0, 0);
  const uint32_t lamp = sb + LAM_OFF + 16 * (32 * wg + 8 * w + g);
  const uint2* rp = S->RS + (8 * cb + 4 * wg + w) * 16 + 2 * g - (g & 1);
  auto setup = [&]() {
    v = ld_rlx2(rp);
    mbar_wait(BAR(B_LM));
    tag = lds32(sb + MISC_OFF) & 1;
    asm volatile("ld.shared.v2.f32 {%0,%1},[%2];" : "=f"(lam.x), "=f"(lam.y) : "r"(lamp));
    if (q == 3) st_rlx2(Eb + tb * 1280, tag ^ 1, tag ^ 1);
    const float2 l2 = cmul(lam, lam), l4 = cmul(l2, l2), l8 = cmul(l4, l4), l16 = cmul(l8, l8), l32 = cmul(l16, l16);
    mu = full ? cmul(l32, l8) : l32; mu2 = cmul(mu, mu);
  };
  {
    uint64_t tw = LY ? WTAB1 : WTAB0, tx = LY ? XTAB1 : XTAB0;
    uint32_t bf = BAR(B_F1);
    if (tid == 0 && wg == 0 && !LY) PROF(351);
    fence_regs(a);
#pragma unroll 1
    for (int kb = 0;; kb++) {
      if (kb == (LY ? 0 : 10)) setup();
      if (kb == 10) break;
      mbar_wait(bf, LY);
      if (tid == 0 && wg == 0 && kb == 0) PROF(LY ? 20 : 4);
      const uint64_t da = make_desc(sb + ((uint32_t)tw & 63) * 4096 + wg * 8192, 16, 1024, 1);
      const uint64_t db = make_desc(sb + ((uint32_t)tx & 63) * 4096, 16, 1024, 1);
      wg_fence();
#pragma unroll
      for (int kk = 0; kk < 4; kk++) wgmma_ss160(a, da + 2 * kk, db + 2 * kk, 1);
      wg_commit();
      wg_wait<1>();
      if (kb > 0) { if (rels) mbar_arrive_at(rel); rel += 8; }
      bf += 8; tw >>= 6; tx >>= 6;
    }
  }
  if (tid == 0 && wg == 0) PROF(LY ? 19 : 2);
  float rs0, rs1;
  const uint32_t ssm = sb + SSM_OFF + q * 160;
  {
    mbar_wait(BAR(B_ST), LY);
    if (tid == 0 && wg == 0) PROF(LY ? 372 : 371);
#pragma unroll 1
    for (int it = 0; it < SPIN && __any_sync(0xffffffff, untagged(v, tag)); it++) v = ld_rlx2(rp);
    rs0 = untag(v.x); rs1 = untag(v.y);
  }
  if (tid == 0 && wg == 0 && !LY) PROF(39);
  wg_wait<0>(); fence_regs(a);
  if (rels) mbar_arrive_at(rel);
  if (tid == 0 && wg == 0) PROF(LY ? 21 : 5);
  float2 p = make_float2(0.f, 0.f);
#pragma unroll
  for (int j = 0; j < 10; j++) {
    if (j < 8 || full) {
      const uint4 sv = lds4(ssm + 16 * j), nv = lds4(ssm + 640 + 16 * j);
#pragma unroll
      for (int e = 0; e < 4; e++) {
        const int o = 8 * j + e + (e & 2);
        const float r = __uint_as_float(e == 0 ? sv.x : e == 1 ? sv.y : e == 2 ? sv.z : sv.w);
        const float nm = __uint_as_float(e == 0 ? nv.x : e == 1 ? nv.y : e == 2 ? nv.z : nv.w);
        a[o] = fmaf(a[o], r, nm * rs0); a[o + 2] = fmaf(a[o + 2], r, nm * rs1);
        p = cfma(lam, p, make_float2(a[o], a[o + 2]));
      }
    }
  }
  {
    float2 t = make_float2(__shfl_up_sync(0xffffffff, p.x, 1, 4), __shfl_up_sync(0xffffffff, p.y, 1, 4));
    if (q >= 1) p = cfma(mu, t, p);
    t = make_float2(__shfl_up_sync(0xffffffff, p.x, 2, 4), __shfl_up_sync(0xffffffff, p.y, 2, 4));
    if (q >= 2) p = cfma(mu2, t, p);
  }
  if (q == 3 && full) st_rlx2(Eb + tb * 1280, tagf(p.x, tag), tagf(p.y, tag));
  if (tid == 0 && wg == 1) PROF(96 + 64 * LY);
  uint2 ev[3];
#pragma unroll
  for (int i = 0; i < 3; i++) { const int j = tb - 1 - q - 4 * i; ev[i] = j >= 0 ? ld_rlx2(Eb + j * 1280) : make_uint2(tag, tag); }
  float2 x = make_float2(__shfl_up_sync(0xffffffff, p.x, 1, 4), __shfl_up_sync(0xffffffff, p.y, 1, 4));
  if (q == 0) x = make_float2(0.f, 0.f);
  float c0, c1;
  asm volatile("ld.shared.v2.f32 {%0,%1},[%2+8];" : "=f"(c0), "=f"(c1) : "r"(lamp));
  const float c2 = -flip(c1, H.swap), c3 = flip(c0, H.swap);
#pragma unroll
  for (int i = 0; i < 40; i++) {
    const int o = 4 * (i >> 1) + (i & 1);
    const float u = a[o], v = a[o + 2];
    a[o] = fmaf(c0, u, c1 * v); a[o + 2] = fmaf(c2, u, c3 * v);
  }
  fence_regs(a);
  if (LY == 0 && R.b() < 128) {
    const int t0 = 16 * g + 8 * wg + 2 * w;
    if (tid == 0 && wg == 1) PROF(366);
    mbar_wait(BAR(B_XR));
    if (tid == 0 && wg == 1) PROF(367);
    uint4 s = lds4(sb + XR_OFF + 20480 + 256 + 8 * t0);
    if (__any_sync(0xffffffff, untagged(s, tag))) {
#pragma unroll 1
      for (int it = 0; it < SPIN; it++) { s = ld_rlx4(S->S + 128 * (R.b() >> 3) + t0); if (!__any_sync(0xffffffff, untagged(s, tag))) break; }
    }
    resid_load(xr, sb, wg, tid, s);
  }
  float2 mq, om4, fq;
  {
    asm volatile("" : "+f"(lam.x), "+f"(lam.y));
    const float2 one = make_float2(1.f, 0.f), m2 = cmul(lam, lam), m4 = cmul(m2, m2), l8 = cmul(m4, m4), l16 = cmul(l8, l8);
    const float2 l80 = full ? mu2 : cmul(mu2, l16), om = cmul(l80, l80), om2 = cmul(om, om);
    mq = cmul((q & 1) ? mu : one, (q & 2) ? mu2 : one);
    om4 = cmul(om2, om2); fq = cmul((q & 1) ? om : one, (q & 2) ? om2 : one);
  }
  mbar_wait(BAR(B_E1 + 9), LY);
  if (tid == 0 && wg == 1) PROF(368 + LY);
#pragma unroll 1
  for (int it = 0; it < SPIN; it++) {
    const bool m0 = untagged(ev[0], tag), m1 = untagged(ev[1], tag), m2 = untagged(ev[2], tag);
    if (!__any_sync(0xffffffff, m0 || m1 || m2)) break;
    if (m0) ev[0] = ld_rlx2(Eb + (tb - 1 - q) * 1280);
    if (m1) ev[1] = ld_rlx2(Eb + (tb - 5 - q) * 1280);
    if (m2) ev[2] = ld_rlx2(Eb + (tb - 9 - q) * 1280);
  }
  if (tid == 0 && wg == 1) PROF(97 + 64 * LY);
  float2 c = make_float2(untag(ev[2].x), untag(ev[2].y));
#pragma unroll
  for (int i = 1; i >= 0; i--) c = cfma(om4, c, make_float2(untag(ev[i].x), untag(ev[i].y)));
  c = cmul(fq, c);
#pragma unroll
  for (int s = 1; s <= 2; s <<= 1) { c.x += __shfl_xor_sync(0xffffffff, c.x, s); c.y += __shfl_xor_sync(0xffffffff, c.y, s); }
  c = cfma(mq, c, x);
  float2 z = make_float2(fmaf(c0, c.x, c1 * c.y), fmaf(c2, c.x, c3 * c.y));
  if (tid == 0 && wg == 0) PROF(LY ? 22 : 6);
  const float2 lc = make_float2(lam.x, flip(lam.y, H.swap));
  const uint32_t hq = sb + (lane >> 4) * 1024 + (lane & 7) * 128 + (((4 * wg + w) ^ (lane & 7)) << 4);
  const uint32_t hp = hq + R_OFF + (lane & 8) * 2048, hp4 = hq + (LY ? R4_OFF1 : R4_OFF0) + (lane & 8) * 512;
#pragma unroll
  for (int j = 0; j < 20; j += 2) {
    if (j < 16 || full) {
      uint32_t o[4];
#pragma unroll
      for (int i = 0; i < 2; i++) {
        const float2 z0 = cfma(lc, z, make_float2(a[4 * (j + i)], a[4 * (j + i) + 2]));
        z = cfma(lc, z0, make_float2(a[4 * (j + i) + 1], a[4 * (j + i) + 3]));
        o[2 * i] = pack_bf(z0.x, z.x); o[2 * i + 1] = pack_bf(z0.y, z.y);
      }
      asm volatile("stmatrix.sync.aligned.m8n8.x4.trans.shared.b16 [%0], {%1,%2,%3,%4};" ::"r"(j < 16 ? hp + j * 1024 : hp4 + (j - 16) * 1024), "r"(o[0]), "r"(o[1]), "r"(o[2]), "r"(o[3]) : "memory");
      if (j & 2) { __syncwarp(); if (lane == 0) mbar_arrive(BAR(B_SH + j / 4)); }
    }
  }
  if (tid == 0 && wg == 0) PROF(LY ? 23 : 7);
  if (lane == 0) PROF(390 + 4 * wg + w);
}

__device__ __forceinline__ void gate_load(float (&G)[40], uint32_t sb, int LY, int wg, int tid, int tb2) {
  const uint32_t bars = sb + BAR_OFF;
  const int lane = tid & 31, w = tid >> 5;
  mbar_wait(BAR(B_GF), LY);
  const int g = lane >> 2, q = lane & 3;
  const uint32_t gb = sb + (LY ? G_OFF1 : G_OFF0) + wg * 10240 + 512 * q + ((32 * w + 4 * g) ^ (64 * ((tb2 ^ q) & 1)) ^ (16 * (q & 2)));
#pragma unroll
  for (int i = 0; i < 20; i++) { const uint32_t v = lds32((gb ^ (16 * (i & 3))) + 128 * (i & 3) + 2048 * (i >> 2)); G[2 * i] = bf_lo(v); G[2 * i + 1] = bf_hi(v); }
  fence_regs(G);
}
__device__ __forceinline__ void g2_phase(const int LY, const Params& P, Scratch* S, uint32_t sb, int wg, int tid, Role R, float (&xr)[40], long long t_start) {
  sb = opaque(sb);
  const uint32_t bars = sb + BAR_OFF;
  if (LY) {
    const int td = opaque(tid), b = (opaque(R.v) >> 8) & 255;
    const uint32_t tag = lds32(sb + MISC_OFF) & 1;
    const uint2* sp = S->S + 2 * SEQ + 128 * (b >> 3) + 4 * (td & 28) + 8 * wg + 2 * (td >> 5);
    if (!(R.cb() & 1)) mbar_wait(BAR(B_HD), 1);
    uint2 dl[5];
#pragma unroll
    for (int J = 0; J < 5; J++) dl[J] = __ldg((const uint2*)(P.dskip + 80 * (b & 7) + 4 * (td & 3) + 16 * J));
    uint4 sv;
#pragma unroll 1
    for (int it = 0; it < SPIN; it++) { sv = ld_rlx4(sp); if (!__any_sync(0xffffffff, untagged(sv, tag))) break; }
#pragma unroll
    for (int h = 0; h < 2; h++)
#pragma unroll
      for (int J = 0; J < 5; J++)
#pragma unroll
        for (int c = 0; c < 4; c++) {
          const float x2 = xr[IDX(J, c, h)];
          const uint32_t dw = (c & 2) ? dl[J].y : dl[J].x;
          xr[IDX(J, c, h)] = fmaf(fmaf(x2, untag(h ? sv.z : sv.x), untag(h ? sv.w : sv.y)), (c & 1) ? bf_hi(dw) : bf_lo(dw), x2);
        }
    fence_regs(xr);
  }
  float acc[40];
#pragma unroll
  for (int i = 0; i < 40; i++) acc[i] = RIAT == 1 ? 0.f : xr[i];
  fence_regs(acc);
#define G2_STEP(st, cs, hf) { \
    const uint64_t da = make_desc(sb + H_OFF + (st) * 32768 + (hf) * 16384 + wg * 8192, 16, 1024, 1), db = make_desc(sb + (cs) * 20480 + (hf) * 10240, 16, 1024, 1); \
    wg_fence(); \
    _Pragma("unroll") for (int kk = 0; kk < 4; kk++) wgmma_ss80(acc, da + 2 * kk, db + 2 * kk, 1); \
    wg_commit(); }
  mbar_wait(BAR(B_F2), LY);
  if (tid == 0 && wg == 0) PROF(LY ? 25 : 10);
  G2_STEP(0, 0, 0)
  mbar_wait(BAR(B_F3), LY);
  G2_STEP(0, 0, 1)
  tid = opaque(tid); R.v = opaque(R.v);
  const uint32_t tag = lds32(sb + MISC_OFF) & 1;
  const int b = R.b(), tb2 = b >> 3, db_ = b & 7;
  const int w = tid >> 5, lane = tid & 31, g = lane >> 2, q = lane & 3;
  const int t0 = 128 * tb2 + 16 * g + 8 * wg + 2 * w;
  const int d0 = 80 * db_ + 4 * q, mrow = 64 * wg + 16 * w + g;
#define GATE(J, c, h) G[8 * (J) + 2 * (c) + (h)]
  uint32_t rel = mapa(BAR(B_E2), lane ? ((w & 1) ? R.wpart() : R.rank()) : R.cs() == 8 ? 4 * wg + w : wg);
  const bool rels = lane == 0 || (lane == 1 && w < 2);
  const uint32_t mx = sb + MX_OFF + 512 * wg + 4 * tid, bx = BAR(B_KF + 1 + 2 * LY + wg);
  uint32_t pa[8], pb[8];
#pragma unroll
  for (int i = 0; i < 8; i++) { pa[i] = mapa(mx + 1024 * db_, i ^ db_); pb[i] = mapa(bx + (tid >> 10), i ^ db_); asm volatile("" : "+r"(pa[i]), "+r"(pb[i])); }
  uint32_t* Mb = S->M + ((2 * LY * 16 + tb2) * 8) * 256 + (wg * 4 + w) * 32 + (2 * g + (q & 1)) * 2 + (q >> 1);
  {
    uint32_t bf = BAR(B_F2 + 1), st = 1, ra = rel + 8 * (B_EA - B_E2);
    const int lag = wg ? (LY ? STG : STG0) / 2 : 0;
#pragma unroll 1
    for (int kp = 1; kp < 10; kp++) {
      const bool more = LY == 0 || kp < 8;
      wg_wait<1>();
      if (lane == 0 && more) mbar_arrive_at(ra + 8 * (st ? st - 1 : 2));
      mbar_wait(bf, LY);
      if (STG && !(STG & 1) && kp == lag) bar_sync(5, 256);
      G2_STEP(st, kp < 5 ? kp : kp - 5, 0)
      wg_wait<1>();
      if (rels && more) mbar_arrive_at(rel);
      rel += 8;
      mbar_wait(bf + 8 * (B_F3 - B_F2), LY);
      if ((STG & 1) && kp == lag) bar_sync(5, 256);
      G2_STEP(st, kp < 5 ? kp : kp - 5, 1)
      if (kp == MIAT) {
        st_rlx(Mb + db_ * 256, tag ^ 1);
        if (LY == 0) st_rlx(Mb + (16 * 8 + db_) * 256, tag ^ 1);
      }
      bf += 8; st = st == 2 ? 0 : st + 1;
    }
  }
  if (STG && (LY || STG0) && !wg) asm volatile("bar.arrive 5, 256;" ::: "memory");
  wg_wait<0>(); fence_regs(acc);
  if (LY == 0 && rels) mbar_arrive_at(rel);
  if (tid == 0 && wg == 0) PROF(LY ? 26 : 11);
  if (lane == 0) PROF(116 + 64 * LY + wg * 4 + w);

#pragma unroll 1
  for (int rep = 0;; rep++) {
    float m[2][2];
#pragma unroll
    for (int h = 0; h < 2; h++) {
      m[h][0] = m[h][1] = 0.f;
#pragma unroll
      for (int J = 0; J < 5; J++)
#pragma unroll
        for (int c = 0; c < 4; c++) { const float xv = acc[IDX(J, c, h)]; m[h][0] += xv; m[h][1] = fmaf(xv, xv, m[h][1]); }
    }
    float r1[2];
#pragma unroll
    for (int i = 0; i < 2; i++) { const float snd = (q & 1) ? m[0][i] : m[1][i], kp = (q & 1) ? m[1][i] : m[0][i]; r1[i] = kp + __shfl_xor_sync(0xffffffff, snd, 1); }
    const float r2 = ((q & 2) ? r1[1] : r1[0]) + __shfl_xor_sync(0xffffffff, (q & 2) ? r1[0] : r1[1], 2);
    if (R.cs() == 8 && !rep) {
#pragma unroll
      for (int i = 0; i < 8; i++)
        asm volatile("st.async.weak.shared::cluster.mbarrier::complete_tx::bytes.b32 [%0],%1,[%2];" ::"r"(pa[i]), "f"(r2), "r"(pb[i]) : "memory");
      if (tid == 0) mbar_expect_tx(bx, 4096);
    }
    st_rlx(Mb + db_ * 256, tagf(r2, tag));
    if (rep) break;
    if (lane == 0) PROF(100 + 64 * LY + wg * 4 + w);
    float G[40];
    gate_load(G, sb, LY, wg, tid, tb2);
    mbar_wait(BAR(B_CD + 1));
    uint32_t mv[8];
    if (R.cs() == 8) {
      mbar_wait(BAR(B_KF + 1), 1);
      mbar_wait(bx, 1);
#pragma unroll
      for (int i = 0; i < 8; i++) mv[i] = lds32(mx + 1024 * i);
    } else {
#pragma unroll
    for (int i = 0; i < 8; i++) mv[i] = ld_rlx(Mb + i * 256);
#pragma unroll 1
    for (int it = 0; it < SPIN; it++) {
      uint32_t miss = 0;
#pragma unroll
      for (int i = 0; i < 8; i++) miss |= ((mv[i] ^ tag) & 1) << i;
      if (!__any_sync(0xffffffff, miss)) break;
#pragma unroll
      for (int i = 0; i < 8; i++) if ((miss >> i) & 1) mv[i] = ld_rlx(Mb + i * 256);
    }
#pragma unroll
      for (int i = 0; i < 8; i++) mv[i] = __float_as_uint(untag(mv[i]));
      if (MBAR || !LY) bar_sync(4, 256);
    }
    if (lane == 0) PROF(108 + 64 * LY + wg * 4 + w);
#define MV(i) __uint_as_float(mv[i])
    const float s = ((MV(0) + MV(1)) + (MV(2) + MV(3))) + ((MV(4) + MV(5)) + (MV(6) + MV(7)));
#undef MV
    float mm[2], rr[2];
#pragma unroll
    for (int h = 0; h < 2; h++) {
      mm[h] = __shfl_sync(0xffffffff, s, h, 4) * (1.f / DM);
      rr[h] = frsqrt(fmaxf(__shfl_sync(0xffffffff, s, 2 + h, 4) * (1.f / DM) - mm[h] * mm[h], 0.f) + 1e-5f);
    }
    if (tid == 0 && wg == 0) PROF(LY ? 27 : 12);
    const float nm[2] = {-mm[0] * rr[0], -mm[1] * rr[1]};
#pragma unroll
    for (int h = 0; h < 2; h++)
#pragma unroll
      for (int J = 0; J < 5; J++)
#pragma unroll
        for (int c = 0; c < 4; c++) { const float xv = acc[IDX(J, c, h)]; xr[IDX(J, c, h)] = fmaf(fmaf(xv, rr[h], nm[h]), GATE(J, c, h), xv); }
    if (LY) break;
#pragma unroll
    for (int i = 0; i < 40; i++) acc[i] = xr[i] - mm[(i >> 1) & 1];
#pragma unroll
    for (int i = 0; i < 10; i++) {
      const int J = i >> 1, h = i & 1;
      const uint32_t u0 = pack_bf(acc[IDX(J, 0, h)], acc[IDX(J, 1, h)]), u1 = pack_bf(acc[IDX(J, 2, h)], acc[IDX(J, 3, h)]);
      asm volatile("st.shared.v2.u32 [%0],{%1,%2};" ::"r"(sb + US_OFF + ((mrow ^ 64) + 8 * h) * 160 + 32 * J + 8 * q), "r"(u0), "r"(u1) : "memory");
    }
    __syncwarp();
    if (lane == 0) mbar_arrive(BAR(B_GS + 1 + wg));
    if (tid == 0 && wg == 0) PROF(13);
    Mb += 16 * 8 * 256;
  }
  if (LY == 0) {
    if (tid == 0 && wg == 0) PROF(15);
  }
  else {
    float* op = P.out + (size_t)t0 * DM + d0;
#pragma unroll
    for (int i = 0; i < 10; i++) {
      const int J = i >> 1, h = i & 1;
      asm volatile("st.global.v4.f32 [%0],{%1,%2,%3,%4};" ::"l"(op + h * DM + 16 * J),
                   "f"(xr[IDX(J, 0, h)]), "f"(xr[IDX(J, 1, h)]), "f"(xr[IDX(J, 2, h)]), "f"(xr[IDX(J, 3, h)]) : "memory");
    }
  }
  if (tid == 0 && wg == 0 && LY) PROF(28);
#undef IDX
#undef GATE
}

__device__ __forceinline__ void next_stats(Scratch* S, uint32_t sb, int tb2, int tid) {
  const uint32_t bars = sb + BAR_OFF, tag = lds32(sb + MISC_OFF) & 1;
  const uint32_t* Mb = S->M + tb2 * 8 * 256 + 2 * tid;
  mbar_wait(BAR(B_F1 + NSAT), 1);
  float m1, s1, s2;
#pragma unroll 1
  for (int it = 0; it < SPIN; it++) {
    uint32_t a[8], miss = 0;
    uint2 v[8];
#pragma unroll
    for (int i = 0; i < 8; i++) { a[i] = ld_rlx(Mb + i * 256); v[i] = ld_rlx2((const uint2*)(Mb + (16 * 8 + i) * 256)); }
#pragma unroll
    for (int i = 0; i < 8; i++) miss |= (a[i] ^ tag) | (v[i].x ^ tag) | (v[i].y ^ tag);
#define SUM8(F) ((untag(F(0)) + untag(F(1))) + (untag(F(2)) + untag(F(3)))) + ((untag(F(4)) + untag(F(5))) + (untag(F(6)) + untag(F(7))))
#define FA(i) a[i]
#define FX(i) v[i].x
#define FY(i) v[i].y
    m1 = SUM8(FA); s1 = SUM8(FX); s2 = SUM8(FY);
    if (!__any_sync(0xffffffff, miss & 1)) break;
  }
  const float mean = s1 * (1.f / DM), rs = frsqrt(fmaxf(s2 * (1.f / DM) - mean * mean, 0.f) + 1e-5f);
  uint2* sp = S->S + SEQ + 128 * tb2 + 8 * (tid & 14) + 2 * (tid >> 4) + (tid & 1);
  st_rlx2(sp, tagf(rs, tag), tagf(-mean * rs, tag));
  st_rlx2(sp + SEQ, tagf(rs, tag), tagf(-(mean + m1 * (1.f / DM)) * rs, tag));
}
template <int I0, int I1> __device__ __forceinline__ void init_barriers(uint32_t bars) {
#pragma unroll
  for (int i = I0; i < I1; i++) mbar_init(BAR(i), bar_count(i));
}
__device__ __forceinline__ int g2_cb(int kp) { return kp < 5 ? 2 * kp : 2 * kp - 9; }
__device__ __forceinline__ const unsigned* h_flag(Scratch* S, int ly, int tb2, int lane) {
  const int s0 = 128 * min(tb2, 15) / 160;
  const bool two = (128 * tb2 + 127) / 160 != s0;
  return &S->flag[(F_H + (ly * 13 + s0) * 10 + min(lane & 15, 9) + (two && lane >= 16 ? 10 : 0)) * 32];
}
__device__ __forceinline__ void gate_tile(const Params& P, uint32_t dst, uint32_t bar, int tb2, int db) {
  mbar_expect_tx(bar, 20480);
  tma2d(dst, &P.mGT, tb2 * 128, db * 80, bar);
  tma2d(dst + 10240, &P.mGT, tb2 * 128 + 64, db * 80, bar);
}
__global__ void __cluster_dims__() __launch_bounds__(512, 1) fused_kernel(const Head H, const __grid_constant__ Params P) {
  extern __shared__ __align__(1024) uint8_t smem[];
  const uint32_t sb = opaque(smem_u32(smem)), bars = sb + BAR_OFF;
  const int wi = __shfl_sync(0xffffffff, threadIdx.x >> 5, 0), wg = wi >> 2, tid = threadIdx.x & 127;
  const int umap = blockIdx.x >= 96;
#define CLK(v)
  CLK(c_a);
  if (wi == 14) {
    if (elect_one()) { init_barriers<0, NBAR1>(bars); asm volatile("fence.mbarrier_init.release.cluster;" ::: "memory"); }
    __syncwarp();
  } else if (wi >= 12) prefetch_map(wi == 12 ? &P.mB : &P.mA[umap]);
  else if (wg == 2) xb_prefetch<1>(H, blockIdx.x + H.base, tid, 0);
  else if (P.role[blockIdx.x].w) return;
  CLK(c_b);
  asm volatile("barrier.cluster.arrive.relaxed.aligned;" ::: "memory");
  CLK(c_c);
  Role R;
  { const uint4 r = P.role[blockIdx.x]; R.v = r.x; R.c = r.y; R.p = r.z; }
  const int id = R.c & 255;
  const int tb = R.tb(), cb = R.cb(), b = R.b(), tb2 = b >> 3, db = b & 7, rank = R.rank();
  const bool has1 = tb <= 12, has2 = b < 128, full = tb < 12;
  Scratch* const S = H.s;
  unsigned* const epoch_p = &S->epoch[id * 8];
  const long long t_start = 0;
  if (wg < 2) {
    if (threadIdx.x == 0) PROF(50);
    asm volatile("griddepcontrol.launch_dependents;");
    bar_sync(6, 448);
    asm volatile("setmaxnreg.inc.sync.aligned.u32 176;");
    float xr[40];
#pragma unroll
    for (int i = 0; i < 40; i++) xr[i] = 0.f;
#pragma unroll 1
    for (int ly = 0; ly < 2; ly++) {
      if (has1) g1_phase(ly, H, sb, wg, tid, R, xr, t_start);
      if (ly == 0) {
        resid_init(xr); fence_regs(xr);
        conv_loop<false>(sb, R.c, wg, tid, t_start);
        if (tid == 0 && wg == 0) PROF(9);
      }
      if (has2) g2_phase(ly, P, S, sb, wg, tid, R, xr, t_start);
    }
    if (tid == 0 && wg == 0) st_rlx(epoch_p, lds32(sb + MISC_OFF));
  } else if (wg == 2) {
    bar_sync(6, 448);
    if (has1) aux_prep(H, P, sb, R, tid, t_start);
    asm volatile("setmaxnreg.inc.sync.aligned.u32 136;");
    conv_loop<true>(sb, R.c, wg, tid, t_start);
    if (tid == 0) PROF(44);
    {
      const uint32_t bb = (P.role[blockIdx.x].x >> 8) & 255;
      if ((bb & 132) == NSDB && tid < 32) next_stats(H.s, sb, bb >> 3, 32 * (bb & 3) + tid);
    }
  } else {
    if (threadIdx.x == 384) PROF(354);
    asm volatile("setmaxnreg.dec.sync.aligned.u32 24;");
    const int wlo = R.wlo(), whi = R.whi();
    const uint32_t wmask = R.wmask(), umask = R.umask(), f1bytes = full ? 36864 : 32768;
    if (wi < 14) {
      if (threadIdx.x == 384) PROF(340);
      asm volatile("barrier.cluster.wait.aligned;" ::: "memory");
      if (has1 && elect_one()) {
        uint64_t tab = wi == 12 ? WTAB0 : XTAB0;
        PROF(329 + wi);
#pragma unroll 1
        for (int kb = 0; kb < 6; kb++, tab >>= 6) {
          const uint32_t dst = sb + ((uint32_t)tab & 63) * 4096;
          if (wi == 12) {
#pragma unroll 1
            for (int h = wlo; h <= whi; h++) tma4d_mc(dst + h * 8192, &P.mB, kb * 64, 0, 0, 8 * cb + 4 * h, BAR(B_F1 + kb), wmask);
          } else {
            tma4d_mc(dst + R.uj() * 1024, &P.mA[umap], kb * 64, 0, 0, 80 * tb + R.uj(), BAR(B_F1 + kb), umask);
            mbar_expect_tx(BAR(B_F1 + kb), f1bytes);
          }
        }
      }
      if (!has1 && wi == 13) bar_sync(7, 64);
    } else {
      if (wi == 15 && elect_one()) { init_barriers<NBAR1, NBAR>(bars); asm volatile("fence.mbarrier_init.release.cluster;" ::: "memory"); }
      bar_sync(6, 448);
      if (!has1 && wi == 14) bar_sync(7, 64);
    }
    const unsigned e1 = ld_rlx(epoch_p) + 1;
    if (wi == 12) {
      if (elect_one()) {
#pragma unroll 1
        for (int ly = 0; ly < 2; ly++) {
#pragma unroll 1
          for (int i = ly ? 0 : 6; i < 10 && has1; i++) {
            const int kb = (0x9876541032ull >> (4 * i)) & 15;
            if (ly == 0) { mbar_wait(BAR(B_E1 + ((DEP0 >> (4 * kb - 24)) & 15))); mbar_wait(BAR(B_AX + (kb == 9))); }
            else {
              if (has2 && i == (db >= GLATE ? 4 : 2)) {
                wait_cnt(&S->cnt[(C_G + db) * 32], e1 * 80);
                mbar_wait(BAR(B_E2 + 7));
                PROF(47);
                gate_tile(P, sb + G_OFF0, BAR(B_GF), tb2, db);
              }
              if (has2) mbar_wait(BAR(i < 4 ? B_E2 + ((0x9865u >> (4 * i)) & 15) : B_GE));
              else if (i == 0) { mbar_wait(BAR(B_E1 + 9)); mbar_wait(BAR(B_CD + 1)); }
              if (i >= 4) mbar_wait(BAR(i < 6 ? B_F1 + W4AT : B_E1 + i - 6), 1);
            }
            const uint32_t dst = sb + ((uint32_t)((ly ? WTAB1 : WTAB0) >> (6 * kb)) & 63) * 4096;
#pragma unroll 1
            for (int h = wlo; h <= whi; h++) tma4d_mc(dst + h * 8192, &P.mB, kb * 64, 0, 0, 8 * cb + 4 * h, BAR(B_F1 + kb), wmask);
          }
          if (has2) {
            if (ly == 0) {
              mbar_wait(BAR(B_E1 + XRAT));
              mbar_expect_tx(BAR(B_XR), 20480 + 160 + 1024);
              tma4d(sb + XR_OFF, &P.mX, 80 * db, tb2, BAR(B_XR));
              bulk_g2s(sb + XR_OFF + 20480, P.dskip + 80 * db, 160, BAR(B_XR));
              bulk_g2s(sb + XR_OFF + 20480 + 256, S->S + 128 * tb2, 1024, BAR(B_XR));
              if (CWAIT) mbar_wait(BAR(CWAIT == 1 ? B_KF + 2 : CWAIT == 2 ? B_KF + R.nch() - 1 : CWAIT == 3 ? B_KF + R.nch() - 2 : B_HD));
            }
#pragma unroll 1
            for (int kp = 0; kp < 10; kp++) {
              const uint32_t dst = sb + (kp < 5 ? kp : kp - 5) * 20480;
              mbar_wait(BAR(kp >= 5 ? B_E2 + kp - 5 : ly ? B_E1 + ((CTAB1 >> (4 * kp)) & 15) : kp < 3 ? B_SH : kp < 4 ? B_HD : B_CD), ly);
              mbar_expect_tx(BAR(B_F2 + kp), 10240 + 16384);
              tma5d(dst, &P.mC[0], g2_cb(kp) * 64, db * 5, BAR(B_F2 + kp));
              mbar_expect_tx(BAR(B_F3 + kp), 10240 + 16384);
              tma5d(dst + 10240, &P.mC[1], g2_cb(kp) * 64, db * 5, BAR(B_F3 + kp));
              if (ly && kp == 4) { mbar_wait(BAR(B_E1 + 9), 1); gate_tile(P, sb + G_OFF1, BAR(B_GF), tb2, db); }
            }
          }
        }
      }
    } else if (wi == 13) {
      const int h0 = R.cs() == 8 ? rank : 4 * rank;
#pragma unroll 1
      for (int ly = 0; ly < 2; ly++) {
        int lane = lane_id();
        if (has1) {
          const unsigned* fp = &S->flag[(F_U3 + 8 * ((160 * tb) >> 7) + (lane & (full ? 15 : 7))) * 32];
          uint32_t ready = ly ? __ballot_sync(0xffffffff, ld_rlx(fp) == e1) : ~0u;
          if (ly) mbar_wait(BAR(full ? B_KF + 1 : has2 ? B_GS + 1 : B_RF1), has2);
          if (ly && full) mbar_wait(BAR(B_KF + 2), 1);
#pragma unroll 1
          for (int kb = ly ? 0 : 6; kb < 10; kb++) {
            if (ly && kb == UPAT) { mbar_wait(BAR(B_XR)); ready = ~0u; }
            wait_flags(fp, e1, 0x101u * ((1u << (64 * kb / 80)) | (1u << ((64 * kb + 63) / 80))), ready);
            if (kb >= 4) mbar_wait(BAR(B_E1 + (ly ? kb - 4 : (DEP0 >> (4 * kb - 24)) & 15)), ly);
            mbar_wait(BAR(B_AX + (kb == 9)));
            if (elect_one()) {
              if (ly && kb == 0) PROF(34);
              tma4d_mc(sb + ((uint32_t)((ly ? XTAB1 : XTAB0) >> (6 * kb)) & 63) * 4096 + R.uj() * 1024, &P.mA[2 * ly + umap], kb * 64, 0, 0, 80 * tb + R.uj(),
                       BAR(B_F1 + kb), umask);
              mbar_expect_tx(BAR(B_F1 + kb), f1bytes);
            }
            __syncwarp();
          }
        }
        if (ly == 0) {
          if (has1) mbar_wait(BAR(B_E1 + KPF));
          if (elect_one()) {
#pragma unroll 1
            for (int s = 0; s < R.nch(); s++) prefetch_l2(P.ssmk + (size_t)R.ch(s) * SEQ, 4096);
          }
          lane = lane_id();
#pragma unroll
          for (int s = 0; s < 5; s++) {
            asm volatile("st.shared.v4.u32 [%0],{%1,%1,%1,%1};" ::"r"(conv_buf(sb, s) + 16 * lane), "r"(0) : "memory");
            asm volatile("st.shared.u8 [%0],%1;" ::"r"(conv_buf(sb, s) + KC_OFS + lane), "r"(0) : "memory");
          }
          fence_async();
          __syncwarp();
          const unsigned* cp = &S->cnt[(C_KV + (R.ch(min(lane, R.nch() - 1)) >> 6)) * 32];
          uint32_t ready = 0;
#pragma unroll 1
          for (int s = 0, sk = 0; s < R.nch(); s++) {
#pragma unroll 1
            for (; sk < (s ? R.nch() : KUP); sk++)
              if (elect_one()) { mbar_expect_tx(BAR(B_KF + sk), 8192); bulk_g2s(conv_buf(sb, sk) + KC_OFS + 32, P.ssmk + (size_t)R.ch(sk) * SEQ, 4096, BAR(B_KF + sk)); }
            PROFC(s == 0, 329);
#pragma unroll 1
            for (int it = 0; !((ready >> s) & 1) && it < SPIN; it++) ready = __ballot_sync(0xffffffff, (int)(ld_rlx(cp) - e1 * 32) >= 0);
            PROFC(s == 0, 30);
            if (elect_one()) {
              bulk_g2s(conv_buf(sb, s) + KV_PAD, S->kv + (size_t)R.ch(s) * SEQ, 4096, BAR(B_KF + s));
              if (s == 0 && has2) { prefetch_l2(P.cre + (size_t)5 * b * DM, 5 * DM * 2); prefetch_l2(P.cim + (size_t)5 * b * DM, 5 * DM * 2); }
            }
            __syncwarp();
          }
          PROF(31);
          if (!has1) return;
        }
        lane = lane_id();
        const unsigned* fp = h_flag(S, ly, tb2, lane);
        uint32_t ready = __ballot_sync(0xffffffff, ld_rlx(fp) == e1), st = 0;
        if (ly == 0 && !has2) {
          mbar_wait(BAR(B_HD));
          if (lane < 8) mbar_arrive_cl(BAR(B_RF1), lane & 1);
        }
        if (has2) {
          mbar_wait(BAR(B_RF0), ly);
#pragma unroll 1
          for (int kp = 0; kp < 10; kp++) {
            if (kp == 5) { mbar_wait(BAR(B_XR), 1); ready = ~0u; }
            if (kp == 2) { mbar_wait(BAR(B_HD), ly); if (lane < 8) mbar_arrive_cl(BAR(B_RF1), lane & (R.cs() - 1)); }
            wait_flags(fp, e1, 0x10001u << g2_cb(kp), ready);
            if (kp == 2) mbar_wait(BAR(B_RF1), ly);
#pragma unroll
            for (int hf = 0; hf < 2; hf++) {
              if (kp >= 3) { if (hf) mbar_wait(BAR(B_E2 + kp - 3), ly); else mbar_wait(BAR(B_EA + st), ly ^ (kp >= 6 && kp < 9)); }
              if (elect_one()) {
                if (kp == 0 && !hf) PROF(33 + 2 * ly);
                tma4d_mc(sb + H_OFF + st * 32768 + hf * 16384 + h0 * 2048, &P.mH, g2_cb(kp) * 128 + hf * 64, 0, 2 * h0,
                         ly * 16 + tb2, BAR((hf ? B_F3 : B_F2) + kp), (1u << R.cs()) - 1);
              }
              __syncwarp();
            }
            st = st == 2 ? 0 : st + 1;
          }
        }
      }
    } else if (wi == 14) {
      if (!has1) return;
      prefetch_if(P.dskip + 64 * (tid & 31), (tid & 31) < 10);
      if (elect_one()) { prefetch_map(&P.sK); prefetch_map(&P.mX); prefetch_map(&P.sH); prefetch_map(&P.sU); prefetch_map(&P.mC[0]); prefetch_map(&P.mC[1]); prefetch_map(&P.mH); prefetch_map(&P.mGT); prefetch_map(&P.mA[2 + umap]); }
      __syncwarp();
#pragma unroll 1
      for (int ly = 0; ly < 2; ly++) {
        if (ly) {
          mbar_wait(BAR(B_F1 + 1), 1);
          uint32_t ready = 0;
          wait_flags(&S->flag[(F_U3 + 8 * ((160 * tb) >> 7) + ((lane_id() + ly) & (full ? 15 : 7))) * 32], e1, ~0u, ready);
          if (elect_one()) mbar_arrive(BAR(B_XR));
        }
        const int lane = lane_id();
        mbar_wait(BAR(B_E1 + (ly ? STAT_AT1 : STAT_AT)), ly);
        PROFC(lane == 0 && ly == 0, 36);
        {
          const int l = lane - (full ? 0 : 16);
          const uint2* p = S->S + ly * SEQ + 160 * tb + 2 * l;
          uint4 v[3];
#pragma unroll 1
          for (int it = 0; it < SPIN; it++) {
            v[0] = ld_rlx4(p); v[1] = ld_rlx4(p + 64); v[2] = ld_rlx4(p + 96);
            const bool miss = __any_sync(0xffffffff, untagged(v[0], e1 & 1) | untagged(v[1], e1 & 1) | untagged(v[2], e1 & 1));
            PROFC(lane == 0 && ly == 0 && it == 0, 37);
            if (!miss) break;
          }
          PROFC(lane == 0 && ly == 0, 38);
          uint32_t sp = sb + SSM_OFF + 8 * lane + (full ? 0 : 2 * (lane & 16) - 160);
#pragma unroll
          for (int i = 0; i < 3; i++) {
            asm volatile("{ .reg .pred p; setp.ge.u32 p, %0, %5; @p st.shared.v2.u32 [%0],{%1,%3}; @p st.shared.v2.u32 [%0+640],{%2,%4}; }" ::"r"(sp),
                         "r"(v[i].x & ~1u), "r"(v[i].y & ~1u), "r"(v[i].z & ~1u), "r"(v[i].w & ~1u), "r"(sb + SSM_OFF) : "memory");
            sp += (full ? 256 : 320) >> i;
          }
          __syncwarp();
        }
        if (lane == 0) mbar_arrive(BAR(B_ST));
        if (ly && has2) {
          mbar_wait(BAR(B_E1 + 9), 1);
          if (lane < 8) mbar_arrive_cl(BAR(B_RF0), lane & (R.cs() - 1));
        }
        if (lane == 0) {
#pragma unroll 1
          for (int pc = 0; pc < (full ? 5 : 4); pc++) {
            if ((HWM >> (4 * pc)) & 8) {
              mbar_wait(BAR(B_SH + min((HWM >> (4 * pc)) & 7, full ? 4 : 3)), ly);
              PROF(380 + 5 * ly + pc);
              if (pc == 0 && (cb & 1)) delay(ly ? HDLY : HDLY0);
              fence_async();
            }
#pragma unroll
            for (int i = 0; i < 2; i++) tma4d_store(&P.sH, sb + (pc < 4 ? R_OFF + i * 16384 + pc * 4096 : (ly ? R4_OFF1 : R4_OFF0) + i * 4096), 128 * cb + 64 * i, 0, 0, ly * 1024 + 80 * tb + 4 * pc);
          }
          bulk_commit(); bulk_wait();
          PROF(ly ? 17 : 16);
          mbar_arrive(BAR(B_HD));
          release<1>();
          signal_flag(&S->flag[(F_H + (ly * 13 + tb) * 10 + cb) * 32], e1);
          PROF(ly ? 24 : 8);
        }
        __syncwarp();
        if (has2) {
          mbar_wait(BAR(B_F2 + FPAT), ly);
          uint32_t ready = 0;
          wait_flags(h_flag(S, ly, tb2, lane_id() | 1), e1, ~0u, ready);
          if (elect_one()) mbar_arrive(BAR(B_XR));
        }
        if (lane == 0 && has2 && !ly) {
          mbar_wait(BAR(B_CD + 1));
#pragma unroll
          for (int i = 0; i < 2; i++) {
            mbar_wait(BAR(B_GS + 1 + i), 1);
            fence_async();
            tma4d_store(&P.sU, sb + US_OFF + 10240 - 10240 * i, 80 * db, 0, 8 * i, tb2);
          }
          bulk_commit(); bulk_wait();
          PROF(18);
          release<2>(); signal_flag(&S->flag[(F_U3 + b) * 32], e1);
          PROF(14);
          mbar_wait(BAR(B_SG));
          mbar_arrive(BAR(B_GE)); mbar_arrive_cl(BAR(B_GE), R.wpart());
        }
        __syncwarp();
      }
    } else {
      discretise(H, P, sb, R, tid & 31, e1);
      if (elect_one()) {
        mbar_arrive(BAR(B_LM));
        PROF(348);
        if (b < R.nprep()) {
#pragma unroll 1
          for (int task = b, r = 0; task < 320; task += R.nprep(), r++) {
            mbar_wait(BAR(B_PS + r));
            PROF(320 + 3 * r);
            fence_async();
            tma2d_store(&P.sK, sb + KS_OFF + r * 8192, 64 * (task & 31), 64 * (task >> 5));
            bulk_commit(); bulk_wait();
            PROF(321 + 3 * r);
            release<4>();
            signal_cnt(&S->cnt[(C_KV + (task >> 5)) * 32], 1);
            PROF(322 + 3 * r);
          }
          PROF(41);
        }
        if (has2) {
          mbar_wait(BAR(B_SH));
#pragma unroll 1
          for (int i = 0; i < 8; i++) mbar_arrive_cl(BAR(B_RF0), i & (R.cs() - 1));
        }
#pragma unroll 1
        for (int s = 0, s0 = 0; s < R.nch(); s++) {
          mbar_wait(BAR(B_GS + s));
          fence_async();
          bulk_s2g(S->gt + (size_t)R.ch(s) * SEQ, conv_buf(sb, s) + KC_OFS, 4096); bulk_commit();
          if (s == 1 || s >= R.nch() - GSPL) bulk_wait();
          if (s == 1 || s == min(R.nch() - 1, 3)) mbar_arrive(BAR(B_CD + (s > 1)));
          mbar_arrive_if(BAR(B_SG), s == R.nch() - 1);
          if (s >= R.nch() - GSPL) {
            PROF(45);
            release<8>();
#pragma unroll 1
            for (; s0 <= s; s0++) signal_cnt(&S->cnt[(C_G + R.ch(s0) / 80) * 32], 1);
          }
        }
        PROF(46);
      }
    }
  }
}

typedef CUresult (*EncFn)(CUtensorMap*, CUtensorMapDataType, cuuint32_t, void*, const cuuint64_t*, const cuuint64_t*, const cuuint32_t*,
                          const cuuint32_t*, CUtensorMapInterleave, CUtensorMapSwizzle, CUtensorMapL2promotion, CUtensorMapFloatOOBfill);
bool enc(EncFn f, CUtensorMap* m, const void* base, int rank, const cuuint64_t* dims, const cuuint64_t* strides, const cuuint32_t* box, bool swz,
         bool f32 = false) {
  const cuuint32_t es[5] = {1, 1, 1, 1, 1};
  return f(m, f32 ? CU_TENSOR_MAP_DATA_TYPE_FLOAT32 : CU_TENSOR_MAP_DATA_TYPE_BFLOAT16, rank, const_cast<void*>(base), dims, strides, box, es,
           CU_TENSOR_MAP_INTERLEAVE_NONE, swz ? CU_TENSOR_MAP_SWIZZLE_128B : CU_TENSOR_MAP_SWIZZLE_NONE, CU_TENSOR_MAP_L2_PROMOTION_L2_256B,
           CU_TENSOR_MAP_FLOAT_OOB_FILL_NONE) == CUDA_SUCCESS;
}
void make_roles(Params& P, bool big) {
  for (uint32_t bx = 0; bx < (big ? 120u : 12u); bx++) {
    const uint32_t c = bx >> 3, r = bx & 7, id = big ? bx : 120 + bx;
    const uint32_t vA = c < 12 ? (2 * (c >> 1) + (r >> 2)) | (4 * (c & 1) + (r & 3)) << 4 | (r & 4) << 16 | 4 << 19 | (r ^ 4) << 22
                               : (4 * (c - 12) + (r >> 1)) | (8 + (r & 1)) << 4 | (r & 6) << 16 | 2 << 19 | (r ^ 2) << 22;
    const uint32_t vB = (bx < 10 ? 12 : 13) | bx << 4 | 2 << 19 | (bx & 1) << 22 | (bx & 1) << 26;
    P.role[bx].x = (big ? vA | r << 26 | 1u << 29 : vB) | (id < 128 ? (id & ~7u) | (r >> 1) | (r & 1) << 2 : id) << 8;
    P.role[bx].y = id | (big ? 5 : bx < 8 ? 3 : 4) << 10 | 120 << 13 | 132 << 21 | (big ? 4u : 3u) << 29;
    const uint32_t v = P.role[bx].x, cb = (v >> 4) & 15, rank = (v >> 26) & 7, ubase = (v >> 16) & 7, ugs = (v >> 19) & 7, wp = (v >> 22) & 7;
    const uint32_t wlo = rank > wp, whi = wp != rank ? wlo : 1, wmask = 1u << rank | 1u << wp;
    const uint32_t uj = (rank - ubase) * (!big ? 8 : ugs == 4 ? 5 : 10), sm = big ? (0x7296418530ull >> (4 * cb)) & 15 : bx < 8 ? 4 * (bx & 1) + (bx >> 1) : 15;
    P.role[bx].z = wlo | whi << 1 | wmask << 2 | ((1u << ugs) - 1) << (10 + ubase) | uj << 20 | sm << 25;
    P.role[bx].w = 0;
  }
}
void launch(const Head& H, const Params& P, int grid, int cs, bool dependent) {
  cudaLaunchConfig_t cfg = {};
  cfg.gridDim = grid; cfg.blockDim = 512; cfg.dynamicSmemBytes = SMEM_BYTES; cfg.stream = cudaStreamPerThread;
  cudaLaunchAttribute at[2];
  at[0].id = cudaLaunchAttributeClusterDimension; at[0].val.clusterDim.x = cs; at[0].val.clusterDim.y = 1; at[0].val.clusterDim.z = 1;
  at[1].id = cudaLaunchAttributeProgrammaticStreamSerialization; at[1].val.programmaticStreamSerializationAllowed = 1;
  cfg.attrs = at; cfg.numAttrs = dependent ? 2 : 1;
  cudaLaunchKernelEx(&cfg, fused_kernel, H, P);
}

}

extern "C" void kernel_launch(void* const* d_in, const int* in_sizes, int n_in, void* d_out, int out_size) {
  (void)in_sizes; (void)n_in; (void)out_size;
  typedef const __nv_bfloat16* cb;
  void* fp = nullptr; cudaDriverEntryPointQueryResult qr;
  cudaGetDriverEntryPoint("cuTensorMapEncodeTiled", &fp, cudaEnableDefault, &qr);
  EncFn f = (EncFn)fp;
  Scratch* sp = nullptr;
  cudaGetSymbolAddress((void**)&sp, g_scr);
  void *pu = sp->u, *ph = sp->h, *pgt = sp->gt;
  Params P;
  Head H;
  H.s = sp; H.x = (cb)d_in[0]; H.swap = (uintptr_t)d_in[4] < (uintptr_t)d_in[3] ? 0 : 0x80000000u; H.b0 = (cb)d_in[H.swap ? 3 : 4]; H.b1 = (cb)d_in[H.swap ? 4 : 3];
  for (int i = 0; i < 2; i++) {
    const cuuint64_t d[4] = {640, 8, 2, 80}, s[3] = {1280, (cuuint64_t)((uintptr_t)H.b1 - (uintptr_t)H.b0), 8 * 1280}; const cuuint32_t bx[4] = {64, 8, 2, 4};
    if (enc(f, &P.mB, H.b0, 4, d, s, bx, true)) break;
    cudaMemcpyAsync(sp->bcopy, H.b0, DM * DM * 2, cudaMemcpyDeviceToDevice, cudaStreamPerThread);
    cudaMemcpyAsync(sp->bcopy + DM * DM, H.b1, DM * DM * 2, cudaMemcpyDeviceToDevice, cudaStreamPerThread);
    H.b0 = sp->bcopy; H.b1 = sp->bcopy + DM * DM;
  }
  {
    const cuuint64_t d[5] = {640, 2, 4, 2, 40}, s[4] = {1280, 4 * 1280, 2 * 1280, 16 * 1280}; const cuuint32_t bx[5] = {64, 2, 4, 2, 5};
    enc(f, &P.mC[0], d_in[5], 5, d, s, bx, true); enc(f, &P.mC[1], d_in[6], 5, d, s, bx, true); }
  { const cuuint64_t d[2] = {2048, 640}, s[1] = {4096}; const cuuint32_t bx[2] = {64, 80}; enc(f, &P.mGT, pgt, 2, d, s, bx, true); }
  { const cuuint64_t d[4] = {640, 8, 16, 16}, s[3] = {16 * 1280, 1280, 128 * 1280}; const cuuint32_t bx[4] = {80, 8, 16, 1}, bh[4] = {80, 8, 8, 1};
    enc(f, &P.sU, pu, 4, d, s, bh, false); enc(f, &P.mX, d_in[0], 4, d, s, bx, false); }
  { const cuuint64_t d[2] = {2048, 640}, s[1] = {4096}; const cuuint32_t bx[2] = {64, 64}; enc(f, &P.sK, sp->kv, 2, d, s, bx, true); }
  P.lre = (cb)d_in[1]; P.lim = (cb)d_in[2]; P.cre = (cb)d_in[5]; P.cim = (cb)d_in[6]; P.ldt = (cb)d_in[7]; P.dskip = (cb)d_in[8];
  P.out = (float*)d_out;
  P.k = (cb)d_in[10]; P.v = (cb)d_in[11]; P.shk = (cb)d_in[12]; P.ssmk = (cb)d_in[13]; P.ssmd = (cb)d_in[14];
  cudaFuncSetAttribute(fused_kernel, cudaFuncAttributeMaxDynamicSharedMemorySize, SMEM_BYTES);
  for (int big = 1; big >= 0; big--) {
    const cuuint64_t seg = big ? 40 : 32;
    for (int i = 0; i < 4; i++) {
      const cuuint64_t d[4] = {640, 2, 4, 1024}, s[3] = {1280, seg * 1280, 2 * 1280}; const cuuint32_t bx[4] = {64, 2, 4, !big ? 8u : (i & 1) ? 10u : 5u};
      enc(f, &P.mA[i], i < 2 ? d_in[0] : pu, 4, d, s, bx, true);
    }
    {
      const cuuint64_t d[4] = {1280, 8, 16, 32}, s[3] = {16 * 2560, 2560, 128 * 2560}; const cuuint32_t bx[4] = {64, 8, big ? 2u : 8u, 1};
      enc(f, &P.mH, ph, 4, d, s, bx, true); }
    { const cuuint64_t d[4] = {1280, 2, 4, 2048}, s[3] = {2560, seg * 2560, 2 * 2560}; const cuuint32_t bx[4] = {64, 2, 4, 4};
      enc(f, &P.sH, ph, 4, d, s, bx, true); }
    make_roles(P, big);
    H.base = big ? 0 : 120;
    launch(H, P, big ? 120 : 12, big ? 8 : 2, !big);
  }
}
```

```cpp
#include <cuda_runtime.h>
#include <cuda.h>
#include <cuda_bf16.h>
#include <stdint.h>

namespace {

constexpr int SEQ = 2048, DM = 640;
constexpr int SPIN = 1 << 20;
#define PFAT 99
#define KVDLY 500
#define PFD 1
#define XPFAT 9
#define STAT_AT 6
#define KPFAT 3
#define KPFAT2 5
#define KPF 7
#define HDLY 1900
#define GSPL 2
#define CWAIT 0
#define HDLY0 1900
#define CTAB1 0x96543u
#define NSAT 0
#define SKW 1
#define RIAT 2
#define MIAT 5
#define FPAT 1
#define UPAT 7
#define STAT_AT1 4
#define W4AT 0
#define MBAR 1
#define STG 17
#define STG0 17
#define HWM 0xc09
#define NSDB 4
#define GLATE 6
#define KUP 1
#define XRAT 9
#define ORD 1

struct Scratch {
  uint2 E[2 * 13 * 10 * 8 * 16];
  uint32_t M[3 * 16 * 8 * 256];
  uint2 S[3 * SEQ];
  uint2 RS[80 * 16];
  unsigned flag[512 * 32];
  unsigned cnt[32 * 32];
  unsigned epoch[132 * 8];
  unsigned zero[128];
  unsigned prof[132 * 512];
  __align__(1024)
  __nv_bfloat16 u[SEQ * DM];
  __nv_bfloat16 h[2 * SEQ * 1280];
  __nv_bfloat16 kv[DM * SEQ];
  __nv_bfloat16 gt[DM * SEQ];
  __nv_bfloat16 bcopy[2 * DM * DM];
};
__device__ __align__(1024) Scratch g_scr;
#define PROFC(c, i) do {} while (0)
#define PSEL 1
#define PROF(i) do {} while (0)

constexpr int C_KV = 0, C_G = 10;
constexpr int F_U3 = 0, F_H = 128;

constexpr int R_OFF = 196608, R4_OFF0 = 73728, R4_OFF1 = 122880, H_OFF = 131072, KS_OFF = 131072, CV_OFF = 86272, G_OFF0 = 40960, G_OFF1 = 102400, US_OFF = 98304, XR_OFF = 163840, MX_OFF = 32768;
constexpr int LAM_OFF = 229376, SSM_OFF = LAM_OFF + 1024, BAR_OFF = SSM_OFF + 1344;
constexpr int B_F1 = 0, B_E1 = 10, B_RF0 = 20, B_RF1 = 21, NBAR1 = 22;
constexpr int B_F2 = 22, B_KF = 32, B_GF = 37, B_CD = 38, B_XR = 40, B_ST = 41, B_HD = 42, B_LM = 43, B_E2 = 44, B_GS = 54, B_PS = 59, B_AX = 62, B_SH = 64, B_SG = 69, B_GE = 70, B_EA = 71, B_F3 = 74, NBAR = 84;
__host__ __device__ constexpr int bar_count(int i) { return i < B_E1 ? 1 : i < B_RF0 ? 9 : i < B_F2 ? 8 : i < B_E2 ? 1 : i < B_GS ? 12 : i < B_SH ? 4 : i < B_SG ? 8 : i < B_GE ? 1 : i < B_EA ? 2 : i < B_F3 ? 8 : 1; }
constexpr int MISC_OFF = BAR_OFF + NBAR * 8, SMEM_BYTES = MISC_OFF + 32;
constexpr int KV_PAD = 512, KC_OFS = KV_PAD + 4096, CH_STRIDE = 8960;
__device__ __forceinline__ uint32_t conv_buf(uint32_t sb, int slot) { return sb + CV_OFF + slot * CH_STRIDE; }
constexpr uint64_t tab6(int a, int b, int c, int d, int e, int f, int g, int h, int i, int j) {
  return (uint64_t)a | (uint64_t)b << 6 | (uint64_t)c << 12 | (uint64_t)d << 18 | (uint64_t)e << 24 | (uint64_t)f << 30 | (uint64_t)g << 36 | (uint64_t)h << 42 |
         (uint64_t)i << 48 | (uint64_t)j << 54;
}
constexpr uint64_t WTAB0 = tab6(0, 4, 8, 30, 12, 26, 0, 4, 8, 12), XTAB0 = tab6(40, 45, 50, 34, 16, 21, 40, 45, 50, 16);
constexpr uint64_t WTAB1 = tab6(16, 20, 0, 4, 8, 12, 16, 20, 24, 28), XTAB1 = tab6(40, 45, 50, 32, 40, 45, 50, 32, 40, 45);
constexpr uint32_t DEP0 = 0x4210;

struct Head {
  Scratch* s;
  const __nv_bfloat16 *x, *b0, *b1;
  uint32_t base, swap;
};
struct Params {
  const __nv_bfloat16 *lre, *lim, *ldt, *k, *v, *shk, *cre, *cim, *ssmk, *ssmd, *dskip;
  float* out;
  uint4 role[120];
  CUtensorMap mB, mA[4], mH, mC[2], mGT, mX, sH, sU, sK;
};

__device__ __forceinline__ uint32_t smem_u32(const void* p) { return (uint32_t)__cvta_generic_to_shared(p); }
__device__ __forceinline__ uint32_t opaque(uint32_t x) { uint32_t y; asm volatile("mov.u32 %0, %1;" : "=r"(y) : "r"(x)); return y; }
__device__ __forceinline__ int lane_id() { int y; asm volatile("mov.u32 %0, %%laneid;" : "=r"(y)); return y; }
__device__ __forceinline__ void delay(uint32_t n) {
  asm volatile("{ .reg .pred p; .reg .u32 a, b; mov.u32 a, %%clock; L: mov.u32 b, %%clock; sub.u32 b, b, a; setp.lt.u32 p, b, %0; @p bra.uni L; }" ::"r"(n) : "memory");
}
__device__ __forceinline__ void mbar_init(uint32_t bar, uint32_t cnt) { asm volatile("mbarrier.init.shared::cta.b64 [%0], %1;" ::"r"(bar), "r"(cnt) : "memory"); }
__device__ __forceinline__ void mbar_expect_tx(uint32_t bar, uint32_t bytes) { asm volatile("mbarrier.arrive.expect_tx.shared::cta.b64 _, [%0], %1;" ::"r"(bar), "r"(bytes) : "memory"); }
__device__ __forceinline__ void mbar_arrive(uint32_t bar) { asm volatile("mbarrier.arrive.shared::cta.b64 _, [%0];" ::"r"(bar) : "memory"); }
__device__ __forceinline__ void mbar_arrive_if(uint32_t bar, bool c) {
  asm volatile("{ .reg .pred p; setp.ne.u32 p, %1, 0; @p mbarrier.arrive.shared::cta.b64 _, [%0]; }" ::"r"(bar), "r"((uint32_t)c) : "memory");
}
__device__ __forceinline__ void prefetch_if(const void* p, bool c) { asm volatile("{ .reg .pred p; setp.ne.u32 p, %1, 0; @p prefetch.global.L2 [%0]; }" ::"l"(p), "r"((uint32_t)c)); }
__device__ __forceinline__ void mbar_arrive_cl(uint32_t bar, uint32_t cta) {
  asm volatile("{ .reg .b32 ra; mapa.shared::cluster.u32 ra, %0, %1; mbarrier.arrive.shared::cluster.b64 _, [ra]; }" ::"r"(bar), "r"(cta) : "memory");
}
__device__ __forceinline__ uint32_t mapa(uint32_t a, uint32_t cta) { uint32_t r; asm("mapa.shared::cluster.u32 %0, %1, %2;" : "=r"(r) : "r"(a), "r"(cta)); return r; }
__device__ __forceinline__ void mbar_arrive_at(uint32_t ra) { asm volatile("mbarrier.arrive.shared::cluster.b64 _, [%0];" ::"r"(ra) : "memory"); }
__device__ __forceinline__ void mbar_wait(uint32_t bar, uint32_t parity = 0) {
  asm volatile("{ .reg .pred p; .reg .u32 c; mov.u32 c, 0;\n"
               "W: mbarrier.try_wait.parity.shared::cta.b64 p, [%0], %1; @p bra.uni D;\n"
               "add.u32 c, c, 1; setp.lt.u32 p, c, 0x100000; @p bra.uni W;\nD: }" ::"r"(bar), "r"(parity) : "memory");
}
__device__ __forceinline__ bool elect_one() { uint32_t p; asm volatile("{ .reg .pred P; elect.sync _|P, 0xffffffff; selp.u32 %0,1,0,P; }" : "=r"(p)); return p; }
__device__ __forceinline__ void bar_sync(int id, int n) { __syncwarp(); asm volatile("bar.sync %0, %1;" ::"r"(id), "r"(n) : "memory"); }
__device__ __forceinline__ void tma2d(uint32_t dst, const CUtensorMap* m, int c0, int c1, uint32_t bar) {
  asm volatile("cp.async.bulk.tensor.2d.shared::cluster.global.mbarrier::complete_tx::bytes [%0], [%1, {%3,%4}], [%2];"
               ::"r"(dst), "l"(m), "r"(bar), "r"(c0), "r"(c1) : "memory");
}
__device__ __forceinline__ void tma5d(uint32_t dst, const CUtensorMap* m, int c0, int c4, uint32_t bar) {
  asm volatile("cp.async.bulk.tensor.5d.shared::cluster.global.mbarrier::complete_tx::bytes [%0], [%1, {%3,%5,%5,%5,%4}], [%2];"
               ::"r"(dst), "l"(m), "r"(bar), "r"(c0), "r"(c4), "r"(0) : "memory");
}
__device__ __forceinline__ void tma4d(uint32_t dst, const CUtensorMap* m, int c0, int c3, uint32_t bar) {
  asm volatile("cp.async.bulk.tensor.4d.shared::cluster.global.mbarrier::complete_tx::bytes [%0], [%1, {%3,%5,%5,%4}], [%2];"
               ::"r"(dst), "l"(m), "r"(bar), "r"(c0), "r"(c3), "r"(0) : "memory");
}
__device__ __forceinline__ void tma4d_mc(uint32_t dst, const CUtensorMap* m, int c0, int c1, int c2, int c3, uint32_t bar, uint32_t mask) {
  asm volatile("cp.async.bulk.tensor.4d.shared::cluster.global.mbarrier::complete_tx::bytes.multicast::cluster [%0], [%1, {%3,%4,%5,%6}], [%2], %7;"
               ::"r"(dst), "l"(m), "r"(bar), "r"(c0), "r"(c1), "r"(c2), "r"(c3), "h"((uint16_t)mask) : "memory");
}
__device__ __forceinline__ void bulk_g2s(uint32_t dst, const void* src, uint32_t bytes, uint32_t bar) {
  asm volatile("cp.async.bulk.shared::cluster.global.mbarrier::complete_tx::bytes [%0], [%1], %2, [%3];" ::"r"(dst), "l"(src), "r"(bytes), "r"(bar) : "memory");
}
__device__ __forceinline__ void tma4d_store(const CUtensorMap* m, uint32_t src, int c0, int c1, int c2, int c3) {
  asm volatile("cp.async.bulk.tensor.4d.global.shared::cta.bulk_group [%0, {%2,%3,%4,%5}], [%1];" ::"l"(m), "r"(src), "r"(c0), "r"(c1), "r"(c2), "r"(c3) : "memory");
}
__device__ __forceinline__ void tma2d_store(const CUtensorMap* m, uint32_t src, int c0, int c1) {
  asm volatile("cp.async.bulk.tensor.2d.global.shared::cta.bulk_group [%0, {%2,%3}], [%1];" ::"l"(m), "r"(src), "r"(c0), "r"(c1) : "memory");
}
__device__ __forceinline__ void bulk_s2g(void* dst, uint32_t src, uint32_t bytes) {
  asm volatile("cp.async.bulk.global.shared::cta.bulk_group [%0], [%1], %2;" ::"l"(dst), "r"(src), "r"(bytes) : "memory");
}
__device__ __forceinline__ void bulk_commit() { asm volatile("cp.async.bulk.commit_group;" ::: "memory"); }
__device__ __forceinline__ void bulk_wait() { asm volatile("cp.async.bulk.wait_group 0;" ::: "memory"); }
__device__ __forceinline__ void fence_async() { asm volatile("fence.proxy.async.shared::cta;" ::: "memory"); }
__device__ __forceinline__ void prefetch_l2(const void* src, uint32_t bytes) { asm volatile("cp.async.bulk.prefetch.L2.global [%0], %1;" ::"l"(src), "r"(bytes) : "memory"); }
__device__ __forceinline__ void prefetch_map(const CUtensorMap* m) { asm volatile("prefetch.tensormap [%0];" ::"l"(m) : "memory"); }
__device__ __forceinline__ void wg_fence() { __syncwarp(); asm volatile("wgmma.fence.sync.aligned;" ::: "memory"); }
__device__ __forceinline__ void wg_commit() { asm volatile("wgmma.commit_group.sync.aligned;" ::: "memory"); }
template <int N> __device__ __forceinline__ void wg_wait() { asm volatile("wgmma.wait_group.sync.aligned %0;" ::"n"(N) : "memory"); }
template <int N> __device__ __forceinline__ void fence_regs(float (&d)[N]) {
#pragma unroll
  for (int i = 0; i < N; i++) asm volatile("" : "+f"(d[i])::"memory");
}
__device__ __forceinline__ uint64_t make_desc(uint32_t addr, uint32_t lbo, uint32_t sbo, uint32_t swz) {
  return (uint64_t)((addr & 0x3FFFF) >> 4) | ((uint64_t)(lbo >> 4) << 16) | ((uint64_t)(sbo >> 4) << 32) | ((uint64_t)swz << 62);
}
__device__ __forceinline__ uint32_t ldg1(const void* p) { uint32_t v; asm volatile("ld.global.nc.u32 %0,[%1];" : "=r"(v) : "l"(p)); return v; }
__device__ __forceinline__ uint32_t lds32(uint32_t a) { uint32_t v; asm volatile("ld.shared.u32 %0,[%1];" : "=r"(v) : "r"(a)); return v; }
__device__ __forceinline__ unsigned ld_rlx(const unsigned* p) { unsigned v; asm volatile("ld.relaxed.gpu.global.u32 %0,[%1];" : "=r"(v) : "l"(p) : "memory"); return v; }
__device__ __forceinline__ uint4 ld_rlx4(const void* p) {
  uint4 v; asm volatile("ld.relaxed.gpu.global.v4.u32 {%0,%1,%2,%3},[%4];" : "=r"(v.x), "=r"(v.y), "=r"(v.z), "=r"(v.w) : "l"(p) : "memory"); return v;
}
__device__ __forceinline__ uint2 ld_rlx2(const void* p) { uint2 v; asm volatile("ld.relaxed.gpu.global.v2.u32 {%0,%1},[%2];" : "=r"(v.x), "=r"(v.y) : "l"(p) : "memory"); return v; }
__device__ __forceinline__ void st_rlx2(void* p, uint32_t a, uint32_t b) { asm volatile("st.relaxed.gpu.global.v2.u32 [%0],{%1,%2};" ::"l"(p), "r"(a), "r"(b) : "memory"); }
__device__ __forceinline__ void st_rlx(void* p, uint32_t a) { asm volatile("st.relaxed.gpu.global.u32 [%0],%1;" ::"l"(p), "r"(a) : "memory"); }
#define PUB 15
template <int SITE> __device__ __forceinline__ void release() { if (PUB & SITE) asm volatile("fence.release.gpu;" ::: "memory"); }
__device__ __forceinline__ void signal_flag(unsigned* p, unsigned val) { asm volatile("st.relaxed.gpu.global.u32 [%0],%1;" ::"l"(p), "r"(val) : "memory"); }
__device__ __forceinline__ void signal_cnt(unsigned* p, unsigned n) { asm volatile("red.relaxed.gpu.global.add.u32 [%0],%1;" ::"l"(p), "r"(n) : "memory"); }
__device__ __forceinline__ void wait_flags(const unsigned* p, unsigned val, uint32_t need, uint32_t& ready) {
#pragma unroll 1
  for (int it = 0; (ready & need) != need && it < SPIN; it++) ready = __ballot_sync(0xffffffff, ld_rlx(p) == val);
}
__device__ __forceinline__ void wait_cnt(const unsigned* p, unsigned tgt) {
  asm volatile("{ .reg .pred p; .reg .u32 c; .reg .s32 v; mov.u32 c, 0;\n"
               "W: ld.relaxed.gpu.global.u32 v, [%0]; sub.s32 v, v, %1; setp.ge.s32 p, v, 0; @p bra.uni D;\n"
               "add.u32 c, c, 1; setp.lt.u32 p, c, 0x100000; @p bra.uni W;\nD: }" ::"l"(p), "r"(tgt) : "memory");
}
__device__ __forceinline__ uint32_t pack_bf(float lo, float hi) { uint32_t r; asm("cvt.rn.bf16x2.f32 %0, %1, %2;" : "=r"(r) : "f"(hi), "f"(lo)); return r; }
__device__ __forceinline__ float bf_lo(uint32_t v) { return __uint_as_float(v << 16); }
__device__ __forceinline__ float bf_hi(uint32_t v) { return __uint_as_float(v & 0xffff0000u); }
__device__ __forceinline__ float bf_rn(float x) { return __bfloat162float(__float2bfloat16_rn(x)); }
__device__ __forceinline__ float frcp(float x) { float r; asm("rcp.approx.ftz.f32 %0,%1;" : "=f"(r) : "f"(x)); return r; }
__device__ __forceinline__ float fsqrt(float x) { float r; asm("sqrt.approx.ftz.f32 %0,%1;" : "=f"(r) : "f"(x)); return r; }
__device__ __forceinline__ float frsqrt(float x) { float r; asm("rsqrt.approx.ftz.f32 %0,%1;" : "=f"(r) : "f"(x)); return r; }
__device__ __forceinline__ uint32_t hmul2(uint32_t a, uint32_t b) { uint32_t r; asm("mul.rn.bf16x2 %0,%1,%2;" : "=r"(r) : "r"(a), "r"(b)); return r; }
__device__ __forceinline__ uint32_t hfma2(uint32_t a, uint32_t b, uint32_t c) { uint32_t r; asm("fma.rn.bf16x2 %0,%1,%2,%3;" : "=r"(r) : "r"(a), "r"(b), "r"(c)); return r; }
__device__ __forceinline__ float2 cmul(float2 a, float2 b) { return make_float2(a.x * b.x - a.y * b.y, a.x * b.y + a.y * b.x); }
__device__ __forceinline__ float2 cfma(float2 a, float2 b, float2 c) {
  return make_float2(fmaf(a.x, b.x, fmaf(-a.y, b.y, c.x)), fmaf(a.x, b.y, fmaf(a.y, b.x, c.y)));
}
__device__ __forceinline__ uint32_t tagf(float v, uint32_t tag) { return (__float_as_uint(v) & ~1u) | tag; }
__device__ __forceinline__ float untag(uint32_t v) { return __uint_as_float(v & ~1u); }
__device__ __forceinline__ bool untagged(const uint4& v, uint32_t tag) { return (((v.x ^ tag) | (v.y ^ tag) | (v.z ^ tag) | (v.w ^ tag)) & 1) != 0; }
__device__ __forceinline__ bool untagged(const uint2& v, uint32_t tag) { return (((v.x ^ tag) | (v.y ^ tag)) & 1) != 0; }
__device__ __forceinline__ float2 lam_bar(float lr, float li, float ldt) {
  float dt = bf_rn(expf(ldt)); float e = expf(dt * lr), s, c; sincospif(dt * li * 0.31830988618379067f, &s, &c); return make_float2(e * c, e * s);
}

__device__ __forceinline__ int conv_ch(uint32_t c, int s) { return s * ((c >> 21) & 255) + (c & 255) - (s >= (int)(c >> 29) ? 8 : 0); }
struct Role {
  uint32_t v, c, p;
  __device__ __forceinline__ int tb() const { return v & 15; }
  __device__ __forceinline__ int cb() const { return (v >> 4) & 15; }
  __device__ __forceinline__ int b() const { return (v >> 8) & 255; }
  __device__ __forceinline__ int ubase() const { return (v >> 16) & 7; }
  __device__ __forceinline__ int ugs() const { return (v >> 19) & 7; }
  __device__ __forceinline__ int wpart() const { return (v >> 22) & 7; }
  __device__ __forceinline__ int rank() const { return (v >> 26) & 7; }
  __device__ __forceinline__ int cs() const { return (v >> 29) ? 8 : 2; }
  __device__ __forceinline__ int ch(int s) const { return conv_ch(c, s); }
  __device__ __forceinline__ int wlo() const { return p & 1; }
  __device__ __forceinline__ int whi() const { return (p >> 1) & 1; }
  __device__ __forceinline__ uint32_t wmask() const { return (p >> 2) & 255; }
  __device__ __forceinline__ uint32_t umask() const { return (p >> 10) & 255; }
  __device__ __forceinline__ int uj() const { return (p >> 20) & 31; }
  __device__ __forceinline__ int sm() const { return (p >> 25) & 15; }
  __device__ __forceinline__ int nch() const { return (c >> 10) & 7; }
  __device__ __forceinline__ int nprep() const { return (c >> 13) & 255; }
};

__device__ __forceinline__ void wgmma_ss80(float (&d)[40], uint64_t da, uint64_t db, int sd){
  asm volatile("{ .reg .pred p; setp.ne.b32 p, %42, 0;\n"
   "wgmma.mma_async.sync.aligned.m64n80k16.f32.bf16.bf16 {%0, %1, %2, %3, %4, %5, %6, %7, %8, %9, %10, %11, %12, %13, %14, %15, %16, %17, %18, %19, %20, %21, %22, %23, %24, %25, %26, %27, %28, %29, %30, %31, %32, %33, %34, %35, %36, %37, %38, %39}, %40, %41, p, 1, 1, 0, 0; }\n"
   : "+f"(d[0]), "+f"(d[1]), "+f"(d[2]), "+f"(d[3]), "+f"(d[4]), "+f"(d[5]), "+f"(d[6]), "+f"(d[7]), "+f"(d[8]), "+f"(d[9]), "+f"(d[10]), "+f"(d[11]), "+f"(d[12]), "+f"(d[13]), "+f"(d[14]), "+f"(d[15]), "+f"(d[16]), "+f"(d[17]), "+f"(d[18]), "+f"(d[19]), "+f"(d[20]), "+f"(d[21]), "+f"(d[22]), "+f"(d[23]), "+f"(d[24]), "+f"(d[25]), "+f"(d[26]), "+f"(d[27]), "+f"(d[28]), "+f"(d[29]), "+f"(d[30]), "+f"(d[31]), "+f"(d[32]), "+f"(d[33]), "+f"(d[34]), "+f"(d[35]), "+f"(d[36]), "+f"(d[37]), "+f"(d[38]), "+f"(d[39]) : "l"(da), "l"(db), "r"(sd));
}
__device__ __forceinline__ void wgmma_ss160(float (&d)[80], uint64_t da, uint64_t db, int sd){
  asm volatile("{ .reg .pred p; setp.ne.b32 p, %82, 0;\n"
   "wgmma.mma_async.sync.aligned.m64n160k16.f32.bf16.bf16 {%0, %1, %2, %3, %4, %5, %6, %7, %8, %9, %10, %11, %12, %13, %14, %15, %16, %17, %18, %19, %20, %21, %22, %23, %24, %25, %26, %27, %28, %29, %30, %31, %32, %33, %34, %35, %36, %37, %38, %39, %40, %41, %42, %43, %44, %45, %46, %47, %48, %49, %50, %51, %52, %53, %54, %55, %56, %57, %58, %59, %60, %61, %62, %63, %64, %65, %66, %67, %68, %69, %70, %71, %72, %73, %74, %75, %76, %77, %78, %79}, %80, %81, p, 1, 1, 0, 0; }\n"
   : "+f"(d[0]), "+f"(d[1]), "+f"(d[2]), "+f"(d[3]), "+f"(d[4]), "+f"(d[5]), "+f"(d[6]), "+f"(d[7]), "+f"(d[8]), "+f"(d[9]), "+f"(d[10]), "+f"(d[11]), "+f"(d[12]), "+f"(d[13]), "+f"(d[14]), "+f"(d[15]), "+f"(d[16]), "+f"(d[17]), "+f"(d[18]), "+f"(d[19]), "+f"(d[20]), "+f"(d[21]), "+f"(d[22]), "+f"(d[23]), "+f"(d[24]), "+f"(d[25]), "+f"(d[26]), "+f"(d[27]), "+f"(d[28]), "+f"(d[29]), "+f"(d[30]), "+f"(d[31]), "+f"(d[32]), "+f"(d[33]), "+f"(d[34]), "+f"(d[35]), "+f"(d[36]), "+f"(d[37]), "+f"(d[38]), "+f"(d[39]), "+f"(d[40]), "+f"(d[41]), "+f"(d[42]), "+f"(d[43]), "+f"(d[44]), "+f"(d[45]), "+f"(d[46]), "+f"(d[47]), "+f"(d[48]), "+f"(d[49]), "+f"(d[50]), "+f"(d[51]), "+f"(d[52]), "+f"(d[53]), "+f"(d[54]), "+f"(d[55]), "+f"(d[56]), "+f"(d[57]), "+f"(d[58]), "+f"(d[59]), "+f"(d[60]), "+f"(d[61]), "+f"(d[62]), "+f"(d[63]), "+f"(d[64]), "+f"(d[65]), "+f"(d[66]), "+f"(d[67]), "+f"(d[68]), "+f"(d[69]), "+f"(d[70]), "+f"(d[71]), "+f"(d[72]), "+f"(d[73]), "+f"(d[74]), "+f"(d[75]), "+f"(d[76]), "+f"(d[77]), "+f"(d[78]), "+f"(d[79]) : "l"(da), "l"(db), "r"(sd));
}
template<int N> __device__ __forceinline__ void wgmma_rs(float (&d)[N/2], uint32_t a0, uint32_t a1, uint32_t a2, uint32_t a3, uint64_t db, int sd);
template<> __device__ __forceinline__ void wgmma_rs<16>(float (&d)[8], uint32_t a0, uint32_t a1, uint32_t a2, uint32_t a3, uint64_t db, int sd){
  asm volatile("{ .reg .pred p; setp.ne.b32 p, %13, 0;\n"
   "wgmma.mma_async.sync.aligned.m64n16k16.f32.bf16.bf16 {%0, %1, %2, %3, %4, %5, %6, %7}, {%8,%9,%10,%11}, %12, p, 1, 1, 0; }\n"
   : "+f"(d[0]), "+f"(d[1]), "+f"(d[2]), "+f"(d[3]), "+f"(d[4]), "+f"(d[5]), "+f"(d[6]), "+f"(d[7]) : "r"(a0), "r"(a1), "r"(a2), "r"(a3), "l"(db), "r"(sd));
}
template<> __device__ __forceinline__ void wgmma_rs<32>(float (&d)[16], uint32_t a0, uint32_t a1, uint32_t a2, uint32_t a3, uint64_t db, int sd){
  asm volatile("{ .reg .pred p; setp.ne.b32 p, %21, 0;\n"
   "wgmma.mma_async.sync.aligned.m64n32k16.f32.bf16.bf16 {%0, %1, %2, %3, %4, %5, %6, %7, %8, %9, %10, %11, %12, %13, %14, %15}, {%16,%17,%18,%19}, %20, p, 1, 1, 0; }\n"
   : "+f"(d[0]), "+f"(d[1]), "+f"(d[2]), "+f"(d[3]), "+f"(d[4]), "+f"(d[5]), "+f"(d[6]), "+f"(d[7]), "+f"(d[8]), "+f"(d[9]), "+f"(d[10]), "+f"(d[11]), "+f"(d[12]), "+f"(d[13]), "+f"(d[14]), "+f"(d[15]) : "r"(a0), "r"(a1), "r"(a2), "r"(a3), "l"(db), "r"(sd));
}
template<> __device__ __forceinline__ void wgmma_rs<48>(float (&d)[24], uint32_t a0, uint32_t a1, uint32_t a2, uint32_t a3, uint64_t db, int sd){
  asm volatile("{ .reg .pred p; setp.ne.b32 p, %29, 0;\n"
   "wgmma.mma_async.sync.aligned.m64n48k16.f32.bf16.bf16 {%0, %1, %2, %3, %4, %5, %6, %7, %8, %9, %10, %11, %12, %13, %14, %15, %16, %17, %18, %19, %20, %21, %22, %23}, {%24,%25,%26,%27}, %28, p, 1, 1, 0; }\n"
   : "+f"(d[0]), "+f"(d[1]), "+f"(d[2]), "+f"(d[3]), "+f"(d[4]), "+f"(d[5]), "+f"(d[6]), "+f"(d[7]), "+f"(d[8]), "+f"(d[9]), "+f"(d[10]), "+f"(d[11]), "+f"(d[12]), "+f"(d[13]), "+f"(d[14]), "+f"(d[15]), "+f"(d[16]), "+f"(d[17]), "+f"(d[18]), "+f"(d[19]), "+f"(d[20]), "+f"(d[21]), "+f"(d[22]), "+f"(d[23]) : "r"(a0), "r"(a1), "r"(a2), "r"(a3), "l"(db), "r"(sd));
}
template<> __device__ __forceinline__ void wgmma_rs<64>(float (&d)[32], uint32_t a0, uint32_t a1, uint32_t a2, uint32_t a3, uint64_t db, int sd){
  asm volatile("{ .reg .pred p; setp.ne.b32 p, %37, 0;\n"
   "wgmma.mma_async.sync.aligned.m64n64k16.f32.bf16.bf16 {%0, %1, %2, %3, %4, %5, %6, %7, %8, %9, %10, %11, %12, %13, %14, %15, %16, %17, %18, %19, %20, %21, %22, %23, %24, %25, %26, %27, %28, %29, %30, %31}, {%32,%33,%34,%35}, %36, p, 1, 1, 0; }\n"
   : "+f"(d[0]), "+f"(d[1]), "+f"(d[2]), "+f"(d[3]), "+f"(d[4]), "+f"(d[5]), "+f"(d[6]), "+f"(d[7]), "+f"(d[8]), "+f"(d[9]), "+f"(d[10]), "+f"(d[11]), "+f"(d[12]), "+f"(d[13]), "+f"(d[14]), "+f"(d[15]), "+f"(d[16]), "+f"(d[17]), "+f"(d[18]), "+f"(d[19]), "+f"(d[20]), "+f"(d[21]), "+f"(d[22]), "+f"(d[23]), "+f"(d[24]), "+f"(d[25]), "+f"(d[26]), "+f"(d[27]), "+f"(d[28]), "+f"(d[29]), "+f"(d[30]), "+f"(d[31]) : "r"(a0), "r"(a1), "r"(a2), "r"(a3), "l"(db), "r"(sd));
}
template<> __device__ __forceinline__ void wgmma_rs<80>(float (&d)[40], uint32_t a0, uint32_t a1, uint32_t a2, uint32_t a3, uint64_t db, int sd){
  asm volatile("{ .reg .pred p; setp.ne.b32 p, %45, 0;\n"
   "wgmma.mma_async.sync.aligned.m64n80k16.f32.bf16.bf16 {%0, %1, %2, %3, %4, %5, %6, %7, %8, %9, %10, %11, %12, %13, %14, %15, %16, %17, %18, %19, %20, %21, %22, %23, %24, %25, %26, %27, %28, %29, %30, %31, %32, %33, %34, %35, %36, %37, %38, %39}, {%40,%41,%42,%43}, %44, p, 1, 1, 0; }\n"
   : "+f"(d[0]), "+f"(d[1]), "+f"(d[2]), "+f"(d[3]), "+f"(d[4]), "+f"(d[5]), "+f"(d[6]), "+f"(d[7]), "+f"(d[8]), "+f"(d[9]), "+f"(d[10]), "+f"(d[11]), "+f"(d[12]), "+f"(d[13]), "+f"(d[14]), "+f"(d[15]), "+f"(d[16]), "+f"(d[17]), "+f"(d[18]), "+f"(d[19]), "+f"(d[20]), "+f"(d[21]), "+f"(d[22]), "+f"(d[23]), "+f"(d[24]), "+f"(d[25]), "+f"(d[26]), "+f"(d[27]), "+f"(d[28]), "+f"(d[29]), "+f"(d[30]), "+f"(d[31]), "+f"(d[32]), "+f"(d[33]), "+f"(d[34]), "+f"(d[35]), "+f"(d[36]), "+f"(d[37]), "+f"(d[38]), "+f"(d[39]) : "r"(a0), "r"(a1), "r"(a2), "r"(a3), "l"(db), "r"(sd));
}
template<> __device__ __forceinline__ void wgmma_rs<96>(float (&d)[48], uint32_t a0, uint32_t a1, uint32_t a2, uint32_t a3, uint64_t db, int sd){
  asm volatile("{ .reg .pred p; setp.ne.b32 p, %53, 0;\n"
   "wgmma.mma_async.sync.aligned.m64n96k16.f32.bf16.bf16 {%0, %1, %2, %3, %4, %5, %6, %7, %8, %9, %10, %11, %12, %13, %14, %15, %16, %17, %18, %19, %20, %21, %22, %23, %24, %25, %26, %27, %28, %29, %30, %31, %32, %33, %34, %35, %36, %37, %38, %39, %40, %41, %42, %43, %44, %45, %46, %47}, {%48,%49,%50,%51}, %52, p, 1, 1, 0; }\n"
   : "+f"(d[0]), "+f"(d[1]), "+f"(d[2]), "+f"(d[3]), "+f"(d[4]), "+f"(d[5]), "+f"(d[6]), "+f"(d[7]), "+f"(d[8]), "+f"(d[9]), "+f"(d[10]), "+f"(d[11]), "+f"(d[12]), "+f"(d[13]), "+f"(d[14]), "+f"(d[15]), "+f"(d[16]), "+f"(d[17]), "+f"(d[18]), "+f"(d[19]), "+f"(d[20]), "+f"(d[21]), "+f"(d[22]), "+f"(d[23]), "+f"(d[24]), "+f"(d[25]), "+f"(d[26]), "+f"(d[27]), "+f"(d[28]), "+f"(d[29]), "+f"(d[30]), "+f"(d[31]), "+f"(d[32]), "+f"(d[33]), "+f"(d[34]), "+f"(d[35]), "+f"(d[36]), "+f"(d[37]), "+f"(d[38]), "+f"(d[39]), "+f"(d[40]), "+f"(d[41]), "+f"(d[42]), "+f"(d[43]), "+f"(d[44]), "+f"(d[45]), "+f"(d[46]), "+f"(d[47]) : "r"(a0), "r"(a1), "r"(a2), "r"(a3), "l"(db), "r"(sd));
}
template<> __device__ __forceinline__ void wgmma_rs<112>(float (&d)[56], uint32_t a0, uint32_t a1, uint32_t a2, uint32_t a3, uint64_t db, int sd){
  asm volatile("{ .reg .pred p; setp.ne.b32 p, %61, 0;\n"
   "wgmma.mma_async.sync.aligned.m64n112k16.f32.bf16.bf16 {%0, %1, %2, %3, %4, %5, %6, %7, %8, %9, %10, %11, %12, %13, %14, %15, %16, %17, %18, %19, %20, %21, %22, %23, %24, %25, %26, %27, %28, %29, %30, %31, %32, %33, %34, %35, %36, %37, %38, %39, %40, %41, %42, %43, %44, %45, %46, %47, %48, %49, %50, %51, %52, %53, %54, %55}, {%56,%57,%58,%59}, %60, p, 1, 1, 0; }\n"
   : "+f"(d[0]), "+f"(d[1]), "+f"(d[2]), "+f"(d[3]), "+f"(d[4]), "+f"(d[5]), "+f"(d[6]), "+f"(d[7]), "+f"(d[8]), "+f"(d[9]), "+f"(d[10]), "+f"(d[11]), "+f"(d[12]), "+f"(d[13]), "+f"(d[14]), "+f"(d[15]), "+f"(d[16]), "+f"(d[17]), "+f"(d[18]), "+f"(d[19]), "+f"(d[20]), "+f"(d[21]), "+f"(d[22]), "+f"(d[23]), "+f"(d[24]), "+f"(d[25]), "+f"(d[26]), "+f"(d[27]), "+f"(d[28]), "+f"(d[29]), "+f"(d[30]), "+f"(d[31]), "+f"(d[32]), "+f"(d[33]), "+f"(d[34]), "+f"(d[35]), "+f"(d[36]), "+f"(d[37]), "+f"(d[38]), "+f"(d[39]), "+f"(d[40]), "+f"(d[41]), "+f"(d[42]), "+f"(d[43]), "+f"(d[44]), "+f"(d[45]), "+f"(d[46]), "+f"(d[47]), "+f"(d[48]), "+f"(d[49]), "+f"(d[50]), "+f"(d[51]), "+f"(d[52]), "+f"(d[53]), "+f"(d[54]), "+f"(d[55]) : "r"(a0), "r"(a1), "r"(a2), "r"(a3), "l"(db), "r"(sd));
}
template<> __device__ __forceinline__ void wgmma_rs<128>(float (&d)[64], uint32_t a0, uint32_t a1, uint32_t a2, uint32_t a3, uint64_t db, int sd){
  asm volatile("{ .reg .pred p; setp.ne.b32 p, %69, 0;\n"
   "wgmma.mma_async.sync.aligned.m64n128k16.f32.bf16.bf16 {%0, %1, %2, %3, %4, %5, %6, %7, %8, %9, %10, %11, %12, %13, %14, %15, %16, %17, %18, %19, %20, %21, %22, %23, %24, %25, %26, %27, %28, %29, %30, %31, %32, %33, %34, %35, %36, %37, %38, %39, %40, %41, %42, %43, %44, %45, %46, %47, %48, %49, %50, %51, %52, %53, %54, %55, %56, %57, %58, %59, %60, %61, %62, %63}, {%64,%65,%66,%67}, %68, p, 1, 1, 0; }\n"
   : "+f"(d[0]), "+f"(d[1]), "+f"(d[2]), "+f"(d[3]), "+f"(d[4]), "+f"(d[5]), "+f"(d[6]), "+f"(d[7]), "+f"(d[8]), "+f"(d[9]), "+f"(d[10]), "+f"(d[11]), "+f"(d[12]), "+f"(d[13]), "+f"(d[14]), "+f"(d[15]), "+f"(d[16]), "+f"(d[17]), "+f"(d[18]), "+f"(d[19]), "+f"(d[20]), "+f"(d[21]), "+f"(d[22]), "+f"(d[23]), "+f"(d[24]), "+f"(d[25]), "+f"(d[26]), "+f"(d[27]), "+f"(d[28]), "+f"(d[29]), "+f"(d[30]), "+f"(d[31]), "+f"(d[32]), "+f"(d[33]), "+f"(d[34]), "+f"(d[35]), "+f"(d[36]), "+f"(d[37]), "+f"(d[38]), "+f"(d[39]), "+f"(d[40]), "+f"(d[41]), "+f"(d[42]), "+f"(d[43]), "+f"(d[44]), "+f"(d[45]), "+f"(d[46]), "+f"(d[47]), "+f"(d[48]), "+f"(d[49]), "+f"(d[50]), "+f"(d[51]), "+f"(d[52]), "+f"(d[53]), "+f"(d[54]), "+f"(d[55]), "+f"(d[56]), "+f"(d[57]), "+f"(d[58]), "+f"(d[59]), "+f"(d[60]), "+f"(d[61]), "+f"(d[62]), "+f"(d[63]) : "r"(a0), "r"(a1), "r"(a2), "r"(a3), "l"(db), "r"(sd));
}

#define BAR(i) (bars + 8u * (uint32_t)(i))

template <int G> __device__ __forceinline__ void conv_frags(uint32_t (&a)[12], uint32_t abase) {
#pragma unroll
  for (int i = 0; i < 12; i++) a[i] = lds32(abase + (G * 4 + i / 3) * 128 + (i % 3) * 4);
}
__device__ __forceinline__ void kv_prefetch(const __nv_bfloat16* pf, int task) { prefetch_if(pf + 64 * (task & 31) * DM + 64 * (task >> 5), task < 320); }
__device__ __forceinline__ void kv_load(const Params& P, Scratch* S, int task, int tid, uint32_t (&k_)[19], uint32_t (&v_)[16], uint4& sk) {
  const int row = 64 * (task & 31) + 16 * (tid >> 5), ch = 64 * (task >> 5) + 2 * (tid & 31);
  const uint32_t* kp = (const uint32_t*)(P.k + (size_t)row * DM + ch);
  const uint32_t* vp = (const uint32_t*)(P.v + (size_t)row * DM + ch);
  const uint32_t* hp = row > 0 ? kp - 3 * (DM / 2) : S->zero;
  const int hs = row > 0 ? DM / 2 : 0;
  asm volatile("ld.global.nc.v4.u32 {%0,%1,%2,%3},[%4];" : "=r"(sk.x), "=r"(sk.y), "=r"(sk.z), "=r"(sk.w) : "l"(P.shk + ch * 4));
#pragma unroll
  for (int i = 0; i < 3; i++) k_[i] = ldg1(hp + i * hs);
#pragma unroll
  for (int i = 0; i < 16; i++) { k_[i + 3] = ldg1(kp + i * (DM / 2)); v_[i] = ldg1(vp + i * (DM / 2)); }
}
template <int SH> __device__ __forceinline__ void xb_prefetch(const Head& H, int id, int tid, int c0) {
  const int ri = tid >> SH, rr = 11 * id + ri - 16;
  const __nv_bfloat16* p = ri < 16 ? H.x + (size_t)(16 * min(id, 127) + ri) * DM : (rr < DM ? H.b0 : H.b1 - DM * DM) + (size_t)rr * DM;
  prefetch_if(p + c0 + 64 * (tid & ((1 << SH) - 1)), ri < 16 || (ri < 27 && rr < 2 * DM));
}
__device__ __forceinline__ uint4 ldg4(const void* p) { uint4 v; asm volatile("ld.global.nc.v4.u32 {%0,%1,%2,%3},[%4];" : "=r"(v.x), "=r"(v.y), "=r"(v.z), "=r"(v.w) : "l"(p)); return v; }
__device__ __forceinline__ uint4 lds4(uint32_t a) { uint4 v; asm volatile("ld.shared.v4.u32 {%0,%1,%2,%3},[%4];" : "=r"(v.x), "=r"(v.y), "=r"(v.z), "=r"(v.w) : "r"(a) : "memory"); return v; }
__device__ __forceinline__ void discretise(const Head& H, const Params& P, uint32_t sb, Role R, int lane, uint32_t e1) {
  const uint32_t dn = __ldg((const unsigned short*)P.ssmd + min(conv_ch(R.c, (lane + 7) & 7), DM - 1));
  const int c = 32 * min(R.cb(), 9) + lane;
  const uint32_t lr2 = ldg1(P.lre + 2 * c), li2 = ldg1(P.lim + 2 * c), ld2 = ldg1(P.ldt + 2 * c);
  asm volatile("st.shared.u32 [%0],%1;" ::"r"(sb + MISC_OFF + 4 * (lane & 7)), "r"((lane & 7) ? dn : e1) : "memory");
#pragma unroll 1
  for (int i = 0; i < 2; i++) {
    const float lr = bf_hi(lr2 << (16 - 16 * i)), li = bf_hi(li2 << (16 - 16 * i));
    const float2 lb = lam_bar(lr, li, bf_hi(ld2 << (16 - 16 * i)));
    const float nx = lb.x - 1.f, ny = lb.y, inv = 2.f * frcp(lr * lr + li * li), cx = (nx * lr + ny * li) * inv, cy = (ny * lr - nx * li) * inv;
    const bool sw = !H.swap;
    asm volatile("st.shared.v4.f32 [%0],{%1,%2,%3,%4};" ::"r"(sb + LAM_OFF + 32 * lane + 16 * i), "f"(lb.x), "f"(sw ? -lb.y : lb.y), "f"(sw ? -cy : cx), "f"(sw ? cx : -cy) : "memory");
  }
  __syncwarp();
}
__device__ __forceinline__ void aux_prep(const Head& H, const Params& P, uint32_t sb, Role R, int tid, long long t_start) {
  Scratch* const S = H.s;
  const uint32_t bars = sb + BAR_OFF;
  tid = opaque(tid);
  const int w = tid >> 5, lane = tid & 31, tb = R.tb(), cb = R.cb();
  uint32_t k_[19], v_[16];
  uint4 sk;
  int task = R.b() < R.nprep() ? R.b() : 320;
  delay(KVDLY);
  PROFC(tid == 0, 345);
  kv_load(P, S, min(task, 319), tid, k_, v_, sk);
  const __nv_bfloat16* pf = (tid < 64 ? P.k : P.v) + (tid & 63) * DM;
  const int j = lane >> 3, sm = min(R.sm(), 9), trow = 160 * tb + 4 * sm + (tb < 12 ? 40 : 32) * w + j;
  const uint32_t so = sb + (2 * w + (j & 1) + 8 * (j >> 1)) * 128 + 16 * (lane & 7), xo = so + sm * 2048, wo = so + (tb & 1) * 8192 + (tb & 6) * 1024;
  const __nv_bfloat16* xp = H.x + (size_t)min(trow, SEQ - 1) * DM + 384 + 8 * (lane & 7);
  const __nv_bfloat16* bp = (j < 2 ? H.b0 : H.b1) + (size_t)(64 * cb + 32 * (tb & 1) + 4 * (tb & 6) + 2 * w + (j & 1)) * DM + 384 + 8 * (lane & 7);
  float s = 0.f, s2 = 0.f, sr = 0.f;
#define STAT(m, n) { const uint32_t xw[4] = {m.x, m.y, m.z, m.w}, bw[4] = {n.x, n.y, n.z, n.w}; \
  _Pragma("unroll") for (int i = 0; i < 4; i++) { const float u = bf_lo(xw[i]), v = bf_hi(xw[i]); s += u + v; s2 = fmaf(u, u, fmaf(v, v, s2)); sr += bf_lo(bw[i]) + bf_hi(bw[i]); } }
#define STATS(K0, K1) _Pragma("unroll 1") for (int kb = K0; kb < K1; kb++) { \
    mbar_wait(BAR(B_F1 + kb)); \
    const uint4 a = lds4(xo + ((uint32_t)(XTAB0 >> (6 * kb)) & 63) * 4096), c = lds4(wo + ((uint32_t)(WTAB0 >> (6 * kb)) & 63) * 4096); \
    STAT(a, c) \
    asm volatile("" : "+f"(s), "+f"(s2), "+f"(sr)); \
    if (XPFAT >= K0 && XPFAT < K1) prefetch_if(((lane & 4) ? bp : xp) + 64 * (lane & 3), kb == XPFAT); \
    kv_prefetch(pf, kb == KPFAT ? task + R.nprep() : kb == KPFAT2 ? task + 2 * R.nprep() : 320); \
  } \
  __syncwarp(); mbar_arrive_if(BAR(B_AX + K0 / 3), lane == 0);
  STATS(0, 3)
  PROFC(tid == 0, 349);
    {
      uint4 m[4], n[4];
#pragma unroll
      for (int i = 0; i < 4; i++) { m[i] = ldg4(xp + 64 * i); n[i] = ldg4(bp + 64 * i); }
      STATS(3, 6)
      PROFC(tid == 0, 346);
      mbar_wait(BAR(B_LM));
      const uint32_t tag = lds32(sb + MISC_OFF) & 1;
#pragma unroll
      for (int i = 0; i < 4; i++) { const uint4 a = m[i], c = n[i]; STAT(a, c) }
      PROFC(tid == 0 && s2 != 1.2345f, 347);
#pragma unroll
      for (int o = 1; o <= 4; o <<= 1) { s += __shfl_xor_sync(0xffffffff, s, o); s2 += __shfl_xor_sync(0xffffffff, s2, o); sr += __shfl_xor_sync(0xffffffff, sr, o); }
      const float mn = s * (1.f / DM), rs = frcp(bf_rn(fsqrt(bf_rn(bf_rn(fmaxf(s2 * (1.f / DM) - mn * mn, 0.f)) + 1e-5f))));
      asm volatile("{ .reg .pred p; setp.ne.u32 p, %2, 0; @p st.relaxed.gpu.global.u32 [%0],%1; }"
                   ::"l"((uint32_t*)(S->RS + (8 * cb + 4 * (tb & 1) + (tb >> 1)) * 16 + 4 * w + (j & 1)) + (lane & 4) + (j >> 1)), "r"(tagf(sr, tag)),
                   "r"((uint32_t)(tb < 8 && (lane & 3) == 0)) : "memory");
      asm volatile("{ .reg .pred p; setp.ne.u32 p, %3, 0; @p st.relaxed.gpu.global.v2.u32 [%0],{%1,%2}; }"
                   ::"l"(S->S + trow), "r"(tagf(rs, tag)), "r"(tagf(-bf_rn(mn) * rs, tag)), "r"((uint32_t)(R.sm() < 10 && (lane & 7) == 0)) : "memory");
      PROFC(tid == 0, 3);
    }
#pragma unroll 1
  for (int r = 0; task < 320; r++) {
    {
      const uint32_t T0 = __byte_perm(sk.x, sk.z, 0x5410), T1 = __byte_perm(sk.x, sk.z, 0x7632);
      const uint32_t T2 = __byte_perm(sk.y, sk.w, 0x5410), T3 = __byte_perm(sk.y, sk.w, 0x7632);
      PROFC(tid == 0 && v_[15] != 0x12345, 336 + r);
      uint32_t o[16];
#pragma unroll
      for (int t = 0; t < 16; t += 2) {
        const uint32_t a = hmul2(hfma2(k_[t + 3], T0, hfma2(k_[t + 2], T1, hfma2(k_[t + 1], T2, hmul2(k_[t], T3)))), v_[t]);
        const uint32_t c = hmul2(hfma2(k_[t + 4], T0, hfma2(k_[t + 3], T1, hfma2(k_[t + 2], T2, hmul2(k_[t + 1], T3)))), v_[t + 1]);
        const int wd = ((7 - t / 2) >> 1) + 4 * ((7 - t / 2) & 1);
        o[wd] = __byte_perm(c, a, 0x5410); o[8 + wd] = __byte_perm(c, a, 0x7632);
        asm volatile("" : "+r"(o[wd]), "+r"(o[8 + wd]));
        if (t == PFAT) kv_prefetch(pf, task + (1 + PFD) * R.nprep());
      }
      PROFC(tid == 0, 330 + 2 * r);
      const int ph = task & 1;
      task += R.nprep();
      if (ORD == 0 && task < 320) kv_load(P, S, task, tid, k_, v_, sk);
      mbar_wait(BAR(B_E1 + 3)); mbar_wait(BAR(B_AX + 1));
#pragma unroll
      for (int i = 0; i < 4; i++) {
        const int row = 2 * lane + (i >> 1);
        asm volatile("st.shared.v4.u32 [%0],{%1,%2,%3,%4};" ::"r"(sb + KS_OFF + r * 8192 + row * 128 + (((2 * w + ((i & 1) ^ ph)) ^ (row & 7)) << 4)),
                     "r"(o[4 * i]), "r"(o[4 * i + 1]), "r"(o[4 * i + 2]), "r"(o[4 * i + 3]) : "memory");
      }
      __syncwarp();
      mbar_arrive_if(BAR(B_PS + r), lane == 0);
      PROFC(tid == 0, 331 + 2 * r);
      if (ORD == 1 && task < 320) kv_load(P, S, task, tid, k_, v_, sk);
    }
  }
#undef STAT
#undef STATS
  PROFC(tid == 0, 40);
}
#define SPLIT(G) asm volatile("{ .reg .pred p; .reg .u32 r; L: mov.u32 r, %%clock; setp.eq.u32 p, r, %0; @p bra.uni L; }" ::"n"(G) : "memory")
template <bool AUX>
__device__ __forceinline__ void conv_loop(uint32_t sb, uint32_t rc, int wg, int tid, long long t_start) {
  sb = opaque(sb); rc = opaque(rc);
  const uint32_t bars = sb + BAR_OFF;
  int slot = AUX ? 0 : wg + 1;
  mbar_wait(BAR(B_LM));
#pragma unroll 1
  while (slot < (int)((rc >> 10) & 7)) {
    tid = opaque(tid);
    const int w = tid >> 5, lane = tid & 31, g = lane >> 2, q = lane & 3;
    const uint32_t Dn = lds32(sb + MISC_OFF + 4 + 4 * slot);
    const uint32_t d0 = (g == 1 && q == 3 - w) ? Dn : 0, d1 = (g == 0 && q == 3 - w) ? Dn : 0;
    const uint32_t cb_ = conv_buf(sb, slot), c0 = cb_ + KC_OFS;
    const uint32_t abase = c0 + 2 * (2 * (g & 1) + 4 * w + 16 * (g >> 1) + 4 * q);
    const uint64_t bd = make_desc(cb_ + KV_PAD, 16, 256, 3);
    const bool hi = lane & 16, s1 = lane & 8;
    const int qo = hi ? (q + 1) & 3 : q;
    const int srcA = hi ? (lane & 12) | ((q + 1) & 3) : (lane & 12) | 16 | ((q + 3) & 3);
    const bool h3 = hi && q == 3, wrap = s1 && qo == 3, back = wrap && hi;
    const bool chi = wrap ? !hi : hi;
    const int cq = s1 ? (qo + 1) & 3 : qo;
    const int srcB = (lane & 4) | (s1 ? 0 : 8) | (chi ? 16 | ((cq + 3) & 3) : cq);
    const uint32_t gp = c0 + ((32 * (2 * w + (g & 1)) + (chi ? 256 : 0)) ^ (chi ? 64 : 0) ^ ((conv_ch(rc, slot) & 8) << 2)) + 4 * (2 * cq + (s1 ? 0 : 1));
    uint32_t a[12], f[16], o[8];
    float S[4], T[4], U[2], keep[2], pv[2] = {0.f, 0.f}, pr[4] = {0.f, 0.f, 0.f, 0.f};
    float e0[64], e1[56], e2[48], e3[40], e4[32], e5[24], e6[16], e7[8];
#define UNR _Pragma("unroll")
#define PERM() UNR for (int i = 0; i < 4; i++) { f[4 * i] = __byte_perm(a[3 * i], a[3 * i + 1], 0x5432); f[4 * i + 1] = a[3 * i + 1]; \
                                                 f[4 * i + 2] = __byte_perm(a[3 * i + 1], a[3 * i + 2], 0x5432); f[4 * i + 3] = a[3 * i + 2]; }
#define MMA(N, E) UNR for (int i = 0; i < 4; i++) wgmma_rs<N>(E, f[4 * i], f[4 * i + 1], f[4 * i + 2], f[4 * i + 3], bd - 8 * i, 1); wg_commit();
#define L1(c) UNR for (int i = 0; i < 4; i++) { const float ev = c[i], od = c[4 + i]; S[i] = hi ? (h3 ? ev : od) : ev; \
                                                T[i] = __shfl_sync(0xffffffff, hi ? (h3 ? pr[i] : ev) : od, srcA); pr[i] = od; }
#define L1E() UNR for (int i = 0; i < 4; i++) S[i] += T[i];
#define L2() UNR for (int h = 0; h < 2; h++) { keep[h] = back ? pv[h] : S[2 * h + 1]; pv[h] = S[2 * h + 1]; U[h] = __shfl_sync(0xffffffff, S[2 * h], srcB); }
#define L2E(j) o[j] = pack_bf(keep[0] + U[0], keep[1] + U[1]);
#define GRP(G, N, P, E) UNR for (int i = 0; i < N / 2; i++) asm volatile("mov.b32 %0,%1;" : "=f"(E[i]) : "f"(P[i + 8])); \
    wg_fence(); if (G < 7) conv_frags<(G + 1) & 7>(a, abase); if (G >= 2) { L2() } L1(P) MMA(N, E) SPLIT(G); \
    if (G < 7) { PERM() } if (G >= 2) { L2E((G + 6) & 7) } L1E() wg_wait<0>(); fence_regs(E);
    PROFC(tid == 0, 300 + 4 * slot);
    mbar_wait(BAR(B_KF + slot));
    if (tid == 0) PROF(361 + slot);
    PROFC(tid == 0, 301 + 4 * slot);
    conv_frags<0>(a, abase);
    wg_fence();
    wgmma_rs<128>(e0, d0 << 16, d0, d1 << 16, d1, bd, 0);
    PERM() conv_frags<1>(a, abase); wg_fence(); MMA(128, e0) SPLIT(0); PERM() wg_wait<0>(); fence_regs(e0);
    GRP(1, 112, e0, e1) GRP(2, 96, e1, e2) GRP(3, 80, e2, e3) GRP(4, 64, e3, e4) GRP(5, 48, e4, e5) GRP(6, 32, e5, e6) GRP(7, 16, e6, e7)
    PROFC(tid == 0, 302 + 4 * slot);
    L2() L1(e7) L2E(6) L1E() L2() L2E(7)
    bar_sync(wg + 1, 128);
#pragma unroll
    for (int jj = 0; jj < 8; jj++) asm volatile("st.shared.u32 [%0],%1;" ::"r"(gp + jj * 512), "r"(o[jj]) : "memory");
#undef PERM
#undef MMA
#undef L1
#undef L1E
#undef L2
#undef L2E
#undef GRP
    PROFC(tid == 0, 303 + 4 * slot);
    __syncwarp();
    if (lane == 0) mbar_arrive(BAR(B_GS + slot));
    if (!AUX) break;
    slot = slot ? slot + 1 : 3;
  }
}

#define IDX(J, c, h) (8 * (J) + 4 * ((c) >> 1) + 2 * (h) + ((c) & 1))
__device__ __forceinline__ uint2 lds2(uint32_t a) { uint2 v; asm volatile("ld.shared.v2.u32 {%0,%1},[%2];" : "=r"(v.x), "=r"(v.y) : "r"(a) : "memory"); return v; }
__device__ __forceinline__ void resid_load(float (&r)[40], uint32_t sb, int wg, int tid, const uint4& s) {
  const uint32_t dp = sb + XR_OFF + 8 * (tid & 3), xp = dp + (64 * wg + 16 * (tid >> 5) + ((tid & 31) >> 2)) * 160;
#pragma unroll
  for (int J = 0; J < 5; J++) {
    const uint2 u = lds2(xp + 32 * J), v = lds2(xp + 32 * J + 1280), d = lds2(dp + 20480 + 32 * J);
    r[8 * J] = __uint_as_float(u.x); r[8 * J + 1] = __uint_as_float(u.y); r[8 * J + 2] = __uint_as_float(v.x); r[8 * J + 3] = __uint_as_float(v.y);
    r[8 * J + 4] = __uint_as_float(d.x); r[8 * J + 5] = __uint_as_float(d.y);
  }
  r[30] = untag(s.x); r[31] = untag(s.y); r[38] = untag(s.z); r[39] = untag(s.w);
}
__device__ __forceinline__ void resid_init(float (&r)[40]) {
  const float s[4] = {r[30], r[31], r[38], r[39]};
#pragma unroll
  for (int J = 0; J < 5; J++) {
    uint32_t w[6];
#pragma unroll
    for (int i = 0; i < 6; i++) w[i] = __float_as_uint(r[8 * J + i]);
#pragma unroll
    for (int i = 0; i < 4; i++) {
      const int h = i >> 1, c = 2 * (i & 1);
      const float rs = s[2 * h], nm = s[2 * h + 1], x0 = bf_lo(w[i]), x1 = bf_hi(w[i]);
      const uint32_t t = hmul2(pack_bf(fmaf(x0, rs, nm), fmaf(x1, rs, nm)), w[4 + (i & 1)]);
      r[IDX(J, c, h)] = x0 + bf_lo(t); r[IDX(J, c + 1, h)] = x1 + bf_hi(t);
    }
  }
}

struct Keep { float2 lam, mu, mu2; uint2 rs; };
__device__ __forceinline__ float flip(float v, uint32_t m) { return __uint_as_float(__float_as_uint(v) ^ m); }
__device__ __forceinline__ void g1_phase(const int LY, const Head& H, uint32_t sb, int wg, int tid, Role R, float (&xr)[40], Keep& K, long long t_start) {
  Scratch* const S = H.s;
  tid = opaque(tid); sb = opaque(sb); R.v = opaque(R.v);
  const uint32_t bars = sb + BAR_OFF;
  const int cb = R.cb(), tb = R.tb();
  const int w = tid >> 5, lane = tid & 31, g = lane >> 2, q = lane & 3;
  const bool full = tb < 12;
  uint2* Eb = S->E + ((LY * 130 + cb) * 8 + 4 * wg + w) * 16 + g;
  float a[80];
#pragma unroll
  for (int i = 0; i < 80; i++) a[i] = 0.f;
  uint32_t rel = mapa(BAR(B_E1), lane ? R.wpart() : R.ubase() + (w & (R.ugs() - 1)));
  const bool rels = lane == 0 || (tid == 1 && wg != R.wlo());
  {
    uint64_t tw = LY ? WTAB1 : WTAB0, tx = LY ? XTAB1 : XTAB0;
    uint32_t bf = BAR(B_F1);
    if (tid == 0 && wg == 0 && !LY) PROF(351);
    fence_regs(a);
#pragma unroll 1
    for (int kb = 0; kb < 10; kb++) {
      mbar_wait(bf, LY);
      if (tid == 0 && wg == 0 && kb == 0) PROF(LY ? 20 : 4);
      const uint64_t da = make_desc(sb + ((uint32_t)tw & 63) * 4096 + wg * 8192, 16, 1024, 1);
      const uint64_t db = make_desc(sb + ((uint32_t)tx & 63) * 4096, 16, 1024, 1);
      wg_fence();
#pragma unroll
      for (int kk = 0; kk < 4; kk++) wgmma_ss160(a, da + 2 * kk, db + 2 * kk, 1);
      wg_commit();
      wg_wait<1>();
      if (kb > 0) { if (rels) mbar_arrive_at(rel); rel += 8; }
      bf += 8; tw >>= 6; tx >>= 6;
    }
  }
  if (tid == 0 && wg == 0) PROF(LY ? 19 : 2);
  const uint32_t lamp = sb + LAM_OFF + 16 * (32 * wg + 8 * w + g), ssm = sb + SSM_OFF + q * 160;
  if (!LY) {
    const uint2* rp = S->RS + (8 * cb + 4 * wg + w) * 16 + 2 * g - (g & 1);
    K.rs = ld_rlx2(rp);
    mbar_wait(BAR(B_LM));
    const uint32_t tg = lds32(sb + MISC_OFF) & 1;
    asm volatile("ld.shared.v2.f32 {%0,%1},[%2];" : "=f"(K.lam.x), "=f"(K.lam.y) : "r"(lamp));
    if (q >= 2) st_rlx2(Eb + tb * 1280 + (~q & 1) * 130 * 128, tg ^ 1, tg ^ 1);
    const float2 l2 = cmul(K.lam, K.lam), l4 = cmul(l2, l2), l8 = cmul(l4, l4), l16 = cmul(l8, l8), l32 = cmul(l16, l16);
    K.mu = full ? cmul(l32, l8) : l32; K.mu2 = cmul(K.mu, K.mu);
#pragma unroll 1
    for (int it = 0; it < SPIN && __any_sync(0xffffffff, untagged(K.rs, tg)); it++) K.rs = ld_rlx2(rp);
    __syncwarp();
  }
  float2 lam = K.lam;
  const float2 mu = K.mu, mu2 = K.mu2;
  const uint32_t tag = K.rs.x & 1;
  const float rs0 = untag(K.rs.x), rs1 = untag(K.rs.y);
  mbar_wait(BAR(B_ST), LY);
  if (tid == 0 && wg == 0 && !LY) PROF(39);
  wg_wait<0>(); fence_regs(a);
  if (rels) mbar_arrive_at(rel);
  if (tid == 0 && wg == 0) PROF(LY ? 21 : 5);
  float2 p = make_float2(0.f, 0.f);
#pragma unroll
  for (int j = 0; j < 10; j++) {
    if (j < 8 || full) {
      const uint4 sv = lds4(ssm + 16 * j), nv = lds4(ssm + 640 + 16 * j);
#pragma unroll
      for (int e = 0; e < 4; e++) {
        const int o = 8 * j + e + (e & 2);
        const float r = __uint_as_float(e == 0 ? sv.x : e == 1 ? sv.y : e == 2 ? sv.z : sv.w);
        const float nm = __uint_as_float(e == 0 ? nv.x : e == 1 ? nv.y : e == 2 ? nv.z : nv.w);
        a[o] = fmaf(a[o], r, nm * rs0); a[o + 2] = fmaf(a[o + 2], r, nm * rs1);
        p = cfma(lam, p, make_float2(a[o], a[o + 2]));
      }
    }
  }
  {
    float2 t = make_float2(__shfl_up_sync(0xffffffff, p.x, 1, 4), __shfl_up_sync(0xffffffff, p.y, 1, 4));
    if (q >= 1) p = cfma(mu, t, p);
    t = make_float2(__shfl_up_sync(0xffffffff, p.x, 2, 4), __shfl_up_sync(0xffffffff, p.y, 2, 4));
    if (q >= 2) p = cfma(mu2, t, p);
  }
  if (q == 3 && full) st_rlx2(Eb + tb * 1280, tagf(p.x, tag), tagf(p.y, tag));
  if (tid == 0 && wg == 1) PROF(96 + 64 * LY);
  uint2 ev[3];
#pragma unroll
  for (int i = 0; i < 3; i++) { const int j = tb - 1 - q - 4 * i; ev[i] = j >= 0 ? ld_rlx2(Eb + j * 1280) : make_uint2(tag, tag); }
  float2 x = make_float2(__shfl_up_sync(0xffffffff, p.x, 1, 4), __shfl_up_sync(0xffffffff, p.y, 1, 4));
  if (q == 0) x = make_float2(0.f, 0.f);
  float c0, c1;
  asm volatile("ld.shared.v2.f32 {%0,%1},[%2+8];" : "=f"(c0), "=f"(c1) : "r"(lamp));
  const float c2 = -flip(c1, H.swap), c3 = flip(c0, H.swap);
#pragma unroll
  for (int i = 0; i < 40; i++) {
    const int o = 4 * (i >> 1) + (i & 1);
    const float u = a[o], v = a[o + 2];
    a[o] = fmaf(c0, u, c1 * v); a[o + 2] = fmaf(c2, u, c3 * v);
  }
  fence_regs(a);
  if (LY == 0 && R.b() < 128) {
    const int t0 = 16 * g + 8 * wg + 2 * w;
    if (tid == 0 && wg == 1) PROF(366);
    mbar_wait(BAR(B_XR));
    if (tid == 0 && wg == 1) PROF(367);
    uint4 s = lds4(sb + XR_OFF + 20480 + 256 + 8 * t0);
    if (__any_sync(0xffffffff, untagged(s, tag))) {
#pragma unroll 1
      for (int it = 0; it < SPIN; it++) { s = ld_rlx4(S->S + 128 * (R.b() >> 3) + t0); if (!__any_sync(0xffffffff, untagged(s, tag))) break; }
    }
    resid_load(xr, sb, wg, tid, s);
  }
  float2 mq, om4, fq;
  {
    asm volatile("" : "+f"(lam.x), "+f"(lam.y));
    const float2 one = make_float2(1.f, 0.f), m2 = cmul(lam, lam), m4 = cmul(m2, m2), l8 = cmul(m4, m4), l16 = cmul(l8, l8);
    const float2 l80 = full ? mu2 : cmul(mu2, l16), om = cmul(l80, l80), om2 = cmul(om, om);
    mq = cmul((q & 1) ? mu : one, (q & 2) ? mu2 : one);
    om4 = cmul(om2, om2); fq = cmul((q & 1) ? om : one, (q & 2) ? om2 : one);
  }
  mbar_wait(BAR(B_E1 + 9), LY);
  if (tid == 0 && wg == 1) PROF(368 + LY);
#pragma unroll 1
  for (int it = 0; it < SPIN; it++) {
    const bool m0 = untagged(ev[0], tag), m1 = untagged(ev[1], tag), m2 = untagged(ev[2], tag);
    if (!__any_sync(0xffffffff, m0 || m1 || m2)) break;
    if (m0) ev[0] = ld_rlx2(Eb + (tb - 1 - q) * 1280);
    if (m1) ev[1] = ld_rlx2(Eb + (tb - 5 - q) * 1280);
    if (m2) ev[2] = ld_rlx2(Eb + (tb - 9 - q) * 1280);
  }
  if (tid == 0 && wg == 1) PROF(97 + 64 * LY);
  float2 c = make_float2(untag(ev[2].x), untag(ev[2].y));
#pragma unroll
  for (int i = 1; i >= 0; i--) c = cfma(om4, c, make_float2(untag(ev[i].x), untag(ev[i].y)));
  c = cmul(fq, c);
#pragma unroll
  for (int s = 1; s <= 2; s <<= 1) { c.x += __shfl_xor_sync(0xffffffff, c.x, s); c.y += __shfl_xor_sync(0xffffffff, c.y, s); }
  c = cfma(mq, c, x);
  float2 z = make_float2(fmaf(c0, c.x, c1 * c.y), fmaf(c2, c.x, c3 * c.y));
  if (tid == 0 && wg == 0) PROF(LY ? 22 : 6);
  const float2 lc = make_float2(lam.x, flip(lam.y, H.swap));
  const uint32_t hq = sb + (lane >> 4) * 1024 + (lane & 7) * 128 + (((4 * wg + w) ^ (lane & 7)) << 4);
  const uint32_t hp = hq + R_OFF + (lane & 8) * 2048, hp4 = hq + (LY ? R4_OFF1 : R4_OFF0) + (lane & 8) * 512;
#pragma unroll
  for (int j = 0; j < 20; j += 2) {
    if (j < 16 || full) {
      uint32_t o[4];
#pragma unroll
      for (int i = 0; i < 2; i++) {
        const float2 z0 = cfma(lc, z, make_float2(a[4 * (j + i)], a[4 * (j + i) + 2]));
        z = cfma(lc, z0, make_float2(a[4 * (j + i) + 1], a[4 * (j + i) + 3]));
        o[2 * i] = pack_bf(z0.x, z.x); o[2 * i + 1] = pack_bf(z0.y, z.y);
      }
      asm volatile("stmatrix.sync.aligned.m8n8.x4.trans.shared.b16 [%0], {%1,%2,%3,%4};" ::"r"(j < 16 ? hp + j * 1024 : hp4 + (j - 16) * 1024), "r"(o[0]), "r"(o[1]), "r"(o[2]), "r"(o[3]) : "memory");
      if (j & 2) { __syncwarp(); if (lane == 0) mbar_arrive(BAR(B_SH + j / 4)); }
    }
  }
  if (tid == 0 && wg == 0) PROF(LY ? 23 : 7);
  if (lane == 0) PROF(390 + 4 * wg + w);
}

__device__ __forceinline__ void gate_load(float (&G)[40], uint32_t sb, int LY, int wg, int tid, int tb2) {
  const uint32_t bars = sb + BAR_OFF;
  const int lane = tid & 31, w = tid >> 5;
  mbar_wait(BAR(B_GF), LY);
  const int g = lane >> 2, q = lane & 3;
  const uint32_t gb = sb + (LY ? G_OFF1 : G_OFF0) + wg * 10240 + 512 * q + ((32 * w + 4 * g) ^ (64 * ((tb2 ^ q) & 1)) ^ (16 * (q & 2)));
#pragma unroll
  for (int i = 0; i < 20; i++) { const uint32_t v = lds32((gb ^ (16 * (i & 3))) + 128 * (i & 3) + 2048 * (i >> 2)); G[2 * i] = bf_lo(v); G[2 * i + 1] = bf_hi(v); }
  fence_regs(G);
}
__device__ __forceinline__ void g2_phase(const int LY, const Params& P, Scratch* S, uint32_t sb, int wg, int tid, Role R, float (&xr)[40], long long t_start) {
  sb = opaque(sb);
  const uint32_t bars = sb + BAR_OFF;
  if (LY) {
    const int td = opaque(tid), b = (opaque(R.v) >> 8) & 255;
    const uint32_t tag = lds32(sb + MISC_OFF) & 1;
    const uint2* sp = S->S + 2 * SEQ + 128 * (b >> 3) + 4 * (td & 28) + 8 * wg + 2 * (td >> 5);
    if (!(R.cb() & 1)) mbar_wait(BAR(B_HD), 1);
    uint2 dl[5];
#pragma unroll
    for (int J = 0; J < 5; J++) dl[J] = __ldg((const uint2*)(P.dskip + 80 * (b & 7) + 4 * (td & 3) + 16 * J));
    uint4 sv;
#pragma unroll 1
    for (int it = 0; it < SPIN; it++) { sv = ld_rlx4(sp); if (!__any_sync(0xffffffff, untagged(sv, tag))) break; }
#pragma unroll
    for (int h = 0; h < 2; h++)
#pragma unroll
      for (int J = 0; J < 5; J++)
#pragma unroll
        for (int c = 0; c < 4; c++) {
          const float x2 = xr[IDX(J, c, h)];
          const uint32_t dw = (c & 2) ? dl[J].y : dl[J].x;
          xr[IDX(J, c, h)] = fmaf(fmaf(x2, untag(h ? sv.z : sv.x), untag(h ? sv.w : sv.y)), (c & 1) ? bf_hi(dw) : bf_lo(dw), x2);
        }
    fence_regs(xr);
  }
  float acc[40];
#pragma unroll
  for (int i = 0; i < 40; i++) acc[i] = RIAT == 1 ? 0.f : xr[i];
  fence_regs(acc);
#define G2_STEP(st, cs, hf) { \
    const uint64_t da = make_desc(sb + H_OFF + (st) * 32768 + (hf) * 16384 + wg * 8192, 16, 1024, 1), db = make_desc(sb + (cs) * 20480 + (hf) * 10240, 16, 1024, 1); \
    wg_fence(); \
    _Pragma("unroll") for (int kk = 0; kk < 4; kk++) wgmma_ss80(acc, da + 2 * kk, db + 2 * kk, 1); \
    wg_commit(); }
  mbar_wait(BAR(B_F2), LY);
  if (tid == 0 && wg == 0) PROF(LY ? 25 : 10);
  G2_STEP(0, 0, 0)
  mbar_wait(BAR(B_F3), LY);
  G2_STEP(0, 0, 1)
  tid = opaque(tid); R.v = opaque(R.v);
  const uint32_t tag = lds32(sb + MISC_OFF) & 1;
  const int b = R.b(), tb2 = b >> 3, db_ = b & 7;
  const int w = tid >> 5, lane = tid & 31, g = lane >> 2, q = lane & 3;
  const int t0 = 128 * tb2 + 16 * g + 8 * wg + 2 * w;
  const int d0 = 80 * db_ + 4 * q, mrow = 64 * wg + 16 * w + g;
#define GATE(J, c, h) G[8 * (J) + 2 * (c) + (h)]
  uint32_t rel = mapa(BAR(B_E2), lane ? ((w & 1) ? R.wpart() : R.rank()) : R.cs() == 8 ? 4 * wg + w : wg);
  const bool rels = lane == 0 || (lane == 1 && w < 2);
  const uint32_t mx = sb + MX_OFF + 512 * wg + 4 * tid, bx = BAR(B_KF + 1 + 2 * LY + wg);
  uint32_t pa[8], pb[8];
#pragma unroll
  for (int i = 0; i < 8; i++) { pa[i] = mapa(mx + 1024 * db_, i ^ db_); pb[i] = mapa(bx + (tid >> 10), i ^ db_); asm volatile("" : "+r"(pa[i]), "+r"(pb[i])); }
  uint32_t* Mb = S->M + ((2 * LY * 16 + tb2) * 8) * 256 + (wg * 4 + w) * 32 + (2 * g + (q & 1)) * 2 + (q >> 1);
  {
    uint32_t bf = BAR(B_F2 + 1), st = 1, ra = rel + 8 * (B_EA - B_E2);
    const int lag = wg ? (LY ? STG : STG0) / 2 : 0;
#pragma unroll 1
    for (int kp = 1; kp < 10; kp++) {
      const bool more = LY == 0 || kp < 8;
      wg_wait<1>();
      if (lane == 0 && more) mbar_arrive_at(ra + 8 * (st ? st - 1 : 2));
      mbar_wait(bf, LY);
      if (STG && !(STG & 1) && kp == lag) bar_sync(5, 256);
      G2_STEP(st, kp < 5 ? kp : kp - 5, 0)
      wg_wait<1>();
      if (rels && more) mbar_arrive_at(rel);
      rel += 8;
      mbar_wait(bf + 8 * (B_F3 - B_F2), LY);
      if ((STG & 1) && kp == lag) bar_sync(5, 256);
      G2_STEP(st, kp < 5 ? kp : kp - 5, 1)
      if (kp == MIAT) {
        st_rlx(Mb + db_ * 256, tag ^ 1);
        if (LY == 0) st_rlx(Mb + (16 * 8 + db_) * 256, tag ^ 1);
      }
      bf += 8; st = st == 2 ? 0 : st + 1;
    }
  }
  if (STG && (LY || STG0) && !wg) asm volatile("bar.arrive 5, 256;" ::: "memory");
  wg_wait<0>(); fence_regs(acc);
  if (LY == 0 && rels) mbar_arrive_at(rel);
  if (tid == 0 && wg == 0) PROF(LY ? 26 : 11);
  if (lane == 0) PROF(116 + 64 * LY + wg * 4 + w);

#pragma unroll 1
  for (int rep = 0;; rep++) {
    float m[2][2];
#pragma unroll
    for (int h = 0; h < 2; h++) {
      m[h][0] = m[h][1] = 0.f;
#pragma unroll
      for (int J = 0; J < 5; J++)
#pragma unroll
        for (int c = 0; c < 4; c++) { const float xv = acc[IDX(J, c, h)]; m[h][0] += xv; m[h][1] = fmaf(xv, xv, m[h][1]); }
    }
    float r1[2];
#pragma unroll
    for (int i = 0; i < 2; i++) { const float snd = (q & 1) ? m[0][i] : m[1][i], kp = (q & 1) ? m[1][i] : m[0][i]; r1[i] = kp + __shfl_xor_sync(0xffffffff, snd, 1); }
    const float r2 = ((q & 2) ? r1[1] : r1[0]) + __shfl_xor_sync(0xffffffff, (q & 2) ? r1[0] : r1[1], 2);
    if (R.cs() == 8 && !rep) {
#pragma unroll
      for (int i = 0; i < 8; i++)
        asm volatile("st.async.weak.shared::cluster.mbarrier::complete_tx::bytes.b32 [%0],%1,[%2];" ::"r"(pa[i]), "f"(r2), "r"(pb[i]) : "memory");
      if (tid == 0) mbar_expect_tx(bx, 4096);
    }
    st_rlx(Mb + db_ * 256, tagf(r2, tag));
    if (rep) break;
    if (lane == 0) PROF(100 + 64 * LY + wg * 4 + w);
    float G[40];
    gate_load(G, sb, LY, wg, tid, tb2);
    mbar_wait(BAR(B_CD + 1));
    uint32_t mv[8];
    if (R.cs() == 8) {
      if (wg && !LY) mbar_wait(BAR(B_KF + 1), 1);
      mbar_wait(bx, 1);
#pragma unroll
      for (int i = 0; i < 8; i++) mv[i] = lds32(mx + 1024 * i);
    } else {
#pragma unroll
    for (int i = 0; i < 8; i++) mv[i] = ld_rlx(Mb + i * 256);
#pragma unroll 1
    for (int it = 0; it < SPIN; it++) {
      uint32_t miss = 0;
#pragma unroll
      for (int i = 0; i < 8; i++) miss |= ((mv[i] ^ tag) & 1) << i;
      if (!__any_sync(0xffffffff, miss)) break;
#pragma unroll
      for (int i = 0; i < 8; i++) if ((miss >> i) & 1) mv[i] = ld_rlx(Mb + i * 256);
    }
#pragma unroll
      for (int i = 0; i < 8; i++) mv[i] = __float_as_uint(untag(mv[i]));
      if (MBAR || !LY) bar_sync(4, 256);
    }
    if (lane == 0) PROF(108 + 64 * LY + wg * 4 + w);
#define MV(i) __uint_as_float(mv[i])
    const float s = ((MV(0) + MV(1)) + (MV(2) + MV(3))) + ((MV(4) + MV(5)) + (MV(6) + MV(7)));
#undef MV
    float mm[2], rr[2];
#pragma unroll
    for (int h = 0; h < 2; h++) {
      mm[h] = __shfl_sync(0xffffffff, s, h, 4) * (1.f / DM);
      rr[h] = frsqrt(fmaxf(__shfl_sync(0xffffffff, s, 2 + h, 4) * (1.f / DM) - mm[h] * mm[h], 0.f) + 1e-5f);
    }
    if (tid == 0 && wg == 0) PROF(LY ? 27 : 12);
    const float nm[2] = {-mm[0] * rr[0], -mm[1] * rr[1]};
#pragma unroll
    for (int h = 0; h < 2; h++)
#pragma unroll
      for (int J = 0; J < 5; J++)
#pragma unroll
        for (int c = 0; c < 4; c++) { const float xv = acc[IDX(J, c, h)]; xr[IDX(J, c, h)] = fmaf(fmaf(xv, rr[h], nm[h]), GATE(J, c, h), xv); }
    if (LY) break;
#pragma unroll
    for (int i = 0; i < 40; i++) acc[i] = xr[i] - mm[(i >> 1) & 1];
#pragma unroll
    for (int i = 0; i < 10; i++) {
      const int J = i >> 1, h = i & 1;
      const uint32_t u0 = pack_bf(acc[IDX(J, 0, h)], acc[IDX(J, 1, h)]), u1 = pack_bf(acc[IDX(J, 2, h)], acc[IDX(J, 3, h)]);
      asm volatile("st.shared.v2.u32 [%0],{%1,%2};" ::"r"(sb + US_OFF + ((mrow ^ 64) + 8 * h) * 160 + 32 * J + 8 * q), "r"(u0), "r"(u1) : "memory");
    }
    __syncwarp();
    if (lane == 0) mbar_arrive(BAR(B_GS + 1 + wg));
    if (tid == 0 && wg == 0) PROF(13);
    Mb += 16 * 8 * 256;
  }
  if (LY == 0) {
    if (tid == 0 && wg == 0) PROF(15);
  }
  else {
    float* op = P.out + (size_t)t0 * DM + d0;
#pragma unroll
    for (int i = 0; i < 10; i++) {
      const int J = i >> 1, h = i & 1;
      asm volatile("st.global.v4.f32 [%0],{%1,%2,%3,%4};" ::"l"(op + h * DM + 16 * J),
                   "f"(xr[IDX(J, 0, h)]), "f"(xr[IDX(J, 1, h)]), "f"(xr[IDX(J, 2, h)]), "f"(xr[IDX(J, 3, h)]) : "memory");
    }
  }
  if (tid == 0 && wg == 0 && LY) PROF(28);
#undef IDX
#undef GATE
}

__device__ __forceinline__ void next_stats(Scratch* S, uint32_t sb, int tb2, int tid) {
  const uint32_t bars = sb + BAR_OFF, tag = lds32(sb + MISC_OFF) & 1;
  const uint32_t* Mb = S->M + tb2 * 8 * 256 + 2 * tid;
  mbar_wait(BAR(B_F1 + NSAT), 1);
  float m1, s1, s2;
#pragma unroll 1
  for (int it = 0; it < SPIN; it++) {
    uint32_t a[8], miss = 0;
    uint2 v[8];
#pragma unroll
    for (int i = 0; i < 8; i++) { a[i] = ld_rlx(Mb + i * 256); v[i] = ld_rlx2((const uint2*)(Mb + (16 * 8 + i) * 256)); }
#pragma unroll
    for (int i = 0; i < 8; i++) miss |= (a[i] ^ tag) | (v[i].x ^ tag) | (v[i].y ^ tag);
#define SUM8(F) ((untag(F(0)) + untag(F(1))) + (untag(F(2)) + untag(F(3)))) + ((untag(F(4)) + untag(F(5))) + (untag(F(6)) + untag(F(7))))
#define FA(i) a[i]
#define FX(i) v[i].x
#define FY(i) v[i].y
    m1 = SUM8(FA); s1 = SUM8(FX); s2 = SUM8(FY);
    if (!__any_sync(0xffffffff, miss & 1)) break;
  }
  const float mean = s1 * (1.f / DM), rs = frsqrt(fmaxf(s2 * (1.f / DM) - mean * mean, 0.f) + 1e-5f);
  uint2* sp = S->S + SEQ + 128 * tb2 + 8 * (tid & 14) + 2 * (tid >> 4) + (tid & 1);
  st_rlx2(sp, tagf(rs, tag), tagf(-mean * rs, tag));
  st_rlx2(sp + SEQ, tagf(rs, tag), tagf(-(mean + m1 * (1.f / DM)) * rs, tag));
}
template <int I0, int I1> __device__ __forceinline__ void init_barriers(uint32_t bars) {
#pragma unroll
  for (int i = I0; i < I1; i++) mbar_init(BAR(i), bar_count(i));
}
__device__ __forceinline__ int g2_cb(int kp) { return kp < 5 ? 2 * kp : 2 * kp - 9; }
__device__ __forceinline__ const unsigned* h_flag(Scratch* S, int ly, int tb2, int lane) {
  const int s0 = 128 * min(tb2, 15) / 160;
  const bool two = (128 * tb2 + 127) / 160 != s0;
  return &S->flag[(F_H + (ly * 13 + s0) * 10 + min(lane & 15, 9) + (two && lane >= 16 ? 10 : 0)) * 32];
}
__device__ __forceinline__ void gate_tile(const Params& P, uint32_t dst, uint32_t bar, int tb2, int db) {
  mbar_expect_tx(bar, 20480);
  tma2d(dst, &P.mGT, tb2 * 128, db * 80, bar);
  tma2d(dst + 10240, &P.mGT, tb2 * 128 + 64, db * 80, bar);
}
__global__ void __cluster_dims__() __launch_bounds__(512, 1) fused_kernel(const Head H, const __grid_constant__ Params P) {
  extern __shared__ __align__(1024) uint8_t smem[];
  const uint32_t sb = opaque(smem_u32(smem)), bars = sb + BAR_OFF;
  const int wi = __shfl_sync(0xffffffff, threadIdx.x >> 5, 0), wg = wi >> 2, tid = threadIdx.x & 127;
  const int umap = blockIdx.x >= 96;
#define CLK(v)
  CLK(c_a);
  if (wi == 14) {
    if (elect_one()) { init_barriers<0, NBAR1>(bars); asm volatile("fence.mbarrier_init.release.cluster;" ::: "memory"); }
    __syncwarp();
  } else if (wi >= 12) prefetch_map(wi == 12 ? &P.mB : &P.mA[umap]);
  else if (wg == 2) xb_prefetch<1>(H, blockIdx.x + H.base, tid, 0);
  else if (P.role[blockIdx.x].w) return;
  CLK(c_b);
  asm volatile("barrier.cluster.arrive.relaxed.aligned;" ::: "memory");
  CLK(c_c);
  Role R;
  { const uint4 r = P.role[blockIdx.x]; R.v = r.x; R.c = r.y; R.p = r.z; }
  const int id = R.c & 255;
  const int tb = R.tb(), cb = R.cb(), b = R.b(), tb2 = b >> 3, db = b & 7, rank = R.rank();
  const bool has1 = tb <= 12, has2 = b < 128, full = tb < 12;
  Scratch* const S = H.s;
  unsigned* const epoch_p = &S->epoch[id * 8];
  const long long t_start = 0;
  if (wg < 2) {
    if (threadIdx.x == 0) PROF(50);
    asm volatile("griddepcontrol.launch_dependents;");
    bar_sync(6, 448);
    asm volatile("setmaxnreg.inc.sync.aligned.u32 176;");
    float xr[40];
    Keep K = {};
#pragma unroll
    for (int i = 0; i < 40; i++) xr[i] = 0.f;
#pragma unroll 1
    for (int ly = 0; ly < 2; ly++) {
      if (has1) g1_phase(ly, H, sb, wg, tid, R, xr, K, t_start);
      if (ly == 0) {
        resid_init(xr); fence_regs(xr);
        conv_loop<false>(sb, R.c, wg, tid, t_start);
        if (tid == 0 && wg == 0) PROF(9);
      }
      if (has2) g2_phase(ly, P, S, sb, wg, tid, R, xr, t_start);
    }
    if (tid == 0 && wg == 0) st_rlx(epoch_p, lds32(sb + MISC_OFF));
  } else if (wg == 2) {
    bar_sync(6, 448);
    if (has1) aux_prep(H, P, sb, R, tid, t_start);
    asm volatile("setmaxnreg.inc.sync.aligned.u32 136;");
    conv_loop<true>(sb, R.c, wg, tid, t_start);
    if (tid == 0) PROF(44);
    {
      const uint32_t bb = (P.role[blockIdx.x].x >> 8) & 255;
      if ((bb & 132) == NSDB && tid < 32) next_stats(H.s, sb, bb >> 3, 32 * (bb & 3) + tid);
    }
  } else {
    if (threadIdx.x == 384) PROF(354);
    asm volatile("setmaxnreg.dec.sync.aligned.u32 24;");
    const int wlo = R.wlo(), whi = R.whi();
    const uint32_t wmask = R.wmask(), umask = R.umask(), f1bytes = full ? 36864 : 32768;
    if (wi < 14) {
      if (threadIdx.x == 384) PROF(340);
      asm volatile("barrier.cluster.wait.aligned;" ::: "memory");
      if (has1 && elect_one()) {
        uint64_t tab = wi == 12 ? WTAB0 : XTAB0;
        PROF(329 + wi);
#pragma unroll 1
        for (int kb = 0; kb < 6; kb++, tab >>= 6) {
          const uint32_t dst = sb + ((uint32_t)tab & 63) * 4096;
          if (wi == 12) {
#pragma unroll 1
            for (int h = wlo; h <= whi; h++) tma4d_mc(dst + h * 8192, &P.mB, kb * 64, 0, 0, 8 * cb + 4 * h, BAR(B_F1 + kb), wmask);
          } else {
            tma4d_mc(dst + R.uj() * 1024, &P.mA[umap], kb * 64, 0, 0, 80 * tb + R.uj(), BAR(B_F1 + kb), umask);
            mbar_expect_tx(BAR(B_F1 + kb), f1bytes);
          }
        }
      }
      if (!has1 && wi == 13) bar_sync(7, 64);
    } else {
      if (wi == 15 && elect_one()) { init_barriers<NBAR1, NBAR>(bars); asm volatile("fence.mbarrier_init.release.cluster;" ::: "memory"); }
      bar_sync(6, 448);
      if (!has1 && wi == 14) bar_sync(7, 64);
    }
    const unsigned e1 = ld_rlx(epoch_p) + 1;
    if (wi == 12) {
      if (elect_one()) {
#pragma unroll 1
        for (int ly = 0; ly < 2; ly++) {
#pragma unroll 1
          for (int i = ly ? 0 : 6; i < 10 && has1; i++) {
            const int kb = (0x9876541032ull >> (4 * i)) & 15;
            if (ly == 0) { mbar_wait(BAR(B_E1 + ((DEP0 >> (4 * kb - 24)) & 15))); mbar_wait(BAR(B_AX + (kb == 9))); }
            else {
              if (has2 && i == (db >= GLATE ? 4 : 2)) {
                wait_cnt(&S->cnt[(C_G + db) * 32], e1 * 80);
                mbar_wait(BAR(B_E2 + 7));
                PROF(47);
                gate_tile(P, sb + G_OFF0, BAR(B_GF), tb2, db);
              }
              if (has2) mbar_wait(BAR(i < 4 ? B_E2 + ((0x9865u >> (4 * i)) & 15) : B_GE));
              else if (i == 0) { mbar_wait(BAR(B_E1 + 9)); mbar_wait(BAR(B_CD + 1)); }
              if (i >= 4) mbar_wait(BAR(i < 6 ? B_F1 + W4AT : B_E1 + i - 6), 1);
            }
            const uint32_t dst = sb + ((uint32_t)((ly ? WTAB1 : WTAB0) >> (6 * kb)) & 63) * 4096;
#pragma unroll 1
            for (int h = wlo; h <= whi; h++) tma4d_mc(dst + h * 8192, &P.mB, kb * 64, 0, 0, 8 * cb + 4 * h, BAR(B_F1 + kb), wmask);
          }
          if (has2) {
            if (ly == 0) {
              mbar_wait(BAR(B_E1 + XRAT));
              mbar_expect_tx(BAR(B_XR), 20480 + 160 + 1024);
              tma4d(sb + XR_OFF, &P.mX, 80 * db, tb2, BAR(B_XR));
              bulk_g2s(sb + XR_OFF + 20480, P.dskip + 80 * db, 160, BAR(B_XR));
              bulk_g2s(sb + XR_OFF + 20480 + 256, S->S + 128 * tb2, 1024, BAR(B_XR));
              if (CWAIT) mbar_wait(BAR(CWAIT == 1 ? B_KF + 2 : CWAIT == 2 ? B_KF + R.nch() - 1 : CWAIT == 3 ? B_KF + R.nch() - 2 : B_HD));
            }
#pragma unroll 1
            for (int kp = 0; kp < 10; kp++) {
              const uint32_t dst = sb + (kp < 5 ? kp : kp - 5) * 20480;
              mbar_wait(BAR(kp >= 5 ? B_E2 + kp - 5 : ly ? B_E1 + ((CTAB1 >> (4 * kp)) & 15) : kp < 3 ? B_SH : kp < 4 ? B_HD : B_CD), ly);
              mbar_expect_tx(BAR(B_F2 + kp), 10240 + 16384);
              tma5d(dst, &P.mC[0], g2_cb(kp) * 64, db * 5, BAR(B_F2 + kp));
              mbar_expect_tx(BAR(B_F3 + kp), 10240 + 16384);
              tma5d(dst + 10240, &P.mC[1], g2_cb(kp) * 64, db * 5, BAR(B_F3 + kp));
              if (ly && kp == 4) { mbar_wait(BAR(B_E1 + 9), 1); gate_tile(P, sb + G_OFF1, BAR(B_GF), tb2, db); }
            }
          }
        }
      }
    } else if (wi == 13) {
      const int h0 = R.cs() == 8 ? rank : 4 * rank;
#pragma unroll 1
      for (int ly = 0; ly < 2; ly++) {
        int lane = lane_id();
        if (has1) {
          const unsigned* fp = &S->flag[(F_U3 + 8 * ((160 * tb) >> 7) + (lane & (full ? 15 : 7))) * 32];
          uint32_t ready = ly ? __ballot_sync(0xffffffff, ld_rlx(fp) == e1) : ~0u;
          if (ly) mbar_wait(BAR(full ? B_KF + 1 : has2 ? B_GS + 1 : B_RF1), has2);
          if (ly && full) mbar_wait(BAR(B_KF + 2), 1);
#pragma unroll 1
          for (int kb = ly ? 0 : 6; kb < 10; kb++) {
            if (ly && kb == UPAT) { mbar_wait(BAR(B_XR)); ready = ~0u; }
            wait_flags(fp, e1, 0x101u * ((1u << (64 * kb / 80)) | (1u << ((64 * kb + 63) / 80))), ready);
            if (kb >= 4) mbar_wait(BAR(B_E1 + (ly ? kb - 4 : (DEP0 >> (4 * kb - 24)) & 15)), ly);
            mbar_wait(BAR(B_AX + (kb == 9)));
            if (elect_one()) {
              if (ly && kb == 0) PROF(34);
              tma4d_mc(sb + ((uint32_t)((ly ? XTAB1 : XTAB0) >> (6 * kb)) & 63) * 4096 + R.uj() * 1024, &P.mA[2 * ly + umap], kb * 64, 0, 0, 80 * tb + R.uj(),
                       BAR(B_F1 + kb), umask);
              mbar_expect_tx(BAR(B_F1 + kb), f1bytes);
            }
            __syncwarp();
          }
        }
        if (ly == 0) {
          if (has1) mbar_wait(BAR(B_E1 + KPF));
          if (elect_one()) {
#pragma unroll 1
            for (int s = 0; s < R.nch(); s++) prefetch_l2(P.ssmk + (size_t)R.ch(s) * SEQ, 4096);
          }
          lane = lane_id();
#pragma unroll
          for (int s = 0; s < 5; s++) {
            asm volatile("st.shared.v4.u32 [%0],{%1,%1,%1,%1};" ::"r"(conv_buf(sb, s) + 16 * lane), "r"(0) : "memory");
            asm volatile("st.shared.u8 [%0],%1;" ::"r"(conv_buf(sb, s) + KC_OFS + lane), "r"(0) : "memory");
          }
          fence_async();
          __syncwarp();
          const unsigned* cp = &S->cnt[(C_KV + (R.ch(min(lane, R.nch() - 1)) >> 6)) * 32];
          uint32_t ready = 0;
#pragma unroll 1
          for (int s = 0, sk = 0; s < R.nch(); s++) {
#pragma unroll 1
            for (; sk < (s ? R.nch() : KUP); sk++)
              if (elect_one()) { mbar_expect_tx(BAR(B_KF + sk), 8192); bulk_g2s(conv_buf(sb, sk) + KC_OFS + 32, P.ssmk + (size_t)R.ch(sk) * SEQ, 4096, BAR(B_KF + sk)); }
            PROFC(s == 0, 329);
#pragma unroll 1
            for (int it = 0; !((ready >> s) & 1) && it < SPIN; it++) ready = __ballot_sync(0xffffffff, (int)(ld_rlx(cp) - e1 * 32) >= 0);
            PROFC(s == 0, 30);
            if (elect_one()) {
              bulk_g2s(conv_buf(sb, s) + KV_PAD, S->kv + (size_t)R.ch(s) * SEQ, 4096, BAR(B_KF + s));
              if (s == 0 && has2) { prefetch_l2(P.cre + (size_t)5 * b * DM, 5 * DM * 2); prefetch_l2(P.cim + (size_t)5 * b * DM, 5 * DM * 2); }
            }
            __syncwarp();
          }
          PROF(31);
          if (!has1) return;
        }
        lane = lane_id();
        const unsigned* fp = h_flag(S, ly, tb2, lane);
        uint32_t ready = __ballot_sync(0xffffffff, ld_rlx(fp) == e1), st = 0;
        if (ly == 0 && !has2) {
          mbar_wait(BAR(B_HD));
          if (lane < 8) mbar_arrive_cl(BAR(B_RF1), lane & 1);
        }
        if (has2) {
          mbar_wait(BAR(B_RF0), ly);
#pragma unroll 1
          for (int kp = 0; kp < 10; kp++) {
            if (kp == 5) { mbar_wait(BAR(B_XR), 1); ready = ~0u; }
            if (kp == 2) { mbar_wait(BAR(B_HD), ly); if (lane < 8) mbar_arrive_cl(BAR(B_RF1), lane & (R.cs() - 1)); }
            wait_flags(fp, e1, 0x10001u << g2_cb(kp), ready);
            if (kp == 2) mbar_wait(BAR(B_RF1), ly);
#pragma unroll
            for (int hf = 0; hf < 2; hf++) {
              if (kp >= 3) { if (hf) mbar_wait(BAR(B_E2 + kp - 3), ly); else mbar_wait(BAR(B_EA + st), ly ^ (kp >= 6 && kp < 9)); }
              if (elect_one()) {
                if (kp == 0 && !hf) PROF(33 + 2 * ly);
                tma4d_mc(sb + H_OFF + st * 32768 + hf * 16384 + h0 * 2048, &P.mH, g2_cb(kp) * 128 + hf * 64, 0, 2 * h0,
                         ly * 16 + tb2, BAR((hf ? B_F3 : B_F2) + kp), (1u << R.cs()) - 1);
              }
              __syncwarp();
            }
            st = st == 2 ? 0 : st + 1;
          }
        }
      }
    } else if (wi == 14) {
      if (!has1) return;
      prefetch_if(P.dskip + 64 * (tid & 31), (tid & 31) < 10);
      if (elect_one()) { prefetch_map(&P.sK); prefetch_map(&P.mX); prefetch_map(&P.sH); prefetch_map(&P.sU); prefetch_map(&P.mC[0]); prefetch_map(&P.mC[1]); prefetch_map(&P.mH); prefetch_map(&P.mGT); prefetch_map(&P.mA[2 + umap]); }
      __syncwarp();
#pragma unroll 1
      for (int ly = 0; ly < 2; ly++) {
        if (ly) {
          mbar_wait(BAR(B_F1 + 1), 1);
          uint32_t ready = 0;
          wait_flags(&S->flag[(F_U3 + 8 * ((160 * tb) >> 7) + ((lane_id() + ly) & (full ? 15 : 7))) * 32], e1, ~0u, ready);
          if (elect_one()) mbar_arrive(BAR(B_XR));
        }
        const int lane = lane_id();
        mbar_wait(BAR(B_E1 + (ly ? STAT_AT1 : STAT_AT)), ly);
        PROFC(lane == 0 && ly == 0, 36);
        {
          const int l = lane - (full ? 0 : 16);
          const uint2* p = S->S + ly * SEQ + 160 * tb + 2 * l;
          uint4 v[3];
#pragma unroll 1
          for (int it = 0; it < SPIN; it++) {
            v[0] = ld_rlx4(p); v[1] = ld_rlx4(p + 64); v[2] = ld_rlx4(p + 96);
            const bool miss = __any_sync(0xffffffff, untagged(v[0], e1 & 1) | untagged(v[1], e1 & 1) | untagged(v[2], e1 & 1));
            PROFC(lane == 0 && ly == 0 && it == 0, 37);
            if (!miss) break;
          }
          PROFC(lane == 0 && ly == 0, 38);
          uint32_t sp = sb + SSM_OFF + 8 * lane + (full ? 0 : 2 * (lane & 16) - 160);
#pragma unroll
          for (int i = 0; i < 3; i++) {
            asm volatile("{ .reg .pred p; setp.ge.u32 p, %0, %5; @p st.shared.v2.u32 [%0],{%1,%3}; @p st.shared.v2.u32 [%0+640],{%2,%4}; }" ::"r"(sp),
                         "r"(v[i].x & ~1u), "r"(v[i].y & ~1u), "r"(v[i].z & ~1u), "r"(v[i].w & ~1u), "r"(sb + SSM_OFF) : "memory");
            sp += (full ? 256 : 320) >> i;
          }
          __syncwarp();
        }
        if (lane == 0) mbar_arrive(BAR(B_ST));
        if (ly && has2) {
          mbar_wait(BAR(B_E1 + 9), 1);
          if (lane < 8) mbar_arrive_cl(BAR(B_RF0), lane & (R.cs() - 1));
        }
        if (lane == 0) {
#pragma unroll 1
          for (int pc = 0; pc < (full ? 5 : 4); pc++) {
            if ((HWM >> (4 * pc)) & 8) {
              mbar_wait(BAR(B_SH + min((HWM >> (4 * pc)) & 7, full ? 4 : 3)), ly);
              PROF(380 + 5 * ly + pc);
              if (pc == 0 && (cb & 1)) delay(ly ? HDLY : HDLY0);
              fence_async();
            }
#pragma unroll
            for (int i = 0; i < 2; i++) tma4d_store(&P.sH, sb + (pc < 4 ? R_OFF + i * 16384 + pc * 4096 : (ly ? R4_OFF1 : R4_OFF0) + i * 4096), 128 * cb + 64 * i, 0, 0, ly * 1024 + 80 * tb + 4 * pc);
          }
          bulk_commit(); bulk_wait();
          PROF(ly ? 17 : 16);
          mbar_arrive(BAR(B_HD));
          release<1>();
          signal_flag(&S->flag[(F_H + (ly * 13 + tb) * 10 + cb) * 32], e1);
          PROF(ly ? 24 : 8);
        }
        __syncwarp();
        if (has2) {
          mbar_wait(BAR(B_F2 + FPAT), ly);
          uint32_t ready = 0;
          wait_flags(h_flag(S, ly, tb2, lane_id() | 1), e1, ~0u, ready);
          if (elect_one()) mbar_arrive(BAR(B_XR));
        }
        if (lane == 0 && has2 && !ly) {
          mbar_wait(BAR(B_CD + 1));
#pragma unroll
          for (int i = 0; i < 2; i++) {
            mbar_wait(BAR(B_GS + 1 + i), 1);
            fence_async();
            tma4d_store(&P.sU, sb + US_OFF + 10240 - 10240 * i, 80 * db, 0, 8 * i, tb2);
          }
          bulk_commit(); bulk_wait();
          PROF(18);
          release<2>(); signal_flag(&S->flag[(F_U3 + b) * 32], e1);
          PROF(14);
          mbar_wait(BAR(B_SG));
          mbar_arrive(BAR(B_GE)); mbar_arrive_cl(BAR(B_GE), R.wpart());
        }
        __syncwarp();
      }
    } else {
      discretise(H, P, sb, R, tid & 31, e1);
      if (elect_one()) {
        mbar_arrive(BAR(B_LM));
        PROF(348);
        if (b < R.nprep()) {
#pragma unroll 1
          for (int task = b, r = 0; task < 320; task += R.nprep(), r++) {
            mbar_wait(BAR(B_PS + r));
            PROF(320 + 3 * r);
            fence_async();
            tma2d_store(&P.sK, sb + KS_OFF + r * 8192, 64 * (task & 31), 64 * (task >> 5));
            bulk_commit(); bulk_wait();
            PROF(321 + 3 * r);
            release<4>();
            signal_cnt(&S->cnt[(C_KV + (task >> 5)) * 32], 1);
            PROF(322 + 3 * r);
          }
          PROF(41);
        }
        if (has2) {
          mbar_wait(BAR(B_SH));
#pragma unroll 1
          for (int i = 0; i < 8; i++) mbar_arrive_cl(BAR(B_RF0), i & (R.cs() - 1));
        }
#pragma unroll 1
        for (int s = 0, s0 = 0; s < R.nch(); s++) {
          mbar_wait(BAR(B_GS + s));
          fence_async();
          bulk_s2g(S->gt + (size_t)R.ch(s) * SEQ, conv_buf(sb, s) + KC_OFS, 4096); bulk_commit();
          if (s == 1 || s >= R.nch() - GSPL) bulk_wait();
          if (s == 1 || s == min(R.nch() - 1, 3)) mbar_arrive(BAR(B_CD + (s > 1)));
          mbar_arrive_if(BAR(B_SG), s == R.nch() - 1);
          if (s >= R.nch() - GSPL) {
            PROF(45);
            release<8>();
#pragma unroll 1
            for (; s0 <= s; s0++) signal_cnt(&S->cnt[(C_G + R.ch(s0) / 80) * 32], 1);
          }
        }
        PROF(46);
      }
    }
  }
}

typedef CUresult (*EncFn)(CUtensorMap*, CUtensorMapDataType, cuuint32_t, void*, const cuuint64_t*, const cuuint64_t*, const cuuint32_t*,
                          const cuuint32_t*, CUtensorMapInterleave, CUtensorMapSwizzle, CUtensorMapL2promotion, CUtensorMapFloatOOBfill);
bool enc(EncFn f, CUtensorMap* m, const void* base, int rank, const cuuint64_t* dims, const cuuint64_t* strides, const cuuint32_t* box, bool swz,
         bool f32 = false) {
  const cuuint32_t es[5] = {1, 1, 1, 1, 1};
  return f(m, f32 ? CU_TENSOR_MAP_DATA_TYPE_FLOAT32 : CU_TENSOR_MAP_DATA_TYPE_BFLOAT16, rank, const_cast<void*>(base), dims, strides, box, es,
           CU_TENSOR_MAP_INTERLEAVE_NONE, swz ? CU_TENSOR_MAP_SWIZZLE_128B : CU_TENSOR_MAP_SWIZZLE_NONE, CU_TENSOR_MAP_L2_PROMOTION_L2_256B,
           CU_TENSOR_MAP_FLOAT_OOB_FILL_NONE) == CUDA_SUCCESS;
}
void make_roles(Params& P, bool big) {
  for (uint32_t bx = 0; bx < (big ? 120u : 12u); bx++) {
    const uint32_t c = bx >> 3, r = bx & 7, id = big ? bx : 120 + bx;
    const uint32_t vA = c < 12 ? (2 * (c >> 1) + (r >> 2)) | (4 * (c & 1) + (r & 3)) << 4 | (r & 4) << 16 | 4 << 19 | (r ^ 4) << 22
                               : (4 * (c - 12) + (r >> 1)) | (8 + (r & 1)) << 4 | (r & 6) << 16 | 2 << 19 | (r ^ 2) << 22;
    const uint32_t vB = (bx < 10 ? 12 : 13) | bx << 4 | 2 << 19 | (bx & 1) << 22 | (bx & 1) << 26;
    P.role[bx].x = (big ? vA | r << 26 | 1u << 29 : vB) | (id < 128 ? (id & ~7u) | (r >> 1) | (r & 1) << 2 : id) << 8;
    P.role[bx].y = id | (big ? 5 : bx < 8 ? 3 : 4) << 10 | 120 << 13 | 132 << 21 | (big ? 4u : 3u) << 29;
    const uint32_t v = P.role[bx].x, cb = (v >> 4) & 15, rank = (v >> 26) & 7, ubase = (v >> 16) & 7, ugs = (v >> 19) & 7, wp = (v >> 22) & 7;
    const uint32_t wlo = rank > wp, whi = wp != rank ? wlo : 1, wmask = 1u << rank | 1u << wp;
    const uint32_t uj = (rank - ubase) * (!big ? 8 : ugs == 4 ? 5 : 10), sm = big ? (0x7296418530ull >> (4 * cb)) & 15 : bx < 8 ? 4 * (bx & 1) + (bx >> 1) : 15;
    P.role[bx].z = wlo | whi << 1 | wmask << 2 | ((1u << ugs) - 1) << (10 + ubase) | uj << 20 | sm << 25;
    P.role[bx].w = 0;
  }
}
void launch(const Head& H, const Params& P, int grid, int cs, bool dependent) {
  cudaLaunchConfig_t cfg = {};
  cfg.gridDim = grid; cfg.blockDim = 512; cfg.dynamicSmemBytes = SMEM_BYTES; cfg.stream = cudaStreamPerThread;
  cudaLaunchAttribute at[2];
  at[0].id = cudaLaunchAttributeClusterDimension; at[0].val.clusterDim.x = cs; at[0].val.clusterDim.y = 1; at[0].val.clusterDim.z = 1;
  at[1].id = cudaLaunchAttributeProgrammaticStreamSerialization; at[1].val.programmaticStreamSerializationAllowed = 1;
  cfg.attrs = at; cfg.numAttrs = dependent ? 2 : 1;
  cudaLaunchKernelEx(&cfg, fused_kernel, H, P);
}

}

extern "C" void kernel_launch(void* const* d_in, const int* in_sizes, int n_in, void* d_out, int out_size) {
  (void)in_sizes; (void)n_in; (void)out_size;
  typedef const __nv_bfloat16* cb;
  void* fp = nullptr; cudaDriverEntryPointQueryResult qr;
  cudaGetDriverEntryPoint("cuTensorMapEncodeTiled", &fp, cudaEnableDefault, &qr);
  EncFn f = (EncFn)fp;
  Scratch* sp = nullptr;
  cudaGetSymbolAddress((void**)&sp, g_scr);
  void *pu = sp->u, *ph = sp->h, *pgt = sp->gt;
  Params P;
  Head H;
  H.s = sp; H.x = (cb)d_in[0]; H.swap = (uintptr_t)d_in[4] < (uintptr_t)d_in[3] ? 0 : 0x80000000u; H.b0 = (cb)d_in[H.swap ? 3 : 4]; H.b1 = (cb)d_in[H.swap ? 4 : 3];
  for (int i = 0; i < 2; i++) {
    const cuuint64_t d[4] = {640, 8, 2, 80}, s[3] = {1280, (cuuint64_t)((uintptr_t)H.b1 - (uintptr_t)H.b0), 8 * 1280}; const cuuint32_t bx[4] = {64, 8, 2, 4};
    if (enc(f, &P.mB, H.b0, 4, d, s, bx, true)) break;
    cudaMemcpyAsync(sp->bcopy, H.b0, DM * DM * 2, cudaMemcpyDeviceToDevice, cudaStreamPerThread);
    cudaMemcpyAsync(sp->bcopy + DM * DM, H.b1, DM * DM * 2, cudaMemcpyDeviceToDevice, cudaStreamPerThread);
    H.b0 = sp->bcopy; H.b1 = sp->bcopy + DM * DM;
  }
  {
    const cuuint64_t d[5] = {640, 2, 4, 2, 40}, s[4] = {1280, 4 * 1280, 2 * 1280, 16 * 1280}; const cuuint32_t bx[5] = {64, 2, 4, 2, 5};
    enc(f, &P.mC[0], d_in[5], 5, d, s, bx, true); enc(f, &P.mC[1], d_in[6], 5, d, s, bx, true); }
  { const cuuint64_t d[2] = {2048, 640}, s[1] = {4096}; const cuuint32_t bx[2] = {64, 80}; enc(f, &P.mGT, pgt, 2, d, s, bx, true); }
  { const cuuint64_t d[4] = {640, 8, 16, 16}, s[3] = {16 * 1280, 1280, 128 * 1280}; const cuuint32_t bx[4] = {80, 8, 16, 1}, bh[4] = {80, 8, 8, 1};
    enc(f, &P.sU, pu, 4, d, s, bh, false); enc(f, &P.mX, d_in[0], 4, d, s, bx, false); }
  { const cuuint64_t d[2] = {2048, 640}, s[1] = {4096}; const cuuint32_t bx[2] = {64, 64}; enc(f, &P.sK, sp->kv, 2, d, s, bx, true); }
  P.lre = (cb)d_in[1]; P.lim = (cb)d_in[2]; P.cre = (cb)d_in[5]; P.cim = (cb)d_in[6]; P.ldt = (cb)d_in[7]; P.dskip = (cb)d_in[8];
  P.out = (float*)d_out;
  P.k = (cb)d_in[10]; P.v = (cb)d_in[11]; P.shk = (cb)d_in[12]; P.ssmk = (cb)d_in[13]; P.ssmd = (cb)d_in[14];
  cudaFuncSetAttribute(fused_kernel, cudaFuncAttributeMaxDynamicSharedMemorySize, SMEM_BYTES);
  for (int big = 1; big >= 0; big--) {
    const cuuint64_t seg = big ? 40 : 32;
    for (int i = 0; i < 4; i++) {
      const cuuint64_t d[4] = {640, 2, 4, 1024}, s[3] = {1280, seg * 1280, 2 * 1280}; const cuuint32_t bx[4] = {64, 2, 4, !big ? 8u : (i & 1) ? 10u : 5u};
      enc(f, &P.mA[i], i < 2 ? d_in[0] : pu, 4, d, s, bx, true);
    }
    {
      const cuuint64_t d[4] = {1280, 8, 16, 32}, s[3] = {16 * 2560, 2560, 128 * 2560}; const cuuint32_t bx[4] = {64, 8, big ? 2u : 8u, 1};
      enc(f, &P.mH, ph, 4, d, s, bx, true); }
    { const cuuint64_t d[4] = {1280, 2, 4, 2048}, s[3] = {2560, seg * 2560, 2 * 2560}; const cuuint32_t bx[4] = {64, 2, 4, 4};
      enc(f, &P.sH, ph, 4, d, s, bx, true); }
    make_roles(P, big);
    H.base = big ? 0 : 120;
    launch(H, P, big ? 120 : 12, big ? 8 : 2, !big);
  }
}
```

```cpp
#include <cuda_runtime.h>
#include <cuda.h>
#include <cuda_bf16.h>
#include <stdint.h>

namespace {

constexpr int SEQ = 2048, DM = 640;
constexpr int SPIN = 1 << 20;
#define PFAT 99
#define KVDLY 300
#define PFD 1
#define XPFAT 9
#define STAT_AT 6
#define KPFAT 3
#define KPFAT2 5
#define KPF 7
#define HDLY 1900
#define GSPL 2
#define CWAIT 0
#define HDLY0 1900
#define CTAB1 0x96543u
#define NSAT 0
#define SKW 1
#define RIAT 2
#define MIAT 5
#define FPAT 1
#define UPAT 7
#define STAT_AT1 4
#define W4AT 0
#define MBAR 1
#define STG 17
#define STG0 17
#define HWM 0xc09
#define NSDB 4
#define UH 2
#define GLATE 6
#define KUP 1
#define XRAT 9
#define ORD 1

struct Scratch {
  uint2 E[2 * 13 * 10 * 8 * 16];
  uint32_t M[3 * 16 * 8 * 256];
  uint2 S[3 * SEQ];
  uint2 RS[80 * 16];
  unsigned flag[512 * 32];
  unsigned cnt[32 * 32];
  unsigned epoch[132 * 8];
  unsigned zero[128];
  unsigned prof[132 * 512];
  __align__(1024)
  __nv_bfloat16 u[SEQ * DM];
  __nv_bfloat16 h[2 * SEQ * 1280];
  __nv_bfloat16 kv[DM * SEQ];
  __nv_bfloat16 gt[DM * SEQ];
  __nv_bfloat16 bcopy[2 * DM * DM];
};
__device__ __align__(1024) Scratch g_scr;
#define PROFC(c, i) do {} while (0)
#define PSEL 1
#define PROF(i) do {} while (0)

constexpr int C_KV = 0, C_G = 10;
constexpr int F_U3 = 0, F_H = 128;

constexpr int R_OFF = 196608, R4_OFF0 = 73728, R4_OFF1 = 122880, H_OFF = 131072, KS_OFF = 131072, CV_OFF = 86272, G_OFF0 = 40960, G_OFF1 = 102400, US_OFF = 98304, XR_OFF = 163840, MX_OFF = 32768;
constexpr int LAM_OFF = 229376, SSM_OFF = LAM_OFF + 1024, BAR_OFF = SSM_OFF + 1344;
constexpr int B_F1 = 0, B_E1 = 10, B_RF0 = 20, B_RF1 = 21, NBAR1 = 22;
constexpr int B_F2 = 22, B_KF = 32, B_GF = 37, B_CD = 38, B_XR = 40, B_ST = 41, B_HD = 42, B_LM = 43, B_E2 = 44, B_GS = 54, B_PS = 59, B_AX = 62, B_SH = 64, B_SG = 69, B_GE = 70, B_EA = 71, B_F3 = 74, NBAR = 84;
__host__ __device__ constexpr int bar_count(int i) { return i < B_E1 ? 1 : i < B_RF0 ? 9 : i < B_F2 ? 8 : i < B_E2 ? 1 : i < B_GS ? 12 : i < B_SH ? 4 : i < B_SG ? 8 : i < B_GE ? 1 : i < B_EA ? 2 : i < B_F3 ? 8 : 1; }
constexpr int MISC_OFF = BAR_OFF + NBAR * 8, SMEM_BYTES = MISC_OFF + 32;
constexpr int KV_PAD = 512, KC_OFS = KV_PAD + 4096, CH_STRIDE = 8960;
__device__ __forceinline__ uint32_t conv_buf(uint32_t sb, int slot) { return sb + CV_OFF + slot * CH_STRIDE; }
constexpr uint64_t tab6(int a, int b, int c, int d, int e, int f, int g, int h, int i, int j) {
  return (uint64_t)a | (uint64_t)b << 6 | (uint64_t)c << 12 | (uint64_t)d << 18 | (uint64_t)e << 24 | (uint64_t)f << 30 | (uint64_t)g << 36 | (uint64_t)h << 42 |
         (uint64_t)i << 48 | (uint64_t)j << 54;
}
constexpr uint64_t WTAB0 = tab6(0, 4, 8, 30, 12, 26, 0, 4, 8, 12), XTAB0 = tab6(40, 45, 50, 34, 16, 21, 40, 45, 50, 16);
constexpr uint64_t WTAB1 = tab6(16, 20, 0, 4, 8, 12, 16, 20, 24, 28), XTAB1 = tab6(40, 45, 50, 32, 40, 45, 50, 32, 40, 45);
constexpr uint32_t DEP0 = 0x4210;

struct Head {
  Scratch* s;
  const __nv_bfloat16 *x, *b0, *b1;
  uint32_t base, swap;
};
struct Params {
  const __nv_bfloat16 *lre, *lim, *ldt, *k, *v, *shk, *cre, *cim, *ssmk, *ssmd, *dskip;
  float* out;
  uint4 role[120];
  CUtensorMap mB, mA[4], mH, mC[2], mGT, mX, sH, sU, sK;
};

__device__ __forceinline__ uint32_t smem_u32(const void* p) { return (uint32_t)__cvta_generic_to_shared(p); }
__device__ __forceinline__ uint32_t opaque(uint32_t x) { uint32_t y; asm volatile("mov.u32 %0, %1;" : "=r"(y) : "r"(x)); return y; }
__device__ __forceinline__ int lane_id() { int y; asm volatile("mov.u32 %0, %%laneid;" : "=r"(y)); return y; }
__device__ __forceinline__ void delay(uint32_t n) {
  asm volatile("{ .reg .pred p; .reg .u32 a, b; mov.u32 a, %%clock; L: mov.u32 b, %%clock; sub.u32 b, b, a; setp.lt.u32 p, b, %0; @p bra.uni L; }" ::"r"(n) : "memory");
}
__device__ __forceinline__ void mbar_init(uint32_t bar, uint32_t cnt) { asm volatile("mbarrier.init.shared::cta.b64 [%0], %1;" ::"r"(bar), "r"(cnt) : "memory"); }
__device__ __forceinline__ void mbar_expect_tx(uint32_t bar, uint32_t bytes) { asm volatile("mbarrier.arrive.expect_tx.shared::cta.b64 _, [%0], %1;" ::"r"(bar), "r"(bytes) : "memory"); }
__device__ __forceinline__ void mbar_arrive(uint32_t bar) { asm volatile("mbarrier.arrive.shared::cta.b64 _, [%0];" ::"r"(bar) : "memory"); }
__device__ __forceinline__ void mbar_arrive_if(uint32_t bar, bool c) {
  asm volatile("{ .reg .pred p; setp.ne.u32 p, %1, 0; @p mbarrier.arrive.shared::cta.b64 _, [%0]; }" ::"r"(bar), "r"((uint32_t)c) : "memory");
}
__device__ __forceinline__ void prefetch_if(const void* p, bool c) { asm volatile("{ .reg .pred p; setp.ne.u32 p, %1, 0; @p prefetch.global.L2 [%0]; }" ::"l"(p), "r"((uint32_t)c)); }
__device__ __forceinline__ void mbar_arrive_cl(uint32_t bar, uint32_t cta) {
  asm volatile("{ .reg .b32 ra; mapa.shared::cluster.u32 ra, %0, %1; mbarrier.arrive.shared::cluster.b64 _, [ra]; }" ::"r"(bar), "r"(cta) : "memory");
}
__device__ __forceinline__ uint32_t mapa(uint32_t a, uint32_t cta) { uint32_t r; asm("mapa.shared::cluster.u32 %0, %1, %2;" : "=r"(r) : "r"(a), "r"(cta)); return r; }
__device__ __forceinline__ void mbar_arrive_at(uint32_t ra) { asm volatile("mbarrier.arrive.shared::cluster.b64 _, [%0];" ::"r"(ra) : "memory"); }
__device__ __forceinline__ void mbar_wait(uint32_t bar, uint32_t parity = 0) {
  asm volatile("{ .reg .pred p; .reg .u32 c; mov.u32 c, 0;\n"
               "W: mbarrier.try_wait.parity.shared::cta.b64 p, [%0], %1; @p bra.uni D;\n"
               "add.u32 c, c, 1; setp.lt.u32 p, c, 0x100000; @p bra.uni W;\nD: }" ::"r"(bar), "r"(parity) : "memory");
}
__device__ __forceinline__ bool elect_one() { uint32_t p; asm volatile("{ .reg .pred P; elect.sync _|P, 0xffffffff; selp.u32 %0,1,0,P; }" : "=r"(p)); return p; }
__device__ __forceinline__ void bar_sync(int id, int n) { __syncwarp(); asm volatile("bar.sync %0, %1;" ::"r"(id), "r"(n) : "memory"); }
__device__ __forceinline__ void tma2d(uint32_t dst, const CUtensorMap* m, int c0, int c1, uint32_t bar) {
  asm volatile("cp.async.bulk.tensor.2d.shared::cluster.global.mbarrier::complete_tx::bytes [%0], [%1, {%3,%4}], [%2];"
               ::"r"(dst), "l"(m), "r"(bar), "r"(c0), "r"(c1) : "memory");
}
__device__ __forceinline__ void tma5d(uint32_t dst, const CUtensorMap* m, int c0, int c4, uint32_t bar) {
  asm volatile("cp.async.bulk.tensor.5d.shared::cluster.global.mbarrier::complete_tx::bytes [%0], [%1, {%3,%5,%5,%5,%4}], [%2];"
               ::"r"(dst), "l"(m), "r"(bar), "r"(c0), "r"(c4), "r"(0) : "memory");
}
__device__ __forceinline__ void tma4d(uint32_t dst, const CUtensorMap* m, int c0, int c3, uint32_t bar) {
  asm volatile("cp.async.bulk.tensor.4d.shared::cluster.global.mbarrier::complete_tx::bytes [%0], [%1, {%3,%5,%5,%4}], [%2];"
               ::"r"(dst), "l"(m), "r"(bar), "r"(c0), "r"(c3), "r"(0) : "memory");
}
__device__ __forceinline__ void tma4d_mc(uint32_t dst, const CUtensorMap* m, int c0, int c1, int c2, int c3, uint32_t bar, uint32_t mask) {
  asm volatile("cp.async.bulk.tensor.4d.shared::cluster.global.mbarrier::complete_tx::bytes.multicast::cluster [%0], [%1, {%3,%4,%5,%6}], [%2], %7;"
               ::"r"(dst), "l"(m), "r"(bar), "r"(c0), "r"(c1), "r"(c2), "r"(c3), "h"((uint16_t)mask) : "memory");
}
__device__ __forceinline__ void bulk_g2s(uint32_t dst, const void* src, uint32_t bytes, uint32_t bar) {
  asm volatile("cp.async.bulk.shared::cluster.global.mbarrier::complete_tx::bytes [%0], [%1], %2, [%3];" ::"r"(dst), "l"(src), "r"(bytes), "r"(bar) : "memory");
}
__device__ __forceinline__ void tma4d_store(const CUtensorMap* m, uint32_t src, int c0, int c1, int c2, int c3) {
  asm volatile("cp.async.bulk.tensor.4d.global.shared::cta.bulk_group [%0, {%2,%3,%4,%5}], [%1];" ::"l"(m), "r"(src), "r"(c0), "r"(c1), "r"(c2), "r"(c3) : "memory");
}
__device__ __forceinline__ void tma2d_store(const CUtensorMap* m, uint32_t src, int c0, int c1) {
  asm volatile("cp.async.bulk.tensor.2d.global.shared::cta.bulk_group [%0, {%2,%3}], [%1];" ::"l"(m), "r"(src), "r"(c0), "r"(c1) : "memory");
}
__device__ __forceinline__ void bulk_s2g(void* dst, uint32_t src, uint32_t bytes) {
  asm volatile("cp.async.bulk.global.shared::cta.bulk_group [%0], [%1], %2;" ::"l"(dst), "r"(src), "r"(bytes) : "memory");
}
__device__ __forceinline__ void bulk_commit() { asm volatile("cp.async.bulk.commit_group;" ::: "memory"); }
__device__ __forceinline__ void bulk_wait() { asm volatile("cp.async.bulk.wait_group 0;" ::: "memory"); }
__device__ __forceinline__ void fence_async() { asm volatile("fence.proxy.async.shared::cta;" ::: "memory"); }
__device__ __forceinline__ void prefetch_l2(const void* src, uint32_t bytes) { asm volatile("cp.async.bulk.prefetch.L2.global [%0], %1;" ::"l"(src), "r"(bytes) : "memory"); }
__device__ __forceinline__ void prefetch_map(const CUtensorMap* m) { asm volatile("prefetch.tensormap [%0];" ::"l"(m) : "memory"); }
__device__ __forceinline__ void wg_fence() { __syncwarp(); asm volatile("wgmma.fence.sync.aligned;" ::: "memory"); }
__device__ __forceinline__ void wg_commit() { asm volatile("wgmma.commit_group.sync.aligned;" ::: "memory"); }
template <int N> __device__ __forceinline__ void wg_wait() { asm volatile("wgmma.wait_group.sync.aligned %0;" ::"n"(N) : "memory"); }
template <int N> __device__ __forceinline__ void fence_regs(float (&d)[N]) {
#pragma unroll
  for (int i = 0; i < N; i++) asm volatile("" : "+f"(d[i])::"memory");
}
__device__ __forceinline__ uint64_t make_desc(uint32_t addr, uint32_t lbo, uint32_t sbo, uint32_t swz) {
  return (uint64_t)((addr & 0x3FFFF) >> 4) | ((uint64_t)(lbo >> 4) << 16) | ((uint64_t)(sbo >> 4) << 32) | ((uint64_t)swz << 62);
}
__device__ __forceinline__ uint32_t ldg1(const void* p) { uint32_t v; asm volatile("ld.global.nc.u32 %0,[%1];" : "=r"(v) : "l"(p)); return v; }
__device__ __forceinline__ uint32_t lds32(uint32_t a) { uint32_t v; asm volatile("ld.shared.u32 %0,[%1];" : "=r"(v) : "r"(a)); return v; }
__device__ __forceinline__ unsigned ld_rlx(const unsigned* p) { unsigned v; asm volatile("ld.relaxed.gpu.global.u32 %0,[%1];" : "=r"(v) : "l"(p) : "memory"); return v; }
__device__ __forceinline__ uint4 ld_rlx4(const void* p) {
  uint4 v; asm volatile("ld.relaxed.gpu.global.v4.u32 {%0,%1,%2,%3},[%4];" : "=r"(v.x), "=r"(v.y), "=r"(v.z), "=r"(v.w) : "l"(p) : "memory"); return v;
}
__device__ __forceinline__ uint2 ld_rlx2(const void* p) { uint2 v; asm volatile("ld.relaxed.gpu.global.v2.u32 {%0,%1},[%2];" : "=r"(v.x), "=r"(v.y) : "l"(p) : "memory"); return v; }
__device__ __forceinline__ void st_rlx2(void* p, uint32_t a, uint32_t b) { asm volatile("st.relaxed.gpu.global.v2.u32 [%0],{%1,%2};" ::"l"(p), "r"(a), "r"(b) : "memory"); }
__device__ __forceinline__ void st_rlx(void* p, uint32_t a) { asm volatile("st.relaxed.gpu.global.u32 [%0],%1;" ::"l"(p), "r"(a) : "memory"); }
#define PUB 15
template <int SITE> __device__ __forceinline__ void release() { if (PUB & SITE) asm volatile("fence.release.gpu;" ::: "memory"); }
__device__ __forceinline__ void signal_flag(unsigned* p, unsigned val) { asm volatile("st.relaxed.gpu.global.u32 [%0],%1;" ::"l"(p), "r"(val) : "memory"); }
__device__ __forceinline__ void signal_cnt(unsigned* p, unsigned n) { asm volatile("red.relaxed.gpu.global.add.u32 [%0],%1;" ::"l"(p), "r"(n) : "memory"); }
__device__ __forceinline__ void wait_flags(const unsigned* p, unsigned val, uint32_t need, uint32_t& ready) {
#pragma unroll 1
  for (int it = 0; (ready & need) != need && it < SPIN; it++) ready = __ballot_sync(0xffffffff, ld_rlx(p) == val);
}
__device__ __forceinline__ void wait_cnt(const unsigned* p, unsigned tgt) {
  asm volatile("{ .reg .pred p; .reg .u32 c; .reg .s32 v; mov.u32 c, 0;\n"
               "W: ld.relaxed.gpu.global.u32 v, [%0]; sub.s32 v, v, %1; setp.ge.s32 p, v, 0; @p bra.uni D;\n"
               "add.u32 c, c, 1; setp.lt.u32 p, c, 0x100000; @p bra.uni W;\nD: }" ::"l"(p), "r"(tgt) : "memory");
}
__device__ __forceinline__ uint32_t pack_bf(float lo, float hi) { uint32_t r; asm("cvt.rn.bf16x2.f32 %0, %1, %2;" : "=r"(r) : "f"(hi), "f"(lo)); return r; }
__device__ __forceinline__ float bf_lo(uint32_t v) { return __uint_as_float(v << 16); }
__device__ __forceinline__ float bf_hi(uint32_t v) { return __uint_as_float(v & 0xffff0000u); }
__device__ __forceinline__ float bf_rn(float x) { return __bfloat162float(__float2bfloat16_rn(x)); }
__device__ __forceinline__ float frcp(float x) { float r; asm("rcp.approx.ftz.f32 %0,%1;" : "=f"(r) : "f"(x)); return r; }
__device__ __forceinline__ float fsqrt(float x) { float r; asm("sqrt.approx.ftz.f32 %0,%1;" : "=f"(r) : "f"(x)); return r; }
__device__ __forceinline__ float frsqrt(float x) { float r; asm("rsqrt.approx.ftz.f32 %0,%1;" : "=f"(r) : "f"(x)); return r; }
__device__ __forceinline__ uint32_t hmul2(uint32_t a, uint32_t b) { uint32_t r; asm("mul.rn.bf16x2 %0,%1,%2;" : "=r"(r) : "r"(a), "r"(b)); return r; }
__device__ __forceinline__ uint32_t hfma2(uint32_t a, uint32_t b, uint32_t c) { uint32_t r; asm("fma.rn.bf16x2 %0,%1,%2,%3;" : "=r"(r) : "r"(a), "r"(b), "r"(c)); return r; }
__device__ __forceinline__ float2 cmul(float2 a, float2 b) { return make_float2(a.x * b.x - a.y * b.y, a.x * b.y + a.y * b.x); }
__device__ __forceinline__ float2 cfma(float2 a, float2 b, float2 c) {
  return make_float2(fmaf(a.x, b.x, fmaf(-a.y, b.y, c.x)), fmaf(a.x, b.y, fmaf(a.y, b.x, c.y)));
}
__device__ __forceinline__ uint32_t tagf(float v, uint32_t tag) { return (__float_as_uint(v) & ~1u) | tag; }
__device__ __forceinline__ float untag(uint32_t v) { return __uint_as_float(v & ~1u); }
__device__ __forceinline__ bool untagged(const uint4& v, uint32_t tag) { return (((v.x ^ tag) | (v.y ^ tag) | (v.z ^ tag) | (v.w ^ tag)) & 1) != 0; }
__device__ __forceinline__ bool untagged(const uint2& v, uint32_t tag) { return (((v.x ^ tag) | (v.y ^ tag)) & 1) != 0; }
__device__ __forceinline__ float2 lam_bar(float lr, float li, float ldt) {
  float dt = bf_rn(expf(ldt)); float e = expf(dt * lr), s, c; sincospif(dt * li * 0.31830988618379067f, &s, &c); return make_float2(e * c, e * s);
}

__device__ __forceinline__ int conv_ch(uint32_t c, int s) { return s * ((c >> 21) & 255) + (c & 255) - (s >= (int)(c >> 29) ? 8 : 0); }
struct Role {
  uint32_t v, c, p;
  __device__ __forceinline__ int tb() const { return v & 15; }
  __device__ __forceinline__ int cb() const { return (v >> 4) & 15; }
  __device__ __forceinline__ int b() const { return (v >> 8) & 255; }
  __device__ __forceinline__ int ubase() const { return (v >> 16) & 7; }
  __device__ __forceinline__ int ugs() const { return (v >> 19) & 7; }
  __device__ __forceinline__ int wpart() const { return (v >> 22) & 7; }
  __device__ __forceinline__ int rank() const { return (v >> 26) & 7; }
  __device__ __forceinline__ int cs() const { return (v >> 29) ? 8 : 2; }
  __device__ __forceinline__ int ch(int s) const { return conv_ch(c, s); }
  __device__ __forceinline__ int wlo() const { return p & 1; }
  __device__ __forceinline__ int whi() const { return (p >> 1) & 1; }
  __device__ __forceinline__ uint32_t wmask() const { return (p >> 2) & 255; }
  __device__ __forceinline__ uint32_t umask() const { return (p >> 10) & 255; }
  __device__ __forceinline__ int uj() const { return (p >> 20) & 31; }
  __device__ __forceinline__ int sm() const { return (p >> 25) & 15; }
  __device__ __forceinline__ int nch() const { return (c >> 10) & 7; }
  __device__ __forceinline__ int nprep() const { return (c >> 13) & 255; }
};

__device__ __forceinline__ void wgmma_ss80(float (&d)[40], uint64_t da, uint64_t db, int sd){
  asm volatile("{ .reg .pred p; setp.ne.b32 p, %42, 0;\n"
   "wgmma.mma_async.sync.aligned.m64n80k16.f32.bf16.bf16 {%0, %1, %2, %3, %4, %5, %6, %7, %8, %9, %10, %11, %12, %13, %14, %15, %16, %17, %18, %19, %20, %21, %22, %23, %24, %25, %26, %27, %28, %29, %30, %31, %32, %33, %34, %35, %36, %37, %38, %39}, %40, %41, p, 1, 1, 0, 0; }\n"
   : "+f"(d[0]), "+f"(d[1]), "+f"(d[2]), "+f"(d[3]), "+f"(d[4]), "+f"(d[5]), "+f"(d[6]), "+f"(d[7]), "+f"(d[8]), "+f"(d[9]), "+f"(d[10]), "+f"(d[11]), "+f"(d[12]), "+f"(d[13]), "+f"(d[14]), "+f"(d[15]), "+f"(d[16]), "+f"(d[17]), "+f"(d[18]), "+f"(d[19]), "+f"(d[20]), "+f"(d[21]), "+f"(d[22]), "+f"(d[23]), "+f"(d[24]), "+f"(d[25]), "+f"(d[26]), "+f"(d[27]), "+f"(d[28]), "+f"(d[29]), "+f"(d[30]), "+f"(d[31]), "+f"(d[32]), "+f"(d[33]), "+f"(d[34]), "+f"(d[35]), "+f"(d[36]), "+f"(d[37]), "+f"(d[38]), "+f"(d[39]) : "l"(da), "l"(db), "r"(sd));
}
__device__ __forceinline__ void wgmma_ss160(float (&d)[80], uint64_t da, uint64_t db, int sd){
  asm volatile("{ .reg .pred p; setp.ne.b32 p, %82, 0;\n"
   "wgmma.mma_async.sync.aligned.m64n160k16.f32.bf16.bf16 {%0, %1, %2, %3, %4, %5, %6, %7, %8, %9, %10, %11, %12, %13, %14, %15, %16, %17, %18, %19, %20, %21, %22, %23, %24, %25, %26, %27, %28, %29, %30, %31, %32, %33, %34, %35, %36, %37, %38, %39, %40, %41, %42, %43, %44, %45, %46, %47, %48, %49, %50, %51, %52, %53, %54, %55, %56, %57, %58, %59, %60, %61, %62, %63, %64, %65, %66, %67, %68, %69, %70, %71, %72, %73, %74, %75, %76, %77, %78, %79}, %80, %81, p, 1, 1, 0, 0; }\n"
   : "+f"(d[0]), "+f"(d[1]), "+f"(d[2]), "+f"(d[3]), "+f"(d[4]), "+f"(d[5]), "+f"(d[6]), "+f"(d[7]), "+f"(d[8]), "+f"(d[9]), "+f"(d[10]), "+f"(d[11]), "+f"(d[12]), "+f"(d[13]), "+f"(d[14]), "+f"(d[15]), "+f"(d[16]), "+f"(d[17]), "+f"(d[18]), "+f"(d[19]), "+f"(d[20]), "+f"(d[21]), "+f"(d[22]), "+f"(d[23]), "+f"(d[24]), "+f"(d[25]), "+f"(d[26]), "+f"(d[27]), "+f"(d[28]), "+f"(d[29]), "+f"(d[30]), "+f"(d[31]), "+f"(d[32]), "+f"(d[33]), "+f"(d[34]), "+f"(d[35]), "+f"(d[36]), "+f"(d[37]), "+f"(d[38]), "+f"(d[39]), "+f"(d[40]), "+f"(d[41]), "+f"(d[42]), "+f"(d[43]), "+f"(d[44]), "+f"(d[45]), "+f"(d[46]), "+f"(d[47]), "+f"(d[48]), "+f"(d[49]), "+f"(d[50]), "+f"(d[51]), "+f"(d[52]), "+f"(d[53]), "+f"(d[54]), "+f"(d[55]), "+f"(d[56]), "+f"(d[57]), "+f"(d[58]), "+f"(d[59]), "+f"(d[60]), "+f"(d[61]), "+f"(d[62]), "+f"(d[63]), "+f"(d[64]), "+f"(d[65]), "+f"(d[66]), "+f"(d[67]), "+f"(d[68]), "+f"(d[69]), "+f"(d[70]), "+f"(d[71]), "+f"(d[72]), "+f"(d[73]), "+f"(d[74]), "+f"(d[75]), "+f"(d[76]), "+f"(d[77]), "+f"(d[78]), "+f"(d[79]) : "l"(da), "l"(db), "r"(sd));
}
template<int N> __device__ __forceinline__ void wgmma_rs(float (&d)[N/2], uint32_t a0, uint32_t a1, uint32_t a2, uint32_t a3, uint64_t db, int sd);
template<> __device__ __forceinline__ void wgmma_rs<16>(float (&d)[8], uint32_t a0, uint32_t a1, uint32_t a2, uint32_t a3, uint64_t db, int sd){
  asm volatile("{ .reg .pred p; setp.ne.b32 p, %13, 0;\n"
   "wgmma.mma_async.sync.aligned.m64n16k16.f32.bf16.bf16 {%0, %1, %2, %3, %4, %5, %6, %7}, {%8,%9,%10,%11}, %12, p, 1, 1, 0; }\n"
   : "+f"(d[0]), "+f"(d[1]), "+f"(d[2]), "+f"(d[3]), "+f"(d[4]), "+f"(d[5]), "+f"(d[6]), "+f"(d[7]) : "r"(a0), "r"(a1), "r"(a2), "r"(a3), "l"(db), "r"(sd));
}
template<> __device__ __forceinline__ void wgmma_rs<32>(float (&d)[16], uint32_t a0, uint32_t a1, uint32_t a2, uint32_t a3, uint64_t db, int sd){
  asm volatile("{ .reg .pred p; setp.ne.b32 p, %21, 0;\n"
   "wgmma.mma_async.sync.aligned.m64n32k16.f32.bf16.bf16 {%0, %1, %2, %3, %4, %5, %6, %7, %8, %9, %10, %11, %12, %13, %14, %15}, {%16,%17,%18,%19}, %20, p, 1, 1, 0; }\n"
   : "+f"(d[0]), "+f"(d[1]), "+f"(d[2]), "+f"(d[3]), "+f"(d[4]), "+f"(d[5]), "+f"(d[6]), "+f"(d[7]), "+f"(d[8]), "+f"(d[9]), "+f"(d[10]), "+f"(d[11]), "+f"(d[12]), "+f"(d[13]), "+f"(d[14]), "+f"(d[15]) : "r"(a0), "r"(a1), "r"(a2), "r"(a3), "l"(db), "r"(sd));
}
template<> __device__ __forceinline__ void wgmma_rs<48>(float (&d)[24], uint32_t a0, uint32_t a1, uint32_t a2, uint32_t a3, uint64_t db, int sd){
  asm volatile("{ .reg .pred p; setp.ne.b32 p, %29, 0;\n"
   "wgmma.mma_async.sync.aligned.m64n48k16.f32.bf16.bf16 {%0, %1, %2, %3, %4, %5, %6, %7, %8, %9, %10, %11, %12, %13, %14, %15, %16, %17, %18, %19, %20, %21, %22, %23}, {%24,%25,%26,%27}, %28, p, 1, 1, 0; }\n"
   : "+f"(d[0]), "+f"(d[1]), "+f"(d[2]), "+f"(d[3]), "+f"(d[4]), "+f"(d[5]), "+f"(d[6]), "+f"(d[7]), "+f"(d[8]), "+f"(d[9]), "+f"(d[10]), "+f"(d[11]), "+f"(d[12]), "+f"(d[13]), "+f"(d[14]), "+f"(d[15]), "+f"(d[16]), "+f"(d[17]), "+f"(d[18]), "+f"(d[19]), "+f"(d[20]), "+f"(d[21]), "+f"(d[22]), "+f"(d[23]) : "r"(a0), "r"(a1), "r"(a2), "r"(a3), "l"(db), "r"(sd));
}
template<> __device__ __forceinline__ void wgmma_rs<64>(float (&d)[32], uint32_t a0, uint32_t a1, uint32_t a2, uint32_t a3, uint64_t db, int sd){
  asm volatile("{ .reg .pred p; setp.ne.b32 p, %37, 0;\n"
   "wgmma.mma_async.sync.aligned.m64n64k16.f32.bf16.bf16 {%0, %1, %2, %3, %4, %5, %6, %7, %8, %9, %10, %11, %12, %13, %14, %15, %16, %17, %18, %19, %20, %21, %22, %23, %24, %25, %26, %27, %28, %29, %30, %31}, {%32,%33,%34,%35}, %36, p, 1, 1, 0; }\n"
   : "+f"(d[0]), "+f"(d[1]), "+f"(d[2]), "+f"(d[3]), "+f"(d[4]), "+f"(d[5]), "+f"(d[6]), "+f"(d[7]), "+f"(d[8]), "+f"(d[9]), "+f"(d[10]), "+f"(d[11]), "+f"(d[12]), "+f"(d[13]), "+f"(d[14]), "+f"(d[15]), "+f"(d[16]), "+f"(d[17]), "+f"(d[18]), "+f"(d[19]), "+f"(d[20]), "+f"(d[21]), "+f"(d[22]), "+f"(d[23]), "+f"(d[24]), "+f"(d[25]), "+f"(d[26]), "+f"(d[27]), "+f"(d[28]), "+f"(d[29]), "+f"(d[30]), "+f"(d[31]) : "r"(a0), "r"(a1), "r"(a2), "r"(a3), "l"(db), "r"(sd));
}
template<> __device__ __forceinline__ void wgmma_rs<80>(float (&d)[40], uint32_t a0, uint32_t a1, uint32_t a2, uint32_t a3, uint64_t db, int sd){
  asm volatile("{ .reg .pred p; setp.ne.b32 p, %45, 0;\n"
   "wgmma.mma_async.sync.aligned.m64n80k16.f32.bf16.bf16 {%0, %1, %2, %3, %4, %5, %6, %7, %8, %9, %10, %11, %12, %13, %14, %15, %16, %17, %18, %19, %20, %21, %22, %23, %24, %25, %26, %27, %28, %29, %30, %31, %32, %33, %34, %35, %36, %37, %38, %39}, {%40,%41,%42,%43}, %44, p, 1, 1, 0; }\n"
   : "+f"(d[0]), "+f"(d[1]), "+f"(d[2]), "+f"(d[3]), "+f"(d[4]), "+f"(d[5]), "+f"(d[6]), "+f"(d[7]), "+f"(d[8]), "+f"(d[9]), "+f"(d[10]), "+f"(d[11]), "+f"(d[12]), "+f"(d[13]), "+f"(d[14]), "+f"(d[15]), "+f"(d[16]), "+f"(d[17]), "+f"(d[18]), "+f"(d[19]), "+f"(d[20]), "+f"(d[21]), "+f"(d[22]), "+f"(d[23]), "+f"(d[24]), "+f"(d[25]), "+f"(d[26]), "+f"(d[27]), "+f"(d[28]), "+f"(d[29]), "+f"(d[30]), "+f"(d[31]), "+f"(d[32]), "+f"(d[33]), "+f"(d[34]), "+f"(d[35]), "+f"(d[36]), "+f"(d[37]), "+f"(d[38]), "+f"(d[39]) : "r"(a0), "r"(a1), "r"(a2), "r"(a3), "l"(db), "r"(sd));
}
template<> __device__ __forceinline__ void wgmma_rs<96>(float (&d)[48], uint32_t a0, uint32_t a1, uint32_t a2, uint32_t a3, uint64_t db, int sd){
  asm volatile("{ .reg .pred p; setp.ne.b32 p, %53, 0;\n"
   "wgmma.mma_async.sync.aligned.m64n96k16.f32.bf16.bf16 {%0, %1, %2, %3, %4, %5, %6, %7, %8, %9, %10, %11, %12, %13, %14, %15, %16, %17, %18, %19, %20, %21, %22, %23, %24, %25, %26, %27, %28, %29, %30, %31, %32, %33, %34, %35, %36, %37, %38, %39, %40, %41, %42, %43, %44, %45, %46, %47}, {%48,%49,%50,%51}, %52, p, 1, 1, 0; }\n"
   : "+f"(d[0]), "+f"(d[1]), "+f"(d[2]), "+f"(d[3]), "+f"(d[4]), "+f"(d[5]), "+f"(d[6]), "+f"(d[7]), "+f"(d[8]), "+f"(d[9]), "+f"(d[10]), "+f"(d[11]), "+f"(d[12]), "+f"(d[13]), "+f"(d[14]), "+f"(d[15]), "+f"(d[16]), "+f"(d[17]), "+f"(d[18]), "+f"(d[19]), "+f"(d[20]), "+f"(d[21]), "+f"(d[22]), "+f"(d[23]), "+f"(d[24]), "+f"(d[25]), "+f"(d[26]), "+f"(d[27]), "+f"(d[28]), "+f"(d[29]), "+f"(d[30]), "+f"(d[31]), "+f"(d[32]), "+f"(d[33]), "+f"(d[34]), "+f"(d[35]), "+f"(d[36]), "+f"(d[37]), "+f"(d[38]), "+f"(d[39]), "+f"(d[40]), "+f"(d[41]), "+f"(d[42]), "+f"(d[43]), "+f"(d[44]), "+f"(d[45]), "+f"(d[46]), "+f"(d[47]) : "r"(a0), "r"(a1), "r"(a2), "r"(a3), "l"(db), "r"(sd));
}
template<> __device__ __forceinline__ void wgmma_rs<112>(float (&d)[56], uint32_t a0, uint32_t a1, uint32_t a2, uint32_t a3, uint64_t db, int sd){
  asm volatile("{ .reg .pred p; setp.ne.b32 p, %61, 0;\n"
   "wgmma.mma_async.sync.aligned.m64n112k16.f32.bf16.bf16 {%0, %1, %2, %3, %4, %5, %6, %7, %8, %9, %10, %11, %12, %13, %14, %15, %16, %17, %18, %19, %20, %21, %22, %23, %24, %25, %26, %27, %28, %29, %30, %31, %32, %33, %34, %35, %36, %37, %38, %39, %40, %41, %42, %43, %44, %45, %46, %47, %48, %49, %50, %51, %52, %53, %54, %55}, {%56,%57,%58,%59}, %60, p, 1, 1, 0; }\n"
   : "+f"(d[0]), "+f"(d[1]), "+f"(d[2]), "+f"(d[3]), "+f"(d[4]), "+f"(d[5]), "+f"(d[6]), "+f"(d[7]), "+f"(d[8]), "+f"(d[9]), "+f"(d[10]), "+f"(d[11]), "+f"(d[12]), "+f"(d[13]), "+f"(d[14]), "+f"(d[15]), "+f"(d[16]), "+f"(d[17]), "+f"(d[18]), "+f"(d[19]), "+f"(d[20]), "+f"(d[21]), "+f"(d[22]), "+f"(d[23]), "+f"(d[24]), "+f"(d[25]), "+f"(d[26]), "+f"(d[27]), "+f"(d[28]), "+f"(d[29]), "+f"(d[30]), "+f"(d[31]), "+f"(d[32]), "+f"(d[33]), "+f"(d[34]), "+f"(d[35]), "+f"(d[36]), "+f"(d[37]), "+f"(d[38]), "+f"(d[39]), "+f"(d[40]), "+f"(d[41]), "+f"(d[42]), "+f"(d[43]), "+f"(d[44]), "+f"(d[45]), "+f"(d[46]), "+f"(d[47]), "+f"(d[48]), "+f"(d[49]), "+f"(d[50]), "+f"(d[51]), "+f"(d[52]), "+f"(d[53]), "+f"(d[54]), "+f"(d[55]) : "r"(a0), "r"(a1), "r"(a2), "r"(a3), "l"(db), "r"(sd));
}
template<> __device__ __forceinline__ void wgmma_rs<128>(float (&d)[64], uint32_t a0, uint32_t a1, uint32_t a2, uint32_t a3, uint64_t db, int sd){
  asm volatile("{ .reg .pred p; setp.ne.b32 p, %69, 0;\n"
   "wgmma.mma_async.sync.aligned.m64n128k16.f32.bf16.bf16 {%0, %1, %2, %3, %4, %5, %6, %7, %8, %9, %10, %11, %12, %13, %14, %15, %16, %17, %18, %19, %20, %21, %22, %23, %24, %25, %26, %27, %28, %29, %30, %31, %32, %33, %34, %35, %36, %37, %38, %39, %40, %41, %42, %43, %44, %45, %46, %47, %48, %49, %50, %51, %52, %53, %54, %55, %56, %57, %58, %59, %60, %61, %62, %63}, {%64,%65,%66,%67}, %68, p, 1, 1, 0; }\n"
   : "+f"(d[0]), "+f"(d[1]), "+f"(d[2]), "+f"(d[3]), "+f"(d[4]), "+f"(d[5]), "+f"(d[6]), "+f"(d[7]), "+f"(d[8]), "+f"(d[9]), "+f"(d[10]), "+f"(d[11]), "+f"(d[12]), "+f"(d[13]), "+f"(d[14]), "+f"(d[15]), "+f"(d[16]), "+f"(d[17]), "+f"(d[18]), "+f"(d[19]), "+f"(d[20]), "+f"(d[21]), "+f"(d[22]), "+f"(d[23]), "+f"(d[24]), "+f"(d[25]), "+f"(d[26]), "+f"(d[27]), "+f"(d[28]), "+f"(d[29]), "+f"(d[30]), "+f"(d[31]), "+f"(d[32]), "+f"(d[33]), "+f"(d[34]), "+f"(d[35]), "+f"(d[36]), "+f"(d[37]), "+f"(d[38]), "+f"(d[39]), "+f"(d[40]), "+f"(d[41]), "+f"(d[42]), "+f"(d[43]), "+f"(d[44]), "+f"(d[45]), "+f"(d[46]), "+f"(d[47]), "+f"(d[48]), "+f"(d[49]), "+f"(d[50]), "+f"(d[51]), "+f"(d[52]), "+f"(d[53]), "+f"(d[54]), "+f"(d[55]), "+f"(d[56]), "+f"(d[57]), "+f"(d[58]), "+f"(d[59]), "+f"(d[60]), "+f"(d[61]), "+f"(d[62]), "+f"(d[63]) : "r"(a0), "r"(a1), "r"(a2), "r"(a3), "l"(db), "r"(sd));
}

#define BAR(i) (bars + 8u * (uint32_t)(i))

template <int G> __device__ __forceinline__ void conv_frags(uint32_t (&a)[12], uint32_t abase) {
#pragma unroll
  for (int i = 0; i < 12; i++) a[i] = lds32(abase + (G * 4 + i / 3) * 128 + (i % 3) * 4);
}
__device__ __forceinline__ void kv_prefetch(const __nv_bfloat16* pf, int task) { prefetch_if(pf + 64 * (task & 31) * DM + 64 * (task >> 5), task < 320); }
__device__ __forceinline__ void kv_load(const Params& P, Scratch* S, int task, int tid, uint32_t (&k_)[19], uint32_t (&v_)[16], uint4& sk) {
  const int row = 64 * (task & 31) + 16 * (tid >> 5), ch = 64 * (task >> 5) + 2 * (tid & 31);
  const uint32_t* kp = (const uint32_t*)(P.k + (size_t)row * DM + ch);
  const uint32_t* vp = (const uint32_t*)(P.v + (size_t)row * DM + ch);
  const uint32_t* hp = row > 0 ? kp - 3 * (DM / 2) : S->zero;
  const int hs = row > 0 ? DM / 2 : 0;
  asm volatile("ld.global.nc.v4.u32 {%0,%1,%2,%3},[%4];" : "=r"(sk.x), "=r"(sk.y), "=r"(sk.z), "=r"(sk.w) : "l"(P.shk + ch * 4));
#pragma unroll
  for (int i = 0; i < 3; i++) k_[i] = ldg1(hp + i * hs);
#pragma unroll
  for (int i = 0; i < 16; i++) { k_[i + 3] = ldg1(kp + i * (DM / 2)); v_[i] = ldg1(vp + i * (DM / 2)); }
}
template <int SH> __device__ __forceinline__ void xb_prefetch(const Head& H, int id, int tid, int c0) {
  const int ri = tid >> SH, rr = 11 * id + ri - 16;
  const __nv_bfloat16* p = ri < 16 ? H.x + (size_t)(16 * min(id, 127) + ri) * DM : (rr < DM ? H.b0 : H.b1 - DM * DM) + (size_t)rr * DM;
  prefetch_if(p + c0 + 64 * (tid & ((1 << SH) - 1)), ri < 16 || (ri < 27 && rr < 2 * DM));
}
__device__ __forceinline__ uint4 ldg4(const void* p) { uint4 v; asm volatile("ld.global.nc.v4.u32 {%0,%1,%2,%3},[%4];" : "=r"(v.x), "=r"(v.y), "=r"(v.z), "=r"(v.w) : "l"(p)); return v; }
__device__ __forceinline__ uint4 lds4(uint32_t a) { uint4 v; asm volatile("ld.shared.v4.u32 {%0,%1,%2,%3},[%4];" : "=r"(v.x), "=r"(v.y), "=r"(v.z), "=r"(v.w) : "r"(a) : "memory"); return v; }
__device__ __forceinline__ void discretise(const Head& H, const Params& P, uint32_t sb, Role R, int lane, uint32_t e1) {
  const uint32_t dn = __ldg((const unsigned short*)P.ssmd + min(conv_ch(R.c, (lane + 7) & 7), DM - 1));
  const int c = 32 * min(R.cb(), 9) + lane;
  const uint32_t lr2 = ldg1(P.lre + 2 * c), li2 = ldg1(P.lim + 2 * c), ld2 = ldg1(P.ldt + 2 * c);
  asm volatile("st.shared.u32 [%0],%1;" ::"r"(sb + MISC_OFF + 4 * (lane & 7)), "r"((lane & 7) ? dn : e1) : "memory");
#pragma unroll 1
  for (int i = 0; i < 2; i++) {
    const float lr = bf_hi(lr2 << (16 - 16 * i)), li = bf_hi(li2 << (16 - 16 * i));
    const float2 lb = lam_bar(lr, li, bf_hi(ld2 << (16 - 16 * i)));
    const float nx = lb.x - 1.f, ny = lb.y, inv = 2.f * frcp(lr * lr + li * li), cx = (nx * lr + ny * li) * inv, cy = (ny * lr - nx * li) * inv;
    const bool sw = !H.swap;
    asm volatile("st.shared.v4.f32 [%0],{%1,%2,%3,%4};" ::"r"(sb + LAM_OFF + 32 * lane + 16 * i), "f"(lb.x), "f"(sw ? -lb.y : lb.y), "f"(sw ? -cy : cx), "f"(sw ? cx : -cy) : "memory");
  }
  __syncwarp();
}
__device__ __forceinline__ void aux_prep(const Head& H, const Params& P, uint32_t sb, Role R, int tid, long long t_start) {
  Scratch* const S = H.s;
  const uint32_t bars = sb + BAR_OFF;
  tid = opaque(tid);
  const int w = tid >> 5, lane = tid & 31, tb = R.tb(), cb = R.cb();
  uint32_t k_[19], v_[16];
  uint4 sk;
  int task = R.b() < R.nprep() ? R.b() : 320;
  delay(KVDLY);
  PROFC(tid == 0, 345);
  kv_load(P, S, min(task, 319), tid, k_, v_, sk);
  const __nv_bfloat16* pf = (tid < 64 ? P.k : P.v) + (tid & 63) * DM;
  const int j = lane >> 3, sm = min(R.sm(), 9), trow = 160 * tb + 4 * sm + (tb < 12 ? 40 : 32) * w + j;
  const uint32_t so = sb + (2 * w + (j & 1) + 8 * (j >> 1)) * 128 + 16 * (lane & 7), xo = so + sm * 2048, wo = so + (tb & 1) * 8192 + (tb & 6) * 1024;
  const __nv_bfloat16* xp = H.x + (size_t)min(trow, SEQ - 1) * DM + 384 + 8 * (lane & 7);
  const __nv_bfloat16* bp = (j < 2 ? H.b0 : H.b1) + (size_t)(64 * cb + 32 * (tb & 1) + 4 * (tb & 6) + 2 * w + (j & 1)) * DM + 384 + 8 * (lane & 7);
  float s = 0.f, s2 = 0.f, sr = 0.f;
#define STAT(m, n) { const uint32_t xw[4] = {m.x, m.y, m.z, m.w}, bw[4] = {n.x, n.y, n.z, n.w}; \
  _Pragma("unroll") for (int i = 0; i < 4; i++) { const float u = bf_lo(xw[i]), v = bf_hi(xw[i]); s += u + v; s2 = fmaf(u, u, fmaf(v, v, s2)); sr += bf_lo(bw[i]) + bf_hi(bw[i]); } }
#define STATS(K0, K1) _Pragma("unroll 1") for (int kb = K0; kb < K1; kb++) { \
    mbar_wait(BAR(B_F1 + kb)); \
    const uint4 a = lds4(xo + ((uint32_t)(XTAB0 >> (6 * kb)) & 63) * 4096), c = lds4(wo + ((uint32_t)(WTAB0 >> (6 * kb)) & 63) * 4096); \
    STAT(a, c) \
    asm volatile("" : "+f"(s), "+f"(s2), "+f"(sr)); \
    if (XPFAT >= K0 && XPFAT < K1) prefetch_if(((lane & 4) ? bp : xp) + 64 * (lane & 3), kb == XPFAT); \
    kv_prefetch(pf, kb == KPFAT ? task + R.nprep() : kb == KPFAT2 ? task + 2 * R.nprep() : 320); \
  } \
  __syncwarp(); mbar_arrive_if(BAR(B_AX + K0 / 3), lane == 0);
  STATS(0, 3)
  PROFC(tid == 0, 349);
    {
      uint4 m[4], n[4];
#pragma unroll
      for (int i = 0; i < 4; i++) { m[i] = ldg4(xp + 64 * i); n[i] = ldg4(bp + 64 * i); }
      STATS(3, 6)
      PROFC(tid == 0, 346);
      mbar_wait(BAR(B_LM));
      const uint32_t tag = lds32(sb + MISC_OFF) & 1;
#pragma unroll
      for (int i = 0; i < 4; i++) { const uint4 a = m[i], c = n[i]; STAT(a, c) }
      PROFC(tid == 0 && s2 != 1.2345f, 347);
#pragma unroll
      for (int o = 1; o <= 4; o <<= 1) { s += __shfl_xor_sync(0xffffffff, s, o); s2 += __shfl_xor_sync(0xffffffff, s2, o); sr += __shfl_xor_sync(0xffffffff, sr, o); }
      const float mn = s * (1.f / DM), rs = frcp(bf_rn(fsqrt(bf_rn(bf_rn(fmaxf(s2 * (1.f / DM) - mn * mn, 0.f)) + 1e-5f))));
      asm volatile("{ .reg .pred p; setp.ne.u32 p, %2, 0; @p st.relaxed.gpu.global.u32 [%0],%1; }"
                   ::"l"((uint32_t*)(S->RS + (8 * cb + 4 * (tb & 1) + (tb >> 1)) * 16 + 4 * w + (j & 1)) + (lane & 4) + (j >> 1)), "r"(tagf(sr, tag)),
                   "r"((uint32_t)(tb < 8 && (lane & 3) == 0)) : "memory");
      asm volatile("{ .reg .pred p; setp.ne.u32 p, %3, 0; @p st.relaxed.gpu.global.v2.u32 [%0],{%1,%2}; }"
                   ::"l"(S->S + trow), "r"(tagf(rs, tag)), "r"(tagf(-bf_rn(mn) * rs, tag)), "r"((uint32_t)(R.sm() < 10 && (lane & 7) == 0)) : "memory");
      PROFC(tid == 0, 3);
    }
#pragma unroll 1
  for (int r = 0; task < 320; r++) {
    {
      const uint32_t T0 = __byte_perm(sk.x, sk.z, 0x5410), T1 = __byte_perm(sk.x, sk.z, 0x7632);
      const uint32_t T2 = __byte_perm(sk.y, sk.w, 0x5410), T3 = __byte_perm(sk.y, sk.w, 0x7632);
      PROFC(tid == 0 && v_[15] != 0x12345, 336 + r);
      uint32_t o[16];
#pragma unroll
      for (int t = 0; t < 16; t += 2) {
        const uint32_t a = hmul2(hfma2(k_[t + 3], T0, hfma2(k_[t + 2], T1, hfma2(k_[t + 1], T2, hmul2(k_[t], T3)))), v_[t]);
        const uint32_t c = hmul2(hfma2(k_[t + 4], T0, hfma2(k_[t + 3], T1, hfma2(k_[t + 2], T2, hmul2(k_[t + 1], T3)))), v_[t + 1]);
        const int wd = ((7 - t / 2) >> 1) + 4 * ((7 - t / 2) & 1);
        o[wd] = __byte_perm(c, a, 0x5410); o[8 + wd] = __byte_perm(c, a, 0x7632);
        asm volatile("" : "+r"(o[wd]), "+r"(o[8 + wd]));
        if (t == PFAT) kv_prefetch(pf, task + (1 + PFD) * R.nprep());
      }
      PROFC(tid == 0, 330 + 2 * r);
      const int ph = task & 1;
      task += R.nprep();
      if (ORD == 0 && task < 320) kv_load(P, S, task, tid, k_, v_, sk);
      mbar_wait(BAR(B_E1 + 3)); mbar_wait(BAR(B_AX + 1));
#pragma unroll
      for (int i = 0; i < 4; i++) {
        const int row = 2 * lane + (i >> 1);
        asm volatile("st.shared.v4.u32 [%0],{%1,%2,%3,%4};" ::"r"(sb + KS_OFF + r * 8192 + row * 128 + (((2 * w + ((i & 1) ^ ph)) ^ (row & 7)) << 4)),
                     "r"(o[4 * i]), "r"(o[4 * i + 1]), "r"(o[4 * i + 2]), "r"(o[4 * i + 3]) : "memory");
      }
      __syncwarp();
      mbar_arrive_if(BAR(B_PS + r), lane == 0);
      PROFC(tid == 0, 331 + 2 * r);
      if (ORD == 1 && task < 320) kv_load(P, S, task, tid, k_, v_, sk);
    }
  }
#undef STAT
#undef STATS
  PROFC(tid == 0, 40);
}
#define SPLIT(G) asm volatile("{ .reg .pred p; .reg .u32 r; L: mov.u32 r, %%clock; setp.eq.u32 p, r, %0; @p bra.uni L; }" ::"n"(G) : "memory")
template <bool AUX>
__device__ __forceinline__ void conv_loop(uint32_t sb, uint32_t rc, int wg, int tid, long long t_start) {
  sb = opaque(sb); rc = opaque(rc);
  const uint32_t bars = sb + BAR_OFF;
  int slot = AUX ? 0 : wg + 1;
  mbar_wait(BAR(B_LM));
#pragma unroll 1
  while (slot < (int)((rc >> 10) & 7)) {
    tid = opaque(tid);
    const int w = tid >> 5, lane = tid & 31, g = lane >> 2, q = lane & 3;
    const uint32_t Dn = lds32(sb + MISC_OFF + 4 + 4 * slot);
    const uint32_t d0 = (g == 1 && q == 3 - w) ? Dn : 0, d1 = (g == 0 && q == 3 - w) ? Dn : 0;
    const uint32_t cb_ = conv_buf(sb, slot), c0 = cb_ + KC_OFS;
    const uint32_t abase = c0 + 2 * (2 * (g & 1) + 4 * w + 16 * (g >> 1) + 4 * q);
    const uint64_t bd = make_desc(cb_ + KV_PAD, 16, 256, 3);
    const bool hi = lane & 16, s1 = lane & 8;
    const int qo = hi ? (q + 1) & 3 : q;
    const int srcA = hi ? (lane & 12) | ((q + 1) & 3) : (lane & 12) | 16 | ((q + 3) & 3);
    const bool h3 = hi && q == 3, wrap = s1 && qo == 3, back = wrap && hi;
    const bool chi = wrap ? !hi : hi;
    const int cq = s1 ? (qo + 1) & 3 : qo;
    const int srcB = (lane & 4) | (s1 ? 0 : 8) | (chi ? 16 | ((cq + 3) & 3) : cq);
    const uint32_t gp = c0 + ((32 * (2 * w + (g & 1)) + (chi ? 256 : 0)) ^ (chi ? 64 : 0) ^ ((conv_ch(rc, slot) & 8) << 2)) + 4 * (2 * cq + (s1 ? 0 : 1));
    uint32_t a[12], f[16], o[8];
    float S[4], T[4], U[2], keep[2], pv[2] = {0.f, 0.f}, pr[4] = {0.f, 0.f, 0.f, 0.f};
    float e0[64], e1[56], e2[48], e3[40], e4[32], e5[24], e6[16], e7[8];
#define UNR _Pragma("unroll")
#define PERM() UNR for (int i = 0; i < 4; i++) { f[4 * i] = __byte_perm(a[3 * i], a[3 * i + 1], 0x5432); f[4 * i + 1] = a[3 * i + 1]; \
                                                 f[4 * i + 2] = __byte_perm(a[3 * i + 1], a[3 * i + 2], 0x5432); f[4 * i + 3] = a[3 * i + 2]; }
#define MMA(N, E) UNR for (int i = 0; i < 4; i++) wgmma_rs<N>(E, f[4 * i], f[4 * i + 1], f[4 * i + 2], f[4 * i + 3], bd - 8 * i, 1); wg_commit();
#define L1(c) UNR for (int i = 0; i < 4; i++) { const float ev = c[i], od = c[4 + i]; S[i] = hi ? (h3 ? ev : od) : ev; \
                                                T[i] = __shfl_sync(0xffffffff, hi ? (h3 ? pr[i] : ev) : od, srcA); pr[i] = od; }
#define L1E() UNR for (int i = 0; i < 4; i++) S[i] += T[i];
#define L2() UNR for (int h = 0; h < 2; h++) { keep[h] = back ? pv[h] : S[2 * h + 1]; pv[h] = S[2 * h + 1]; U[h] = __shfl_sync(0xffffffff, S[2 * h], srcB); }
#define L2E(j) o[j] = pack_bf(keep[0] + U[0], keep[1] + U[1]);
#define GRP(G, N, P, E) UNR for (int i = 0; i < N / 2; i++) asm volatile("mov.b32 %0,%1;" : "=f"(E[i]) : "f"(P[i + 8])); \
    wg_fence(); if (G < 7) conv_frags<(G + 1) & 7>(a, abase); if (G >= 2) { L2() } L1(P) MMA(N, E) SPLIT(G); \
    if (G < 7) { PERM() } if (G >= 2) { L2E((G + 6) & 7) } L1E() wg_wait<0>(); fence_regs(E);
    PROFC(tid == 0, 300 + 4 * slot);
    mbar_wait(BAR(B_KF + slot));
    if (tid == 0) PROF(361 + slot);
    PROFC(tid == 0, 301 + 4 * slot);
    conv_frags<0>(a, abase);
    wg_fence();
    wgmma_rs<128>(e0, d0 << 16, d0, d1 << 16, d1, bd, 0);
    PERM() conv_frags<1>(a, abase); wg_fence(); MMA(128, e0) SPLIT(0); PERM() wg_wait<0>(); fence_regs(e0);
    GRP(1, 112, e0, e1) GRP(2, 96, e1, e2) GRP(3, 80, e2, e3) GRP(4, 64, e3, e4) GRP(5, 48, e4, e5) GRP(6, 32, e5, e6) GRP(7, 16, e6, e7)
    PROFC(tid == 0, 302 + 4 * slot);
    L2() L1(e7) L2E(6) L1E() L2() L2E(7)
    bar_sync(wg + 1, 128);
#pragma unroll
    for (int jj = 0; jj < 8; jj++) asm volatile("st.shared.u32 [%0],%1;" ::"r"(gp + jj * 512), "r"(o[jj]) : "memory");
#undef PERM
#undef MMA
#undef L1
#undef L1E
#undef L2
#undef L2E
#undef GRP
    PROFC(tid == 0, 303 + 4 * slot);
    __syncwarp();
    if (lane == 0) mbar_arrive(BAR(B_GS + slot));
    if (!AUX) break;
    slot = slot ? slot + 1 : 3;
  }
}

#define IDX(J, c, h) (8 * (J) + 4 * ((c) >> 1) + 2 * (h) + ((c) & 1))
__device__ __forceinline__ uint2 lds2(uint32_t a) { uint2 v; asm volatile("ld.shared.v2.u32 {%0,%1},[%2];" : "=r"(v.x), "=r"(v.y) : "r"(a) : "memory"); return v; }
__device__ __forceinline__ void resid_load(float (&r)[40], uint32_t sb, int wg, int tid, const uint4& s) {
  const uint32_t dp = sb + XR_OFF + 8 * (tid & 3), xp = dp + (64 * wg + 16 * (tid >> 5) + ((tid & 31) >> 2)) * 160;
#pragma unroll
  for (int J = 0; J < 5; J++) {
    const uint2 u = lds2(xp + 32 * J), v = lds2(xp + 32 * J + 1280), d = lds2(dp + 20480 + 32 * J);
    r[8 * J] = __uint_as_float(u.x); r[8 * J + 1] = __uint_as_float(u.y); r[8 * J + 2] = __uint_as_float(v.x); r[8 * J + 3] = __uint_as_float(v.y);
    r[8 * J + 4] = __uint_as_float(d.x); r[8 * J + 5] = __uint_as_float(d.y);
  }
  r[30] = untag(s.x); r[31] = untag(s.y); r[38] = untag(s.z); r[39] = untag(s.w);
}
__device__ __forceinline__ void resid_init(float (&r)[40]) {
  const float s[4] = {r[30], r[31], r[38], r[39]};
#pragma unroll
  for (int J = 0; J < 5; J++) {
    uint32_t w[6];
#pragma unroll
    for (int i = 0; i < 6; i++) w[i] = __float_as_uint(r[8 * J + i]);
#pragma unroll
    for (int i = 0; i < 4; i++) {
      const int h = i >> 1, c = 2 * (i & 1);
      const float rs = s[2 * h], nm = s[2 * h + 1], x0 = bf_lo(w[i]), x1 = bf_hi(w[i]);
      const uint32_t t = hmul2(pack_bf(fmaf(x0, rs, nm), fmaf(x1, rs, nm)), w[4 + (i & 1)]);
      r[IDX(J, c, h)] = x0 + bf_lo(t); r[IDX(J, c + 1, h)] = x1 + bf_hi(t);
    }
  }
}

__device__ __forceinline__ float flip(float v, uint32_t m) { return __uint_as_float(__float_as_uint(v) ^ m); }
__device__ __forceinline__ void g1_phase(const int LY, const Head& H, uint32_t sb, int wg, int tid, Role R, float (&xr)[40], long long t_start) {
  Scratch* const S = H.s;
  tid = opaque(tid); sb = opaque(sb); R.v = opaque(R.v);
  const uint32_t bars = sb + BAR_OFF;
  const int cb = R.cb(), tb = R.tb();
  const int w = tid >> 5, lane = tid & 31, g = lane >> 2, q = lane & 3;
  const bool full = tb < 12;
  uint2* Eb = S->E + ((LY * 130 + cb) * 8 + 4 * wg + w) * 16 + g;
  float a[80];
#pragma unroll
  for (int i = 0; i < 80; i++) a[i] = 0.f;
  uint32_t rel = mapa(BAR(B_E1), lane ? R.wpart() : R.ubase() + (w & (R.ugs() - 1)));
  const bool rels = lane == 0 || (tid == 1 && wg != R.wlo());
  {
    uint64_t tw = LY ? WTAB1 : WTAB0, tx = LY ? XTAB1 : XTAB0;
    uint32_t bf = BAR(B_F1);
    if (tid == 0 && wg == 0 && !LY) PROF(351);
    fence_regs(a);
    mbar_wait(bf, LY);
    if (tid == 0 && wg == 0) PROF(LY ? 20 : 4);
#pragma unroll 1
    for (int kb = 0; kb < 10; kb++) {
      const uint64_t da = make_desc(sb + ((uint32_t)tw & 63) * 4096 + wg * 8192, 16, 1024, 1);
      const uint64_t db = make_desc(sb + ((uint32_t)tx & 63) * 4096, 16, 1024, 1);
      wg_fence();
#pragma unroll
      for (int kk = 0; kk < 4; kk++) wgmma_ss160(a, da + 2 * kk, db + 2 * kk, 1);
      wg_commit();
      wg_wait<1>();
      if (kb > 0) { if (rels) mbar_arrive_at(rel); rel += 8; }
      bf += 8; tw >>= 6; tx >>= 6;
      if (kb < 9) mbar_wait(bf, LY);
    }
  }
  if (tid == 0 && wg == 0) PROF(LY ? 19 : 2);
  mbar_wait(BAR(B_LM));
  const uint32_t tag = lds32(sb + MISC_OFF) & 1;
  if (q == 3) st_rlx2(Eb + tb * 1280, tag ^ 1, tag ^ 1);
  float2 lam, mu, mu2;
  float rs0, rs1;
  const uint32_t lamp = sb + LAM_OFF + 16 * (32 * wg + 8 * w + g);
  {
    const uint2* rp = S->RS + (8 * cb + 4 * wg + w) * 16 + 2 * g - (g & 1);
    uint2 v = ld_rlx2(rp);
    asm volatile("ld.shared.v2.f32 {%0,%1},[%2];" : "=f"(lam.x), "=f"(lam.y) : "r"(lamp));
    const float2 l2 = cmul(lam, lam), l4 = cmul(l2, l2), l8 = cmul(l4, l4), l16 = cmul(l8, l8), l32 = cmul(l16, l16);
    mu = full ? cmul(l32, l8) : l32; mu2 = cmul(mu, mu);
#pragma unroll 1
    for (int it = 0; it < SPIN && __any_sync(0xffffffff, untagged(v, tag)); it++) v = ld_rlx2(rp);
    rs0 = untag(v.x); rs1 = untag(v.y);
  }
  if (tid == 0 && wg == 0 && !LY) PROF(39);
  mbar_wait(BAR(B_ST), LY);
  const uint32_t ssm = sb + SSM_OFF + q * (full ? 336 : 272);
  wg_wait<0>(); fence_regs(a);
  if (rels) mbar_arrive_at(rel);
  if (tid == 0 && wg == 0) PROF(LY ? 21 : 5);
  float2 p = make_float2(0.f, 0.f);
#pragma unroll
  for (int j = 0; j < 20; j++) {
    if (j < 16 || full) {
      float4 sv;
      asm volatile("ld.shared.v4.f32 {%0,%1,%2,%3},[%4];" : "=f"(sv.x), "=f"(sv.y), "=f"(sv.z), "=f"(sv.w) : "r"(ssm + 16 * j));
#pragma unroll
      for (int e = 0; e < 2; e++) {
        const int o = 4 * j + e;
        const float r = e ? sv.z : sv.x, nm = e ? sv.w : sv.y;
        a[o] = fmaf(a[o], r, nm * rs0); a[o + 2] = fmaf(a[o + 2], r, nm * rs1);
        p = cfma(lam, p, make_float2(a[o], a[o + 2]));
      }
    }
  }
  {
    float2 t = make_float2(__shfl_up_sync(0xffffffff, p.x, 1, 4), __shfl_up_sync(0xffffffff, p.y, 1, 4));
    if (q >= 1) p = cfma(mu, t, p);
    t = make_float2(__shfl_up_sync(0xffffffff, p.x, 2, 4), __shfl_up_sync(0xffffffff, p.y, 2, 4));
    if (q >= 2) p = cfma(mu2, t, p);
  }
  if (q == 3 && full) st_rlx2(Eb + tb * 1280, tagf(p.x, tag), tagf(p.y, tag));
  if (tid == 0 && wg == 1) PROF(96 + 64 * LY);
  uint2 ev[3];
#pragma unroll
  for (int i = 0; i < 3; i++) { const int j = tb - 1 - q - 4 * i; ev[i] = j >= 0 ? ld_rlx2(Eb + j * 1280) : make_uint2(tag, tag); }
  float2 x = make_float2(__shfl_up_sync(0xffffffff, p.x, 1, 4), __shfl_up_sync(0xffffffff, p.y, 1, 4));
  if (q == 0) x = make_float2(0.f, 0.f);
  float c0, c1;
  asm volatile("ld.shared.v2.f32 {%0,%1},[%2+8];" : "=f"(c0), "=f"(c1) : "r"(lamp));
  const float c2 = -flip(c1, H.swap), c3 = flip(c0, H.swap);
#pragma unroll
  for (int i = 0; i < 40; i++) {
    const int o = 4 * (i >> 1) + (i & 1);
    const float u = a[o], v = a[o + 2];
    a[o] = fmaf(c0, u, c1 * v); a[o + 2] = fmaf(c2, u, c3 * v);
  }
  fence_regs(a);
  if (LY == 0 && R.b() < 128) {
    const int t0 = 16 * g + 8 * wg + 2 * w;
    if (tid == 0 && wg == 1) PROF(366);
    mbar_wait(BAR(B_XR));
    if (tid == 0 && wg == 1) PROF(367);
    uint4 s = lds4(sb + XR_OFF + 20480 + 256 + 8 * t0);
    if (__any_sync(0xffffffff, untagged(s, tag))) {
#pragma unroll 1
      for (int it = 0; it < SPIN; it++) { s = ld_rlx4(S->S + 128 * (R.b() >> 3) + t0); if (!__any_sync(0xffffffff, untagged(s, tag))) break; }
    }
    resid_load(xr, sb, wg, tid, s);
  }
  float2 mq, om4, fq;
  {
    asm volatile("" : "+f"(lam.x), "+f"(lam.y));
    const float2 one = make_float2(1.f, 0.f), l2 = cmul(lam, lam), l4 = cmul(l2, l2), l8 = cmul(l4, l4), l16 = cmul(l8, l8);
    const float2 l80 = full ? mu2 : cmul(mu2, l16), om = cmul(l80, l80), om2 = cmul(om, om);
    mq = cmul((q & 1) ? mu : one, (q & 2) ? mu2 : one);
    om4 = cmul(om2, om2); fq = cmul((q & 1) ? om : one, (q & 2) ? om2 : one);
  }
  mbar_wait(BAR(B_E1 + 9), LY);
  if (tid == 0 && wg == 1) PROF(368 + LY);
#pragma unroll 1
  for (int it = 0; it < SPIN; it++) {
    const bool m0 = untagged(ev[0], tag), m1 = untagged(ev[1], tag), m2 = untagged(ev[2], tag);
    if (!__any_sync(0xffffffff, m0 || m1 || m2)) break;
    if (m0) ev[0] = ld_rlx2(Eb + (tb - 1 - q) * 1280);
    if (m1) ev[1] = ld_rlx2(Eb + (tb - 5 - q) * 1280);
    if (m2) ev[2] = ld_rlx2(Eb + (tb - 9 - q) * 1280);
  }
  if (tid == 0 && wg == 1) PROF(97 + 64 * LY);
  float2 c = make_float2(untag(ev[2].x), untag(ev[2].y));
#pragma unroll
  for (int i = 1; i >= 0; i--) c = cfma(om4, c, make_float2(untag(ev[i].x), untag(ev[i].y)));
  c = cmul(fq, c);
#pragma unroll
  for (int s = 1; s <= 2; s <<= 1) { c.x += __shfl_xor_sync(0xffffffff, c.x, s); c.y += __shfl_xor_sync(0xffffffff, c.y, s); }
  c = cfma(mq, c, x);
  float2 z = make_float2(fmaf(c0, c.x, c1 * c.y), fmaf(c2, c.x, c3 * c.y));
  if (tid == 0 && wg == 0) PROF(LY ? 22 : 6);
  const float2 lc = make_float2(lam.x, flip(lam.y, H.swap));
  const uint32_t hq = sb + (lane >> 4) * 1024 + (lane & 7) * 128 + (((4 * wg + w) ^ (lane & 7)) << 4);
  const uint32_t hp = hq + R_OFF + (lane & 8) * 2048, hp4 = hq + (LY ? R4_OFF1 : R4_OFF0) + (lane & 8) * 512;
#pragma unroll
  for (int j = 0; j < 20; j += 2) {
    if (j < 16 || full) {
      uint32_t o[4];
#pragma unroll
      for (int i = 0; i < 2; i++) {
        const float2 z0 = cfma(lc, z, make_float2(a[4 * (j + i)], a[4 * (j + i) + 2]));
        z = cfma(lc, z0, make_float2(a[4 * (j + i) + 1], a[4 * (j + i) + 3]));
        o[2 * i] = pack_bf(z0.x, z.x); o[2 * i + 1] = pack_bf(z0.y, z.y);
      }
      asm volatile("stmatrix.sync.aligned.m8n8.x4.trans.shared.b16 [%0], {%1,%2,%3,%4};" ::"r"(j < 16 ? hp + j * 1024 : hp4 + (j - 16) * 1024), "r"(o[0]), "r"(o[1]), "r"(o[2]), "r"(o[3]) : "memory");
      if (j & 2) { __syncwarp(); if (lane == 0) mbar_arrive(BAR(B_SH + j / 4)); }
    }
  }
  if (tid == 0 && wg == 0) PROF(LY ? 23 : 7);
  if (lane == 0) PROF(390 + 4 * wg + w);
}

__device__ __forceinline__ void gate_load(float (&G)[40], uint32_t sb, int LY, int wg, int tid, int tb2) {
  const uint32_t bars = sb + BAR_OFF;
  const int lane = tid & 31, w = tid >> 5;
  mbar_wait(BAR(B_GF), LY);
  const int g = lane >> 2, q = lane & 3;
  const uint32_t gb = sb + (LY ? G_OFF1 : G_OFF0) + wg * 10240 + 512 * q + ((32 * w + 4 * g) ^ (64 * ((tb2 ^ q) & 1)) ^ (16 * (q & 2)));
#pragma unroll
  for (int i = 0; i < 20; i++) { const uint32_t v = lds32((gb ^ (16 * (i & 3))) + 128 * (i & 3) + 2048 * (i >> 2)); G[2 * i] = bf_lo(v); G[2 * i + 1] = bf_hi(v); }
  fence_regs(G);
}
__device__ __forceinline__ void g2_phase(const int LY, const Params& P, Scratch* S, uint32_t sb, int wg, int tid, Role R, float (&xr)[40], long long t_start) {
  sb = opaque(sb);
  const uint32_t bars = sb + BAR_OFF;
  if (LY) {
    const int td = opaque(tid), b = (opaque(R.v) >> 8) & 255;
    const uint32_t tag = lds32(sb + MISC_OFF) & 1;
    const uint2* sp = S->S + 2 * SEQ + 128 * (b >> 3) + 4 * (td & 28) + 8 * wg + 2 * (td >> 5);
    if (!(R.cb() & 1)) mbar_wait(BAR(B_HD), 1);
    uint2 dl[5];
#pragma unroll
    for (int J = 0; J < 5; J++) dl[J] = __ldg((const uint2*)(P.dskip + 80 * (b & 7) + 4 * (td & 3) + 16 * J));
    uint4 sv;
#pragma unroll 1
    for (int it = 0; it < SPIN; it++) { sv = ld_rlx4(sp); if (!__any_sync(0xffffffff, untagged(sv, tag))) break; }
#pragma unroll
    for (int h = 0; h < 2; h++)
#pragma unroll
      for (int J = 0; J < 5; J++)
#pragma unroll
        for (int c = 0; c < 4; c++) {
          const float x2 = xr[IDX(J, c, h)];
          const uint32_t dw = (c & 2) ? dl[J].y : dl[J].x;
          xr[IDX(J, c, h)] = fmaf(fmaf(x2, untag(h ? sv.z : sv.x), untag(h ? sv.w : sv.y)), (c & 1) ? bf_hi(dw) : bf_lo(dw), x2);
        }
    fence_regs(xr);
  }
  float acc[40];
#pragma unroll
  for (int i = 0; i < 40; i++) acc[i] = RIAT == 1 ? 0.f : xr[i];
  fence_regs(acc);
#define G2_STEP(st, cs, hf) { \
    const uint64_t da = make_desc(sb + H_OFF + (st) * 32768 + (hf) * 16384 + wg * 8192, 16, 1024, 1), db = make_desc(sb + (cs) * 20480 + (hf) * 10240, 16, 1024, 1); \
    wg_fence(); \
    _Pragma("unroll") for (int kk = 0; kk < 4; kk++) wgmma_ss80(acc, da + 2 * kk, db + 2 * kk, 1); \
    wg_commit(); }
  mbar_wait(BAR(B_F2), LY);
  if (tid == 0 && wg == 0) PROF(LY ? 25 : 10);
  G2_STEP(0, 0, 0)
  mbar_wait(BAR(B_F3), LY);
  G2_STEP(0, 0, 1)
  tid = opaque(tid); R.v = opaque(R.v);
  const uint32_t tag = lds32(sb + MISC_OFF) & 1;
  const int b = R.b(), tb2 = b >> 3, db_ = b & 7;
  const int w = tid >> 5, lane = tid & 31, g = lane >> 2, q = lane & 3;
  const int t0 = 128 * tb2 + 16 * g + 8 * wg + 2 * w;
  const int d0 = 80 * db_ + 4 * q, mrow = 64 * wg + 16 * w + g;
#define GATE(J, c, h) G[8 * (J) + 2 * (c) + (h)]
  uint32_t rel = mapa(BAR(B_E2), lane ? ((w & 1) ? R.wpart() : R.rank()) : R.cs() == 8 ? 4 * wg + w : wg);
  const bool rels = lane == 0 || (lane == 1 && w < 2);
  uint32_t* Mb = S->M + ((2 * LY * 16 + tb2) * 8) * 256 + (wg * 4 + w) * 32 + (2 * g + (q & 1)) * 2 + (q >> 1);
  {
    uint32_t bf = BAR(B_F2 + 1), st = 1, ra = rel + 8 * (B_EA - B_E2);
    const int lag = wg ? (LY ? STG : STG0) / 2 : 0;
#pragma unroll 1
    for (int kp = 1; kp < 10; kp++) {
      const bool more = LY == 0 || kp < 8;
      wg_wait<1>();
      if (lane == 0 && more) mbar_arrive_at(ra + 8 * (st ? st - 1 : 2));
      mbar_wait(bf, LY);
      if (STG && !(STG & 1) && kp == lag) bar_sync(5, 256);
      G2_STEP(st, kp < 5 ? kp : kp - 5, 0)
      wg_wait<1>();
      if (rels && more) mbar_arrive_at(rel);
      rel += 8;
      mbar_wait(bf + 8 * (B_F3 - B_F2), LY);
      if ((STG & 1) && kp == lag) bar_sync(5, 256);
      G2_STEP(st, kp < 5 ? kp : kp - 5, 1)
      if (kp == MIAT) {
        st_rlx(Mb + db_ * 256, tag ^ 1);
        if (LY == 0) st_rlx(Mb + (16 * 8 + db_) * 256, tag ^ 1);
      }
      bf += 8; st = st == 2 ? 0 : st + 1;
    }
  }
  if (STG && (LY || STG0) && !wg) asm volatile("bar.arrive 5, 256;" ::: "memory");
  const uint32_t mx = sb + MX_OFF + 512 * wg + 4 * tid, bx = BAR(B_KF + 1 + 2 * LY + wg);
  uint32_t pa[8], pb[8];
#pragma unroll
  for (int i = 0; i < 8; i++) { pa[i] = mapa(mx + 1024 * db_, i ^ db_); pb[i] = mapa(bx + (tid >> 10), i ^ db_); asm volatile("" : "+r"(pa[i]), "+r"(pb[i])); }
  wg_wait<0>(); fence_regs(acc);
  if (LY == 0 && rels) mbar_arrive_at(rel);
  if (tid == 0 && wg == 0) PROF(LY ? 26 : 11);
  if (lane == 0) PROF(116 + 64 * LY + wg * 4 + w);

#pragma unroll 1
  for (int rep = 0;; rep++) {
    float m[2][2];
#pragma unroll
    for (int h = 0; h < 2; h++) {
      m[h][0] = m[h][1] = 0.f;
#pragma unroll
      for (int J = 0; J < 5; J++)
#pragma unroll
        for (int c = 0; c < 4; c++) { const float xv = acc[IDX(J, c, h)]; m[h][0] += xv; m[h][1] = fmaf(xv, xv, m[h][1]); }
    }
    float r1[2];
#pragma unroll
    for (int i = 0; i < 2; i++) { const float snd = (q & 1) ? m[0][i] : m[1][i], kp = (q & 1) ? m[1][i] : m[0][i]; r1[i] = kp + __shfl_xor_sync(0xffffffff, snd, 1); }
    const float r2 = ((q & 2) ? r1[1] : r1[0]) + __shfl_xor_sync(0xffffffff, (q & 2) ? r1[0] : r1[1], 2);
    if (R.cs() == 8 && !rep) {
#pragma unroll
      for (int i = 0; i < 8; i++)
        asm volatile("st.async.weak.shared::cluster.mbarrier::complete_tx::bytes.b32 [%0],%1,[%2];" ::"r"(pa[i]), "f"(r2), "r"(pb[i]) : "memory");
      if (tid == 0) mbar_expect_tx(bx, 4096);
    }
    st_rlx(Mb + db_ * 256, tagf(r2, tag));
    if (rep) break;
    if (lane == 0) PROF(100 + 64 * LY + wg * 4 + w);
    float G[40];
    gate_load(G, sb, LY, wg, tid, tb2);
    mbar_wait(BAR(B_CD + 1));
    uint32_t mv[8];
    if (R.cs() == 8) {
      mbar_wait(bx, 1);
#pragma unroll
      for (int i = 0; i < 8; i++) mv[i] = lds32(mx + 1024 * i);
    } else {
#pragma unroll
    for (int i = 0; i < 8; i++) mv[i] = ld_rlx(Mb + i * 256);
#pragma unroll 1
    for (int it = 0; it < SPIN; it++) {
      uint32_t miss = 0;
#pragma unroll
      for (int i = 0; i < 8; i++) miss |= ((mv[i] ^ tag) & 1) << i;
      if (!__any_sync(0xffffffff, miss)) break;
#pragma unroll
      for (int i = 0; i < 8; i++) if ((miss >> i) & 1) mv[i] = ld_rlx(Mb + i * 256);
    }
#pragma unroll
      for (int i = 0; i < 8; i++) mv[i] = __float_as_uint(untag(mv[i]));
      if (MBAR || !LY) bar_sync(4, 256);
    }
    if (lane == 0) PROF(108 + 64 * LY + wg * 4 + w);
#define MV(i) __uint_as_float(mv[i])
    const float s = ((MV(0) + MV(1)) + (MV(2) + MV(3))) + ((MV(4) + MV(5)) + (MV(6) + MV(7)));
#undef MV
    float mm[2], rr[2];
#pragma unroll
    for (int h = 0; h < 2; h++) {
      mm[h] = __shfl_sync(0xffffffff, s, h, 4) * (1.f / DM);
      rr[h] = frsqrt(fmaxf(__shfl_sync(0xffffffff, s, 2 + h, 4) * (1.f / DM) - mm[h] * mm[h], 0.f) + 1e-5f);
    }
    if (tid == 0 && wg == 0) PROF(LY ? 27 : 12);
    const float nm[2] = {-mm[0] * rr[0], -mm[1] * rr[1]};
#pragma unroll
    for (int h = 0; h < 2; h++)
#pragma unroll
      for (int J = 0; J < 5; J++)
#pragma unroll
        for (int c = 0; c < 4; c++) { const float xv = acc[IDX(J, c, h)]; xr[IDX(J, c, h)] = fmaf(fmaf(xv, rr[h], nm[h]), GATE(J, c, h), xv); }
    if (LY) break;
#pragma unroll
    for (int i = 0; i < 40; i++) acc[i] = xr[i] - mm[(i >> 1) & 1];
    if (R.cs() == 8) mbar_wait(BAR(B_KF + 1), 1);
#pragma unroll
    for (int i = 0; i < 10; i++) {
      const int J = i >> 1, h = i & 1;
      const uint32_t u0 = pack_bf(acc[IDX(J, 0, h)], acc[IDX(J, 1, h)]), u1 = pack_bf(acc[IDX(J, 2, h)], acc[IDX(J, 3, h)]);
      asm volatile("st.shared.v2.u32 [%0],{%1,%2};" ::"r"(sb + US_OFF + ((mrow ^ 64) + 8 * h) * 160 + 32 * J + 8 * q), "r"(u0), "r"(u1) : "memory");
    }
    __syncwarp();
    if (lane == 0) mbar_arrive(BAR(B_GS + 1 + wg));
    if (tid == 0 && wg == 0) PROF(13);
    Mb += 16 * 8 * 256;
  }
  if (LY == 0) {
    if (tid == 0 && wg == 0) PROF(15);
  }
  else {
    float* op = P.out + (size_t)t0 * DM + d0;
#pragma unroll
    for (int i = 0; i < 10; i++) {
      const int J = i >> 1, h = i & 1;
      asm volatile("st.global.v4.f32 [%0],{%1,%2,%3,%4};" ::"l"(op + h * DM + 16 * J),
                   "f"(xr[IDX(J, 0, h)]), "f"(xr[IDX(J, 1, h)]), "f"(xr[IDX(J, 2, h)]), "f"(xr[IDX(J, 3, h)]) : "memory");
    }
  }
  if (tid == 0 && wg == 0 && LY) PROF(28);
#undef IDX
#undef GATE
}

__device__ __forceinline__ void next_stats(Scratch* S, uint32_t sb, int tb2, int tid) {
  const uint32_t bars = sb + BAR_OFF, tag = lds32(sb + MISC_OFF) & 1;
  const uint32_t* Mb = S->M + tb2 * 8 * 256 + 2 * tid;
  mbar_wait(BAR(B_F1 + NSAT), 1);
  float m1, s1, s2;
#pragma unroll 1
  for (int it = 0; it < SPIN; it++) {
    uint32_t a[8], miss = 0;
    uint2 v[8];
#pragma unroll
    for (int i = 0; i < 8; i++) { a[i] = ld_rlx(Mb + i * 256); v[i] = ld_rlx2((const uint2*)(Mb + (16 * 8 + i) * 256)); }
#pragma unroll
    for (int i = 0; i < 8; i++) miss |= (a[i] ^ tag) | (v[i].x ^ tag) | (v[i].y ^ tag);
#define SUM8(F) ((untag(F(0)) + untag(F(1))) + (untag(F(2)) + untag(F(3)))) + ((untag(F(4)) + untag(F(5))) + (untag(F(6)) + untag(F(7))))
#define FA(i) a[i]
#define FX(i) v[i].x
#define FY(i) v[i].y
    m1 = SUM8(FA); s1 = SUM8(FX); s2 = SUM8(FY);
    if (!__any_sync(0xffffffff, miss & 1)) break;
  }
  const float mean = s1 * (1.f / DM), rs = frsqrt(fmaxf(s2 * (1.f / DM) - mean * mean, 0.f) + 1e-5f);
  uint2* sp = S->S + SEQ + 128 * tb2 + 8 * (tid & 14) + 2 * (tid >> 4) + (tid & 1);
  st_rlx2(sp, tagf(rs, tag), tagf(-mean * rs, tag));
  st_rlx2(sp + SEQ, tagf(rs, tag), tagf(-(mean + m1 * (1.f / DM)) * rs, tag));
}
template <int I0, int I1> __device__ __forceinline__ void init_barriers(uint32_t bars) {
#pragma unroll
  for (int i = I0; i < I1; i++) mbar_init(BAR(i), bar_count(i));
}
__device__ __forceinline__ int g2_cb(int kp) { return kp < 5 ? 2 * kp : 2 * kp - 9; }
__device__ __forceinline__ const unsigned* h_flag(Scratch* S, int ly, int tb2, int lane) {
  const int s0 = 128 * min(tb2, 15) / 160;
  const bool two = (128 * tb2 + 127) / 160 != s0;
  return &S->flag[(F_H + (ly * 13 + s0) * 10 + min(lane & 15, 9) + (two && lane >= 16 ? 10 : 0)) * 32];
}
__device__ __forceinline__ void gate_tile(const Params& P, uint32_t dst, uint32_t bar, int tb2, int db) {
  tma2d(dst, &P.mGT, tb2 * 128, db * 80, bar);
  tma2d(dst + 10240, &P.mGT, tb2 * 128 + 64, db * 80, bar);
}
__global__ void __cluster_dims__() __launch_bounds__(512, 1) fused_kernel(const Head H, const __grid_constant__ Params P) {
  extern __shared__ __align__(1024) uint8_t smem[];
  const uint32_t sb = opaque(smem_u32(smem)), bars = sb + BAR_OFF;
  const int wi = __shfl_sync(0xffffffff, threadIdx.x >> 5, 0), wg = wi >> 2, tid = threadIdx.x & 127;
  const int umap = blockIdx.x >= 96;
#define CLK(v)
  CLK(c_a);
  if (wi == 14) {
    if (elect_one()) { init_barriers<0, NBAR1>(bars); asm volatile("fence.mbarrier_init.release.cluster;" ::: "memory"); }
    __syncwarp();
  } else if (wi >= 12) prefetch_map(wi == 12 ? &P.mB : &P.mA[umap]);
  else if (wg == 2) xb_prefetch<1>(H, blockIdx.x + H.base, tid, 0);
  else if (P.role[blockIdx.x].w) return;
  CLK(c_b);
  asm volatile("barrier.cluster.arrive.relaxed.aligned;" ::: "memory");
  CLK(c_c);
  Role R;
  { const uint4 r = P.role[blockIdx.x]; R.v = r.x; R.c = r.y; R.p = r.z; }
  const int id = R.c & 255;
  const int tb = R.tb(), cb = R.cb(), b = R.b(), tb2 = b >> 3, db = b & 7, rank = R.rank();
  const bool has1 = tb <= 12, has2 = b < 128, full = tb < 12;
  Scratch* const S = H.s;
  unsigned* const epoch_p = &S->epoch[id * 8];
  const long long t_start = 0;
  if (wg < 2) {
    if (threadIdx.x == 0) PROF(50);
    asm volatile("griddepcontrol.launch_dependents;");
    bar_sync(6, 448);
    asm volatile("setmaxnreg.inc.sync.aligned.u32 176;");
    float xr[40];
#pragma unroll
    for (int i = 0; i < 40; i++) xr[i] = 0.f;
#pragma unroll 1
    for (int ly = 0; ly < 2; ly++) {
      if (has1) g1_phase(ly, H, sb, wg, tid, R, xr, t_start);
      if (ly == 0) {
        resid_init(xr); fence_regs(xr);
        conv_loop<false>(sb, R.c, wg, tid, t_start);
        if (tid == 0 && wg == 0) PROF(9);
      }
      if (has2) g2_phase(ly, P, S, sb, wg, tid, R, xr, t_start);
    }
    if (tid == 0 && wg == 0) st_rlx(epoch_p, lds32(sb + MISC_OFF));
  } else if (wg == 2) {
    bar_sync(6, 448);
    if (has1) aux_prep(H, P, sb, R, tid, t_start);
    asm volatile("setmaxnreg.inc.sync.aligned.u32 136;");
    conv_loop<true>(sb, R.c, wg, tid, t_start);
    if (tid == 0) PROF(44);
    {
      const uint32_t bb = (P.role[blockIdx.x].x >> 8) & 255;
      if ((bb & 132) == NSDB && tid < 32) next_stats(H.s, sb, bb >> 3, 32 * (bb & 3) + tid);
    }
  } else {
    if (threadIdx.x == 384) PROF(354);
    asm volatile("setmaxnreg.dec.sync.aligned.u32 24;");
    const int wlo = R.wlo(), whi = R.whi();
    const uint32_t wmask = R.wmask(), umask = R.umask(), f1bytes = full ? 36864 : 32768;
    if (wi < 14) {
      if (threadIdx.x == 384) PROF(340);
      asm volatile("barrier.cluster.wait.aligned;" ::: "memory");
      if (has1 && elect_one()) {
        uint64_t tab = wi == 12 ? WTAB0 : XTAB0;
        PROF(329 + wi);
#pragma unroll 1
        for (int kb = 0; kb < 6; kb++, tab >>= 6) {
          const uint32_t dst = sb + ((uint32_t)tab & 63) * 4096;
          if (wi == 12) {
#pragma unroll 1
            for (int h = wlo; h <= whi; h++) tma4d_mc(dst + h * 8192, &P.mB, kb * 64, 0, 0, 8 * cb + 4 * h, BAR(B_F1 + kb), wmask);
          } else {
            tma4d_mc(dst + R.uj() * 1024, &P.mA[umap], kb * 64, 0, 0, 80 * tb + R.uj(), BAR(B_F1 + kb), umask);
            mbar_expect_tx(BAR(B_F1 + kb), f1bytes);
          }
        }
      }
      if (!has1 && wi == 13) bar_sync(7, 64);
    } else {
      if (wi == 15 && elect_one()) { init_barriers<NBAR1, NBAR>(bars); asm volatile("fence.mbarrier_init.release.cluster;" ::: "memory"); }
      bar_sync(6, 448);
      if (!has1 && wi == 14) bar_sync(7, 64);
    }
    const unsigned e1 = ld_rlx(epoch_p) + 1;
    if (wi == 12) {
      if (elect_one()) {
#pragma unroll 1
        for (int ly = 0; ly < 2; ly++) {
#pragma unroll 1
          for (int i = ly ? 0 : 6; i < 10 && has1; i++) {
            const int kb = (0x9876541032ull >> (4 * i)) & 15;
            if (ly == 0) { mbar_wait(BAR(B_E1 + ((DEP0 >> (4 * kb - 24)) & 15))); mbar_wait(BAR(B_AX + (kb == 9))); }
            else {
              if (has2 && i == (db >= GLATE ? 4 : 2)) {
                mbar_expect_tx(BAR(B_GF), 20480);
                wait_cnt(&S->cnt[(C_G + db) * 32], e1 * 80);
                if (i == 2) mbar_wait(BAR(B_E2 + 7));
                PROF(47);
                gate_tile(P, sb + G_OFF0, BAR(B_GF), tb2, db);
              }
              if (has2) mbar_wait(BAR(i < 4 ? B_E2 + ((0x9865u >> (4 * i)) & 15) : B_GE));
              else if (i == 0) { mbar_wait(BAR(B_E1 + 9)); mbar_wait(BAR(B_CD + 1)); }
              if (i >= 4) mbar_wait(BAR(i < 6 ? B_F1 + W4AT : B_E1 + i - 6), 1);
            }
            const uint32_t dst = sb + ((uint32_t)((ly ? WTAB1 : WTAB0) >> (6 * kb)) & 63) * 4096;
#pragma unroll 1
            for (int h = wlo; h <= whi; h++) tma4d_mc(dst + h * 8192, &P.mB, kb * 64, 0, 0, 8 * cb + 4 * h, BAR(B_F1 + kb), wmask);
          }
          if (has2) {
            if (ly == 0) {
              mbar_wait(BAR(B_E1 + XRAT));
              mbar_expect_tx(BAR(B_XR), 20480 + 160 + 1024);
              tma4d(sb + XR_OFF, &P.mX, 80 * db, tb2, BAR(B_XR));
              bulk_g2s(sb + XR_OFF + 20480, P.dskip + 80 * db, 160, BAR(B_XR));
              bulk_g2s(sb + XR_OFF + 20480 + 256, S->S + 128 * tb2, 1024, BAR(B_XR));
              if (CWAIT) mbar_wait(BAR(CWAIT == 1 ? B_KF + 2 : CWAIT == 2 ? B_KF + R.nch() - 1 : CWAIT == 3 ? B_KF + R.nch() - 2 : B_HD));
            }
#pragma unroll 1
            for (int kp = 0; kp < 10; kp++) {
              const uint32_t dst = sb + (kp < 5 ? kp : kp - 5) * 20480;
              mbar_wait(BAR(kp >= 5 ? B_E2 + kp - 5 : ly ? B_E1 + ((CTAB1 >> (4 * kp)) & 15) : kp < 3 ? B_SH : kp < 4 ? B_HD : B_CD), ly);
              mbar_expect_tx(BAR(B_F2 + kp), 10240 + 16384);
              tma5d(dst, &P.mC[0], g2_cb(kp) * 64, db * 5, BAR(B_F2 + kp));
              mbar_expect_tx(BAR(B_F3 + kp), 10240 + 16384);
              tma5d(dst + 10240, &P.mC[1], g2_cb(kp) * 64, db * 5, BAR(B_F3 + kp));
              if (ly && kp == 4) { mbar_wait(BAR(B_E1 + 9), 1); mbar_expect_tx(BAR(B_GF), 20480); gate_tile(P, sb + G_OFF1, BAR(B_GF), tb2, db); }
            }
          }
        }
      }
    } else if (wi == 13) {
      const int h0 = R.cs() == 8 ? rank : 4 * rank;
#pragma unroll 1
      for (int ly = 0; ly < 2; ly++) {
        int lane = lane_id();
        if (has1) {
          const unsigned* fp = &S->flag[(F_U3 + 8 * ((160 * tb) >> 7) + (lane & (full ? 15 : 7))) * 32];
          uint32_t ready = ly ? __ballot_sync(0xffffffff, ld_rlx(fp) == e1) : ~0u;
          if (ly) mbar_wait(BAR(full ? B_KF + 1 : has2 ? B_GS + 1 : B_RF1), has2);
          if (ly && full) mbar_wait(BAR(B_KF + 2), 1);
#pragma unroll 1
          for (int kb = ly ? 0 : 6; kb < 10; kb++) {
            if (ly && kb == UPAT) { mbar_wait(BAR(B_XR)); ready = ~0u; }
            const int nl = ly && kb < UH && R.rank() >= 4 ? 2 - 2 * (R.rank() & 1) : 1;
            if (nl) wait_flags(fp, e1, 0x101u * ((1u << (64 * kb / 80)) | (1u << ((64 * kb + 63) / 80))), ready);
            if (kb >= 4) mbar_wait(BAR(B_E1 + (ly ? kb - 4 : (DEP0 >> (4 * kb - 24)) & 15)), ly);
            mbar_wait(BAR(B_AX + (kb == 9)));
            if (elect_one()) {
              if (ly && kb == 0) PROF(34);
#pragma unroll 1
              for (int i = 0, uj = R.uj(); i < nl; i++, uj += 5 << umap)
                tma4d_mc(sb + ((uint32_t)((ly ? XTAB1 : XTAB0) >> (6 * kb)) & 63) * 4096 + uj * 1024, &P.mA[2 * ly + umap], kb * 64, 0, 0, 80 * tb + uj,
                         BAR(B_F1 + kb), umask);
              mbar_expect_tx(BAR(B_F1 + kb), f1bytes);
            }
            __syncwarp();
          }
        }
        if (ly == 0) {
          if (has1) mbar_wait(BAR(B_E1 + KPF));
          if (elect_one()) {
#pragma unroll 1
            for (int s = 0; s < R.nch(); s++) prefetch_l2(P.ssmk + (size_t)R.ch(s) * SEQ, 4096);
          }
          lane = lane_id();
#pragma unroll
          for (int s = 0; s < 5; s++) {
            asm volatile("st.shared.v4.u32 [%0],{%1,%1,%1,%1};" ::"r"(conv_buf(sb, s) + 16 * lane), "r"(0) : "memory");
            asm volatile("st.shared.u8 [%0],%1;" ::"r"(conv_buf(sb, s) + KC_OFS + lane), "r"(0) : "memory");
          }
          fence_async();
          __syncwarp();
          const unsigned* cp = &S->cnt[(C_KV + (R.ch(min(lane, R.nch() - 1)) >> 6)) * 32];
          uint32_t ready = 0;
#pragma unroll 1
          for (int s = 0, sk = 0; s < R.nch(); s++) {
#pragma unroll 1
            for (; sk < (s ? R.nch() : KUP); sk++)
              if (elect_one()) { mbar_expect_tx(BAR(B_KF + sk), 8192); bulk_g2s(conv_buf(sb, sk) + KC_OFS + 32, P.ssmk + (size_t)R.ch(sk) * SEQ, 4096, BAR(B_KF + sk)); }
            PROFC(s == 0, 329);
#pragma unroll 1
            for (int it = 0; !((ready >> s) & 1) && it < SPIN; it++) ready = __ballot_sync(0xffffffff, (int)(ld_rlx(cp) - e1 * 32) >= 0);
            PROFC(s == 0, 30);
            if (elect_one()) {
              bulk_g2s(conv_buf(sb, s) + KV_PAD, S->kv + (size_t)R.ch(s) * SEQ, 4096, BAR(B_KF + s));
              if (s == 0 && has2) { prefetch_l2(P.cre + (size_t)5 * b * DM, 5 * DM * 2); prefetch_l2(P.cim + (size_t)5 * b * DM, 5 * DM * 2); }
            }
            __syncwarp();
          }
          PROF(31);
          if (!has1) return;
        }
        lane = lane_id();
        const unsigned* fp = h_flag(S, ly, tb2, lane);
        uint32_t ready = __ballot_sync(0xffffffff, ld_rlx(fp) == e1), st = 0;
        if (ly == 0 && !has2) {
          mbar_wait(BAR(B_HD));
          if (lane < 8) mbar_arrive_cl(BAR(B_RF1), lane & 1);
        }
        if (has2) {
          mbar_wait(BAR(B_RF0), ly);
#pragma unroll 1
          for (int kp = 0; kp < 10; kp++) {
            if (kp == 5) { mbar_wait(BAR(B_XR), 1); ready = ~0u; }
            if (kp == 2) { mbar_wait(BAR(B_HD), ly); if (lane < 8) mbar_arrive_cl(BAR(B_RF1), lane & (R.cs() - 1)); }
            wait_flags(fp, e1, 0x10001u << g2_cb(kp), ready);
            if (kp == 2) mbar_wait(BAR(B_RF1), ly);
#pragma unroll
            for (int hf = 0; hf < 2; hf++) {
              if (kp >= 3) { if (hf) mbar_wait(BAR(B_E2 + kp - 3), ly); else mbar_wait(BAR(B_EA + st), ly ^ (kp >= 6 && kp < 9)); }
              if (elect_one()) {
                if (kp == 0 && !hf) PROF(33 + 2 * ly);
                tma4d_mc(sb + H_OFF + st * 32768 + hf * 16384 + h0 * 2048, &P.mH, g2_cb(kp) * 128 + hf * 64, 0, 2 * h0,
                         ly * 16 + tb2, BAR((hf ? B_F3 : B_F2) + kp), (1u << R.cs()) - 1);
              }
              __syncwarp();
            }
            st = st == 2 ? 0 : st + 1;
          }
        }
      }
    } else if (wi == 14) {
      if (!has1) return;
      prefetch_if(P.dskip + 64 * (tid & 31), (tid & 31) < 10);
      if (elect_one()) { prefetch_map(&P.sK); prefetch_map(&P.mX); prefetch_map(&P.sH); prefetch_map(&P.sU); prefetch_map(&P.mC[0]); prefetch_map(&P.mC[1]); prefetch_map(&P.mH); prefetch_map(&P.mGT); prefetch_map(&P.mA[2 + umap]); }
      __syncwarp();
#pragma unroll 1
      for (int ly = 0; ly < 2; ly++) {
        if (ly) {
          mbar_wait(BAR(B_F1 + 1), 1);
          uint32_t ready = 0;
          wait_flags(&S->flag[(F_U3 + 8 * ((160 * tb) >> 7) + ((lane_id() + ly) & (full ? 15 : 7))) * 32], e1, ~0u, ready);
          if (elect_one()) mbar_arrive(BAR(B_XR));
        }
        const int lane = lane_id();
        mbar_wait(BAR(B_E1 + (ly ? STAT_AT1 : STAT_AT)), ly);
        PROFC(lane == 0 && ly == 0, 36);
        {
          const int l = lane - (full ? 0 : 16);
          const uint2* p = S->S + ly * SEQ + 160 * tb + 2 * l;
          uint4 v[3];
#pragma unroll 1
          for (int it = 0; it < SPIN; it++) {
            v[0] = ld_rlx4(p); v[1] = ld_rlx4(p + 64); v[2] = ld_rlx4(p + 96);
            const bool miss = __any_sync(0xffffffff, untagged(v[0], e1 & 1) | untagged(v[1], e1 & 1) | untagged(v[2], e1 & 1));
            PROFC(lane == 0 && ly == 0 && it == 0, 37);
            if (!miss) break;
          }
          PROFC(lane == 0 && ly == 0, 38);
#pragma unroll
          for (int i = 0; i < 3; i++) {
            const int pr = l + (i == 2 ? 48 : 32 * i);
            if (pr >= 0) asm volatile("st.shared.v4.u32 [%0],{%1,%2,%3,%4};" ::"r"(sb + SSM_OFF + 16 * (pr + ((pr * (full ? 205 : 256)) >> 12))), "r"(v[i].x & ~1u),
                                      "r"(v[i].y & ~1u), "r"(v[i].z & ~1u), "r"(v[i].w & ~1u) : "memory");
          }
          __syncwarp();
        }
        if (lane == 0) mbar_arrive(BAR(B_ST));
        if (ly && has2) {
          mbar_wait(BAR(B_E1 + 9), 1);
          if (lane < 8) mbar_arrive_cl(BAR(B_RF0), lane & (R.cs() - 1));
        }
        if (lane == 0) {
#pragma unroll 1
          for (int pc = 0; pc < (full ? 5 : 4); pc++) {
            if ((HWM >> (4 * pc)) & 8) {
              mbar_wait(BAR(B_SH + min((HWM >> (4 * pc)) & 7, full ? 4 : 3)), ly);
              PROF(380 + 5 * ly + pc);
              if (pc == 0 && (cb & 1)) delay(ly ? HDLY : HDLY0);
              fence_async();
            }
#pragma unroll
            for (int i = 0; i < 2; i++) tma4d_store(&P.sH, sb + (pc < 4 ? R_OFF + i * 16384 + pc * 4096 : (ly ? R4_OFF1 : R4_OFF0) + i * 4096), 128 * cb + 64 * i, 0, 0, ly * 1024 + 80 * tb + 4 * pc);
          }
          bulk_commit(); bulk_wait();
          PROF(ly ? 17 : 16);
          mbar_arrive(BAR(B_HD));
          release<1>();
          signal_flag(&S->flag[(F_H + (ly * 13 + tb) * 10 + cb) * 32], e1);
          PROF(ly ? 24 : 8);
        }
        __syncwarp();
        if (has2) {
          mbar_wait(BAR(B_F2 + FPAT), ly);
          uint32_t ready = 0;
          wait_flags(h_flag(S, ly, tb2, lane_id() | 1), e1, ~0u, ready);
          if (elect_one()) mbar_arrive(BAR(B_XR));
        }
        if (lane == 0 && has2 && !ly) {
          mbar_wait(BAR(B_CD + 1));
#pragma unroll
          for (int i = 0; i < 2; i++) {
            mbar_wait(BAR(B_GS + 1 + i), 1);
            fence_async();
            tma4d_store(&P.sU, sb + US_OFF + 10240 - 10240 * i, 80 * db, 0, 8 * i, tb2);
          }
          bulk_commit(); bulk_wait();
          PROF(18);
          release<2>(); signal_flag(&S->flag[(F_U3 + b) * 32], e1);
          PROF(14);
          mbar_wait(BAR(B_SG));
          mbar_arrive(BAR(B_GE)); mbar_arrive_cl(BAR(B_GE), R.wpart());
        }
        __syncwarp();
      }
    } else {
      discretise(H, P, sb, R, tid & 31, e1);
      if (elect_one()) {
        mbar_arrive(BAR(B_LM));
        PROF(348);
        if (b < R.nprep()) {
#pragma unroll 1
          for (int task = b, r = 0; task < 320; task += R.nprep(), r++) {
            mbar_wait(BAR(B_PS + r));
            PROF(320 + 3 * r);
            fence_async();
            tma2d_store(&P.sK, sb + KS_OFF + r * 8192, 64 * (task & 31), 64 * (task >> 5));
            bulk_commit(); bulk_wait();
            PROF(321 + 3 * r);
            release<4>();
            signal_cnt(&S->cnt[(C_KV + (task >> 5)) * 32], 1);
            PROF(322 + 3 * r);
          }
          PROF(41);
        }
        if (has2) {
          mbar_wait(BAR(B_SH));
#pragma unroll 1
          for (int i = 0; i < 8; i++) mbar_arrive_cl(BAR(B_RF0), i & (R.cs() - 1));
        }
#pragma unroll 1
        for (int s = 0, s0 = 0; s < R.nch(); s++) {
          mbar_wait(BAR(B_GS + s));
          fence_async();
          bulk_s2g(S->gt + (size_t)R.ch(s) * SEQ, conv_buf(sb, s) + KC_OFS, 4096); bulk_commit();
          if (s == 1 || s >= R.nch() - GSPL) bulk_wait();
          if (s == 1 || s == min(R.nch() - 1, 3)) mbar_arrive(BAR(B_CD + (s > 1)));
          mbar_arrive_if(BAR(B_SG), s == R.nch() - 1);
          if (s >= R.nch() - GSPL) {
            PROF(45);
            release<8>();
#pragma unroll 1
            for (; s0 <= s; s0++) signal_cnt(&S->cnt[(C_G + R.ch(s0) / 80) * 32], 1);
          }
        }
        PROF(46);
      }
    }
  }
}

typedef CUresult (*EncFn)(CUtensorMap*, CUtensorMapDataType, cuuint32_t, void*, const cuuint64_t*, const cuuint64_t*, const cuuint32_t*,
                          const cuuint32_t*, CUtensorMapInterleave, CUtensorMapSwizzle, CUtensorMapL2promotion, CUtensorMapFloatOOBfill);
bool enc(EncFn f, CUtensorMap* m, const void* base, int rank, const cuuint64_t* dims, const cuuint64_t* strides, const cuuint32_t* box, bool swz,
         bool f32 = false) {
  const cuuint32_t es[5] = {1, 1, 1, 1, 1};
  return f(m, f32 ? CU_TENSOR_MAP_DATA_TYPE_FLOAT32 : CU_TENSOR_MAP_DATA_TYPE_BFLOAT16, rank, const_cast<void*>(base), dims, strides, box, es,
           CU_TENSOR_MAP_INTERLEAVE_NONE, swz ? CU_TENSOR_MAP_SWIZZLE_128B : CU_TENSOR_MAP_SWIZZLE_NONE, CU_TENSOR_MAP_L2_PROMOTION_L2_256B,
           CU_TENSOR_MAP_FLOAT_OOB_FILL_NONE) == CUDA_SUCCESS;
}
void make_roles(Params& P, bool big) {
  for (uint32_t bx = 0; bx < (big ? 120u : 12u); bx++) {
    const uint32_t c = bx >> 3, r = bx & 7, id = big ? bx : 120 + bx;
    const uint32_t vA = c < 12 ? (2 * (c >> 1) + (r >> 2)) | (4 * (c & 1) + (r & 3)) << 4 | (r & 4) << 16 | 4 << 19 | (r ^ 4) << 22
                               : (4 * (c - 12) + (r >> 1)) | (8 + (r & 1)) << 4 | (r & 6) << 16 | 2 << 19 | (r ^ 2) << 22;
    const uint32_t vB = (bx < 10 ? 12 : 13) | bx << 4 | 2 << 19 | (bx & 1) << 22 | (bx & 1) << 26;
    P.role[bx].x = (big ? vA | r << 26 | 1u << 29 : vB) | (id < 128 ? (id & ~7u) | (r >> 1) | (r & 1) << 2 : id) << 8;
    P.role[bx].y = id | (big ? 5 : bx < 8 ? 3 : 4) << 10 | 120 << 13 | 132 << 21 | (big ? 4u : 3u) << 29;
    const uint32_t v = P.role[bx].x, cb = (v >> 4) & 15, rank = (v >> 26) & 7, ubase = (v >> 16) & 7, ugs = (v >> 19) & 7, wp = (v >> 22) & 7;
    const uint32_t wlo = rank > wp, whi = wp != rank ? wlo : 1, wmask = 1u << rank | 1u << wp;
    const uint32_t uj = (rank - ubase) * (!big ? 8 : ugs == 4 ? 5 : 10), sm = big ? (0x7296418530ull >> (4 * cb)) & 15 : bx < 8 ? 4 * (bx & 1) + (bx >> 1) : 15;
    P.role[bx].z = wlo | whi << 1 | wmask << 2 | ((1u << ugs) - 1) << (10 + ubase) | uj << 20 | sm << 25;
    P.role[bx].w = 0;
  }
}
void launch(const Head& H, const Params& P, int grid, int cs, bool dependent) {
  cudaLaunchConfig_t cfg = {};
  cfg.gridDim = grid; cfg.blockDim = 512; cfg.dynamicSmemBytes = SMEM_BYTES; cfg.stream = cudaStreamPerThread;
  cudaLaunchAttribute at[2];
  at[0].id = cudaLaunchAttributeClusterDimension; at[0].val.clusterDim.x = cs; at[0].val.clusterDim.y = 1; at[0].val.clusterDim.z = 1;
  at[1].id = cudaLaunchAttributeProgrammaticStreamSerialization; at[1].val.programmaticStreamSerializationAllowed = 1;
  cfg.attrs = at; cfg.numAttrs = dependent ? 2 : 1;
  cudaLaunchKernelEx(&cfg, fused_kernel, H, P);
}

}

extern "C" void kernel_launch(void* const* d_in, const int* in_sizes, int n_in, void* d_out, int out_size) {
  (void)in_sizes; (void)n_in; (void)out_size;
  typedef const __nv_bfloat16* cb;
  void* fp = nullptr; cudaDriverEntryPointQueryResult qr;
  cudaGetDriverEntryPoint("cuTensorMapEncodeTiled", &fp, cudaEnableDefault, &qr);
  EncFn f = (EncFn)fp;
  Scratch* sp = nullptr;
  cudaGetSymbolAddress((void**)&sp, g_scr);
  void *pu = sp->u, *ph = sp->h, *pgt = sp->gt;
  Params P;
  Head H;
  H.s = sp; H.x = (cb)d_in[0]; H.swap = (uintptr_t)d_in[4] < (uintptr_t)d_in[3] ? 0 : 0x80000000u; H.b0 = (cb)d_in[H.swap ? 3 : 4]; H.b1 = (cb)d_in[H.swap ? 4 : 3];
  for (int i = 0; i < 2; i++) {
    const cuuint64_t d[4] = {640, 8, 2, 80}, s[3] = {1280, (cuuint64_t)((uintptr_t)H.b1 - (uintptr_t)H.b0), 8 * 1280}; const cuuint32_t bx[4] = {64, 8, 2, 4};
    if (enc(f, &P.mB, H.b0, 4, d, s, bx, true)) break;
    cudaMemcpyAsync(sp->bcopy, H.b0, DM * DM * 2, cudaMemcpyDeviceToDevice, cudaStreamPerThread);
    cudaMemcpyAsync(sp->bcopy + DM * DM, H.b1, DM * DM * 2, cudaMemcpyDeviceToDevice, cudaStreamPerThread);
    H.b0 = sp->bcopy; H.b1 = sp->bcopy + DM * DM;
  }
  {
    const cuuint64_t d[5] = {640, 2, 4, 2, 40}, s[4] = {1280, 4 * 1280, 2 * 1280, 16 * 1280}; const cuuint32_t bx[5] = {64, 2, 4, 2, 5};
    enc(f, &P.mC[0], d_in[5], 5, d, s, bx, true); enc(f, &P.mC[1], d_in[6], 5, d, s, bx, true); }
  { const cuuint64_t d[2] = {2048, 640}, s[1] = {4096}; const cuuint32_t bx[2] = {64, 80}; enc(f, &P.mGT, pgt, 2, d, s, bx, true); }
  { const cuuint64_t d[4] = {640, 8, 16, 16}, s[3] = {16 * 1280, 1280, 128 * 1280}; const cuuint32_t bx[4] = {80, 8, 16, 1}, bh[4] = {80, 8, 8, 1};
    enc(f, &P.sU, pu, 4, d, s, bh, false); enc(f, &P.mX, d_in[0], 4, d, s, bx, false); }
  { const cuuint64_t d[2] = {2048, 640}, s[1] = {4096}; const cuuint32_t bx[2] = {64, 64}; enc(f, &P.sK, sp->kv, 2, d, s, bx, true); }
  P.lre = (cb)d_in[1]; P.lim = (cb)d_in[2]; P.cre = (cb)d_in[5]; P.cim = (cb)d_in[6]; P.ldt = (cb)d_in[7]; P.dskip = (cb)d_in[8];
  P.out = (float*)d_out;
  P.k = (cb)d_in[10]; P.v = (cb)d_in[11]; P.shk = (cb)d_in[12]; P.ssmk = (cb)d_in[13]; P.ssmd = (cb)d_in[14];
  cudaFuncSetAttribute(fused_kernel, cudaFuncAttributeMaxDynamicSharedMemorySize, SMEM_BYTES);
  for (int big = 1; big >= 0; big--) {
    const cuuint64_t seg = big ? 40 : 32;
    for (int i = 0; i < 4; i++) {
      const cuuint64_t d[4] = {640, 2, 4, 1024}, s[3] = {1280, seg * 1280, 2 * 1280}; const cuuint32_t bx[4] = {64, 2, 4, !big ? 8u : (i & 1) ? 10u : 5u};
      enc(f, &P.mA[i], i < 2 ? d_in[0] : pu, 4, d, s, bx, true);
    }
    {
      const cuuint64_t d[4] = {1280, 8, 16, 32}, s[3] = {16 * 2560, 2560, 128 * 2560}; const cuuint32_t bx[4] = {64, 8, big ? 2u : 8u, 1};
      enc(f, &P.mH, ph, 4, d, s, bx, true); }
    { const cuuint64_t d[4] = {1280, 2, 4, 2048}, s[3] = {2560, seg * 2560, 2 * 2560}; const cuuint32_t bx[4] = {64, 2, 4, 4};
      enc(f, &P.sH, ph, 4, d, s, bx, true); }
    make_roles(P, big);
    H.base = big ? 0 : 120;
    launch(H, P, big ? 120 : 12, big ? 8 : 2, !big);
  }
}
```

```cpp
#include <cuda_runtime.h>
#include <cuda.h>
#include <cuda_bf16.h>
#include <stdint.h>

namespace {

constexpr int SEQ = 2048, DM = 640;
constexpr int SPIN = 1 << 20;
#define PFAT 99
#define KVDLY 300
#define PFD 1
#define XPFAT 9
#define STAT_AT 6
#define KPFAT 3
#define KPFAT2 5
#define KPF 7
#define HDLY 1900
#define GSPL 2
#define CWAIT 0
#define HDLY0 1900
#define CTAB1 0x96543u
#define NSAT 0
#define SKW 1
#define RIAT 2
#define MIAT 5
#define FPAT 1
#define UPAT 7
#define STAT_AT1 4
#define W4AT 0
#define MBAR 1
#define STG 17
#define STG0 17
#define HWM 0xc09
#define NSDB 4
#define UH 2
#define GLATE 6
#define KUP 1
#define XRAT 9
#define ORD 1

struct Scratch {
  uint2 E[2 * 13 * 10 * 8 * 16];
  uint32_t M[3 * 16 * 8 * 256];
  uint2 S[3 * SEQ];
  uint2 RS[80 * 16];
  unsigned flag[512 * 32];
  unsigned cnt[32 * 32];
  unsigned epoch[132 * 8];
  unsigned zero[128];
  unsigned prof[132 * 512];
  __align__(1024)
  __nv_bfloat16 u[SEQ * DM];
  __nv_bfloat16 h[2 * SEQ * 1280];
  __nv_bfloat16 kv[DM * SEQ];
  __nv_bfloat16 gt[DM * SEQ];
  __nv_bfloat16 bcopy[2 * DM * DM];
};
__device__ __align__(1024) Scratch g_scr;
#define PROFC(c, i) do {} while (0)
#define PSEL 1
#define PROF(i) do {} while (0)

constexpr int C_KV = 0, C_G = 10;
constexpr int F_U3 = 0, F_H = 128;

constexpr int R_OFF = 196608, R4_OFF0 = 73728, R4_OFF1 = 122880, H_OFF = 131072, KS_OFF = 131072, CV_OFF = 86272, G_OFF0 = 40960, G_OFF1 = 102400, US_OFF = 98304, XR_OFF = 163840, MX_OFF = 32768;
constexpr int LAM_OFF = 229376, SSM_OFF = LAM_OFF + 1024, BAR_OFF = SSM_OFF + 1344;
constexpr int B_F1 = 0, B_E1 = 10, B_RF0 = 20, B_RF1 = 21, NBAR1 = 22;
constexpr int B_F2 = 22, B_KF = 32, B_GF = 37, B_CD = 38, B_XR = 40, B_ST = 41, B_HD = 42, B_LM = 43, B_E2 = 44, B_GS = 54, B_PS = 59, B_AX = 62, B_SH = 64, B_SG = 69, B_GE = 70, B_EA = 71, B_F3 = 74, NBAR = 84;
__host__ __device__ constexpr int bar_count(int i) { return i < B_E1 ? 1 : i < B_RF0 ? 9 : i < B_F2 ? 8 : i < B_E2 ? 1 : i < B_GS ? 12 : i < B_SH ? 4 : i < B_SG ? 8 : i < B_GE ? 1 : i < B_EA ? 2 : i < B_F3 ? 8 : 1; }
constexpr int MISC_OFF = BAR_OFF + NBAR * 8, SMEM_BYTES = MISC_OFF + 32;
constexpr int KV_PAD = 512, KC_OFS = KV_PAD + 4096, CH_STRIDE = 8960;
__device__ __forceinline__ uint32_t conv_buf(uint32_t sb, int slot) { return sb + CV_OFF + slot * CH_STRIDE; }
constexpr uint64_t tab6(int a, int b, int c, int d, int e, int f, int g, int h, int i, int j) {
  return (uint64_t)a | (uint64_t)b << 6 | (uint64_t)c << 12 | (uint64_t)d << 18 | (uint64_t)e << 24 | (uint64_t)f << 30 | (uint64_t)g << 36 | (uint64_t)h << 42 |
         (uint64_t)i << 48 | (uint64_t)j << 54;
}
constexpr uint64_t WTAB0 = tab6(0, 4, 8, 30, 12, 26, 0, 4, 8, 12), XTAB0 = tab6(40, 45, 50, 34, 16, 21, 40, 45, 50, 16);
constexpr uint64_t WTAB1 = tab6(16, 20, 0, 4, 8, 12, 16, 20, 24, 28), XTAB1 = tab6(40, 45, 50, 32, 40, 45, 50, 32, 40, 45);
constexpr uint32_t DEP0 = 0x4210;

struct Head {
  Scratch* s;
  const __nv_bfloat16 *x, *b0, *b1;
  uint32_t base, swap;
};
struct Params {
  const __nv_bfloat16 *lre, *lim, *ldt, *k, *v, *shk, *cre, *cim, *ssmk, *ssmd, *dskip;
  float* out;
  uint4 role[120];
  CUtensorMap mB, mA[4], mH, mC[2], mGT, mX, sH, sU, sK;
};

__device__ __forceinline__ uint32_t smem_u32(const void* p) { return (uint32_t)__cvta_generic_to_shared(p); }
__device__ __forceinline__ uint32_t opaque(uint32_t x) { uint32_t y; asm volatile("mov.u32 %0, %1;" : "=r"(y) : "r"(x)); return y; }
__device__ __forceinline__ int lane_id() { int y; asm volatile("mov.u32 %0, %%laneid;" : "=r"(y)); return y; }
__device__ __forceinline__ void delay(uint32_t n) {
  asm volatile("{ .reg .pred p; .reg .u32 a, b; mov.u32 a, %%clock; L: mov.u32 b, %%clock; sub.u32 b, b, a; setp.lt.u32 p, b, %0; @p bra.uni L; }" ::"r"(n) : "memory");
}
__device__ __forceinline__ void mbar_init(uint32_t bar, uint32_t cnt) { asm volatile("mbarrier.init.shared::cta.b64 [%0], %1;" ::"r"(bar), "r"(cnt) : "memory"); }
__device__ __forceinline__ void mbar_expect_tx(uint32_t bar, uint32_t bytes) { asm volatile("mbarrier.arrive.expect_tx.shared::cta.b64 _, [%0], %1;" ::"r"(bar), "r"(bytes) : "memory"); }
__device__ __forceinline__ void mbar_arrive(uint32_t bar) { asm volatile("mbarrier.arrive.shared::cta.b64 _, [%0];" ::"r"(bar) : "memory"); }
__device__ __forceinline__ void mbar_arrive_if(uint32_t bar, bool c) {
  asm volatile("{ .reg .pred p; setp.ne.u32 p, %1, 0; @p mbarrier.arrive.shared::cta.b64 _, [%0]; }" ::"r"(bar), "r"((uint32_t)c) : "memory");
}
__device__ __forceinline__ void prefetch_if(const void* p, bool c) { asm volatile("{ .reg .pred p; setp.ne.u32 p, %1, 0; @p prefetch.global.L2 [%0]; }" ::"l"(p), "r"((uint32_t)c)); }
__device__ __forceinline__ void mbar_arrive_cl(uint32_t bar, uint32_t cta) {
  asm volatile("{ .reg .b32 ra; mapa.shared::cluster.u32 ra, %0, %1; mbarrier.arrive.shared::cluster.b64 _, [ra]; }" ::"r"(bar), "r"(cta) : "memory");
}
__device__ __forceinline__ uint32_t mapa(uint32_t a, uint32_t cta) { uint32_t r; asm("mapa.shared::cluster.u32 %0, %1, %2;" : "=r"(r) : "r"(a), "r"(cta)); return r; }
__device__ __forceinline__ void mbar_arrive_at(uint32_t ra) { asm volatile("mbarrier.arrive.shared::cluster.b64 _, [%0];" ::"r"(ra) : "memory"); }
__device__ __forceinline__ void mbar_wait(uint32_t bar, uint32_t parity = 0) {
  asm volatile("{ .reg .pred p; .reg .u32 c; mov.u32 c, 0;\n"
               "W: mbarrier.try_wait.parity.shared::cta.b64 p, [%0], %1; @p bra.uni D;\n"
               "add.u32 c, c, 1; setp.lt.u32 p, c, 0x100000; @p bra.uni W;\nD: }" ::"r"(bar), "r"(parity) : "memory");
}
__device__ __forceinline__ bool elect_one() { uint32_t p; asm volatile("{ .reg .pred P; elect.sync _|P, 0xffffffff; selp.u32 %0,1,0,P; }" : "=r"(p)); return p; }
__device__ __forceinline__ void bar_sync(int id, int n) { __syncwarp(); asm volatile("bar.sync %0, %1;" ::"r"(id), "r"(n) : "memory"); }
__device__ __forceinline__ void tma2d(uint32_t dst, const CUtensorMap* m, int c0, int c1, uint32_t bar) {
  asm volatile("cp.async.bulk.tensor.2d.shared::cluster.global.mbarrier::complete_tx::bytes [%0], [%1, {%3,%4}], [%2];"
               ::"r"(dst), "l"(m), "r"(bar), "r"(c0), "r"(c1) : "memory");
}
__device__ __forceinline__ void tma5d(uint32_t dst, const CUtensorMap* m, int c0, int c4, uint32_t bar) {
  asm volatile("cp.async.bulk.tensor.5d.shared::cluster.global.mbarrier::complete_tx::bytes [%0], [%1, {%3,%5,%5,%5,%4}], [%2];"
               ::"r"(dst), "l"(m), "r"(bar), "r"(c0), "r"(c4), "r"(0) : "memory");
}
__device__ __forceinline__ void tma4d(uint32_t dst, const CUtensorMap* m, int c0, int c3, uint32_t bar) {
  asm volatile("cp.async.bulk.tensor.4d.shared::cluster.global.mbarrier::complete_tx::bytes [%0], [%1, {%3,%5,%5,%4}], [%2];"
               ::"r"(dst), "l"(m), "r"(bar), "r"(c0), "r"(c3), "r"(0) : "memory");
}
__device__ __forceinline__ void tma4d_mc(uint32_t dst, const CUtensorMap* m, int c0, int c1, int c2, int c3, uint32_t bar, uint32_t mask) {
  asm volatile("cp.async.bulk.tensor.4d.shared::cluster.global.mbarrier::complete_tx::bytes.multicast::cluster [%0], [%1, {%3,%4,%5,%6}], [%2], %7;"
               ::"r"(dst), "l"(m), "r"(bar), "r"(c0), "r"(c1), "r"(c2), "r"(c3), "h"((uint16_t)mask) : "memory");
}
__device__ __forceinline__ void bulk_g2s(uint32_t dst, const void* src, uint32_t bytes, uint32_t bar) {
  asm volatile("cp.async.bulk.shared::cluster.global.mbarrier::complete_tx::bytes [%0], [%1], %2, [%3];" ::"r"(dst), "l"(src), "r"(bytes), "r"(bar) : "memory");
}
__device__ __forceinline__ void tma4d_store(const CUtensorMap* m, uint32_t src, int c0, int c1, int c2, int c3) {
  asm volatile("cp.async.bulk.tensor.4d.global.shared::cta.bulk_group [%0, {%2,%3,%4,%5}], [%1];" ::"l"(m), "r"(src), "r"(c0), "r"(c1), "r"(c2), "r"(c3) : "memory");
}
__device__ __forceinline__ void tma2d_store(const CUtensorMap* m, uint32_t src, int c0, int c1) {
  asm volatile("cp.async.bulk.tensor.2d.global.shared::cta.bulk_group [%0, {%2,%3}], [%1];" ::"l"(m), "r"(src), "r"(c0), "r"(c1) : "memory");
}
__device__ __forceinline__ void bulk_s2g(void* dst, uint32_t src, uint32_t bytes) {
  asm volatile("cp.async.bulk.global.shared::cta.bulk_group [%0], [%1], %2;" ::"l"(dst), "r"(src), "r"(bytes) : "memory");
}
__device__ __forceinline__ void bulk_commit() { asm volatile("cp.async.bulk.commit_group;" ::: "memory"); }
__device__ __forceinline__ void bulk_wait() { asm volatile("cp.async.bulk.wait_group 0;" ::: "memory"); }
__device__ __forceinline__ void fence_async() { asm volatile("fence.proxy.async.shared::cta;" ::: "memory"); }
__device__ __forceinline__ void prefetch_l2(const void* src, uint32_t bytes) { asm volatile("cp.async.bulk.prefetch.L2.global [%0], %1;" ::"l"(src), "r"(bytes) : "memory"); }
__device__ __forceinline__ void prefetch_map(const CUtensorMap* m) { asm volatile("prefetch.tensormap [%0];" ::"l"(m) : "memory"); }
__device__ __forceinline__ void wg_fence() { __syncwarp(); asm volatile("wgmma.fence.sync.aligned;" ::: "memory"); }
__device__ __forceinline__ void wg_commit() { asm volatile("wgmma.commit_group.sync.aligned;" ::: "memory"); }
template <int N> __device__ __forceinline__ void wg_wait() { asm volatile("wgmma.wait_group.sync.aligned %0;" ::"n"(N) : "memory"); }
template <int N> __device__ __forceinline__ void fence_regs(float (&d)[N]) {
#pragma unroll
  for (int i = 0; i < N; i++) asm volatile("" : "+f"(d[i])::"memory");
}
__device__ __forceinline__ uint64_t make_desc(uint32_t addr, uint32_t lbo, uint32_t sbo, uint32_t swz) {
  return (uint64_t)((addr & 0x3FFFF) >> 4) | ((uint64_t)(lbo >> 4) << 16) | ((uint64_t)(sbo >> 4) << 32) | ((uint64_t)swz << 62);
}
__device__ __forceinline__ uint32_t ldg1(const void* p) { uint32_t v; asm volatile("ld.global.nc.u32 %0,[%1];" : "=r"(v) : "l"(p)); return v; }
__device__ __forceinline__ uint32_t lds32(uint32_t a) { uint32_t v; asm volatile("ld.shared.u32 %0,[%1];" : "=r"(v) : "r"(a)); return v; }
__device__ __forceinline__ unsigned ld_rlx(const unsigned* p) { unsigned v; asm volatile("ld.relaxed.gpu.global.u32 %0,[%1];" : "=r"(v) : "l"(p) : "memory"); return v; }
__device__ __forceinline__ uint4 ld_rlx4(const void* p) {
  uint4 v; asm volatile("ld.relaxed.gpu.global.v4.u32 {%0,%1,%2,%3},[%4];" : "=r"(v.x), "=r"(v.y), "=r"(v.z), "=r"(v.w) : "l"(p) : "memory"); return v;
}
__device__ __forceinline__ uint2 ld_rlx2(const void* p) { uint2 v; asm volatile("ld.relaxed.gpu.global.v2.u32 {%0,%1},[%2];" : "=r"(v.x), "=r"(v.y) : "l"(p) : "memory"); return v; }
__device__ __forceinline__ void st_rlx2(void* p, uint32_t a, uint32_t b) { asm volatile("st.relaxed.gpu.global.v2.u32 [%0],{%1,%2};" ::"l"(p), "r"(a), "r"(b) : "memory"); }
__device__ __forceinline__ void st_rlx(void* p, uint32_t a) { asm volatile("st.relaxed.gpu.global.u32 [%0],%1;" ::"l"(p), "r"(a) : "memory"); }
#define PUB 15
template <int SITE> __device__ __forceinline__ void release() { if (PUB & SITE) asm volatile("fence.release.gpu;" ::: "memory"); }
__device__ __forceinline__ void signal_flag(unsigned* p, unsigned val) { asm volatile("st.relaxed.gpu.global.u32 [%0],%1;" ::"l"(p), "r"(val) : "memory"); }
__device__ __forceinline__ void signal_cnt(unsigned* p, unsigned n) { asm volatile("red.relaxed.gpu.global.add.u32 [%0],%1;" ::"l"(p), "r"(n) : "memory"); }
__device__ __forceinline__ void wait_flags(const unsigned* p, unsigned val, uint32_t need, uint32_t& ready) {
#pragma unroll 1
  for (int it = 0; (ready & need) != need && it < SPIN; it++) ready = __ballot_sync(0xffffffff, ld_rlx(p) == val);
}
__device__ __forceinline__ void wait_cnt(const unsigned* p, unsigned tgt) {
  asm volatile("{ .reg .pred p; .reg .u32 c; .reg .s32 v; mov.u32 c, 0;\n"
               "W: ld.relaxed.gpu.global.u32 v, [%0]; sub.s32 v, v, %1; setp.ge.s32 p, v, 0; @p bra.uni D;\n"
               "add.u32 c, c, 1; setp.lt.u32 p, c, 0x100000; @p bra.uni W;\nD: }" ::"l"(p), "r"(tgt) : "memory");
}
__device__ __forceinline__ uint32_t pack_bf(float lo, float hi) { uint32_t r; asm("cvt.rn.bf16x2.f32 %0, %1, %2;" : "=r"(r) : "f"(hi), "f"(lo)); return r; }
__device__ __forceinline__ float bf_lo(uint32_t v) { return __uint_as_float(v << 16); }
__device__ __forceinline__ float bf_hi(uint32_t v) { return __uint_as_float(v & 0xffff0000u); }
__device__ __forceinline__ float bf_rn(float x) { return __bfloat162float(__float2bfloat16_rn(x)); }
__device__ __forceinline__ float frcp(float x) { float r; asm("rcp.approx.ftz.f32 %0,%1;" : "=f"(r) : "f"(x)); return r; }
__device__ __forceinline__ float fsqrt(float x) { float r; asm("sqrt.approx.ftz.f32 %0,%1;" : "=f"(r) : "f"(x)); return r; }
__device__ __forceinline__ float frsqrt(float x) { float r; asm("rsqrt.approx.ftz.f32 %0,%1;" : "=f"(r) : "f"(x)); return r; }
__device__ __forceinline__ uint32_t hmul2(uint32_t a, uint32_t b) { uint32_t r; asm("mul.rn.bf16x2 %0,%1,%2;" : "=r"(r) : "r"(a), "r"(b)); return r; }
__device__ __forceinline__ uint32_t hfma2(uint32_t a, uint32_t b, uint32_t c) { uint32_t r; asm("fma.rn.bf16x2 %0,%1,%2,%3;" : "=r"(r) : "r"(a), "r"(b), "r"(c)); return r; }
__device__ __forceinline__ float2 cmul(float2 a, float2 b) { return make_float2(a.x * b.x - a.y * b.y, a.x * b.y + a.y * b.x); }
__device__ __forceinline__ float2 cfma(float2 a, float2 b, float2 c) {
  return make_float2(fmaf(a.x, b.x, fmaf(-a.y, b.y, c.x)), fmaf(a.x, b.y, fmaf(a.y, b.x, c.y)));
}
__device__ __forceinline__ uint32_t tagf(float v, uint32_t tag) { return (__float_as_uint(v) & ~1u) | tag; }
__device__ __forceinline__ float untag(uint32_t v) { return __uint_as_float(v & ~1u); }
__device__ __forceinline__ bool untagged(const uint4& v, uint32_t tag) { return (((v.x ^ tag) | (v.y ^ tag) | (v.z ^ tag) | (v.w ^ tag)) & 1) != 0; }
__device__ __forceinline__ bool untagged(const uint2& v, uint32_t tag) { return (((v.x ^ tag) | (v.y ^ tag)) & 1) != 0; }
__device__ __forceinline__ float2 lam_bar(float lr, float li, float ldt) {
  float dt = bf_rn(expf(ldt)); float e = expf(dt * lr), s, c; sincospif(dt * li * 0.31830988618379067f, &s, &c); return make_float2(e * c, e * s);
}

__device__ __forceinline__ int conv_ch(uint32_t c, int s) { return s * ((c >> 21) & 255) + (c & 255) - (s >= (int)(c >> 29) ? 8 : 0); }
struct Role {
  uint32_t v, c, p;
  __device__ __forceinline__ int tb() const { return v & 15; }
  __device__ __forceinline__ int cb() const { return (v >> 4) & 15; }
  __device__ __forceinline__ int b() const { return (v >> 8) & 255; }
  __device__ __forceinline__ int ubase() const { return (v >> 16) & 7; }
  __device__ __forceinline__ int ugs() const { return (v >> 19) & 7; }
  __device__ __forceinline__ int wpart() const { return (v >> 22) & 7; }
  __device__ __forceinline__ int rank() const { return (v >> 26) & 7; }
  __device__ __forceinline__ int cs() const { return (v >> 29) ? 8 : 2; }
  __device__ __forceinline__ int ch(int s) const { return conv_ch(c, s); }
  __device__ __forceinline__ int wlo() const { return p & 1; }
  __device__ __forceinline__ int whi() const { return (p >> 1) & 1; }
  __device__ __forceinline__ uint32_t wmask() const { return (p >> 2) & 255; }
  __device__ __forceinline__ uint32_t umask() const { return (p >> 10) & 255; }
  __device__ __forceinline__ int uj() const { return (p >> 20) & 31; }
  __device__ __forceinline__ int sm() const { return (p >> 25) & 15; }
  __device__ __forceinline__ int nch() const { return (c >> 10) & 7; }
  __device__ __forceinline__ int nprep() const { return (c >> 13) & 255; }
};

__device__ __forceinline__ void wgmma_ss80(float (&d)[40], uint64_t da, uint64_t db, int sd){
  asm volatile("{ .reg .pred p; setp.ne.b32 p, %42, 0;\n"
   "wgmma.mma_async.sync.aligned.m64n80k16.f32.bf16.bf16 {%0, %1, %2, %3, %4, %5, %6, %7, %8, %9, %10, %11, %12, %13, %14, %15, %16, %17, %18, %19, %20, %21, %22, %23, %24, %25, %26, %27, %28, %29, %30, %31, %32, %33, %34, %35, %36, %37, %38, %39}, %40, %41, p, 1, 1, 0, 0; }\n"
   : "+f"(d[0]), "+f"(d[1]), "+f"(d[2]), "+f"(d[3]), "+f"(d[4]), "+f"(d[5]), "+f"(d[6]), "+f"(d[7]), "+f"(d[8]), "+f"(d[9]), "+f"(d[10]), "+f"(d[11]), "+f"(d[12]), "+f"(d[13]), "+f"(d[14]), "+f"(d[15]), "+f"(d[16]), "+f"(d[17]), "+f"(d[18]), "+f"(d[19]), "+f"(d[20]), "+f"(d[21]), "+f"(d[22]), "+f"(d[23]), "+f"(d[24]), "+f"(d[25]), "+f"(d[26]), "+f"(d[27]), "+f"(d[28]), "+f"(d[29]), "+f"(d[30]), "+f"(d[31]), "+f"(d[32]), "+f"(d[33]), "+f"(d[34]), "+f"(d[35]), "+f"(d[36]), "+f"(d[37]), "+f"(d[38]), "+f"(d[39]) : "l"(da), "l"(db), "r"(sd));
}
__device__ __forceinline__ void wgmma_ss160(float (&d)[80], uint64_t da, uint64_t db, int sd){
  asm volatile("{ .reg .pred p; setp.ne.b32 p, %82, 0;\n"
   "wgmma.mma_async.sync.aligned.m64n160k16.f32.bf16.bf16 {%0, %1, %2, %3, %4, %5, %6, %7, %8, %9, %10, %11, %12, %13, %14, %15, %16, %17, %18, %19, %20, %21, %22, %23, %24, %25, %26, %27, %28, %29, %30, %31, %32, %33, %34, %35, %36, %37, %38, %39, %40, %41, %42, %43, %44, %45, %46, %47, %48, %49, %50, %51, %52, %53, %54, %55, %56, %57, %58, %59, %60, %61, %62, %63, %64, %65, %66, %67, %68, %69, %70, %71, %72, %73, %74, %75, %76, %77, %78, %79}, %80, %81, p, 1, 1, 0, 0; }\n"
   : "+f"(d[0]), "+f"(d[1]), "+f"(d[2]), "+f"(d[3]), "+f"(d[4]), "+f"(d[5]), "+f"(d[6]), "+f"(d[7]), "+f"(d[8]), "+f"(d[9]), "+f"(d[10]), "+f"(d[11]), "+f"(d[12]), "+f"(d[13]), "+f"(d[14]), "+f"(d[15]), "+f"(d[16]), "+f"(d[17]), "+f"(d[18]), "+f"(d[19]), "+f"(d[20]), "+f"(d[21]), "+f"(d[22]), "+f"(d[23]), "+f"(d[24]), "+f"(d[25]), "+f"(d[26]), "+f"(d[27]), "+f"(d[28]), "+f"(d[29]), "+f"(d[30]), "+f"(d[31]), "+f"(d[32]), "+f"(d[33]), "+f"(d[34]), "+f"(d[35]), "+f"(d[36]), "+f"(d[37]), "+f"(d[38]), "+f"(d[39]), "+f"(d[40]), "+f"(d[41]), "+f"(d[42]), "+f"(d[43]), "+f"(d[44]), "+f"(d[45]), "+f"(d[46]), "+f"(d[47]), "+f"(d[48]), "+f"(d[49]), "+f"(d[50]), "+f"(d[51]), "+f"(d[52]), "+f"(d[53]), "+f"(d[54]), "+f"(d[55]), "+f"(d[56]), "+f"(d[57]), "+f"(d[58]), "+f"(d[59]), "+f"(d[60]), "+f"(d[61]), "+f"(d[62]), "+f"(d[63]), "+f"(d[64]), "+f"(d[65]), "+f"(d[66]), "+f"(d[67]), "+f"(d[68]), "+f"(d[69]), "+f"(d[70]), "+f"(d[71]), "+f"(d[72]), "+f"(d[73]), "+f"(d[74]), "+f"(d[75]), "+f"(d[76]), "+f"(d[77]), "+f"(d[78]), "+f"(d[79]) : "l"(da), "l"(db), "r"(sd));
}
template<int N> __device__ __forceinline__ void wgmma_rs(float (&d)[N/2], uint32_t a0, uint32_t a1, uint32_t a2, uint32_t a3, uint64_t db, int sd);
template<> __device__ __forceinline__ void wgmma_rs<16>(float (&d)[8], uint32_t a0, uint32_t a1, uint32_t a2, uint32_t a3, uint64_t db, int sd){
  asm volatile("{ .reg .pred p; setp.ne.b32 p, %13, 0;\n"
   "wgmma.mma_async.sync.aligned.m64n16k16.f32.bf16.bf16 {%0, %1, %2, %3, %4, %5, %6, %7}, {%8,%9,%10,%11}, %12, p, 1, 1, 0; }\n"
   : "+f"(d[0]), "+f"(d[1]), "+f"(d[2]), "+f"(d[3]), "+f"(d[4]), "+f"(d[5]), "+f"(d[6]), "+f"(d[7]) : "r"(a0), "r"(a1), "r"(a2), "r"(a3), "l"(db), "r"(sd));
}
template<> __device__ __forceinline__ void wgmma_rs<32>(float (&d)[16], uint32_t a0, uint32_t a1, uint32_t a2, uint32_t a3, uint64_t db, int sd){
  asm volatile("{ .reg .pred p; setp.ne.b32 p, %21, 0;\n"
   "wgmma.mma_async.sync.aligned.m64n32k16.f32.bf16.bf16 {%0, %1, %2, %3, %4, %5, %6, %7, %8, %9, %10, %11, %12, %13, %14, %15}, {%16,%17,%18,%19}, %20, p, 1, 1, 0; }\n"
   : "+f"(d[0]), "+f"(d[1]), "+f"(d[2]), "+f"(d[3]), "+f"(d[4]), "+f"(d[5]), "+f"(d[6]), "+f"(d[7]), "+f"(d[8]), "+f"(d[9]), "+f"(d[10]), "+f"(d[11]), "+f"(d[12]), "+f"(d[13]), "+f"(d[14]), "+f"(d[15]) : "r"(a0), "r"(a1), "r"(a2), "r"(a3), "l"(db), "r"(sd));
}
template<> __device__ __forceinline__ void wgmma_rs<48>(float (&d)[24], uint32_t a0, uint32_t a1, uint32_t a2, uint32_t a3, uint64_t db, int sd){
  asm volatile("{ .reg .pred p; setp.ne.b32 p, %29, 0;\n"
   "wgmma.mma_async.sync.aligned.m64n48k16.f32.bf16.bf16 {%0, %1, %2, %3, %4, %5, %6, %7, %8, %9, %10, %11, %12, %13, %14, %15, %16, %17, %18, %19, %20, %21, %22, %23}, {%24,%25,%26,%27}, %28, p, 1, 1, 0; }\n"
   : "+f"(d[0]), "+f"(d[1]), "+f"(d[2]), "+f"(d[3]), "+f"(d[4]), "+f"(d[5]), "+f"(d[6]), "+f"(d[7]), "+f"(d[8]), "+f"(d[9]), "+f"(d[10]), "+f"(d[11]), "+f"(d[12]), "+f"(d[13]), "+f"(d[14]), "+f"(d[15]), "+f"(d[16]), "+f"(d[17]), "+f"(d[18]), "+f"(d[19]), "+f"(d[20]), "+f"(d[21]), "+f"(d[22]), "+f"(d[23]) : "r"(a0), "r"(a1), "r"(a2), "r"(a3), "l"(db), "r"(sd));
}
template<> __device__ __forceinline__ void wgmma_rs<64>(float (&d)[32], uint32_t a0, uint32_t a1, uint32_t a2, uint32_t a3, uint64_t db, int sd){
  asm volatile("{ .reg .pred p; setp.ne.b32 p, %37, 0;\n"
   "wgmma.mma_async.sync.aligned.m64n64k16.f32.bf16.bf16 {%0, %1, %2, %3, %4, %5, %6, %7, %8, %9, %10, %11, %12, %13, %14, %15, %16, %17, %18, %19, %20, %21, %22, %23, %24, %25, %26, %27, %28, %29, %30, %31}, {%32,%33,%34,%35}, %36, p, 1, 1, 0; }\n"
   : "+f"(d[0]), "+f"(d[1]), "+f"(d[2]), "+f"(d[3]), "+f"(d[4]), "+f"(d[5]), "+f"(d[6]), "+f"(d[7]), "+f"(d[8]), "+f"(d[9]), "+f"(d[10]), "+f"(d[11]), "+f"(d[12]), "+f"(d[13]), "+f"(d[14]), "+f"(d[15]), "+f"(d[16]), "+f"(d[17]), "+f"(d[18]), "+f"(d[19]), "+f"(d[20]), "+f"(d[21]), "+f"(d[22]), "+f"(d[23]), "+f"(d[24]), "+f"(d[25]), "+f"(d[26]), "+f"(d[27]), "+f"(d[28]), "+f"(d[29]), "+f"(d[30]), "+f"(d[31]) : "r"(a0), "r"(a1), "r"(a2), "r"(a3), "l"(db), "r"(sd));
}
template<> __device__ __forceinline__ void wgmma_rs<80>(float (&d)[40], uint32_t a0, uint32_t a1, uint32_t a2, uint32_t a3, uint64_t db, int sd){
  asm volatile("{ .reg .pred p; setp.ne.b32 p, %45, 0;\n"
   "wgmma.mma_async.sync.aligned.m64n80k16.f32.bf16.bf16 {%0, %1, %2, %3, %4, %5, %6, %7, %8, %9, %10, %11, %12, %13, %14, %15, %16, %17, %18, %19, %20, %21, %22, %23, %24, %25, %26, %27, %28, %29, %30, %31, %32, %33, %34, %35, %36, %37, %38, %39}, {%40,%41,%42,%43}, %44, p, 1, 1, 0; }\n"
   : "+f"(d[0]), "+f"(d[1]), "+f"(d[2]), "+f"(d[3]), "+f"(d[4]), "+f"(d[5]), "+f"(d[6]), "+f"(d[7]), "+f"(d[8]), "+f"(d[9]), "+f"(d[10]), "+f"(d[11]), "+f"(d[12]), "+f"(d[13]), "+f"(d[14]), "+f"(d[15]), "+f"(d[16]), "+f"(d[17]), "+f"(d[18]), "+f"(d[19]), "+f"(d[20]), "+f"(d[21]), "+f"(d[22]), "+f"(d[23]), "+f"(d[24]), "+f"(d[25]), "+f"(d[26]), "+f"(d[27]), "+f"(d[28]), "+f"(d[29]), "+f"(d[30]), "+f"(d[31]), "+f"(d[32]), "+f"(d[33]), "+f"(d[34]), "+f"(d[35]), "+f"(d[36]), "+f"(d[37]), "+f"(d[38]), "+f"(d[39]) : "r"(a0), "r"(a1), "r"(a2), "r"(a3), "l"(db), "r"(sd));
}
template<> __device__ __forceinline__ void wgmma_rs<96>(float (&d)[48], uint32_t a0, uint32_t a1, uint32_t a2, uint32_t a3, uint64_t db, int sd){
  asm volatile("{ .reg .pred p; setp.ne.b32 p, %53, 0;\n"
   "wgmma.mma_async.sync.aligned.m64n96k16.f32.bf16.bf16 {%0, %1, %2, %3, %4, %5, %6, %7, %8, %9, %10, %11, %12, %13, %14, %15, %16, %17, %18, %19, %20, %21, %22, %23, %24, %25, %26, %27, %28, %29, %30, %31, %32, %33, %34, %35, %36, %37, %38, %39, %40, %41, %42, %43, %44, %45, %46, %47}, {%48,%49,%50,%51}, %52, p, 1, 1, 0; }\n"
   : "+f"(d[0]), "+f"(d[1]), "+f"(d[2]), "+f"(d[3]), "+f"(d[4]), "+f"(d[5]), "+f"(d[6]), "+f"(d[7]), "+f"(d[8]), "+f"(d[9]), "+f"(d[10]), "+f"(d[11]), "+f"(d[12]), "+f"(d[13]), "+f"(d[14]), "+f"(d[15]), "+f"(d[16]), "+f"(d[17]), "+f"(d[18]), "+f"(d[19]), "+f"(d[20]), "+f"(d[21]), "+f"(d[22]), "+f"(d[23]), "+f"(d[24]), "+f"(d[25]), "+f"(d[26]), "+f"(d[27]), "+f"(d[28]), "+f"(d[29]), "+f"(d[30]), "+f"(d[31]), "+f"(d[32]), "+f"(d[33]), "+f"(d[34]), "+f"(d[35]), "+f"(d[36]), "+f"(d[37]), "+f"(d[38]), "+f"(d[39]), "+f"(d[40]), "+f"(d[41]), "+f"(d[42]), "+f"(d[43]), "+f"(d[44]), "+f"(d[45]), "+f"(d[46]), "+f"(d[47]) : "r"(a0), "r"(a1), "r"(a2), "r"(a3), "l"(db), "r"(sd));
}
template<> __device__ __forceinline__ void wgmma_rs<112>(float (&d)[56], uint32_t a0, uint32_t a1, uint32_t a2, uint32_t a3, uint64_t db, int sd){
  asm volatile("{ .reg .pred p; setp.ne.b32 p, %61, 0;\n"
   "wgmma.mma_async.sync.aligned.m64n112k16.f32.bf16.bf16 {%0, %1, %2, %3, %4, %5, %6, %7, %8, %9, %10, %11, %12, %13, %14, %15, %16, %17, %18, %19, %20, %21, %22, %23, %24, %25, %26, %27, %28, %29, %30, %31, %32, %33, %34, %35, %36, %37, %38, %39, %40, %41, %42, %43, %44, %45, %46, %47, %48, %49, %50, %51, %52, %53, %54, %55}, {%56,%57,%58,%59}, %60, p, 1, 1, 0; }\n"
   : "+f"(d[0]), "+f"(d[1]), "+f"(d[2]), "+f"(d[3]), "+f"(d[4]), "+f"(d[5]), "+f"(d[6]), "+f"(d[7]), "+f"(d[8]), "+f"(d[9]), "+f"(d[10]), "+f"(d[11]), "+f"(d[12]), "+f"(d[13]), "+f"(d[14]), "+f"(d[15]), "+f"(d[16]), "+f"(d[17]), "+f"(d[18]), "+f"(d[19]), "+f"(d[20]), "+f"(d[21]), "+f"(d[22]), "+f"(d[23]), "+f"(d[24]), "+f"(d[25]), "+f"(d[26]), "+f"(d[27]), "+f"(d[28]), "+f"(d[29]), "+f"(d[30]), "+f"(d[31]), "+f"(d[32]), "+f"(d[33]), "+f"(d[34]), "+f"(d[35]), "+f"(d[36]), "+f"(d[37]), "+f"(d[38]), "+f"(d[39]), "+f"(d[40]), "+f"(d[41]), "+f"(d[42]), "+f"(d[43]), "+f"(d[44]), "+f"(d[45]), "+f"(d[46]), "+f"(d[47]), "+f"(d[48]), "+f"(d[49]), "+f"(d[50]), "+f"(d[51]), "+f"(d[52]), "+f"(d[53]), "+f"(d[54]), "+f"(d[55]) : "r"(a0), "r"(a1), "r"(a2), "r"(a3), "l"(db), "r"(sd));
}
template<> __device__ __forceinline__ void wgmma_rs<128>(float (&d)[64], uint32_t a0, uint32_t a1, uint32_t a2, uint32_t a3, uint64_t db, int sd){
  asm volatile("{ .reg .pred p; setp.ne.b32 p, %69, 0;\n"
   "wgmma.mma_async.sync.aligned.m64n128k16.f32.bf16.bf16 {%0, %1, %2, %3, %4, %5, %6, %7, %8, %9, %10, %11, %12, %13, %14, %15, %16, %17, %18, %19, %20, %21, %22, %23, %24, %25, %26, %27, %28, %29, %30, %31, %32, %33, %34, %35, %36, %37, %38, %39, %40, %41, %42, %43, %44, %45, %46, %47, %48, %49, %50, %51, %52, %53, %54, %55, %56, %57, %58, %59, %60, %61, %62, %63}, {%64,%65,%66,%67}, %68, p, 1, 1, 0; }\n"
   : "+f"(d[0]), "+f"(d[1]), "+f"(d[2]), "+f"(d[3]), "+f"(d[4]), "+f"(d[5]), "+f"(d[6]), "+f"(d[7]), "+f"(d[8]), "+f"(d[9]), "+f"(d[10]), "+f"(d[11]), "+f"(d[12]), "+f"(d[13]), "+f"(d[14]), "+f"(d[15]), "+f"(d[16]), "+f"(d[17]), "+f"(d[18]), "+f"(d[19]), "+f"(d[20]), "+f"(d[21]), "+f"(d[22]), "+f"(d[23]), "+f"(d[24]), "+f"(d[25]), "+f"(d[26]), "+f"(d[27]), "+f"(d[28]), "+f"(d[29]), "+f"(d[30]), "+f"(d[31]), "+f"(d[32]), "+f"(d[33]), "+f"(d[34]), "+f"(d[35]), "+f"(d[36]), "+f"(d[37]), "+f"(d[38]), "+f"(d[39]), "+f"(d[40]), "+f"(d[41]), "+f"(d[42]), "+f"(d[43]), "+f"(d[44]), "+f"(d[45]), "+f"(d[46]), "+f"(d[47]), "+f"(d[48]), "+f"(d[49]), "+f"(d[50]), "+f"(d[51]), "+f"(d[52]), "+f"(d[53]), "+f"(d[54]), "+f"(d[55]), "+f"(d[56]), "+f"(d[57]), "+f"(d[58]), "+f"(d[59]), "+f"(d[60]), "+f"(d[61]), "+f"(d[62]), "+f"(d[63]) : "r"(a0), "r"(a1), "r"(a2), "r"(a3), "l"(db), "r"(sd));
}

#define BAR(i) (bars + 8u * (uint32_t)(i))

template <int G> __device__ __forceinline__ void conv_frags(uint32_t (&a)[12], uint32_t abase) {
#pragma unroll
  for (int i = 0; i < 12; i++) a[i] = lds32(abase + (G * 4 + i / 3) * 128 + (i % 3) * 4);
}
__device__ __forceinline__ void kv_prefetch(const __nv_bfloat16* pf, int task) { prefetch_if(pf + 64 * (task & 31) * DM + 64 * (task >> 5), task < 320); }
__device__ __forceinline__ void kv_load(const Params& P, Scratch* S, int task, int tid, uint32_t (&k_)[19], uint32_t (&v_)[16], uint4& sk) {
  const int row = 64 * (task & 31) + 16 * (tid >> 5), ch = 64 * (task >> 5) + 2 * (tid & 31);
  const uint32_t* kp = (const uint32_t*)(P.k + (size_t)row * DM + ch);
  const uint32_t* vp = (const uint32_t*)(P.v + (size_t)row * DM + ch);
  const uint32_t* hp = row > 0 ? kp - 3 * (DM / 2) : S->zero;
  const int hs = row > 0 ? DM / 2 : 0;
  asm volatile("ld.global.nc.v4.u32 {%0,%1,%2,%3},[%4];" : "=r"(sk.x), "=r"(sk.y), "=r"(sk.z), "=r"(sk.w) : "l"(P.shk + ch * 4));
#pragma unroll
  for (int i = 0; i < 3; i++) k_[i] = ldg1(hp + i * hs);
#pragma unroll
  for (int i = 0; i < 16; i++) { k_[i + 3] = ldg1(kp + i * (DM / 2)); v_[i] = ldg1(vp + i * (DM / 2)); }
}
template <int SH> __device__ __forceinline__ void xb_prefetch(const Head& H, int id, int tid, int c0) {
  const int ri = tid >> SH, rr = 11 * id + ri - 16;
  const __nv_bfloat16* p = ri < 16 ? H.x + (size_t)(16 * min(id, 127) + ri) * DM : (rr < DM ? H.b0 : H.b1 - DM * DM) + (size_t)rr * DM;
  prefetch_if(p + c0 + 64 * (tid & ((1 << SH) - 1)), ri < 16 || (ri < 27 && rr < 2 * DM));
}
__device__ __forceinline__ uint4 ldg4(const void* p) { uint4 v; asm volatile("ld.global.nc.v4.u32 {%0,%1,%2,%3},[%4];" : "=r"(v.x), "=r"(v.y), "=r"(v.z), "=r"(v.w) : "l"(p)); return v; }
__device__ __forceinline__ uint4 lds4(uint32_t a) { uint4 v; asm volatile("ld.shared.v4.u32 {%0,%1,%2,%3},[%4];" : "=r"(v.x), "=r"(v.y), "=r"(v.z), "=r"(v.w) : "r"(a) : "memory"); return v; }
__device__ __forceinline__ void discretise(const Head& H, const Params& P, uint32_t sb, Role R, int lane, uint32_t e1) {
  const uint32_t dn = __ldg((const unsigned short*)P.ssmd + min(conv_ch(R.c, (lane + 7) & 7), DM - 1));
  const int c = 32 * min(R.cb(), 9) + lane;
  const uint32_t lr2 = ldg1(P.lre + 2 * c), li2 = ldg1(P.lim + 2 * c), ld2 = ldg1(P.ldt + 2 * c);
  asm volatile("st.shared.u32 [%0],%1;" ::"r"(sb + MISC_OFF + 4 * (lane & 7)), "r"((lane & 7) ? dn : e1) : "memory");
#pragma unroll 1
  for (int i = 0; i < 2; i++) {
    const float lr = bf_hi(lr2 << (16 - 16 * i)), li = bf_hi(li2 << (16 - 16 * i));
    const float2 lb = lam_bar(lr, li, bf_hi(ld2 << (16 - 16 * i)));
    const float nx = lb.x - 1.f, ny = lb.y, inv = 2.f * frcp(lr * lr + li * li), cx = (nx * lr + ny * li) * inv, cy = (ny * lr - nx * li) * inv;
    const bool sw = !H.swap;
    asm volatile("st.shared.v4.f32 [%0],{%1,%2,%3,%4};" ::"r"(sb + LAM_OFF + 32 * lane + 16 * i), "f"(lb.x), "f"(sw ? -lb.y : lb.y), "f"(sw ? -cy : cx), "f"(sw ? cx : -cy) : "memory");
  }
  __syncwarp();
}
__device__ __forceinline__ void aux_prep(const Head& H, const Params& P, uint32_t sb, Role R, int tid, long long t_start) {
  Scratch* const S = H.s;
  const uint32_t bars = sb + BAR_OFF;
  tid = opaque(tid);
  const int w = tid >> 5, lane = tid & 31, tb = R.tb(), cb = R.cb();
  uint32_t k_[19], v_[16];
  uint4 sk;
  int task = R.b() < R.nprep() ? R.b() : 320;
  delay(KVDLY);
  PROFC(tid == 0, 345);
  kv_load(P, S, min(task, 319), tid, k_, v_, sk);
  const __nv_bfloat16* pf = (tid < 64 ? P.k : P.v) + (tid & 63) * DM;
  const int j = lane >> 3, sm = min(R.sm(), 9), trow = 160 * tb + 4 * sm + (tb < 12 ? 40 : 32) * w + j;
  const uint32_t so = sb + (2 * w + (j & 1) + 8 * (j >> 1)) * 128 + 16 * (lane & 7), xo = so + sm * 2048, wo = so + (tb & 1) * 8192 + (tb & 6) * 1024;
  const __nv_bfloat16* xp = H.x + (size_t)min(trow, SEQ - 1) * DM + 384 + 8 * (lane & 7);
  const __nv_bfloat16* bp = (j < 2 ? H.b0 : H.b1) + (size_t)(64 * cb + 32 * (tb & 1) + 4 * (tb & 6) + 2 * w + (j & 1)) * DM + 384 + 8 * (lane & 7);
  float s = 0.f, s2 = 0.f, sr = 0.f;
#define STAT(m, n) { const uint32_t xw[4] = {m.x, m.y, m.z, m.w}, bw[4] = {n.x, n.y, n.z, n.w}; \
  _Pragma("unroll") for (int i = 0; i < 4; i++) { const float u = bf_lo(xw[i]), v = bf_hi(xw[i]); s += u + v; s2 = fmaf(u, u, fmaf(v, v, s2)); sr += bf_lo(bw[i]) + bf_hi(bw[i]); } }
#define STATS(K0, K1) _Pragma("unroll 1") for (int kb = K0; kb < K1; kb++) { \
    mbar_wait(BAR(B_F1 + kb)); \
    const uint4 a = lds4(xo + ((uint32_t)(XTAB0 >> (6 * kb)) & 63) * 4096), c = lds4(wo + ((uint32_t)(WTAB0 >> (6 * kb)) & 63) * 4096); \
    STAT(a, c) \
    asm volatile("" : "+f"(s), "+f"(s2), "+f"(sr)); \
    if (XPFAT >= K0 && XPFAT < K1) prefetch_if(((lane & 4) ? bp : xp) + 64 * (lane & 3), kb == XPFAT); \
    kv_prefetch(pf, kb == KPFAT ? task + R.nprep() : kb == KPFAT2 ? task + 2 * R.nprep() : 320); \
  } \
  __syncwarp(); mbar_arrive_if(BAR(B_AX + K0 / 3), lane == 0);
  STATS(0, 3)
  PROFC(tid == 0, 349);
    {
      uint4 m[4], n[4];
#pragma unroll
      for (int i = 0; i < 4; i++) { m[i] = ldg4(xp + 64 * i); n[i] = ldg4(bp + 64 * i); }
      STATS(3, 6)
      PROFC(tid == 0, 346);
      mbar_wait(BAR(B_LM));
      const uint32_t tag = lds32(sb + MISC_OFF) & 1;
#pragma unroll
      for (int i = 0; i < 4; i++) { const uint4 a = m[i], c = n[i]; STAT(a, c) }
      PROFC(tid == 0 && s2 != 1.2345f, 347);
#pragma unroll
      for (int o = 1; o <= 4; o <<= 1) { s += __shfl_xor_sync(0xffffffff, s, o); s2 += __shfl_xor_sync(0xffffffff, s2, o); sr += __shfl_xor_sync(0xffffffff, sr, o); }
      const float mn = s * (1.f / DM), rs = frcp(bf_rn(fsqrt(bf_rn(bf_rn(fmaxf(s2 * (1.f / DM) - mn * mn, 0.f)) + 1e-5f))));
      asm volatile("{ .reg .pred p; setp.ne.u32 p, %2, 0; @p st.relaxed.gpu.global.u32 [%0],%1; }"
                   ::"l"((uint32_t*)(S->RS + (8 * cb + 4 * (tb & 1) + (tb >> 1)) * 16 + 4 * w + (j & 1)) + (lane & 4) + (j >> 1)), "r"(tagf(sr, tag)),
                   "r"((uint32_t)(tb < 8 && (lane & 3) == 0)) : "memory");
      asm volatile("{ .reg .pred p; setp.ne.u32 p, %3, 0; @p st.relaxed.gpu.global.v2.u32 [%0],{%1,%2}; }"
                   ::"l"(S->S + trow), "r"(tagf(rs, tag)), "r"(tagf(-bf_rn(mn) * rs, tag)), "r"((uint32_t)(R.sm() < 10 && (lane & 7) == 0)) : "memory");
      PROFC(tid == 0, 3);
    }
#pragma unroll 1
  for (int r = 0; task < 320; r++) {
    {
      const uint32_t T0 = __byte_perm(sk.x, sk.z, 0x5410), T1 = __byte_perm(sk.x, sk.z, 0x7632);
      const uint32_t T2 = __byte_perm(sk.y, sk.w, 0x5410), T3 = __byte_perm(sk.y, sk.w, 0x7632);
      PROFC(tid == 0 && v_[15] != 0x12345, 336 + r);
      uint32_t o[16];
#pragma unroll
      for (int t = 0; t < 16; t += 2) {
        const uint32_t a = hmul2(hfma2(k_[t + 3], T0, hfma2(k_[t + 2], T1, hfma2(k_[t + 1], T2, hmul2(k_[t], T3)))), v_[t]);
        const uint32_t c = hmul2(hfma2(k_[t + 4], T0, hfma2(k_[t + 3], T1, hfma2(k_[t + 2], T2, hmul2(k_[t + 1], T3)))), v_[t + 1]);
        const int wd = ((7 - t / 2) >> 1) + 4 * ((7 - t / 2) & 1);
        o[wd] = __byte_perm(c, a, 0x5410); o[8 + wd] = __byte_perm(c, a, 0x7632);
        asm volatile("" : "+r"(o[wd]), "+r"(o[8 + wd]));
        if (t == PFAT) kv_prefetch(pf, task + (1 + PFD) * R.nprep());
      }
      PROFC(tid == 0, 330 + 2 * r);
      const int ph = task & 1;
      task += R.nprep();
      if (ORD == 0 && task < 320) kv_load(P, S, task, tid, k_, v_, sk);
      mbar_wait(BAR(B_E1 + 3)); mbar_wait(BAR(B_AX + 1));
#pragma unroll
      for (int i = 0; i < 4; i++) {
        const int row = 2 * lane + (i >> 1);
        asm volatile("st.shared.v4.u32 [%0],{%1,%2,%3,%4};" ::"r"(sb + KS_OFF + r * 8192 + row * 128 + (((2 * w + ((i & 1) ^ ph)) ^ (row & 7)) << 4)),
                     "r"(o[4 * i]), "r"(o[4 * i + 1]), "r"(o[4 * i + 2]), "r"(o[4 * i + 3]) : "memory");
      }
      __syncwarp();
      mbar_arrive_if(BAR(B_PS + r), lane == 0);
      PROFC(tid == 0, 331 + 2 * r);
      if (ORD == 1 && task < 320) kv_load(P, S, task, tid, k_, v_, sk);
    }
  }
#undef STAT
#undef STATS
  PROFC(tid == 0, 40);
}
#define SPLIT(G) asm volatile("{ .reg .pred p; .reg .u32 r; L: mov.u32 r, %%clock; setp.eq.u32 p, r, %0; @p bra.uni L; }" ::"n"(G) : "memory")
template <bool AUX>
__device__ __forceinline__ void conv_loop(uint32_t sb, uint32_t rc, int wg, int tid, long long t_start) {
  sb = opaque(sb); rc = opaque(rc);
  const uint32_t bars = sb + BAR_OFF;
  int slot = AUX ? 0 : wg + 1;
  mbar_wait(BAR(B_LM));
#pragma unroll 1
  while (slot < (int)((rc >> 10) & 7)) {
    tid = opaque(tid);
    const int w = tid >> 5, lane = tid & 31, g = lane >> 2, q = lane & 3;
    const uint32_t Dn = lds32(sb + MISC_OFF + 4 + 4 * slot);
    const uint32_t d0 = (g == 1 && q == 3 - w) ? Dn : 0, d1 = (g == 0 && q == 3 - w) ? Dn : 0;
    const uint32_t cb_ = conv_buf(sb, slot), c0 = cb_ + KC_OFS;
    const uint32_t abase = c0 + 2 * (2 * (g & 1) + 4 * w + 16 * (g >> 1) + 4 * q);
    const uint64_t bd = make_desc(cb_ + KV_PAD, 16, 256, 3);
    const bool hi = lane & 16, s1 = lane & 8;
    const int qo = hi ? (q + 1) & 3 : q;
    const int srcA = hi ? (lane & 12) | ((q + 1) & 3) : (lane & 12) | 16 | ((q + 3) & 3);
    const bool h3 = hi && q == 3, wrap = s1 && qo == 3, back = wrap && hi;
    const bool chi = wrap ? !hi : hi;
    const int cq = s1 ? (qo + 1) & 3 : qo;
    const int srcB = (lane & 4) | (s1 ? 0 : 8) | (chi ? 16 | ((cq + 3) & 3) : cq);
    const uint32_t gp = c0 + ((32 * (2 * w + (g & 1)) + (chi ? 256 : 0)) ^ (chi ? 64 : 0) ^ ((conv_ch(rc, slot) & 8) << 2)) + 4 * (2 * cq + (s1 ? 0 : 1));
    uint32_t a[12], f[16], o[8];
    float S[4], T[4], U[2], keep[2], pv[2] = {0.f, 0.f}, pr[4] = {0.f, 0.f, 0.f, 0.f};
    float e0[64], e1[56], e2[48], e3[40], e4[32], e5[24], e6[16], e7[8];
#define UNR _Pragma("unroll")
#define PERM() UNR for (int i = 0; i < 4; i++) { f[4 * i] = __byte_perm(a[3 * i], a[3 * i + 1], 0x5432); f[4 * i + 1] = a[3 * i + 1]; \
                                                 f[4 * i + 2] = __byte_perm(a[3 * i + 1], a[3 * i + 2], 0x5432); f[4 * i + 3] = a[3 * i + 2]; }
#define MMA(N, E) UNR for (int i = 0; i < 4; i++) wgmma_rs<N>(E, f[4 * i], f[4 * i + 1], f[4 * i + 2], f[4 * i + 3], bd - 8 * i, 1); wg_commit();
#define L1(c) UNR for (int i = 0; i < 4; i++) { const float ev = c[i], od = c[4 + i]; S[i] = hi ? (h3 ? ev : od) : ev; \
                                                T[i] = __shfl_sync(0xffffffff, hi ? (h3 ? pr[i] : ev) : od, srcA); pr[i] = od; }
#define L1E() UNR for (int i = 0; i < 4; i++) S[i] += T[i];
#define L2() UNR for (int h = 0; h < 2; h++) { keep[h] = back ? pv[h] : S[2 * h + 1]; pv[h] = S[2 * h + 1]; U[h] = __shfl_sync(0xffffffff, S[2 * h], srcB); }
#define L2E(j) o[j] = pack_bf(keep[0] + U[0], keep[1] + U[1]);
#define GRP(G, N, P, E) UNR for (int i = 0; i < N / 2; i++) asm volatile("mov.b32 %0,%1;" : "=f"(E[i]) : "f"(P[i + 8])); \
    wg_fence(); if (G < 7) conv_frags<(G + 1) & 7>(a, abase); if (G >= 2) { L2() } L1(P) MMA(N, E) SPLIT(G); \
    if (G < 7) { PERM() } if (G >= 2) { L2E((G + 6) & 7) } L1E() wg_wait<0>(); fence_regs(E);
    PROFC(tid == 0, 300 + 4 * slot);
    mbar_wait(BAR(B_KF + slot));
    if (tid == 0) PROF(361 + slot);
    PROFC(tid == 0, 301 + 4 * slot);
    conv_frags<0>(a, abase);
    wg_fence();
    wgmma_rs<128>(e0, d0 << 16, d0, d1 << 16, d1, bd, 0);
    PERM() conv_frags<1>(a, abase); wg_fence(); MMA(128, e0) SPLIT(0); PERM() wg_wait<0>(); fence_regs(e0);
    GRP(1, 112, e0, e1) GRP(2, 96, e1, e2) GRP(3, 80, e2, e3) GRP(4, 64, e3, e4) GRP(5, 48, e4, e5) GRP(6, 32, e5, e6) GRP(7, 16, e6, e7)
    PROFC(tid == 0, 302 + 4 * slot);
    L2() L1(e7) L2E(6) L1E() L2() L2E(7)
    bar_sync(wg + 1, 128);
#pragma unroll
    for (int jj = 0; jj < 8; jj++) asm volatile("st.shared.u32 [%0],%1;" ::"r"(gp + jj * 512), "r"(o[jj]) : "memory");
#undef PERM
#undef MMA
#undef L1
#undef L1E
#undef L2
#undef L2E
#undef GRP
    PROFC(tid == 0, 303 + 4 * slot);
    __syncwarp();
    if (lane == 0) mbar_arrive(BAR(B_GS + slot));
    if (!AUX) break;
    slot = slot ? slot + 1 : 3;
  }
}

#define IDX(J, c, h) (8 * (J) + 4 * ((c) >> 1) + 2 * (h) + ((c) & 1))
__device__ __forceinline__ uint2 lds2(uint32_t a) { uint2 v; asm volatile("ld.shared.v2.u32 {%0,%1},[%2];" : "=r"(v.x), "=r"(v.y) : "r"(a) : "memory"); return v; }
__device__ __forceinline__ void resid_load(float (&r)[40], uint32_t sb, int wg, int tid, const uint4& s) {
  const uint32_t dp = sb + XR_OFF + 8 * (tid & 3), xp = dp + (64 * wg + 16 * (tid >> 5) + ((tid & 31) >> 2)) * 160;
#pragma unroll
  for (int J = 0; J < 5; J++) {
    const uint2 u = lds2(xp + 32 * J), v = lds2(xp + 32 * J + 1280), d = lds2(dp + 20480 + 32 * J);
    r[8 * J] = __uint_as_float(u.x); r[8 * J + 1] = __uint_as_float(u.y); r[8 * J + 2] = __uint_as_float(v.x); r[8 * J + 3] = __uint_as_float(v.y);
    r[8 * J + 4] = __uint_as_float(d.x); r[8 * J + 5] = __uint_as_float(d.y);
  }
  r[30] = untag(s.x); r[31] = untag(s.y); r[38] = untag(s.z); r[39] = untag(s.w);
}
__device__ __forceinline__ void resid_init(float (&r)[40]) {
  const float s[4] = {r[30], r[31], r[38], r[39]};
#pragma unroll
  for (int J = 0; J < 5; J++) {
    uint32_t w[6];
#pragma unroll
    for (int i = 0; i < 6; i++) w[i] = __float_as_uint(r[8 * J + i]);
#pragma unroll
    for (int i = 0; i < 4; i++) {
      const int h = i >> 1, c = 2 * (i & 1);
      const float rs = s[2 * h], nm = s[2 * h + 1], x0 = bf_lo(w[i]), x1 = bf_hi(w[i]);
      const uint32_t t = hmul2(pack_bf(fmaf(x0, rs, nm), fmaf(x1, rs, nm)), w[4 + (i & 1)]);
      r[IDX(J, c, h)] = x0 + bf_lo(t); r[IDX(J, c + 1, h)] = x1 + bf_hi(t);
    }
  }
}

__device__ __forceinline__ float flip(float v, uint32_t m) { return __uint_as_float(__float_as_uint(v) ^ m); }
__device__ __forceinline__ void g1_phase(const int LY, const Head& H, uint32_t sb, int wg, int tid, Role R, float (&xr)[40], long long t_start) {
  Scratch* const S = H.s;
  tid = opaque(tid); sb = opaque(sb); R.v = opaque(R.v);
  const uint32_t bars = sb + BAR_OFF;
  const int cb = R.cb(), tb = R.tb();
  const int w = tid >> 5, lane = tid & 31, g = lane >> 2, q = lane & 3;
  const bool full = tb < 12;
  uint2* Eb = S->E + ((LY * 130 + cb) * 8 + 4 * wg + w) * 16 + g;
  float a[80];
#pragma unroll
  for (int i = 0; i < 80; i++) a[i] = 0.f;
  uint32_t rel = mapa(BAR(B_E1), lane ? R.wpart() : R.ubase() + (w & (R.ugs() - 1)));
  const bool rels = lane == 0 || (tid == 1 && wg != R.wlo());
  {
    uint64_t tw = LY ? WTAB1 : WTAB0, tx = LY ? XTAB1 : XTAB0;
    uint32_t bf = BAR(B_F1);
    if (tid == 0 && wg == 0 && !LY) PROF(351);
    fence_regs(a);
    mbar_wait(bf, LY);
    if (tid == 0 && wg == 0) PROF(LY ? 20 : 4);
#pragma unroll 1
    for (int kb = 0; kb < 10; kb++) {
      const uint64_t da = make_desc(sb + ((uint32_t)tw & 63) * 4096 + wg * 8192, 16, 1024, 1);
      const uint64_t db = make_desc(sb + ((uint32_t)tx & 63) * 4096, 16, 1024, 1);
      wg_fence();
#pragma unroll
      for (int kk = 0; kk < 4; kk++) wgmma_ss160(a, da + 2 * kk, db + 2 * kk, 1);
      wg_commit();
      wg_wait<1>();
      if (kb > 0) { if (rels) mbar_arrive_at(rel); rel += 8; }
      bf += 8; tw >>= 6; tx >>= 6;
      if (kb < 9) mbar_wait(bf, LY);
    }
  }
  if (tid == 0 && wg == 0) PROF(LY ? 19 : 2);
  mbar_wait(BAR(B_LM));
  const uint32_t tag = lds32(sb + MISC_OFF) & 1;
  if (q == 3) st_rlx2(Eb + tb * 1280, tag ^ 1, tag ^ 1);
  float2 lam, mu, mu2;
  float rs0, rs1;
  const uint32_t lamp = sb + LAM_OFF + 16 * (32 * wg + 8 * w + g);
  {
    const uint2* rp = S->RS + (8 * cb + 4 * wg + w) * 16 + 2 * g - (g & 1);
    uint2 v = ld_rlx2(rp);
    asm volatile("ld.shared.v2.f32 {%0,%1},[%2];" : "=f"(lam.x), "=f"(lam.y) : "r"(lamp));
    const float2 l2 = cmul(lam, lam), l4 = cmul(l2, l2), l8 = cmul(l4, l4), l16 = cmul(l8, l8), l32 = cmul(l16, l16);
    mu = full ? cmul(l32, l8) : l32; mu2 = cmul(mu, mu);
#pragma unroll 1
    for (int it = 0; it < SPIN && __any_sync(0xffffffff, untagged(v, tag)); it++) v = ld_rlx2(rp);
    rs0 = untag(v.x); rs1 = untag(v.y);
  }
  if (tid == 0 && wg == 0 && !LY) PROF(39);
  mbar_wait(BAR(B_ST), LY);
  const uint32_t ssm = sb + SSM_OFF + q * (full ? 336 : 272);
  wg_wait<0>(); fence_regs(a);
  if (rels) mbar_arrive_at(rel);
  if (tid == 0 && wg == 0) PROF(LY ? 21 : 5);
  float2 p = make_float2(0.f, 0.f);
#pragma unroll
  for (int j = 0; j < 20; j++) {
    if (j < 16 || full) {
      float4 sv;
      asm volatile("ld.shared.v4.f32 {%0,%1,%2,%3},[%4];" : "=f"(sv.x), "=f"(sv.y), "=f"(sv.z), "=f"(sv.w) : "r"(ssm + 16 * j));
#pragma unroll
      for (int e = 0; e < 2; e++) {
        const int o = 4 * j + e;
        const float r = e ? sv.z : sv.x, nm = e ? sv.w : sv.y;
        a[o] = fmaf(a[o], r, nm * rs0); a[o + 2] = fmaf(a[o + 2], r, nm * rs1);
        p = cfma(lam, p, make_float2(a[o], a[o + 2]));
      }
    }
  }
  {
    float2 t = make_float2(__shfl_up_sync(0xffffffff, p.x, 1, 4), __shfl_up_sync(0xffffffff, p.y, 1, 4));
    if (q >= 1) p = cfma(mu, t, p);
    t = make_float2(__shfl_up_sync(0xffffffff, p.x, 2, 4), __shfl_up_sync(0xffffffff, p.y, 2, 4));
    if (q >= 2) p = cfma(mu2, t, p);
  }
  if (q == 3 && full) st_rlx2(Eb + tb * 1280, tagf(p.x, tag), tagf(p.y, tag));
  if (tid == 0 && wg == 1) PROF(96 + 64 * LY);
  uint2 ev[3];
#pragma unroll
  for (int i = 0; i < 3; i++) { const int j = tb - 1 - q - 4 * i; ev[i] = j >= 0 ? ld_rlx2(Eb + j * 1280) : make_uint2(tag, tag); }
  float2 x = make_float2(__shfl_up_sync(0xffffffff, p.x, 1, 4), __shfl_up_sync(0xffffffff, p.y, 1, 4));
  if (q == 0) x = make_float2(0.f, 0.f);
  float c0, c1;
  asm volatile("ld.shared.v2.f32 {%0,%1},[%2+8];" : "=f"(c0), "=f"(c1) : "r"(lamp));
  const float c2 = -flip(c1, H.swap), c3 = flip(c0, H.swap);
#pragma unroll
  for (int i = 0; i < 40; i++) {
    const int o = 4 * (i >> 1) + (i & 1);
    const float u = a[o], v = a[o + 2];
    a[o] = fmaf(c0, u, c1 * v); a[o + 2] = fmaf(c2, u, c3 * v);
  }
  fence_regs(a);
  if (LY == 0 && R.b() < 128) {
    const int t0 = 16 * g + 8 * wg + 2 * w;
    if (tid == 0 && wg == 1) PROF(366);
    mbar_wait(BAR(B_XR));
    if (tid == 0 && wg == 1) PROF(367);
    uint4 s = lds4(sb + XR_OFF + 20480 + 256 + 8 * t0);
    if (__any_sync(0xffffffff, untagged(s, tag))) {
#pragma unroll 1
      for (int it = 0; it < SPIN; it++) { s = ld_rlx4(S->S + 128 * (R.b() >> 3) + t0); if (!__any_sync(0xffffffff, untagged(s, tag))) break; }
    }
    resid_load(xr, sb, wg, tid, s);
  }
  float2 mq, om4, fq;
  {
    asm volatile("" : "+f"(lam.x), "+f"(lam.y));
    const float2 one = make_float2(1.f, 0.f), l2 = cmul(lam, lam), l4 = cmul(l2, l2), l8 = cmul(l4, l4), l16 = cmul(l8, l8);
    const float2 l80 = full ? mu2 : cmul(mu2, l16), om = cmul(l80, l80), om2 = cmul(om, om);
    mq = cmul((q & 1) ? mu : one, (q & 2) ? mu2 : one);
    om4 = cmul(om2, om2); fq = cmul((q & 1) ? om : one, (q & 2) ? om2 : one);
  }
  mbar_wait(BAR(B_E1 + 9), LY);
  if (tid == 0 && wg == 1) PROF(368 + LY);
#pragma unroll 1
  for (int it = 0; it < SPIN; it++) {
    const bool m0 = untagged(ev[0], tag), m1 = untagged(ev[1], tag), m2 = untagged(ev[2], tag);
    if (!__any_sync(0xffffffff, m0 || m1 || m2)) break;
    if (m0) ev[0] = ld_rlx2(Eb + (tb - 1 - q) * 1280);
    if (m1) ev[1] = ld_rlx2(Eb + (tb - 5 - q) * 1280);
    if (m2) ev[2] = ld_rlx2(Eb + (tb - 9 - q) * 1280);
  }
  if (tid == 0 && wg == 1) PROF(97 + 64 * LY);
  float2 c = make_float2(untag(ev[2].x), untag(ev[2].y));
#pragma unroll
  for (int i = 1; i >= 0; i--) c = cfma(om4, c, make_float2(untag(ev[i].x), untag(ev[i].y)));
  c = cmul(fq, c);
#pragma unroll
  for (int s = 1; s <= 2; s <<= 1) { c.x += __shfl_xor_sync(0xffffffff, c.x, s); c.y += __shfl_xor_sync(0xffffffff, c.y, s); }
  c = cfma(mq, c, x);
  float2 z = make_float2(fmaf(c0, c.x, c1 * c.y), fmaf(c2, c.x, c3 * c.y));
  if (tid == 0 && wg == 0) PROF(LY ? 22 : 6);
  const float2 lc = make_float2(lam.x, flip(lam.y, H.swap));
  const uint32_t hq = sb + (lane >> 4) * 1024 + (lane & 7) * 128 + (((4 * wg + w) ^ (lane & 7)) << 4);
  const uint32_t hp = hq + R_OFF + (lane & 8) * 2048, hp4 = hq + (LY ? R4_OFF1 : R4_OFF0) + (lane & 8) * 512;
#pragma unroll
  for (int j = 0; j < 20; j += 2) {
    if (j < 16 || full) {
      uint32_t o[4];
#pragma unroll
      for (int i = 0; i < 2; i++) {
        const float2 z0 = cfma(lc, z, make_float2(a[4 * (j + i)], a[4 * (j + i) + 2]));
        z = cfma(lc, z0, make_float2(a[4 * (j + i) + 1], a[4 * (j + i) + 3]));
        o[2 * i] = pack_bf(z0.x, z.x); o[2 * i + 1] = pack_bf(z0.y, z.y);
      }
      asm volatile("stmatrix.sync.aligned.m8n8.x4.trans.shared.b16 [%0], {%1,%2,%3,%4};" ::"r"(j < 16 ? hp + j * 1024 : hp4 + (j - 16) * 1024), "r"(o[0]), "r"(o[1]), "r"(o[2]), "r"(o[3]) : "memory");
      if (j & 2) { __syncwarp(); if (lane == 0) mbar_arrive(BAR(B_SH + j / 4)); }
    }
  }
  if (tid == 0 && wg == 0) PROF(LY ? 23 : 7);
  if (lane == 0) PROF(390 + 4 * wg + w);
}

__device__ __forceinline__ void gate_load(float (&G)[40], uint32_t sb, int LY, int wg, int tid, int tb2) {
  const uint32_t bars = sb + BAR_OFF;
  const int lane = tid & 31, w = tid >> 5;
  mbar_wait(BAR(B_GF), LY);
  const int g = lane >> 2, q = lane & 3;
  const uint32_t gb = sb + (LY ? G_OFF1 : G_OFF0) + wg * 10240 + 512 * q + ((32 * w + 4 * g) ^ (64 * ((tb2 ^ q) & 1)) ^ (16 * (q & 2)));
#pragma unroll
  for (int i = 0; i < 20; i++) { const uint32_t v = lds32((gb ^ (16 * (i & 3))) + 128 * (i & 3) + 2048 * (i >> 2)); G[2 * i] = bf_lo(v); G[2 * i + 1] = bf_hi(v); }
  fence_regs(G);
}
__device__ __forceinline__ void g2_phase(const int LY, const Params& P, Scratch* S, uint32_t sb, int wg, int tid, Role R, float (&xr)[40], long long t_start) {
  sb = opaque(sb);
  const uint32_t bars = sb + BAR_OFF;
  if (LY) {
    const int td = opaque(tid), b = (opaque(R.v) >> 8) & 255;
    const uint32_t tag = lds32(sb + MISC_OFF) & 1;
    const uint2* sp = S->S + 2 * SEQ + 128 * (b >> 3) + 4 * (td & 28) + 8 * wg + 2 * (td >> 5);
    if (!(R.cb() & 1)) mbar_wait(BAR(B_HD), 1);
    uint2 dl[5];
#pragma unroll
    for (int J = 0; J < 5; J++) dl[J] = __ldg((const uint2*)(P.dskip + 80 * (b & 7) + 4 * (td & 3) + 16 * J));
    uint4 sv;
#pragma unroll 1
    for (int it = 0; it < SPIN; it++) { sv = ld_rlx4(sp); if (!__any_sync(0xffffffff, untagged(sv, tag))) break; }
#pragma unroll
    for (int h = 0; h < 2; h++)
#pragma unroll
      for (int J = 0; J < 5; J++)
#pragma unroll
        for (int c = 0; c < 4; c++) {
          const float x2 = xr[IDX(J, c, h)];
          const uint32_t dw = (c & 2) ? dl[J].y : dl[J].x;
          xr[IDX(J, c, h)] = fmaf(fmaf(x2, untag(h ? sv.z : sv.x), untag(h ? sv.w : sv.y)), (c & 1) ? bf_hi(dw) : bf_lo(dw), x2);
        }
    fence_regs(xr);
  }
  float acc[40];
#pragma unroll
  for (int i = 0; i < 40; i++) acc[i] = RIAT == 1 ? 0.f : xr[i];
  fence_regs(acc);
#define G2_STEP(st, cs, hf) { \
    const uint64_t da = make_desc(sb + H_OFF + (st) * 32768 + (hf) * 16384 + wg * 8192, 16, 1024, 1), db = make_desc(sb + (cs) * 20480 + (hf) * 10240, 16, 1024, 1); \
    wg_fence(); \
    _Pragma("unroll") for (int kk = 0; kk < 4; kk++) wgmma_ss80(acc, da + 2 * kk, db + 2 * kk, 1); \
    wg_commit(); }
  mbar_wait(BAR(B_F2), LY);
  if (tid == 0 && wg == 0) PROF(LY ? 25 : 10);
  G2_STEP(0, 0, 0)
  mbar_wait(BAR(B_F3), LY);
  G2_STEP(0, 0, 1)
  tid = opaque(tid); R.v = opaque(R.v);
  const uint32_t tag = lds32(sb + MISC_OFF) & 1;
  const int b = R.b(), tb2 = b >> 3, db_ = b & 7;
  const int w = tid >> 5, lane = tid & 31, g = lane >> 2, q = lane & 3;
  const int t0 = 128 * tb2 + 16 * g + 8 * wg + 2 * w;
  const int d0 = 80 * db_ + 4 * q, mrow = 64 * wg + 16 * w + g;
#define GATE(J, c, h) G[8 * (J) + 2 * (c) + (h)]
  uint32_t rel = mapa(BAR(B_E2), lane ? ((w & 1) ? R.wpart() : R.rank()) : R.cs() == 8 ? 4 * wg + w : wg);
  const bool rels = lane == 0 || (lane == 1 && w < 2);
  uint32_t* Mb = S->M + ((2 * LY * 16 + tb2) * 8) * 256 + (wg * 4 + w) * 32 + (2 * g + (q & 1)) * 2 + (q >> 1);
  {
    uint32_t bf = BAR(B_F2 + 1), st = 1, ra = rel + 8 * (B_EA - B_E2);
    const int lag = wg ? (LY ? STG : STG0) / 2 : 0;
#pragma unroll 1
    for (int kp = 1; kp < 10; kp++) {
      const bool more = LY == 0 || kp < 8;
      wg_wait<1>();
      if (lane == 0 && more) mbar_arrive_at(ra + 8 * (st ? st - 1 : 2));
      mbar_wait(bf, LY);
      if (STG && !(STG & 1) && kp == lag) bar_sync(5, 256);
      G2_STEP(st, kp < 5 ? kp : kp - 5, 0)
      wg_wait<1>();
      if (rels && more) mbar_arrive_at(rel);
      rel += 8;
      mbar_wait(bf + 8 * (B_F3 - B_F2), LY);
      if ((STG & 1) && kp == lag) bar_sync(5, 256);
      G2_STEP(st, kp < 5 ? kp : kp - 5, 1)
      if (kp == MIAT) {
        st_rlx(Mb + db_ * 256, tag ^ 1);
        if (LY == 0) st_rlx(Mb + (16 * 8 + db_) * 256, tag ^ 1);
      }
      bf += 8; st = st == 2 ? 0 : st + 1;
    }
  }
  if (STG && (LY || STG0) && !wg) asm volatile("bar.arrive 5, 256;" ::: "memory");
  const uint32_t mx = sb + MX_OFF + 512 * wg + 4 * tid, bx = BAR(B_KF + 1 + 2 * LY + wg);
  uint32_t pa[8], pb[8];
#pragma unroll
  for (int i = 0; i < 8; i++) { pa[i] = mapa(mx + 1024 * db_, i ^ db_); pb[i] = mapa(bx + (tid >> 10), i ^ db_); asm volatile("" : "+r"(pa[i]), "+r"(pb[i])); }
  wg_wait<0>(); fence_regs(acc);
  if (LY == 0 && rels) mbar_arrive_at(rel);
  if (tid == 0 && wg == 0) PROF(LY ? 26 : 11);
  if (lane == 0) PROF(116 + 64 * LY + wg * 4 + w);

#pragma unroll 1
  for (int rep = 0;; rep++) {
    float m[2][2];
#pragma unroll
    for (int h = 0; h < 2; h++) {
      m[h][0] = m[h][1] = 0.f;
#pragma unroll
      for (int J = 0; J < 5; J++)
#pragma unroll
        for (int c = 0; c < 4; c++) { const float xv = acc[IDX(J, c, h)]; m[h][0] += xv; m[h][1] = fmaf(xv, xv, m[h][1]); }
    }
    float r1[2];
#pragma unroll
    for (int i = 0; i < 2; i++) { const float snd = (q & 1) ? m[0][i] : m[1][i], kp = (q & 1) ? m[1][i] : m[0][i]; r1[i] = kp + __shfl_xor_sync(0xffffffff, snd, 1); }
    const float r2 = ((q & 2) ? r1[1] : r1[0]) + __shfl_xor_sync(0xffffffff, (q & 2) ? r1[0] : r1[1], 2);
    if (R.cs() == 8 && !rep) {
#pragma unroll
      for (int i = 0; i < 8; i++)
        asm volatile("st.async.weak.shared::cluster.mbarrier::complete_tx::bytes.b32 [%0],%1,[%2];" ::"r"(pa[i]), "f"(r2), "r"(pb[i]) : "memory");
      if (tid == 0) mbar_expect_tx(bx, 4096);
    }
    st_rlx(Mb + db_ * 256, tagf(r2, tag));
    if (rep) break;
    if (lane == 0) PROF(100 + 64 * LY + wg * 4 + w);
    float G[40];
    gate_load(G, sb, LY, wg, tid, tb2);
    mbar_wait(BAR(B_CD + 1));
    uint32_t mv[8];
    if (R.cs() == 8) {
      mbar_wait(bx, 1);
#pragma unroll
      for (int i = 0; i < 8; i++) mv[i] = lds32(mx + 1024 * i);
    } else {
#pragma unroll
    for (int i = 0; i < 8; i++) mv[i] = ld_rlx(Mb + i * 256);
#pragma unroll 1
    for (int it = 0; it < SPIN; it++) {
      uint32_t miss = 0;
#pragma unroll
      for (int i = 0; i < 8; i++) miss |= ((mv[i] ^ tag) & 1) << i;
      if (!__any_sync(0xffffffff, miss)) break;
#pragma unroll
      for (int i = 0; i < 8; i++) if ((miss >> i) & 1) mv[i] = ld_rlx(Mb + i * 256);
    }
#pragma unroll
      for (int i = 0; i < 8; i++) mv[i] = __float_as_uint(untag(mv[i]));
      if (MBAR || !LY) bar_sync(4, 256);
    }
    if (lane == 0) PROF(108 + 64 * LY + wg * 4 + w);
#define MV(i) __uint_as_float(mv[i])
    const float s = ((MV(0) + MV(1)) + (MV(2) + MV(3))) + ((MV(4) + MV(5)) + (MV(6) + MV(7)));
#undef MV
    float mm[2], rr[2];
#pragma unroll
    for (int h = 0; h < 2; h++) {
      mm[h] = __shfl_sync(0xffffffff, s, h, 4) * (1.f / DM);
      rr[h] = frsqrt(fmaxf(__shfl_sync(0xffffffff, s, 2 + h, 4) * (1.f / DM) - mm[h] * mm[h], 0.f) + 1e-5f);
    }
    if (tid == 0 && wg == 0) PROF(LY ? 27 : 12);
    const float nm[2] = {-mm[0] * rr[0], -mm[1] * rr[1]};
#pragma unroll
    for (int h = 0; h < 2; h++)
#pragma unroll
      for (int J = 0; J < 5; J++)
#pragma unroll
        for (int c = 0; c < 4; c++) { const float xv = acc[IDX(J, c, h)]; xr[IDX(J, c, h)] = fmaf(fmaf(xv, rr[h], nm[h]), GATE(J, c, h), xv); }
    if (LY) break;
#pragma unroll
    for (int i = 0; i < 40; i++) acc[i] = xr[i] - mm[(i >> 1) & 1];
    if (R.cs() == 8) mbar_wait(BAR(B_KF + 1), 1);
#pragma unroll
    for (int i = 0; i < 10; i++) {
      const int J = i >> 1, h = i & 1;
      const uint32_t u0 = pack_bf(acc[IDX(J, 0, h)], acc[IDX(J, 1, h)]), u1 = pack_bf(acc[IDX(J, 2, h)], acc[IDX(J, 3, h)]);
      asm volatile("st.shared.v2.u32 [%0],{%1,%2};" ::"r"(sb + US_OFF + ((mrow ^ 64) + 8 * h) * 160 + 32 * J + 8 * q), "r"(u0), "r"(u1) : "memory");
    }
    __syncwarp();
    if (lane == 0) mbar_arrive(BAR(B_GS + 1 + wg));
    if (tid == 0 && wg == 0) PROF(13);
    Mb += 16 * 8 * 256;
  }
  if (LY == 0) {
    if (tid == 0 && wg == 0) PROF(15);
  }
  else {
    float* op = P.out + (size_t)t0 * DM + d0;
#pragma unroll
    for (int i = 0; i < 10; i++) {
      const int J = i >> 1, h = i & 1;
      asm volatile("st.global.v4.f32 [%0],{%1,%2,%3,%4};" ::"l"(op + h * DM + 16 * J),
                   "f"(xr[IDX(J, 0, h)]), "f"(xr[IDX(J, 1, h)]), "f"(xr[IDX(J, 2, h)]), "f"(xr[IDX(J, 3, h)]) : "memory");
    }
  }
  if (tid == 0 && wg == 0 && LY) PROF(28);
#undef IDX
#undef GATE
}

__device__ __forceinline__ void next_stats(Scratch* S, uint32_t sb, int tb2, int tid) {
  const uint32_t bars = sb + BAR_OFF, tag = lds32(sb + MISC_OFF) & 1;
  const uint32_t* Mb = S->M + tb2 * 8 * 256 + 2 * tid;
  mbar_wait(BAR(B_F1 + NSAT), 1);
  float m1, s1, s2;
#pragma unroll 1
  for (int it = 0; it < SPIN; it++) {
    uint32_t a[8], miss = 0;
    uint2 v[8];
#pragma unroll
    for (int i = 0; i < 8; i++) { a[i] = ld_rlx(Mb + i * 256); v[i] = ld_rlx2((const uint2*)(Mb + (16 * 8 + i) * 256)); }
#pragma unroll
    for (int i = 0; i < 8; i++) miss |= (a[i] ^ tag) | (v[i].x ^ tag) | (v[i].y ^ tag);
#define SUM8(F) ((untag(F(0)) + untag(F(1))) + (untag(F(2)) + untag(F(3)))) + ((untag(F(4)) + untag(F(5))) + (untag(F(6)) + untag(F(7))))
#define FA(i) a[i]
#define FX(i) v[i].x
#define FY(i) v[i].y
    m1 = SUM8(FA); s1 = SUM8(FX); s2 = SUM8(FY);
    if (!__any_sync(0xffffffff, miss & 1)) break;
  }
  const float mean = s1 * (1.f / DM), rs = frsqrt(fmaxf(s2 * (1.f / DM) - mean * mean, 0.f) + 1e-5f);
  uint2* sp = S->S + SEQ + 128 * tb2 + 8 * (tid & 14) + 2 * (tid >> 4) + (tid & 1);
  st_rlx2(sp, tagf(rs, tag), tagf(-mean * rs, tag));
  st_rlx2(sp + SEQ, tagf(rs, tag), tagf(-(mean + m1 * (1.f / DM)) * rs, tag));
}
template <int I0, int I1> __device__ __forceinline__ void init_barriers(uint32_t bars) {
#pragma unroll
  for (int i = I0; i < I1; i++) mbar_init(BAR(i), bar_count(i));
}
__device__ __forceinline__ int g2_cb(int kp) { return kp < 5 ? 2 * kp : 2 * kp - 9; }
__device__ __forceinline__ const unsigned* h_flag(Scratch* S, int ly, int tb2, int lane) {
  const int s0 = 128 * min(tb2, 15) / 160;
  const bool two = (128 * tb2 + 127) / 160 != s0;
  return &S->flag[(F_H + (ly * 13 + s0) * 10 + min(lane & 15, 9) + (two && lane >= 16 ? 10 : 0)) * 32];
}
__device__ __forceinline__ void gate_tile(const Params& P, uint32_t dst, uint32_t bar, int tb2, int db) {
  tma2d(dst, &P.mGT, tb2 * 128, db * 80, bar);
  tma2d(dst + 10240, &P.mGT, tb2 * 128 + 64, db * 80, bar);
}
__global__ void __cluster_dims__() __launch_bounds__(512, 1) fused_kernel(const Head H, const __grid_constant__ Params P) {
  extern __shared__ __align__(1024) uint8_t smem[];
  const uint32_t sb = opaque(smem_u32(smem)), bars = sb + BAR_OFF;
  const int wi = __shfl_sync(0xffffffff, threadIdx.x >> 5, 0), wg = wi >> 2, tid = threadIdx.x & 127;
  const int umap = blockIdx.x >= 96;
#define CLK(v)
  CLK(c_a);
  if (wi == 14) {
    if (elect_one()) { init_barriers<0, NBAR1>(bars); asm volatile("fence.mbarrier_init.release.cluster;" ::: "memory"); }
    __syncwarp();
  } else if (wi >= 12) prefetch_map(wi == 12 ? &P.mB : &P.mA[umap]);
  else if (wg == 2) xb_prefetch<1>(H, blockIdx.x + H.base, tid, 0);
  else if (P.role[blockIdx.x].w) return;
  CLK(c_b);
  asm volatile("barrier.cluster.arrive.relaxed.aligned;" ::: "memory");
  CLK(c_c);
  Role R;
  { const uint4 r = P.role[blockIdx.x]; R.v = r.x; R.c = r.y; R.p = r.z; }
  const int id = R.c & 255;
  const int tb = R.tb(), cb = R.cb(), b = R.b(), tb2 = b >> 3, db = b & 7, rank = R.rank();
  const bool has1 = tb <= 12, has2 = b < 128, full = tb < 12;
  Scratch* const S = H.s;
  unsigned* const epoch_p = &S->epoch[id * 8];
  const long long t_start = 0;
  if (wg < 2) {
    if (threadIdx.x == 0) PROF(50);
    asm volatile("griddepcontrol.launch_dependents;");
    bar_sync(6, 448);
    asm volatile("setmaxnreg.inc.sync.aligned.u32 176;");
    float xr[40];
#pragma unroll
    for (int i = 0; i < 40; i++) xr[i] = 0.f;
#pragma unroll 1
    for (int ly = 0; ly < 2; ly++) {
      if (has1) g1_phase(ly, H, sb, wg, tid, R, xr, t_start);
      if (ly == 0) {
        resid_init(xr); fence_regs(xr);
        conv_loop<false>(sb, R.c, wg, tid, t_start);
        if (tid == 0 && wg == 0) PROF(9);
      }
      if (has2) g2_phase(ly, P, S, sb, wg, tid, R, xr, t_start);
    }
    if (tid == 0 && wg == 0) st_rlx(epoch_p, lds32(sb + MISC_OFF));
  } else if (wg == 2) {
    bar_sync(6, 448);
    if (has1) aux_prep(H, P, sb, R, tid, t_start);
    asm volatile("setmaxnreg.inc.sync.aligned.u32 136;");
    conv_loop<true>(sb, R.c, wg, tid, t_start);
    if (tid == 0) PROF(44);
    {
      const uint32_t bb = (P.role[blockIdx.x].x >> 8) & 255;
      if ((bb & 132) == NSDB && tid < 32) next_stats(H.s, sb, bb >> 3, 32 * (bb & 3) + tid);
    }
  } else {
    if (threadIdx.x == 384) PROF(354);
    asm volatile("setmaxnreg.dec.sync.aligned.u32 24;");
    const int wlo = R.wlo(), whi = R.whi();
    const uint32_t wmask = R.wmask(), umask = R.umask(), f1bytes = full ? 36864 : 32768;
    if (wi < 14) {
      if (threadIdx.x == 384) PROF(340);
      asm volatile("barrier.cluster.wait.aligned;" ::: "memory");
      if (has1 && elect_one()) {
        uint64_t tab = wi == 12 ? WTAB0 : XTAB0;
        PROF(329 + wi);
#pragma unroll 1
        for (int kb = 0; kb < 6; kb++, tab >>= 6) {
          const uint32_t dst = sb + ((uint32_t)tab & 63) * 4096;
          if (wi == 12) {
#pragma unroll 1
            for (int h = wlo; h <= whi; h++) tma4d_mc(dst + h * 8192, &P.mB, kb * 64, 0, 0, 8 * cb + 4 * h, BAR(B_F1 + kb), wmask);
          } else {
            tma4d_mc(dst + R.uj() * 1024, &P.mA[umap], kb * 64, 0, 0, 80 * tb + R.uj(), BAR(B_F1 + kb), umask);
            mbar_expect_tx(BAR(B_F1 + kb), f1bytes);
          }
        }
      }
      if (!has1 && wi == 13) bar_sync(7, 64);
    } else {
      if (wi == 15 && elect_one()) { init_barriers<NBAR1, NBAR>(bars); asm volatile("fence.mbarrier_init.release.cluster;" ::: "memory"); }
      bar_sync(6, 448);
      if (!has1 && wi == 14) bar_sync(7, 64);
    }
    const unsigned e1 = ld_rlx(epoch_p) + 1;
    if (wi == 12) {
      if (elect_one()) {
#pragma unroll 1
        for (int ly = 0; ly < 2; ly++) {
#pragma unroll 1
          for (int i = ly ? 0 : 6; i < 10 && has1; i++) {
            const int kb = (0x9876541032ull >> (4 * i)) & 15;
            if (ly == 0) { mbar_wait(BAR(B_E1 + ((DEP0 >> (4 * kb - 24)) & 15))); mbar_wait(BAR(B_AX + (kb == 9))); }
            else {
              if (has2 && i == (db >= GLATE ? 4 : 2)) {
                mbar_expect_tx(BAR(B_GF), 20480);
                wait_cnt(&S->cnt[(C_G + db) * 32], e1 * 80);
                if (i == 2) mbar_wait(BAR(B_E2 + 7));
                PROF(47);
                gate_tile(P, sb + G_OFF0, BAR(B_GF), tb2, db);
              }
              if (has2) mbar_wait(BAR(i < 4 ? B_E2 + ((0x9865u >> (4 * i)) & 15) : B_GE));
              else if (i == 0) { mbar_wait(BAR(B_E1 + 9)); mbar_wait(BAR(B_CD + 1)); }
              if (i >= 4) mbar_wait(BAR(i < 6 ? B_F1 + W4AT : B_E1 + i - 6), 1);
            }
            const uint32_t dst = sb + ((uint32_t)((ly ? WTAB1 : WTAB0) >> (6 * kb)) & 63) * 4096;
#pragma unroll 1
            for (int h = wlo; h <= whi; h++) tma4d_mc(dst + h * 8192, &P.mB, kb * 64, 0, 0, 8 * cb + 4 * h, BAR(B_F1 + kb), wmask);
          }
          if (has2) {
            if (ly == 0) {
              mbar_wait(BAR(B_E1 + XRAT));
              mbar_expect_tx(BAR(B_XR), 20480 + 160 + 1024);
              tma4d(sb + XR_OFF, &P.mX, 80 * db, tb2, BAR(B_XR));
              bulk_g2s(sb + XR_OFF + 20480, P.dskip + 80 * db, 160, BAR(B_XR));
              bulk_g2s(sb + XR_OFF + 20480 + 256, S->S + 128 * tb2, 1024, BAR(B_XR));
              if (CWAIT) mbar_wait(BAR(CWAIT == 1 ? B_KF + 2 : CWAIT == 2 ? B_KF + R.nch() - 1 : CWAIT == 3 ? B_KF + R.nch() - 2 : B_HD));
            }
#pragma unroll 1
            for (int kp = 0; kp < 10; kp++) {
              const uint32_t dst = sb + (kp < 5 ? kp : kp - 5) * 20480;
              mbar_wait(BAR(kp >= 5 ? B_E2 + kp - 5 : ly ? B_E1 + ((CTAB1 >> (4 * kp)) & 15) : kp < 3 ? B_SH : kp < 4 ? B_HD : B_CD), ly);
              mbar_expect_tx(BAR(B_F2 + kp), 10240 + 16384);
              tma5d(dst, &P.mC[0], g2_cb(kp) * 64, db * 5, BAR(B_F2 + kp));
              mbar_expect_tx(BAR(B_F3 + kp), 10240 + 16384);
              tma5d(dst + 10240, &P.mC[1], g2_cb(kp) * 64, db * 5, BAR(B_F3 + kp));
              if (ly && kp == 4) { mbar_wait(BAR(B_E1 + 9), 1); mbar_expect_tx(BAR(B_GF), 20480); gate_tile(P, sb + G_OFF1, BAR(B_GF), tb2, db); }
            }
          }
        }
      }
    } else if (wi == 13) {
      const int h0 = R.cs() == 8 ? rank : 4 * rank;
#pragma unroll 1
      for (int ly = 0; ly < 2; ly++) {
        int lane = lane_id();
        if (has1) {
          const unsigned* fp = &S->flag[(F_U3 + 8 * ((160 * tb) >> 7) + (lane & (full ? 15 : 7))) * 32];
          uint32_t ready = ly ? __ballot_sync(0xffffffff, ld_rlx(fp) == e1) : ~0u;
          if (ly) mbar_wait(BAR(full ? B_KF + 1 : has2 ? B_GS + 1 : B_RF1), has2);
          if (ly && full) mbar_wait(BAR(B_KF + 2), 1);
#pragma unroll 1
          for (int kb = ly ? 0 : 6; kb < 10; kb++) {
            if (ly && kb == UPAT) { mbar_wait(BAR(B_XR)); ready = ~0u; }
            const int nl = ly && kb < UH && R.rank() >= 4 ? 2 - 2 * (R.rank() & 1) : 1;
            if (nl) wait_flags(fp, e1, 0x101u * ((1u << (64 * kb / 80)) | (1u << ((64 * kb + 63) / 80))), ready);
            if (kb >= 4) mbar_wait(BAR(B_E1 + (ly ? kb - 4 : (DEP0 >> (4 * kb - 24)) & 15)), ly);
            mbar_wait(BAR(B_AX + (kb == 9)));
            if (elect_one()) {
              if (ly && kb == 0) PROF(34);
#pragma unroll 1
              for (int i = 0, uj = R.uj(); i < nl; i++, uj += 5 << umap)
                tma4d_mc(sb + ((uint32_t)((ly ? XTAB1 : XTAB0) >> (6 * kb)) & 63) * 4096 + uj * 1024, &P.mA[2 * ly + umap], kb * 64, 0, 0, 80 * tb + uj,
                         BAR(B_F1 + kb), umask);
              mbar_expect_tx(BAR(B_F1 + kb), f1bytes);
            }
            __syncwarp();
          }
        }
        if (ly == 0) {
          if (has1) mbar_wait(BAR(B_E1 + KPF));
          if (elect_one()) {
#pragma unroll 1
            for (int s = 0; s < R.nch(); s++) prefetch_l2(P.ssmk + (size_t)R.ch(s) * SEQ, 4096);
          }
          lane = lane_id();
#pragma unroll
          for (int s = 0; s < 5; s++) {
            asm volatile("st.shared.v4.u32 [%0],{%1,%1,%1,%1};" ::"r"(conv_buf(sb, s) + 16 * lane), "r"(0) : "memory");
            asm volatile("st.shared.u8 [%0],%1;" ::"r"(conv_buf(sb, s) + KC_OFS + lane), "r"(0) : "memory");
          }
          fence_async();
          __syncwarp();
          const unsigned* cp = &S->cnt[(C_KV + (R.ch(min(lane, R.nch() - 1)) >> 6)) * 32];
          uint32_t ready = 0;
#pragma unroll 1
          for (int s = 0, sk = 0; s < R.nch(); s++) {
#pragma unroll 1
            for (; sk < (s ? R.nch() : KUP); sk++)
              if (elect_one()) { mbar_expect_tx(BAR(B_KF + sk), 8192); bulk_g2s(conv_buf(sb, sk) + KC_OFS + 32, P.ssmk + (size_t)R.ch(sk) * SEQ, 4096, BAR(B_KF + sk)); }
            PROFC(s == 0, 329);
#pragma unroll 1
            for (int it = 0; !((ready >> s) & 1) && it < SPIN; it++) ready = __ballot_sync(0xffffffff, (int)(ld_rlx(cp) - e1 * 32) >= 0);
            PROFC(s == 0, 30);
            if (elect_one()) {
              bulk_g2s(conv_buf(sb, s) + KV_PAD, S->kv + (size_t)R.ch(s) * SEQ, 4096, BAR(B_KF + s));
              if (s == 0 && has2) { prefetch_l2(P.cre + (size_t)5 * b * DM, 5 * DM * 2); prefetch_l2(P.cim + (size_t)5 * b * DM, 5 * DM * 2); }
            }
            __syncwarp();
          }
          PROF(31);
          if (!has1) return;
        }
        lane = lane_id();
        const unsigned* fp = h_flag(S, ly, tb2, lane);
        uint32_t ready = __ballot_sync(0xffffffff, ld_rlx(fp) == e1), st = 0;
        if (ly == 0 && !has2) {
          mbar_wait(BAR(B_HD));
          if (lane < 8) mbar_arrive_cl(BAR(B_RF1), lane & 1);
        }
        if (has2) {
          mbar_wait(BAR(B_RF0), ly);
#pragma unroll 1
          for (int kp = 0; kp < 10; kp++) {
            if (kp == 5) { mbar_wait(BAR(B_XR), 1); ready = ~0u; }
            if (kp == 2) { mbar_wait(BAR(B_HD), ly); if (lane < 8) mbar_arrive_cl(BAR(B_RF1), lane & (R.cs() - 1)); }
            wait_flags(fp, e1, 0x10001u << g2_cb(kp), ready);
            if (kp == 2) mbar_wait(BAR(B_RF1), ly);
#pragma unroll
            for (int hf = 0; hf < 2; hf++) {
              if (kp >= 3) { if (hf) mbar_wait(BAR(B_E2 + kp - 3), ly); else mbar_wait(BAR(B_EA + st), ly ^ (kp >= 6 && kp < 9)); }
              if (elect_one()) {
                if (kp == 0 && !hf) PROF(33 + 2 * ly);
                tma4d_mc(sb + H_OFF + st * 32768 + hf * 16384 + h0 * 2048, &P.mH, g2_cb(kp) * 128 + hf * 64, 0, 2 * h0,
                         ly * 16 + tb2, BAR((hf ? B_F3 : B_F2) + kp), (1u << R.cs()) - 1);
              }
              __syncwarp();
            }
            st = st == 2 ? 0 : st + 1;
          }
        }
      }
    } else if (wi == 14) {
      if (!has1) return;
      prefetch_if(P.dskip + 64 * (tid & 31), (tid & 31) < 10);
      if (elect_one()) { prefetch_map(&P.sK); prefetch_map(&P.mX); prefetch_map(&P.sH); prefetch_map(&P.sU); prefetch_map(&P.mC[0]); prefetch_map(&P.mC[1]); prefetch_map(&P.mH); prefetch_map(&P.mGT); prefetch_map(&P.mA[2 + umap]); }
      __syncwarp();
#pragma unroll 1
      for (int ly = 0; ly < 2; ly++) {
        if (ly) {
          mbar_wait(BAR(B_F1 + 1), 1);
          uint32_t ready = 0;
          wait_flags(&S->flag[(F_U3 + 8 * ((160 * tb) >> 7) + ((lane_id() + ly) & (full ? 15 : 7))) * 32], e1, ~0u, ready);
          if (elect_one()) mbar_arrive(BAR(B_XR));
        }
        const int lane = lane_id();
        mbar_wait(BAR(B_E1 + (ly ? STAT_AT1 : STAT_AT)), ly);
        PROFC(lane == 0 && ly == 0, 36);
        {
          const int l = lane - (full ? 0 : 16);
          const uint2* p = S->S + ly * SEQ + 160 * tb + 2 * l;
          uint4 v[3];
#pragma unroll 1
          for (int it = 0; it < SPIN; it++) {
            v[0] = ld_rlx4(p); v[1] = ld_rlx4(p + 64); v[2] = ld_rlx4(p + 96);
            const bool miss = __any_sync(0xffffffff, untagged(v[0], e1 & 1) | untagged(v[1], e1 & 1) | untagged(v[2], e1 & 1));
            PROFC(lane == 0 && ly == 0 && it == 0, 37);
            if (!miss) break;
          }
          PROFC(lane == 0 && ly == 0, 38);
#pragma unroll
          for (int i = 0; i < 3; i++) {
            const int pr = l + (i == 2 ? 48 : 32 * i);
            if (pr >= 0) asm volatile("st.shared.v4.u32 [%0],{%1,%2,%3,%4};" ::"r"(sb + SSM_OFF + 16 * (pr + ((pr * (full ? 205 : 256)) >> 12))), "r"(v[i].x & ~1u),
                                      "r"(v[i].y & ~1u), "r"(v[i].z & ~1u), "r"(v[i].w & ~1u) : "memory");
          }
          __syncwarp();
        }
        if (lane == 0) mbar_arrive(BAR(B_ST));
        if (ly && has2) {
          mbar_wait(BAR(B_E1 + 9), 1);
          if (lane < 8) mbar_arrive_cl(BAR(B_RF0), lane & (R.cs() - 1));
        }
        if (lane == 0) {
#pragma unroll 1
          for (int pc = 0; pc < (full ? 5 : 4); pc++) {
            if ((HWM >> (4 * pc)) & 8) {
              mbar_wait(BAR(B_SH + min((HWM >> (4 * pc)) & 7, full ? 4 : 3)), ly);
              PROF(380 + 5 * ly + pc);
              if (pc == 0 && (cb & 1)) delay(ly ? HDLY : HDLY0);
              fence_async();
            }
#pragma unroll
            for (int i = 0; i < 2; i++) tma4d_store(&P.sH, sb + (pc < 4 ? R_OFF + i * 16384 + pc * 4096 : (ly ? R4_OFF1 : R4_OFF0) + i * 4096), 128 * cb + 64 * i, 0, 0, ly * 1024 + 80 * tb + 4 * pc);
          }
          bulk_commit(); bulk_wait();
          PROF(ly ? 17 : 16);
          mbar_arrive(BAR(B_HD));
          release<1>();
          signal_flag(&S->flag[(F_H + (ly * 13 + tb) * 10 + cb) * 32], e1);
          PROF(ly ? 24 : 8);
        }
        __syncwarp();
        if (has2) {
          mbar_wait(BAR(B_F2 + FPAT), ly);
          uint32_t ready = 0;
          wait_flags(h_flag(S, ly, tb2, lane_id() | 1), e1, ~0u, ready);
          if (elect_one()) mbar_arrive(BAR(B_XR));
        }
        if (lane == 0 && has2 && !ly) {
          mbar_wait(BAR(B_CD + 1));
#pragma unroll
          for (int i = 0; i < 2; i++) {
            mbar_wait(BAR(B_GS + 1 + i), 1);
            fence_async();
            tma4d_store(&P.sU, sb + US_OFF + 10240 - 10240 * i, 80 * db, 0, 8 * i, tb2);
          }
          bulk_commit(); bulk_wait();
          PROF(18);
          release<2>(); signal_flag(&S->flag[(F_U3 + b) * 32], e1);
          PROF(14);
          mbar_wait(BAR(B_SG));
          mbar_arrive(BAR(B_GE)); mbar_arrive_cl(BAR(B_GE), R.wpart());
        }
        __syncwarp();
      }
    } else {
      discretise(H, P, sb, R, tid & 31, e1);
      if (elect_one()) {
        mbar_arrive(BAR(B_LM));
        PROF(348);
        if (b < R.nprep()) {
#pragma unroll 1
          for (int task = b, r = 0; task < 320; task += R.nprep(), r++) {
            mbar_wait(BAR(B_PS + r));
            PROF(320 + 3 * r);
            fence_async();
            tma2d_store(&P.sK, sb + KS_OFF + r * 8192, 64 * (task & 31), 64 * (task >> 5));
            bulk_commit(); bulk_wait();
            PROF(321 + 3 * r);
            release<4>();
            signal_cnt(&S->cnt[(C_KV + (task >> 5)) * 32], 1);
            PROF(322 + 3 * r);
          }
          PROF(41);
        }
        if (has2) {
          mbar_wait(BAR(B_SH));
#pragma unroll 1
          for (int i = 0; i < 8; i++) mbar_arrive_cl(BAR(B_RF0), i & (R.cs() - 1));
        }
#pragma unroll 1
        for (int s = 0, s0 = 0; s < R.nch(); s++) {
          mbar_wait(BAR(B_GS + s));
          fence_async();
          bulk_s2g(S->gt + (size_t)R.ch(s) * SEQ, conv_buf(sb, s) + KC_OFS, 4096); bulk_commit();
          if (s == 1 || s >= R.nch() - GSPL) bulk_wait();
          if (s == 1 || s == min(R.nch() - 1, 3)) mbar_arrive(BAR(B_CD + (s > 1)));
          if (s >= R.nch() - GSPL) {
            PROF(45);
#pragma unroll 1
            for (bool first = true; s0 <= s; s0++, first = false) {
              unsigned* cp = &S->cnt[(C_G + R.ch(s0) / 80) * 32];
              asm volatile("" : "+l"(cp));
              if (first) release<8>();
              signal_cnt(cp, 1);
            }
          }
        }
        mbar_arrive(BAR(B_SG));
        PROF(46);
      }
    }
  }
}

typedef CUresult (*EncFn)(CUtensorMap*, CUtensorMapDataType, cuuint32_t, void*, const cuuint64_t*, const cuuint64_t*, const cuuint32_t*,
                          const cuuint32_t*, CUtensorMapInterleave, CUtensorMapSwizzle, CUtensorMapL2promotion, CUtensorMapFloatOOBfill);
bool enc(EncFn f, CUtensorMap* m, const void* base, int rank, const cuuint64_t* dims, const cuuint64_t* strides, const cuuint32_t* box, bool swz,
         bool f32 = false) {
  const cuuint32_t es[5] = {1, 1, 1, 1, 1};
  return f(m, f32 ? CU_TENSOR_MAP_DATA_TYPE_FLOAT32 : CU_TENSOR_MAP_DATA_TYPE_BFLOAT16, rank, const_cast<void*>(base), dims, strides, box, es,
           CU_TENSOR_MAP_INTERLEAVE_NONE, swz ? CU_TENSOR_MAP_SWIZZLE_128B : CU_TENSOR_MAP_SWIZZLE_NONE, CU_TENSOR_MAP_L2_PROMOTION_L2_256B,
           CU_TENSOR_MAP_FLOAT_OOB_FILL_NONE) == CUDA_SUCCESS;
}
void make_roles(Params& P, bool big) {
  for (uint32_t bx = 0; bx < (big ? 120u : 12u); bx++) {
    const uint32_t c = bx >> 3, r = bx & 7, id = big ? bx : 120 + bx;
    const uint32_t vA = c < 12 ? (2 * (c >> 1) + (r >> 2)) | (4 * (c & 1) + (r & 3)) << 4 | (r & 4) << 16 | 4 << 19 | (r ^ 4) << 22
                               : (4 * (c - 12) + (r >> 1)) | (8 + (r & 1)) << 4 | (r & 6) << 16 | 2 << 19 | (r ^ 2) << 22;
    const uint32_t vB = (bx < 10 ? 12 : 13) | bx << 4 | 2 << 19 | (bx & 1) << 22 | (bx & 1) << 26;
    P.role[bx].x = (big ? vA | r << 26 | 1u << 29 : vB) | (id < 128 ? (id & ~7u) | (r >> 1) | (r & 1) << 2 : id) << 8;
    P.role[bx].y = id | (big ? 5 : bx < 8 ? 3 : 4) << 10 | 120 << 13 | 132 << 21 | (big ? 4u : 3u) << 29;
    const uint32_t v = P.role[bx].x, cb = (v >> 4) & 15, rank = (v >> 26) & 7, ubase = (v >> 16) & 7, ugs = (v >> 19) & 7, wp = (v >> 22) & 7;
    const uint32_t wlo = rank > wp, whi = wp != rank ? wlo : 1, wmask = 1u << rank | 1u << wp;
    const uint32_t uj = (rank - ubase) * (!big ? 8 : ugs == 4 ? 5 : 10), sm = big ? (0x7296418530ull >> (4 * cb)) & 15 : bx < 8 ? 4 * (bx & 1) + (bx >> 1) : 15;
    P.role[bx].z = wlo | whi << 1 | wmask << 2 | ((1u << ugs) - 1) << (10 + ubase) | uj << 20 | sm << 25;
    P.role[bx].w = 0;
  }
}
void launch(const Head& H, const Params& P, int grid, int cs, bool dependent) {
  cudaLaunchConfig_t cfg = {};
  cfg.gridDim = grid; cfg.blockDim = 512; cfg.dynamicSmemBytes = SMEM_BYTES; cfg.stream = cudaStreamPerThread;
  cudaLaunchAttribute at[2];
  at[0].id = cudaLaunchAttributeClusterDimension; at[0].val.clusterDim.x = cs; at[0].val.clusterDim.y = 1; at[0].val.clusterDim.z = 1;
  at[1].id = cudaLaunchAttributeProgrammaticStreamSerialization; at[1].val.programmaticStreamSerializationAllowed = 1;
  cfg.attrs = at; cfg.numAttrs = dependent ? 2 : 1;
  cudaLaunchKernelEx(&cfg, fused_kernel, H, P);
}

}

extern "C" void kernel_launch(void* const* d_in, const int* in_sizes, int n_in, void* d_out, int out_size) {
  (void)in_sizes; (void)n_in; (void)out_size;
  typedef const __nv_bfloat16* cb;
  void* fp = nullptr; cudaDriverEntryPointQueryResult qr;
  cudaGetDriverEntryPoint("cuTensorMapEncodeTiled", &fp, cudaEnableDefault, &qr);
  EncFn f = (EncFn)fp;
  Scratch* sp = nullptr;
  cudaGetSymbolAddress((void**)&sp, g_scr);
  void *pu = sp->u, *ph = sp->h, *pgt = sp->gt;
  Params P;
  Head H;
  H.s = sp; H.x = (cb)d_in[0]; H.swap = (uintptr_t)d_in[4] < (uintptr_t)d_in[3] ? 0 : 0x80000000u; H.b0 = (cb)d_in[H.swap ? 3 : 4]; H.b1 = (cb)d_in[H.swap ? 4 : 3];
  for (int i = 0; i < 2; i++) {
    const cuuint64_t d[4] = {640, 8, 2, 80}, s[3] = {1280, (cuuint64_t)((uintptr_t)H.b1 - (uintptr_t)H.b0), 8 * 1280}; const cuuint32_t bx[4] = {64, 8, 2, 4};
    if (enc(f, &P.mB, H.b0, 4, d, s, bx, true)) break;
    cudaMemcpyAsync(sp->bcopy, H.b0, DM * DM * 2, cudaMemcpyDeviceToDevice, cudaStreamPerThread);
    cudaMemcpyAsync(sp->bcopy + DM * DM, H.b1, DM * DM * 2, cudaMemcpyDeviceToDevice, cudaStreamPerThread);
    H.b0 = sp->bcopy; H.b1 = sp->bcopy + DM * DM;
  }
  {
    const cuuint64_t d[5] = {640, 2, 4, 2, 40}, s[4] = {1280, 4 * 1280, 2 * 1280, 16 * 1280}; const cuuint32_t bx[5] = {64, 2, 4, 2, 5};
    enc(f, &P.mC[0], d_in[5], 5, d, s, bx, true); enc(f, &P.mC[1], d_in[6], 5, d, s, bx, true); }
  { const cuuint64_t d[2] = {2048, 640}, s[1] = {4096}; const cuuint32_t bx[2] = {64, 80}; enc(f, &P.mGT, pgt, 2, d, s, bx, true); }
  { const cuuint64_t d[4] = {640, 8, 16, 16}, s[3] = {16 * 1280, 1280, 128 * 1280}; const cuuint32_t bx[4] = {80, 8, 16, 1}, bh[4] = {80, 8, 8, 1};
    enc(f, &P.sU, pu, 4, d, s, bh, false); enc(f, &P.mX, d_in[0], 4, d, s, bx, false); }
  { const cuuint64_t d[2] = {2048, 640}, s[1] = {4096}; const cuuint32_t bx[2] = {64, 64}; enc(f, &P.sK, sp->kv, 2, d, s, bx, true); }
  P.lre = (cb)d_in[1]; P.lim = (cb)d_in[2]; P.cre = (cb)d_in[5]; P.cim = (cb)d_in[6]; P.ldt = (cb)d_in[7]; P.dskip = (cb)d_in[8];
  P.out = (float*)d_out;
  P.k = (cb)d_in[10]; P.v = (cb)d_in[11]; P.shk = (cb)d_in[12]; P.ssmk = (cb)d_in[13]; P.ssmd = (cb)d_in[14];
  cudaFuncSetAttribute(fused_kernel, cudaFuncAttributeMaxDynamicSharedMemorySize, SMEM_BYTES);
  for (int big = 1; big >= 0; big--) {
    const cuuint64_t seg = big ? 40 : 32;
    for (int i = 0; i < 4; i++) {
      const cuuint64_t d[4] = {640, 2, 4, 1024}, s[3] = {1280, seg * 1280, 2 * 1280}; const cuuint32_t bx[4] = {64, 2, 4, !big ? 8u : (i & 1) ? 10u : 5u};
      enc(f, &P.mA[i], i < 2 ? d_in[0] : pu, 4, d, s, bx, true);
    }
    {
      const cuuint64_t d[4] = {1280, 8, 16, 32}, s[3] = {16 * 2560, 2560, 128 * 2560}; const cuuint32_t bx[4] = {64, 8, big ? 2u : 8u, 1};
      enc(f, &P.mH, ph, 4, d, s, bx, true); }
    { const cuuint64_t d[4] = {1280, 2, 4, 2048}, s[3] = {2560, seg * 2560, 2 * 2560}; const cuuint32_t bx[4] = {64, 2, 4, 4};
      enc(f, &P.sH, ph, 4, d, s, bx, true); }
    make_roles(P, big);
    H.base = big ? 0 : 120;
    launch(H, P, big ? 120 : 12, big ? 8 : 2, !big);
  }
}
```
